```python
import torch

def _softmax(x, axis=-1):
    return torch.softmax(x, dim=axis)

def _gelu(x):
    return torch.nn.functional.gelu(x, approximate='tanh')

def _silu(x):
    return torch.nn.functional.silu(x)

def _sigmoid(x):
    return torch.sigmoid(x)

def _layernorm(x, axis=-1, eps=1e-05):
    m = x.mean(dim=axis, keepdim=True)
    v = x.var(dim=axis, keepdim=True, unbiased=False)
    return (x - m) / torch.sqrt(v + eps)

def _scatter_add(tgt, idx, src, axis=0):
    return tgt.clone().index_add_(axis, idx, src)

def _segment_sum(src, seg, n):
    out = torch.zeros((n,) + src.shape[1:], dtype=src.dtype)
    return out.index_add_(0, seg, src)

def _pad(x, pw):
    flat = tuple((v for pair in reversed(pw) for v in pair))
    return torch.nn.functional.pad(x, flat)
kernel_name = 'recurrent_scan__memory_aug_recurrent_mem_tr__mixer_s_mlp__prompt'

def setup_inputs():

    _w = lambda a: (lambda t: t.to(torch.bfloat16) if t.is_floating_point() else t)(torch.as_tensor(a))

    def _A_setup():
        B, S, Dm = (1, 2048, 1024)
        H, Dh = (32, 128)
        M, seg = (8, 32)
        seg = min(seg, S)
        S = S // seg * seg
        return {'x': _w((lambda *s: torch.randn(*s, dtype=torch.bfloat16) * 0.05)(B, S, Dm)), 'mem0': _w((lambda *s: torch.randn(*s, dtype=torch.bfloat16) * 0.2)(B, M, Dm)), 'Wq': _w((lambda *s: torch.randn(*s, dtype=torch.bfloat16) * 1.6)(Dm, H, Dh) * Dm ** (-0.5)), 'Wk': _w((lambda *s: torch.randn(*s, dtype=torch.bfloat16) * 1.6)(Dm, H, Dh) * Dm ** (-0.5)), 'Wv': _w((lambda *s: torch.randn(*s, dtype=torch.bfloat16) * 0.2)(Dm, H, Dh) * Dm ** (-0.5)), 'Wo': _w((lambda *s: torch.randn(*s, dtype=torch.bfloat16) * 0.2)(H, Dh, Dm) * (H * Dh) ** (-0.5)), 'seg_len': seg}
    _A_in = _A_setup()

    def _B_setup():
        B, S, D, F = (1, 2048, 1024, 3584)
        return {'x': _w((lambda *s: torch.randn(*s, dtype=torch.bfloat16) * 0.05)(B, S, D)), 'w1': _w((lambda *s: torch.randn(*s, dtype=torch.bfloat16) * 3.2)(D, D) * D ** (-0.5)), 'w2': _w((lambda *s: torch.randn(*s, dtype=torch.bfloat16) * 3.2)(D, D) * D ** (-0.5)), 'w3': _w((lambda *s: torch.randn(*s, dtype=torch.bfloat16) * 3.2)(D, F) * D ** (-0.5)), 'w4': _w((lambda *s: torch.randn(*s, dtype=torch.bfloat16) * 3.2)(F, D) * F ** (-0.5))}
    _B_in = _B_setup()
    return {'A_x': _A_in['x'], 'A_mem0': _A_in['mem0'], 'A_Wq': _A_in['Wq'], 'A_Wk': _A_in['Wk'], 'A_Wv': _A_in['Wv'], 'A_Wo': _A_in['Wo'], 'A_seg_len': _A_in['seg_len'], 'B_x': _B_in['x'], 'B_w1': _B_in['w1'], 'B_w2': _B_in['w2'], 'B_w3': _B_in['w3'], 'B_w4': _B_in['w4']}

def reference(A_x, A_mem0, A_Wq, A_Wk, A_Wv, A_Wo, A_seg_len, B_x, B_w1, B_w2, B_w3, B_w4):

    def _A_ref(x, mem0, Wq, Wk, Wv, Wo, seg_len):
        B, S, Dm = x.shape
        H, Dh = (Wq.shape[1], Wq.shape[2])
        M = mem0.shape[1]
        scale = Dh ** (-0.5)
        n_seg = S // seg_len
        L = M + seg_len
        idx = torch.arange(L)
        mask = (idx[:, None] < M) | (idx[:, None] >= idx[None, :])
        mem = mem0
        outs = []
        for s in range(n_seg):
            xs = x[:, s * seg_len:(s + 1) * seg_len, :].clone()
            h = torch.concatenate([mem, xs], axis=1)
            q = torch.einsum('btd,dhe->bhte', h, Wq)
            k = torch.einsum('btd,dhe->bhte', h, Wk)
            v = torch.einsum('btd,dhe->bhte', h, Wv)
            scores = torch.einsum('bhqe,bhke->bhqk', q, k) * scale
            scores = torch.where(mask[None, None], scores, -1000000000.0)
            p = _softmax(scores, axis=-1)
            o = torch.einsum('bhqk,bhke->bhqe', p, v)
            o = torch.einsum('bhte,hed->btd', o, Wo)
            mem = o[:, :M, :].clone()
            outs.append(o[:, M:, :])
        return torch.concatenate(outs, axis=1)

    def _B_ref(x, w1, w2, w3, w4):
        B, S, D = x.shape
        h = _gelu(_layernorm(x, axis=-1) @ w1)
        c = D // 4
        g0 = _pad(h[:, :, 0 * c:1 * c], ((0, 0), (1, 0), (0, 0)))[:, :S, :]
        g1 = _pad(h[:, :, 1 * c:2 * c], ((0, 0), (0, 1), (0, 0)))[:, 1:, :]
        g2 = _pad(h[:, :, 2 * c:3 * c], ((0, 0), (2, 0), (0, 0)))[:, :S, :]
        g3 = _pad(h[:, :, 3 * c:], ((0, 0), (0, 2), (0, 0)))[:, 2:, :]
        hs = torch.concatenate([g0, g1, g2, g3], axis=-1) @ w2
        x1 = x + hs
        h2 = _gelu(_layernorm(x1, axis=-1) @ w3) @ w4
        return x1 + h2
    x = A_x
    xn = _layernorm(x, axis=-1)
    s = _A_ref(xn, A_mem0, A_Wq, A_Wk, A_Wv, A_Wo, A_seg_len)
    g = _silu(_B_ref(xn, B_w1, B_w2, B_w3, B_w4))
    return x + s * g
```

```cpp
#include <cuda_runtime.h>
#include <cuda_bf16.h>
#include <cuda.h>
#include <stdint.h>

typedef __nv_bfloat16 bf16;

namespace cfg {
constexpr int S = 2048;
constexpr int D = 1024;
constexpr int H = 32;
constexpr int DH = 128;
constexpr int HD = H * DH;
constexpr int M = 8;
constexpr int SEG = 32;
constexpr int NSEG = S / SEG;
constexpr int F = 3584;
}

__device__ __forceinline__ uint32_t smem_u32(const void* p) { return (uint32_t)__cvta_generic_to_shared(p); }

__device__ __forceinline__ void mbar_init(uint32_t bar, uint32_t count) {
  asm volatile("mbarrier.init.shared::cta.b64 [%0], %1;" ::"r"(bar), "r"(count) : "memory");
}
__device__ __forceinline__ void mbar_expect_tx(uint32_t bar, uint32_t bytes) {
  asm volatile("mbarrier.arrive.expect_tx.shared::cta.b64 _, [%0], %1;" ::"r"(bar), "r"(bytes) : "memory");
}
__device__ __forceinline__ void mbar_arrive(uint32_t bar) {
  asm volatile("mbarrier.arrive.shared::cta.b64 _, [%0];" ::"r"(bar) : "memory");
}
__device__ __forceinline__ bool mbar_try(uint32_t bar, uint32_t parity) {
  uint32_t done;
  asm volatile("{\n.reg .pred p;\nmbarrier.try_wait.parity.shared::cta.b64 p, [%1], %2, 20000;\nselp.u32 %0, 1, 0, p;\n}"
               : "=r"(done) : "r"(bar), "r"(parity) : "memory");
  return done != 0;
}
__device__ __forceinline__ bool mbar_try_nohint(uint32_t bar, uint32_t parity) {
  uint32_t done;
  asm volatile("{\n.reg .pred p;\nmbarrier.try_wait.parity.shared::cta.b64 p, [%1], %2;\nselp.u32 %0, 1, 0, p;\n}"
               : "=r"(done) : "r"(bar), "r"(parity) : "memory");
  return done != 0;
}
constexpr int MBAR_TRIES = 4096;
constexpr int POLL_TRIES = 1 << 16;
__device__ __forceinline__ void mbar_wait(uint32_t bar, uint32_t parity) {
#pragma unroll 1
  for (int n = 0; n < MBAR_TRIES; n++)
    if (mbar_try(bar, parity)) break;
}
__device__ __forceinline__ void mbar_wait_fast(uint32_t bar, uint32_t parity) {
#pragma unroll 1
  for (int n = 0; n < (POLL_TRIES << 4); n++)
    if (mbar_try_nohint(bar, parity)) break;
}
__device__ __forceinline__ void fence_barrier_init() { asm volatile("fence.mbarrier_init.release.cluster;" ::: "memory"); }
__device__ __forceinline__ void fence_proxy_async_smem() { asm volatile("fence.proxy.async.shared::cta;" ::: "memory"); }

__device__ __forceinline__ void tma_load_2d(uint32_t dst, const CUtensorMap* map, int x, int y, uint32_t bar) {
  asm volatile("cp.async.bulk.tensor.2d.shared::cluster.global.mbarrier::complete_tx::bytes [%0], [%1, {%3, %4}], [%2];"
               ::"r"(dst), "l"(map), "r"(bar), "r"(x), "r"(y) : "memory");
}
__device__ __forceinline__ void tma_load_3d(uint32_t dst, const CUtensorMap* map, int x, int y, int z, uint32_t bar) {
  asm volatile("cp.async.bulk.tensor.3d.shared::cluster.global.mbarrier::complete_tx::bytes [%0], [%1, {%3, %4, %5}], [%2];"
               ::"r"(dst), "l"(map), "r"(bar), "r"(x), "r"(y), "r"(z) : "memory");
}
__device__ __forceinline__ void tma_store_2d(const CUtensorMap* map, uint32_t src, int x, int y) {
  asm volatile("cp.async.bulk.tensor.2d.global.shared::cta.bulk_group [%0, {%2, %3}], [%1];"
               ::"l"(map), "r"(src), "r"(x), "r"(y) : "memory");
}
__device__ __forceinline__ void tma_store_commit() { asm volatile("cp.async.bulk.commit_group;" ::: "memory"); }
__device__ __forceinline__ void tma_store_wait_all() { asm volatile("cp.async.bulk.wait_group 0;" ::: "memory"); }
__device__ __forceinline__ void tma_store_wait_read() { asm volatile("cp.async.bulk.wait_group.read 0;" ::: "memory"); }
__device__ __forceinline__ void prefetch_tmap(const CUtensorMap* map) {
  asm volatile("prefetch.tensormap [%0];" ::"l"(map) : "memory");
}

__device__ __forceinline__ void wg_fence() { asm volatile("wgmma.fence.sync.aligned;" ::: "memory"); }
__device__ __forceinline__ void wg_commit() { asm volatile("wgmma.commit_group.sync.aligned;" ::: "memory"); }
template <int N> __device__ __forceinline__ void wg_wait() { asm volatile("wgmma.wait_group.sync.aligned %0;" ::"n"(N) : "memory"); }

#define named_bar_sync(id, n) asm volatile("bar.sync %0, %1;" ::"n"(id), "n"(n) : "memory")
#define named_bar_arrive(id, n) asm volatile("bar.arrive %0, %1;" ::"n"(id), "n"(n) : "memory")

__device__ __forceinline__ uint64_t make_desc(uint32_t addr, uint32_t lbo, uint32_t sbo) {
  return (uint64_t)((addr & 0x3FFFF) >> 4) | ((uint64_t)(lbo >> 4) << 16) | ((uint64_t)(sbo >> 4) << 32) | (1ull << 62);
}

__device__ __forceinline__ uint32_t pack_bf16(float lo, float hi) {
  uint32_t r;
  asm("cvt.rn.bf16x2.f32 %0, %1, %2;" : "=r"(r) : "f"(hi), "f"(lo));
  return r;
}
__device__ __forceinline__ float bf_lo(uint32_t v) { return __uint_as_float(v << 16); }
__device__ __forceinline__ float bf_hi(uint32_t v) { return __uint_as_float(v & 0xFFFF0000u); }
__device__ __forceinline__ float rbf(float v) { return __bfloat162float(__float2bfloat16_rn(v)); }

__device__ __forceinline__ void pdl_launch_dependents() { asm volatile("griddepcontrol.launch_dependents;" ::: "memory"); }
__device__ __forceinline__ void pdl_wait() { asm volatile("griddepcontrol.wait;" ::: "memory"); }

__device__ __forceinline__ float ex2_approx(float x) { float y; asm("ex2.approx.ftz.f32 %0, %1;" : "=f"(y) : "f"(x)); return y; }
__device__ __forceinline__ float rcp_approx(float x) { float y; asm("rcp.approx.ftz.f32 %0, %1;" : "=f"(y) : "f"(x)); return y; }

__device__ __forceinline__ void mul_sigmoid4(float (&v)[4], const float (&t)[4]) {
#pragma unroll
  for (int i = 0; i < 4; i += 2) {
    const float a = 1.0f + ex2_approx(fminf(t[i], 60.0f)), b = 1.0f + ex2_approx(fminf(t[i + 1], 60.0f));
    const float r = rcp_approx(a * b);
    v[i] *= b * r;
    v[i + 1] *= a * r;
  }
}
__device__ __forceinline__ void gelu4(float (&v)[4]) {
  float t[4];
#pragma unroll
  for (int i = 0; i < 4; i++) t[i] = v[i] * fmaf(v[i] * v[i], -0.10294324f, -2.30220819f);
  mul_sigmoid4(v, t);
}
__device__ __forceinline__ void silu4(float (&v)[4]) {
  float t[4];
#pragma unroll
  for (int i = 0; i < 4; i++) t[i] = v[i] * -1.4426950408889634f;
  mul_sigmoid4(v, t);
}

#define KT_START(id)
#define KT_END(id)

__device__ __forceinline__ void wgmma_ss_n128_tb(float (&d)[64], uint64_t da, uint64_t db, int scale_d) {
  asm volatile("{\n.reg .pred p;\nsetp.ne.b32 p, %66, 0;\n"
    "wgmma.mma_async.sync.aligned.m64n128k16.f32.bf16.bf16 "
    "{%0, %1, %2, %3, %4, %5, %6, %7, %8, %9, %10, %11, %12, %13, %14, %15, "
    "%16, %17, %18, %19, %20, %21, %22, %23, %24, %25, %26, %27, %28, %29, %30, %31, "
    "%32, %33, %34, %35, %36, %37, %38, %39, %40, %41, %42, %43, %44, %45, %46, %47, "
    "%48, %49, %50, %51, %52, %53, %54, %55, %56, %57, %58, %59, %60, %61, %62, %63}, "
    "%64, %65, p, 1, 1, 0, 1;\n}\n"
    : "+f"(d[0]), "+f"(d[1]), "+f"(d[2]), "+f"(d[3]), "+f"(d[4]), "+f"(d[5]), "+f"(d[6]), "+f"(d[7]),
      "+f"(d[8]), "+f"(d[9]), "+f"(d[10]), "+f"(d[11]), "+f"(d[12]), "+f"(d[13]), "+f"(d[14]), "+f"(d[15]),
      "+f"(d[16]), "+f"(d[17]), "+f"(d[18]), "+f"(d[19]), "+f"(d[20]), "+f"(d[21]), "+f"(d[22]), "+f"(d[23]),
      "+f"(d[24]), "+f"(d[25]), "+f"(d[26]), "+f"(d[27]), "+f"(d[28]), "+f"(d[29]), "+f"(d[30]), "+f"(d[31]),
      "+f"(d[32]), "+f"(d[33]), "+f"(d[34]), "+f"(d[35]), "+f"(d[36]), "+f"(d[37]), "+f"(d[38]), "+f"(d[39]),
      "+f"(d[40]), "+f"(d[41]), "+f"(d[42]), "+f"(d[43]), "+f"(d[44]), "+f"(d[45]), "+f"(d[46]), "+f"(d[47]),
      "+f"(d[48]), "+f"(d[49]), "+f"(d[50]), "+f"(d[51]), "+f"(d[52]), "+f"(d[53]), "+f"(d[54]), "+f"(d[55]),
      "+f"(d[56]), "+f"(d[57]), "+f"(d[58]), "+f"(d[59]), "+f"(d[60]), "+f"(d[61]), "+f"(d[62]), "+f"(d[63])
    : "l"(da), "l"(db), "r"(scale_d));
}
__device__ __forceinline__ void wgmma_ss_n224_tb(float (&d)[112], uint64_t da, uint64_t db, int scale_d) {
  asm volatile("{\n.reg .pred p;\nsetp.ne.b32 p, %114, 0;\n"
    "wgmma.mma_async.sync.aligned.m64n224k16.f32.bf16.bf16 "
    "{%0, %1, %2, %3, %4, %5, %6, %7, %8, %9, %10, %11, %12, %13, %14, %15, "
    "%16, %17, %18, %19, %20, %21, %22, %23, %24, %25, %26, %27, %28, %29, %30, %31, "
    "%32, %33, %34, %35, %36, %37, %38, %39, %40, %41, %42, %43, %44, %45, %46, %47, "
    "%48, %49, %50, %51, %52, %53, %54, %55, %56, %57, %58, %59, %60, %61, %62, %63, "
    "%64, %65, %66, %67, %68, %69, %70, %71, %72, %73, %74, %75, %76, %77, %78, %79, "
    "%80, %81, %82, %83, %84, %85, %86, %87, %88, %89, %90, %91, %92, %93, %94, %95, "
    "%96, %97, %98, %99, %100, %101, %102, %103, %104, %105, %106, %107, %108, %109, %110, %111}, "
    "%112, %113, p, 1, 1, 0, 1;\n}\n"
    : "+f"(d[0]), "+f"(d[1]), "+f"(d[2]), "+f"(d[3]), "+f"(d[4]), "+f"(d[5]), "+f"(d[6]), "+f"(d[7]),
      "+f"(d[8]), "+f"(d[9]), "+f"(d[10]), "+f"(d[11]), "+f"(d[12]), "+f"(d[13]), "+f"(d[14]), "+f"(d[15]),
      "+f"(d[16]), "+f"(d[17]), "+f"(d[18]), "+f"(d[19]), "+f"(d[20]), "+f"(d[21]), "+f"(d[22]), "+f"(d[23]),
      "+f"(d[24]), "+f"(d[25]), "+f"(d[26]), "+f"(d[27]), "+f"(d[28]), "+f"(d[29]), "+f"(d[30]), "+f"(d[31]),
      "+f"(d[32]), "+f"(d[33]), "+f"(d[34]), "+f"(d[35]), "+f"(d[36]), "+f"(d[37]), "+f"(d[38]), "+f"(d[39]),
      "+f"(d[40]), "+f"(d[41]), "+f"(d[42]), "+f"(d[43]), "+f"(d[44]), "+f"(d[45]), "+f"(d[46]), "+f"(d[47]),
      "+f"(d[48]), "+f"(d[49]), "+f"(d[50]), "+f"(d[51]), "+f"(d[52]), "+f"(d[53]), "+f"(d[54]), "+f"(d[55]),
      "+f"(d[56]), "+f"(d[57]), "+f"(d[58]), "+f"(d[59]), "+f"(d[60]), "+f"(d[61]), "+f"(d[62]), "+f"(d[63]),
      "+f"(d[64]), "+f"(d[65]), "+f"(d[66]), "+f"(d[67]), "+f"(d[68]), "+f"(d[69]), "+f"(d[70]), "+f"(d[71]),
      "+f"(d[72]), "+f"(d[73]), "+f"(d[74]), "+f"(d[75]), "+f"(d[76]), "+f"(d[77]), "+f"(d[78]), "+f"(d[79]),
      "+f"(d[80]), "+f"(d[81]), "+f"(d[82]), "+f"(d[83]), "+f"(d[84]), "+f"(d[85]), "+f"(d[86]), "+f"(d[87]),
      "+f"(d[88]), "+f"(d[89]), "+f"(d[90]), "+f"(d[91]), "+f"(d[92]), "+f"(d[93]), "+f"(d[94]), "+f"(d[95]),
      "+f"(d[96]), "+f"(d[97]), "+f"(d[98]), "+f"(d[99]), "+f"(d[100]), "+f"(d[101]), "+f"(d[102]), "+f"(d[103]),
      "+f"(d[104]), "+f"(d[105]), "+f"(d[106]), "+f"(d[107]), "+f"(d[108]), "+f"(d[109]), "+f"(d[110]), "+f"(d[111])
    : "l"(da), "l"(db), "r"(scale_d));
}
__device__ __forceinline__ void wgmma_ss_n256_tb(float (&d)[128], uint64_t da, uint64_t db, int scale_d) {
  asm volatile("{\n.reg .pred p;\nsetp.ne.b32 p, %130, 0;\n"
    "wgmma.mma_async.sync.aligned.m64n256k16.f32.bf16.bf16 "
    "{%0, %1, %2, %3, %4, %5, %6, %7, %8, %9, %10, %11, %12, %13, %14, %15, "
    "%16, %17, %18, %19, %20, %21, %22, %23, %24, %25, %26, %27, %28, %29, %30, %31, "
    "%32, %33, %34, %35, %36, %37, %38, %39, %40, %41, %42, %43, %44, %45, %46, %47, "
    "%48, %49, %50, %51, %52, %53, %54, %55, %56, %57, %58, %59, %60, %61, %62, %63, "
    "%64, %65, %66, %67, %68, %69, %70, %71, %72, %73, %74, %75, %76, %77, %78, %79, "
    "%80, %81, %82, %83, %84, %85, %86, %87, %88, %89, %90, %91, %92, %93, %94, %95, "
    "%96, %97, %98, %99, %100, %101, %102, %103, %104, %105, %106, %107, %108, %109, %110, %111, "
    "%112, %113, %114, %115, %116, %117, %118, %119, %120, %121, %122, %123, %124, %125, %126, %127}, "
    "%128, %129, p, 1, 1, 0, 1;\n}\n"
    : "+f"(d[0]), "+f"(d[1]), "+f"(d[2]), "+f"(d[3]), "+f"(d[4]), "+f"(d[5]), "+f"(d[6]), "+f"(d[7]),
      "+f"(d[8]), "+f"(d[9]), "+f"(d[10]), "+f"(d[11]), "+f"(d[12]), "+f"(d[13]), "+f"(d[14]), "+f"(d[15]),
      "+f"(d[16]), "+f"(d[17]), "+f"(d[18]), "+f"(d[19]), "+f"(d[20]), "+f"(d[21]), "+f"(d[22]), "+f"(d[23]),
      "+f"(d[24]), "+f"(d[25]), "+f"(d[26]), "+f"(d[27]), "+f"(d[28]), "+f"(d[29]), "+f"(d[30]), "+f"(d[31]),
      "+f"(d[32]), "+f"(d[33]), "+f"(d[34]), "+f"(d[35]), "+f"(d[36]), "+f"(d[37]), "+f"(d[38]), "+f"(d[39]),
      "+f"(d[40]), "+f"(d[41]), "+f"(d[42]), "+f"(d[43]), "+f"(d[44]), "+f"(d[45]), "+f"(d[46]), "+f"(d[47]),
      "+f"(d[48]), "+f"(d[49]), "+f"(d[50]), "+f"(d[51]), "+f"(d[52]), "+f"(d[53]), "+f"(d[54]), "+f"(d[55]),
      "+f"(d[56]), "+f"(d[57]), "+f"(d[58]), "+f"(d[59]), "+f"(d[60]), "+f"(d[61]), "+f"(d[62]), "+f"(d[63]),
      "+f"(d[64]), "+f"(d[65]), "+f"(d[66]), "+f"(d[67]), "+f"(d[68]), "+f"(d[69]), "+f"(d[70]), "+f"(d[71]),
      "+f"(d[72]), "+f"(d[73]), "+f"(d[74]), "+f"(d[75]), "+f"(d[76]), "+f"(d[77]), "+f"(d[78]), "+f"(d[79]),
      "+f"(d[80]), "+f"(d[81]), "+f"(d[82]), "+f"(d[83]), "+f"(d[84]), "+f"(d[85]), "+f"(d[86]), "+f"(d[87]),
      "+f"(d[88]), "+f"(d[89]), "+f"(d[90]), "+f"(d[91]), "+f"(d[92]), "+f"(d[93]), "+f"(d[94]), "+f"(d[95]),
      "+f"(d[96]), "+f"(d[97]), "+f"(d[98]), "+f"(d[99]), "+f"(d[100]), "+f"(d[101]), "+f"(d[102]), "+f"(d[103]),
      "+f"(d[104]), "+f"(d[105]), "+f"(d[106]), "+f"(d[107]), "+f"(d[108]), "+f"(d[109]), "+f"(d[110]), "+f"(d[111]),
      "+f"(d[112]), "+f"(d[113]), "+f"(d[114]), "+f"(d[115]), "+f"(d[116]), "+f"(d[117]), "+f"(d[118]), "+f"(d[119]),
      "+f"(d[120]), "+f"(d[121]), "+f"(d[122]), "+f"(d[123]), "+f"(d[124]), "+f"(d[125]), "+f"(d[126]), "+f"(d[127])
    : "l"(da), "l"(db), "r"(scale_d));
}
__device__ __forceinline__ void wgmma_rs_n32(float (&d)[16], const uint32_t* a, uint64_t db, int scale_d) {
  asm volatile("{\n.reg .pred p;\nsetp.ne.b32 p, %21, 0;\n"
    "wgmma.mma_async.sync.aligned.m64n32k16.f32.bf16.bf16 "
    "{%0, %1, %2, %3, %4, %5, %6, %7, %8, %9, %10, %11, %12, %13, %14, %15}, "
    "{%16, %17, %18, %19}, %20, p, 1, 1, 0;\n}\n"
    : "+f"(d[0]), "+f"(d[1]), "+f"(d[2]), "+f"(d[3]), "+f"(d[4]), "+f"(d[5]), "+f"(d[6]), "+f"(d[7]),
      "+f"(d[8]), "+f"(d[9]), "+f"(d[10]), "+f"(d[11]), "+f"(d[12]), "+f"(d[13]), "+f"(d[14]), "+f"(d[15])
    : "r"(a[0]), "r"(a[1]), "r"(a[2]), "r"(a[3]), "l"(db), "r"(scale_d));
}
__device__ __forceinline__ void wgmma_ss_n32_ta(float (&d)[16], uint64_t da, uint64_t db, int scale_d) {
  asm volatile("{\n.reg .pred p;\nsetp.ne.b32 p, %18, 0;\n"
    "wgmma.mma_async.sync.aligned.m64n32k16.f32.bf16.bf16 "
    "{%0, %1, %2, %3, %4, %5, %6, %7, %8, %9, %10, %11, %12, %13, %14, %15}, "
    "%16, %17, p, 1, 1, 1, 0;\n}\n"
    : "+f"(d[0]), "+f"(d[1]), "+f"(d[2]), "+f"(d[3]), "+f"(d[4]), "+f"(d[5]), "+f"(d[6]), "+f"(d[7]),
      "+f"(d[8]), "+f"(d[9]), "+f"(d[10]), "+f"(d[11]), "+f"(d[12]), "+f"(d[13]), "+f"(d[14]), "+f"(d[15])
    : "l"(da), "l"(db), "r"(scale_d));
}

#define gwait mbar_wait_fast
enum { EPI_PLAIN = 0, EPI_GELU = 1, EPI_RES = 2, EPI_RES_SILU = 3, EPI_FINAL = 4 };

template <int BN> struct WgAcc;
template <> struct WgAcc<128> { static __device__ __forceinline__ void mma(float (&d)[64], uint64_t a, uint64_t b, int s) { wgmma_ss_n128_tb(d, a, b, s); } };
template <> struct WgAcc<224> { static __device__ __forceinline__ void mma(float (&d)[112], uint64_t a, uint64_t b, int s) { wgmma_ss_n224_tb(d, a, b, s); } };
template <> struct WgAcc<256> { static __device__ __forceinline__ void mma(float (&d)[128], uint64_t a, uint64_t b, int s) { wgmma_ss_n256_tb(d, a, b, s); } };

template <int BN, int STAGES, int EPI, bool ALIAS>
struct GemmCfg {
  static constexpr int NBOX = (BN + 63) / 64;
  static constexpr int A_BYTES = 128 * 128;
  static constexpr int B_BYTES = NBOX * 64 * 128;
  static constexpr int STAGE_BYTES = A_BYTES + B_BYTES;
  static constexpr int NRES = (EPI == EPI_FINAL) ? 2 : (EPI == EPI_RES || EPI == EPI_RES_SILU) ? 1 : 0;
  static constexpr int TILE_BYTES = NBOX * 128 * 128;
  static constexpr int SMEM = STAGES * STAGE_BYTES + (ALIAS ? 0 : NRES * TILE_BYTES) + 1024 + 256;
  static __device__ __forceinline__ constexpr uint32_t piece(int p) {
    return ALIAS ? (p / 3) * STAGE_BYTES + (p % 3) * 16384 : STAGES * STAGE_BYTES + p * 16384;
  }
};

#define GPROF(i)
__device__ unsigned g_gflag[64];

__device__ __forceinline__ void tma_load_2d_mc(uint32_t dst, const CUtensorMap* map, int x, int y, uint32_t bar) {
  asm volatile("cp.async.bulk.tensor.2d.shared::cluster.global.mbarrier::complete_tx::bytes.multicast::cluster "
               "[%0], [%1, {%3, %4}], [%2], %5;"
               ::"r"(dst), "l"(map), "r"(bar), "r"(x), "r"(y), "h"((uint16_t)3) : "memory");
}
__device__ __forceinline__ void mbar_arrive_cluster(uint32_t bar, uint32_t cta) {
  asm volatile("{\n.reg .b32 r;\nmapa.shared::cluster.u32 r, %0, %1;\nmbarrier.arrive.shared::cluster.b64 _, [r];\n}"
               ::"r"(bar), "r"(cta) : "memory");
}
__device__ __forceinline__ void cluster_sync() {
  asm volatile("barrier.cluster.arrive.release.aligned;\nbarrier.cluster.wait.acquire.aligned;" ::: "memory");
}

template <int BN, int STAGES, int EPI, bool SHIFT_A, bool ALIAS, int FLAG>
__device__ __forceinline__ void gemm_body(const CUtensorMap* tmA, const CUtensorMap* tmB, const CUtensorMap* tmC,
                                          const CUtensorMap* tmC2, const CUtensorMap* tmR0, const CUtensorMap* tmR1,
                                          int K, int mt, int nt, unsigned* gflag) {
  using C = GemmCfg<BN, STAGES, EPI, ALIAS>;
  extern __shared__ uint8_t smem_raw[];
  const uint32_t base = (smem_u32(smem_raw) + 1023u) & ~1023u;
  const uint32_t bar_base = base + STAGES * C::STAGE_BYTES + (ALIAS ? 0 : C::NRES * C::TILE_BYTES);
  auto full = [&](int s) { return bar_base + 8 * s; };
  auto empty = [&](int s) { return bar_base + 8 * (STAGES + s); };
  const uint32_t res_bar = bar_base + 8 * 2 * STAGES;

  const int tid = threadIdx.x, warp = tid >> 5, lane = tid & 31;
  const int rank = blockIdx.x & 1;
  const int n0 = nt * BN, m0 = mt * 128;
  const int nkb = K >> 6;

  GPROF(0);
  KT_START(EPI == EPI_RES ? 3 : EPI == EPI_GELU ? 5 : EPI == EPI_RES_SILU ? 6 : 7);
  if (tid == 0) {
    for (int s = 0; s < STAGES; s++) { mbar_init(full(s), 1); mbar_init(empty(s), 4); }
    mbar_init(res_bar, 1);
    fence_barrier_init();
  }
  __syncthreads();
  cluster_sync();
  pdl_launch_dependents();

  if (warp == 8) {
    if (lane == 0) {
      prefetch_tmap(tmA); prefetch_tmap(tmB); prefetch_tmap(tmC);
      pdl_wait();
      auto load_piece = [&](int p) {
        const CUtensorMap* m = p < C::NBOX ? tmR0 : tmR1;
        const int col = n0 + (p % C::NBOX) * 64;
        tma_load_2d(base + C::piece(p), m, col, m0, res_bar);
        tma_load_2d(base + C::piece(p) + 8192, m, col, m0 + 64, res_bar);
      };
      for (int kb = 0; kb < nkb; kb++) {
        const int s = kb % STAGES;
        if (kb >= STAGES) gwait(empty(s), ((kb / STAGES) - 1) & 1);
        const uint32_t sa = base + s * C::STAGE_BYTES, sb = sa + C::A_BYTES;
        mbar_expect_tx(full(s), C::STAGE_BYTES);
        int arow = m0;
        if (SHIFT_A) { const int q = kb >> 2; arow += (q == 0) ? -1 : (q == 1) ? 1 : (q == 2) ? -2 : 2; }
        tma_load_2d(sa, tmA, kb * 64, arow, full(s));
#pragma unroll
        for (int j = 0; j < C::NBOX / 2; j++) {
          const int jj = rank * (C::NBOX / 2) + j;
          tma_load_2d_mc(sb + jj * 8192, tmB, n0 + jj * 64, kb * 64, full(s));
        }
        if (C::NRES > 0 && !ALIAS && kb == STAGES - 1) {
          mbar_expect_tx(res_bar, C::NRES * C::TILE_BYTES);
#pragma unroll
          for (int p = 0; p < C::NRES * C::NBOX; p++) load_piece(p);
        }
      }
      if (C::NRES > 0 && ALIAS) {
        mbar_expect_tx(res_bar, C::NRES * C::TILE_BYTES);
#pragma unroll
        for (int p = 0; p < C::NRES * C::NBOX; p++) {
          if (p % 3 == 0) gwait(empty(p / 3), ((nkb / STAGES) - 1) & 1);
          if (FLAG == 2 && p == C::NBOX) {
#pragma unroll 1
            for (int tries = 0; tries < (POLL_TRIES << 4); tries++) {
              unsigned v;
              asm volatile("ld.acquire.gpu.global.u32 %0, [%1];" : "=r"(v) : "l"(gflag) : "memory");
              if (v >= 2) break;
            }
            asm volatile("fence.proxy.async;" ::: "memory");
          }
          load_piece(p);
        }
      }
    }
  } else {
    const int wg = warp >> 2;
    float acc[BN / 2];
    pdl_wait();
    for (int kb = 0; kb < nkb; kb++) {
      const int s = kb % STAGES;
      gwait(full(s), (kb / STAGES) & 1);
      if (kb == 0) GPROF(1);
      const uint32_t sa = base + s * C::STAGE_BYTES + wg * 8192, sb = base + s * C::STAGE_BYTES + C::A_BYTES;
      wg_fence();
#pragma unroll
      for (int k = 0; k < 4; k++)
        WgAcc<BN>::mma(acc, make_desc(sa + k * 32, 16, 1024), make_desc(sb + k * 2048, 8192, 1024), (kb | k) != 0);
      wg_commit();
      if (kb > 0) {
        wg_wait<1>();
        if ((tid & 127) < 2) mbar_arrive_cluster(empty((kb - 1) % STAGES), tid & 1);
      }
    }
    wg_wait<0>();
    GPROF(2);
    GPROF(3);
    if (C::NRES > 0) gwait(res_bar, 0);
    else named_bar_sync(1, 256);
    const int r0 = wg * 64 + (warp & 3) * 16 + (lane >> 2);
    const int q = lane & 3;
#pragma unroll
    for (int box = 0; box < C::NBOX; box++) {
      constexpr int NB = C::NBOX;
      const bool half = (BN % 64 != 0) && box == NB - 1;
      const uint32_t pbase = base + (C::NRES > 0 ? C::piece(box) : box * 16384);
#pragma unroll
      for (int grp = 0; grp < (half ? 1 : 2); grp++) {
        uint32_t off[4][2], ra[4][2], rb[4][2];
#pragma unroll
        for (int jj = 0; jj < 4; jj++)
#pragma unroll
          for (int h = 0; h < 2; h++) {
            const int r = r0 + h * 8, unit = grp * 4 + jj;
            off[jj][h] = half ? pbase + r * 64 + ((unit ^ ((r >> 1) & 3)) << 4) + q * 4
                              : pbase + r * 128 + ((unit ^ (r & 7)) << 4) + q * 4;
            if (C::NRES > 0) asm volatile("ld.shared.u32 %0, [%1];" : "=r"(ra[jj][h]) : "r"(off[jj][h]));
            if (C::NRES > 1)
              asm volatile("ld.shared.u32 %0, [%1];" : "=r"(rb[jj][h]) : "r"(off[jj][h] + (C::piece(NB + box) - C::piece(box))));
          }
#pragma unroll
        for (int jj = 0; jj < 4; jj++) {
          const int j = box * 8 + grp * 4 + jj;
          const uint32_t s0 = pack_bf16(acc[j * 4], acc[j * 4 + 1]), s1 = pack_bf16(acc[j * 4 + 2], acc[j * 4 + 3]);
          float v[4] = {bf_lo(s0), bf_hi(s0), bf_lo(s1), bf_hi(s1)};
          if (EPI == EPI_GELU) gelu4(v);
          if (EPI == EPI_RES || EPI == EPI_RES_SILU) {
            v[0] += bf_lo(ra[jj][0]); v[1] += bf_hi(ra[jj][0]); v[2] += bf_lo(ra[jj][1]); v[3] += bf_hi(ra[jj][1]);
            if (EPI == EPI_RES_SILU) {
              const uint32_t y0 = pack_bf16(v[0], v[1]), y1 = pack_bf16(v[2], v[3]);
              v[0] = bf_lo(y0); v[1] = bf_hi(y0); v[2] = bf_lo(y1); v[3] = bf_hi(y1);
              silu4(v);
            }
          }
          if (EPI == EPI_FINAL) {
#pragma unroll
            for (int h = 0; h < 2; h++) {
              const uint32_t t = pack_bf16(v[2 * h] * bf_lo(rb[jj][h]), v[2 * h + 1] * bf_hi(rb[jj][h]));
              v[2 * h] = bf_lo(ra[jj][h]) + bf_lo(t);
              v[2 * h + 1] = bf_hi(ra[jj][h]) + bf_hi(t);
            }
          }
          asm volatile("st.shared.u32 [%0], %1;" ::"r"(off[jj][0]), "r"(pack_bf16(v[0], v[1])) : "memory");
          asm volatile("st.shared.u32 [%0], %1;" ::"r"(off[jj][1]), "r"(pack_bf16(v[2], v[3])) : "memory");
        }
      }
      fence_proxy_async_smem();
      if (wg == 0) named_bar_sync(2, 128); else named_bar_sync(3, 128);
      if ((tid & 127) == 0) {
        if (half) tma_store_2d(tmC2, pbase + wg * 4096, n0 + box * 64, m0 + wg * 64);
        else tma_store_2d(tmC, pbase + wg * 8192, n0 + box * 64, m0 + wg * 64);
        tma_store_commit();
      }
    }
    GPROF(4);
    if ((tid & 127) == 0) {
      if (FLAG == 1) {
        tma_store_wait_all();
        asm volatile("fence.proxy.async;" ::: "memory");
        asm volatile("red.release.gpu.global.add.u32 [%0], 1;" ::"l"(gflag) : "memory");
      } else {
        tma_store_wait_read();
      }
    }
  }
  GPROF(5);
  KT_END(EPI == EPI_RES ? 3 : EPI == EPI_GELU ? 5 : EPI == EPI_RES_SILU ? 6 : 7);
  __syncwarp();
  cluster_sync();
}

template <int BN, int STAGES, int EPI, bool SHIFT_A>
__global__ void __launch_bounds__(288, 1)
gemm_kernel(const __grid_constant__ CUtensorMap tmA, const __grid_constant__ CUtensorMap tmB,
            const __grid_constant__ CUtensorMap tmC, const __grid_constant__ CUtensorMap tmX, int K, int tiles_n) {
  const int pair = blockIdx.x >> 1;
  gemm_body<BN, STAGES, EPI, SHIFT_A, false, 0>(&tmA, &tmB, &tmC, &tmX, &tmX, &tmX, K, (pair / tiles_n) * 2 + (blockIdx.x & 1),
                                               pair % tiles_n, nullptr);
}

__global__ void __launch_bounds__(288, 1)
gemm_gate_out_kernel(const __grid_constant__ CUtensorMap tmU, const __grid_constant__ CUtensorMap tmW4,
                     const __grid_constant__ CUtensorMap tmG, const __grid_constant__ CUtensorMap tmX1,
                     const __grid_constant__ CUtensorMap tmO, const __grid_constant__ CUtensorMap tmWo,
                     const __grid_constant__ CUtensorMap tmOut, const __grid_constant__ CUtensorMap tmX) {
  const int cl = blockIdx.x >> 1, pair = cl & 31;
  const int mt = (pair >> 2) * 2 + (blockIdx.x & 1), nt = pair & 3;
  unsigned* flag = &g_gflag[mt * 4 + nt];
  if (cl < 32) gemm_body<256, 4, EPI_RES_SILU, false, true, 1>(&tmU, &tmW4, &tmG, &tmG, &tmX1, &tmX1, cfg::F, mt, nt, flag);
  else gemm_body<256, 4, EPI_FINAL, false, true, 2>(&tmO, &tmWo, &tmOut, &tmOut, &tmX, &tmG, cfg::HD, mt, nt, flag);
}

constexpr int BG_STAGES = 5, BG_SMEM = BG_STAGES * 32768 + 32768 + 1024 + 256;
__global__ void __launch_bounds__(288, 1)
gemm_bg_gelu_kernel(const __grid_constant__ CUtensorMap tmA, const __grid_constant__ CUtensorMap tmB,
                    const __grid_constant__ CUtensorMap tmC, int nkb, int tiles_n, int ntiles) {
  extern __shared__ uint8_t smem_raw[];
  const uint32_t base = (smem_u32(smem_raw) + 1023u) & ~1023u;
  const uint32_t stg = base + BG_STAGES * 32768, bar_base = stg + 32768;
  auto full = [&](int s) { return bar_base + 8 * s; };
  auto empty = [&](int s) { return bar_base + 8 * (BG_STAGES + s); };
  const int tid = threadIdx.x, warp = tid >> 5, lane = tid & 31;
  KT_START(2);
  if (tid == 0) {
    for (int s = 0; s < BG_STAGES; s++) { mbar_init(full(s), 1); mbar_init(empty(s), 2); }
    fence_barrier_init();
  }
  __syncthreads();
  if (warp == 8) {
    if (lane == 0) {
      int it = 0;
      for (int t = blockIdx.x; t < ntiles; t += gridDim.x) {
        const int n0 = (t % tiles_n) * 128, m0 = (t / tiles_n) * 128;
        for (int kb = 0; kb < nkb; kb++, it++) {
          const int s = it % BG_STAGES;
          if (it >= BG_STAGES) mbar_wait(empty(s), ((it / BG_STAGES) - 1) & 1);
          const uint32_t sa = base + s * 32768;
          mbar_expect_tx(full(s), 32768);
          tma_load_2d(sa, &tmA, kb * 64, m0, full(s));
          tma_load_2d(sa + 16384, &tmB, n0, kb * 64, full(s));
          tma_load_2d(sa + 24576, &tmB, n0 + 64, kb * 64, full(s));
        }
      }
    }
    return;
  }
  const int wg = warp >> 2;
  const int r0 = wg * 64 + (warp & 3) * 16 + (lane >> 2), q = lane & 3;
  int it = 0;
  for (int t = blockIdx.x; t < ntiles; t += gridDim.x) {
    const int n0 = (t % tiles_n) * 128, m0 = (t / tiles_n) * 128;
    float acc[64];
    for (int kb = 0; kb < nkb; kb++, it++) {
      const int s = it % BG_STAGES;
      mbar_wait(full(s), (it / BG_STAGES) & 1);
      const uint32_t sa = base + s * 32768 + wg * 8192, sb = base + s * 32768 + 16384;
      wg_fence();
#pragma unroll
      for (int k = 0; k < 4; k++)
        wgmma_ss_n128_tb(acc, make_desc(sa + k * 32, 16, 1024), make_desc(sb + k * 2048, 8192, 1024), (kb | k) != 0);
      wg_commit();
      if (kb > 0) {
        wg_wait<1>();
        if ((tid & 127) == 0) mbar_arrive(empty((it - 1) % BG_STAGES));
      }
    }
    wg_wait<0>();
    if ((tid & 127) == 0) {
      mbar_arrive(empty((it - 1) % BG_STAGES));
      tma_store_wait_read();
    }
    if (wg == 0) named_bar_sync(2, 128); else named_bar_sync(3, 128);
#pragma unroll
    for (int j = 0; j < 16; j++) {
      const uint32_t s0 = pack_bf16(acc[j * 4], acc[j * 4 + 1]), s1 = pack_bf16(acc[j * 4 + 2], acc[j * 4 + 3]);
      float v[4] = {bf_lo(s0), bf_hi(s0), bf_lo(s1), bf_hi(s1)};
      gelu4(v);
#pragma unroll
      for (int h = 0; h < 2; h++) {
        const int r = r0 + h * 8;
        asm volatile("st.shared.u32 [%0], %1;" ::"r"(stg + (j >> 3) * 16384 + r * 128 + (((j & 7) ^ (r & 7)) << 4) + q * 4),
                     "r"(pack_bf16(v[2 * h], v[2 * h + 1])) : "memory");
      }
    }
    fence_proxy_async_smem();
    if (wg == 0) named_bar_sync(2, 128); else named_bar_sync(3, 128);
    if ((tid & 127) == 0) {
      tma_store_2d(&tmC, stg + wg * 8192, n0, m0 + wg * 64);
      tma_store_2d(&tmC, stg + 16384 + wg * 8192, n0 + 64, m0 + wg * 64);
      tma_store_commit();
    }
  }
  if ((tid & 127) == 0) tma_store_wait_read();
  KT_END(2);
}

__device__ __forceinline__ float warp_sum(float v) {
#pragma unroll
  for (int o = 16; o > 0; o >>= 1) v += __shfl_xor_sync(0xffffffffu, v, o);
  return v;
}
__device__ __forceinline__ void ln_row(float (&v)[32]) {
  float s = 0.f;
#pragma unroll
  for (int i = 0; i < 32; i++) s += v[i];
  const float mean = warp_sum(s) * (1.0f / 1024.0f);
  float q = 0.f;
#pragma unroll
  for (int i = 0; i < 32; i++) { const float d = v[i] - mean; q += d * d; }
  const float var = warp_sum(q) * (1.0f / 1024.0f);
  const float mb = rbf(mean);
  const float sd = rbf(sqrtf(rbf(rbf(var) + 1e-5f)));
  const float inv = __fdiv_rn(1.0f, sd);
#pragma unroll
  for (int i = 0; i < 32; i += 2) {
    const uint32_t d = pack_bf16(v[i] - mb, v[i + 1] - mb);
    const uint32_t y = pack_bf16(bf_lo(d) * inv, bf_hi(d) * inv);
    v[i] = bf_lo(y); v[i + 1] = bf_hi(y);
  }
}
__device__ __forceinline__ void load_row(const bf16* p, int lane, float (&v)[32]) {
#pragma unroll
  for (int j = 0; j < 4; j++) {
    const uint4 u = *reinterpret_cast<const uint4*>(p + j * 256 + lane * 8);
    v[j * 8 + 0] = bf_lo(u.x); v[j * 8 + 1] = bf_hi(u.x); v[j * 8 + 2] = bf_lo(u.y); v[j * 8 + 3] = bf_hi(u.y);
    v[j * 8 + 4] = bf_lo(u.z); v[j * 8 + 5] = bf_hi(u.z); v[j * 8 + 6] = bf_lo(u.w); v[j * 8 + 7] = bf_hi(u.w);
  }
}
__device__ __forceinline__ void store_row(bf16* p, int lane, const float (&v)[32]) {
#pragma unroll
  for (int j = 0; j < 4; j++) {
    uint4 u;
    u.x = pack_bf16(v[j * 8 + 0], v[j * 8 + 1]); u.y = pack_bf16(v[j * 8 + 2], v[j * 8 + 3]);
    u.z = pack_bf16(v[j * 8 + 4], v[j * 8 + 5]); u.w = pack_bf16(v[j * 8 + 6], v[j * 8 + 7]);
    *reinterpret_cast<uint4*>(p + j * 256 + lane * 8) = u;
  }
}
__device__ void reset_exchange(int gtid, int nthreads);
template <bool TWICE>
__global__ void __launch_bounds__(256) ln_kernel(const bf16* __restrict__ x, bf16* __restrict__ y1, bf16* __restrict__ y2) {
  const int row = blockIdx.x * 8 + (threadIdx.x >> 5), lane = threadIdx.x & 31;
  KT_START(TWICE ? 0 : 4);
  pdl_launch_dependents();
  pdl_wait();
  if (TWICE) reset_exchange(blockIdx.x * 256 + threadIdx.x, gridDim.x * 256);
  float v[32];
  load_row(x + (size_t)row * cfg::D, lane, v);
  ln_row(v);
  store_row(y1 + (size_t)row * cfg::D, lane, v);
  if (TWICE) {
    ln_row(v);
    store_row(y2 + (size_t)row * cfg::D, lane, v);
  }
  KT_END(TWICE ? 0 : 4);
}

namespace fk {
constexpr uint32_t SM0 = 1024;
constexpr uint32_t WO = SM0, WS = WO + 90112, XN = WS + 65536, VX = XN + 49152, QK = VX + 8192, PT = QK + 8192,
                   SP = PT + 4096, VM = SP + 2560, OB = VM + 2048, BAR = OB + 2048;
constexpr uint32_t MEMB = XN + 16384, RED = XN + 32768, VX2 = WO + 81920;
constexpr int SMEM = 232448;
static_assert(BAR + 512 == SM0 + SMEM, "shared memory layout");
constexpr uint32_t B_XN = BAR, B_H2 = BAR + 448, B_PF = BAR + 16, B_SM = BAR + 32, B_VM = BAR + 40, B_VX = BAR + 48, B_ST = BAR + 56, B_PB = BAR + 64, B_W = BAR + 112,
                   MASKS = BAR + 128, PROBE = BAR + 384;
constexpr int NB_M0 = 1, NB_M1 = 2, NB_C = 3, NB_O = 4, NB_ST = 5, NB_DU = 6, NB_CF = 7, NB_W1 = 8, NB_XE = 9, NB_HD = 10, NB_PZ = 11, NB_O0 = 12;
#define D_H1 850
#define D_H2 1750
#define D_ST 100
#define SCQ 2
#define FLAGS 0
#define D_F 0
#define D_FS 70
#define NS0 4
#define NTA0 2
#define NTA1 2
#define PF0A 3
#define PF0 10
#define PF1A 9
#define PF1 11
#define PAUSE 1
#define PROBE_N 6
#define PROBE_FAST 0
#define SPACK 0
constexpr uint32_t SPW = SPACK ? 4 : 8, SP_SRC = 160 * SPW;
constexpr int H1_BYTES = 64 * 32768, H2_BYTES = 8 * 8192, FL_OFF = H1_BYTES + H2_BYTES, FL_BYTES = 8192;
}

#define PROF(wg, i)
#define PROF2(i)
#define RETRY(i)
#define GTSYNC(i)

__device__ uint4 g_xch[(fk::H1_BYTES + fk::H2_BYTES + fk::FL_BYTES + 8192) / 16];
__device__ unsigned g_mask[64];
__device__ unsigned g_oflag[16];

#define LD_POLL "ld.global.L1::no_allocate"
__device__ __forceinline__ uint4 ld_poll16(const void* p) {
  uint4 v;
  asm volatile(LD_POLL ".v4.u32 {%0,%1,%2,%3}, [%4];" : "=r"(v.x), "=r"(v.y), "=r"(v.z), "=r"(v.w) : "l"(p) : "memory");
  return v;
}
__device__ __forceinline__ uint2 ld_poll8(const void* p) {
  uint2 v;
  asm volatile(LD_POLL ".v2.u32 {%0,%1}, [%2];" : "=r"(v.x), "=r"(v.y) : "l"(p) : "memory");
  return v;
}
__device__ __forceinline__ uint4 ld_strong16(const void* p) {
  uint4 v;
  asm volatile("ld.relaxed.gpu.global.v4.u32 {%0,%1,%2,%3}, [%4];" : "=r"(v.x), "=r"(v.y), "=r"(v.z), "=r"(v.w) : "l"(p) : "memory");
  return v;
}
__device__ __forceinline__ uint2 ld_strong8(const void* p) {
  uint2 v;
  asm volatile("ld.relaxed.gpu.global.v2.u32 {%0,%1}, [%2];" : "=r"(v.x), "=r"(v.y) : "l"(p) : "memory");
  return v;
}
__device__ __forceinline__ void st_pub32(void* p, uint32_t v) { asm volatile("st.relaxed.gpu.global.u32 [%0], %1;" ::"l"(p), "r"(v) : "memory"); }
__device__ __forceinline__ void st_pub16(void* p, uint32_t v) {
  asm volatile("st.relaxed.gpu.global.u16 [%0], %1;" ::"l"(p), "h"((uint16_t)v) : "memory");
}
__device__ __forceinline__ uint32_t ld_strong4(const void* p) {
  uint32_t v;
  asm volatile("ld.relaxed.gpu.global.u32 %0, [%1];" : "=r"(v) : "l"(p) : "memory");
  return v;
}
__device__ __forceinline__ void st_pub64(void* p, uint32_t a, uint32_t b) {
  asm volatile("st.relaxed.gpu.global.v2.u32 [%0], {%1,%2};" ::"l"(p), "r"(a), "r"(b) : "memory");
}
__device__ __forceinline__ void st_pub128(void* p, uint32_t a) {
  asm volatile("st.relaxed.gpu.global.v4.u32 [%0], {%1,%1,%1,%1};" ::"l"(p), "r"(a) : "memory");
}
constexpr uint32_t EMPTY = 0xFFFFFFFFu;
__device__ __forceinline__ uint32_t umax4(const uint4& v) { return max(max(v.x, v.y), max(v.z, v.w)); }
__device__ __forceinline__ void sts128(uint32_t a, uint32_t x, uint32_t y, uint32_t z, uint32_t w) {
  asm volatile("st.shared.v4.u32 [%0], {%1,%2,%3,%4};" ::"r"(a), "r"(x), "r"(y), "r"(z), "r"(w) : "memory");
}
__device__ __forceinline__ void sts64(uint32_t a, uint32_t x, uint32_t y) {
  asm volatile("st.shared.v2.u32 [%0], {%1,%2};" ::"r"(a), "r"(x), "r"(y) : "memory");
}
__device__ __forceinline__ void sts32(uint32_t a, uint32_t x) { asm volatile("st.shared.u32 [%0], %1;" ::"r"(a), "r"(x) : "memory"); }
__device__ __forceinline__ void sts128f(uint32_t a, float x, float y, float z, float w) {
  asm volatile("st.shared.v4.f32 [%0], {%1,%2,%3,%4};" ::"r"(a), "f"(x), "f"(y), "f"(z), "f"(w) : "memory");
}
__device__ __forceinline__ void sts64f(uint32_t a, float x, float y) {
  asm volatile("st.shared.v2.f32 [%0], {%1,%2};" ::"r"(a), "f"(x), "f"(y) : "memory");
}
__device__ __forceinline__ float4 lds128f(uint32_t a) {
  float4 v;
  asm volatile("ld.shared.v4.f32 {%0,%1,%2,%3}, [%4];" : "=f"(v.x), "=f"(v.y), "=f"(v.z), "=f"(v.w) : "r"(a) : "memory");
  return v;
}
__device__ __forceinline__ float2 lds64f(uint32_t a) {
  float2 v;
  asm volatile("ld.shared.v2.f32 {%0,%1}, [%2];" : "=f"(v.x), "=f"(v.y) : "r"(a) : "memory");
  return v;
}
__device__ __forceinline__ void lds128(uint32_t* r, uint32_t a) {
  asm volatile("ld.shared.v4.u32 {%0,%1,%2,%3}, [%4];" : "=r"(r[0]), "=r"(r[1]), "=r"(r[2]), "=r"(r[3]) : "r"(a) : "memory");
}
__device__ __forceinline__ void lds64(uint32_t* r, uint32_t a) {
  asm volatile("ld.shared.v2.u32 {%0,%1}, [%2];" : "=r"(r[0]), "=r"(r[1]) : "r"(a) : "memory");
}
__device__ __forceinline__ uint32_t lds32(uint32_t a) {
  uint32_t v;
  asm volatile("ld.shared.u32 %0, [%1];" : "=r"(v) : "r"(a) : "memory");
  return v;
}
__device__ __forceinline__ void ldsm4(uint32_t* r, uint32_t a) {
  asm volatile("ldmatrix.sync.aligned.m8n8.x4.shared.b16 {%0,%1,%2,%3}, [%4];"
               : "=r"(r[0]), "=r"(r[1]), "=r"(r[2]), "=r"(r[3]) : "r"(a) : "memory");
}
__device__ __forceinline__ void ldsm4t(uint32_t* r, uint32_t a) {
  asm volatile("ldmatrix.sync.aligned.m8n8.x4.trans.shared.b16 {%0,%1,%2,%3}, [%4];"
               : "=r"(r[0]), "=r"(r[1]), "=r"(r[2]), "=r"(r[3]) : "r"(a) : "memory");
}
__device__ __forceinline__ void stsm4(uint32_t a, uint32_t r0, uint32_t r1, uint32_t r2, uint32_t r3) {
  asm volatile("stmatrix.sync.aligned.m8n8.x4.shared.b16 [%0], {%1,%2,%3,%4};"
               ::"r"(a), "r"(r0), "r"(r1), "r"(r2), "r"(r3) : "memory");
}
__device__ __forceinline__ void stsm4t(uint32_t a, uint32_t r0, uint32_t r1, uint32_t r2, uint32_t r3) {
  asm volatile("stmatrix.sync.aligned.m8n8.x4.trans.shared.b16 [%0], {%1,%2,%3,%4};"
               ::"r"(a), "r"(r0), "r"(r1), "r"(r2), "r"(r3) : "memory");
}
__device__ __forceinline__ void mma16816(float* d, const uint32_t* a, uint32_t b0, uint32_t b1) {
  asm volatile("mma.sync.aligned.m16n8k16.row.col.f32.bf16.bf16.f32 {%0,%1,%2,%3}, {%4,%5,%6,%7}, {%8,%9}, {%0,%1,%2,%3};"
               : "+f"(d[0]), "+f"(d[1]), "+f"(d[2]), "+f"(d[3])
               : "r"(a[0]), "r"(a[1]), "r"(a[2]), "r"(a[3]), "r"(b0), "r"(b1));
}
__device__ __forceinline__ void mma16816z(float* d, const uint32_t* a, uint32_t b0, uint32_t b1) {
  asm volatile("mma.sync.aligned.m16n8k16.row.col.f32.bf16.bf16.f32 {%0,%1,%2,%3}, {%4,%5,%6,%7}, {%8,%9}, {%10,%10,%10,%10};"
               : "=f"(d[0]), "=f"(d[1]), "=f"(d[2]), "=f"(d[3])
               : "r"(a[0]), "r"(a[1]), "r"(a[2]), "r"(a[3]), "r"(b0), "r"(b1), "f"(0.f));
}
__device__ __forceinline__ void mma1688(float* d, uint32_t a0, uint32_t a1, uint32_t b0) {
  asm volatile("mma.sync.aligned.m16n8k8.row.col.f32.bf16.bf16.f32 {%0,%1,%2,%3}, {%4,%5}, {%6}, {%0,%1,%2,%3};"
               : "+f"(d[0]), "+f"(d[1]), "+f"(d[2]), "+f"(d[3]) : "r"(a0), "r"(a1), "r"(b0));
}
__device__ __forceinline__ uint32_t movtrans(uint32_t a) {
  uint32_t d;
  asm volatile("movmatrix.sync.aligned.m8n8.trans.b16 %0, %1;" : "=r"(d) : "r"(a));
  return d;
}
__device__ __forceinline__ uint32_t mapa(uint32_t a, uint32_t rank) {
  uint32_t d;
  asm("mapa.shared::cluster.u32 %0, %1, %2;" : "=r"(d) : "r"(a), "r"(rank));
  return d;
}
__device__ __forceinline__ void st_async64(uint32_t a, uint32_t x, uint32_t y, uint32_t bar) {
  asm volatile("st.async.weak.shared::cluster.mbarrier::complete_tx::bytes.v2.b32 [%0], {%1,%2}, [%3];"
               ::"r"(a), "r"(x), "r"(y), "r"(bar) : "memory");
}
__device__ __forceinline__ void st_async64f(uint32_t a, float x, float y, uint32_t bar) {
  st_async64(a, __float_as_uint(x), __float_as_uint(y), bar);
}
__device__ __forceinline__ void bulk_s2s(uint32_t dst, uint32_t src, uint32_t bytes, uint32_t bar) {
  asm volatile("cp.async.bulk.shared::cluster.shared::cta.mbarrier::complete_tx::bytes [%0], [%1], %2, [%3];"
               ::"r"(dst), "r"(src), "r"(bytes), "r"(bar) : "memory");
}
__device__ __forceinline__ void tma_store_3d(const CUtensorMap* map, uint32_t src, int x, int y, int z) {
  asm volatile("cp.async.bulk.tensor.3d.global.shared::cta.bulk_group [%0, {%2, %3, %4}], [%1];"
               ::"l"(map), "r"(src), "r"(x), "r"(y), "r"(z) : "memory");
}
__device__ __forceinline__ void mbar_spin(uint32_t bar, uint32_t parity) {
  asm volatile("{\n.reg .pred p;\n.reg .b32 n;\nmov.u32 n, 0x100000;\nMW_L:\n"
               "mbarrier.try_wait.parity.shared::cta.b64 p, [%0], %1;\n@p bra.uni MW_D;\n"
               "add.s32 n, n, -1;\nsetp.ne.u32 p, n, 0;\n@p bra.uni MW_L;\nMW_D:\n}" ::"r"(bar), "r"(parity) : "memory");
}
__device__ __forceinline__ bool mbar_test(uint32_t bar, uint32_t parity) {
  uint32_t done;
  asm volatile("{\n.reg .pred p;\nmbarrier.test_wait.parity.shared::cta.b64 p, [%1], %2;\nselp.u32 %0, 1, 0, p;\n}"
               : "=r"(done) : "r"(bar), "r"(parity) : "memory");
  return done != 0;
}
__device__ __forceinline__ void mbar_arrive_remote(uint32_t bar) {
  asm volatile("mbarrier.arrive.shared::cluster.b64 _, [%0];" ::"r"(bar) : "memory");
}
__device__ __forceinline__ bool elect_one() {
  uint32_t r;
  asm volatile("{\n.reg .pred p;\nelect.sync _|p, 0xffffffff;\nselp.u32 %0, 1, 0, p;\n}" : "=r"(r));
  return r != 0;
}
__device__ __forceinline__ void st_async32(uint32_t a, uint32_t x, uint32_t bar) {
  asm volatile("st.async.weak.shared::cluster.mbarrier::complete_tx::bytes.b32 [%0], %1, [%2];" ::"r"(a), "r"(x), "r"(bar) : "memory");
}
#define named_bar_and(id, n, in, out) \
  asm volatile("{\n.reg .pred p, q;\nsetp.ne.u32 p, %1, 0;\nbar.red.and.pred q, %2, %3, p;\nselp.u32 %0, 1, 0, q;\n}" \
               : "=r"(out) : "r"(in), "n"(id), "n"(n) : "memory")
__device__ __forceinline__ void bulk_g2s(uint32_t dst, const void* src, uint32_t bytes, uint32_t bar) {
  asm volatile("cp.async.bulk.shared::cluster.global.mbarrier::complete_tx::bytes [%0], [%1], %2, [%3];"
               ::"r"(dst), "l"(src), "r"(bytes), "r"(bar) : "memory");
}
__device__ __forceinline__ uint32_t clk32() { uint32_t c; asm volatile("mov.u32 %0, %%clock;" : "=r"(c)::"memory"); return c; }
__device__ __forceinline__ void spin_until(uint32_t t) { while ((int32_t)(clk32() - t) < 0) {} }
#define PIN(x) asm volatile("" : "+r"(x))
#define MEM_FENCE(addr) \
  asm volatile("{\n.reg .pred p;\nsetp.eq.u32 p, %0, 0xFFFFFFF1;\n@p st.shared.u32 [%0], %0;\n}" ::"r"(addr) : "memory")
#define SCHED_DECL(x) \
  asm volatile(".reg .pred p_never;\n{\n.reg .pred q;\nsetp.eq.u32 q, %0, 0xFFFFFFF1;\nvote.sync.any.pred p_never, q, 0xffffffff;\n}" ::"r"(x))
#define SCHED_FENCE(addr) \
  asm volatile("{\nSF_L:\n@p_never st.volatile.shared.u32 [%0], %0;\n@p_never bra.uni SF_L;\n}" ::"r"(addr) : "memory")
#define OPQ                                                                                     \
  int tid_o = tid;                                                                              \
  asm volatile("" : "+r"(tid_o));                                                               \
  const int lane = tid_o & 31, w = (tid_o >> 5) & 3, t7 = tid_o & 127, lg = lane >> 2,          \
            lq = lane & 3, mi = lane >> 3, mr = lane & 7;                                       \
  (void)w; (void)t7; (void)lg; (void)lq; (void)mi; (void)mr; (void)lane

#define SMAP                                                                                                          \
  const uint32_t SM0 = self + fk::SM0, WO = self + fk::WO, WS = self + fk::WS, XN = self + fk::XN, VX = self + fk::VX, \
                 QK = self + fk::QK, PT = self + fk::PT, SP = self + fk::SP, VM = self + fk::VM, OB = self + fk::OB,   \
                 RED = self + fk::RED, VX2 = self + fk::VX2, MEMB = self + fk::MEMB, B_XN = self + fk::B_XN, B_SM = self + fk::B_SM,       \
                 B_VM = self + fk::B_VM, B_VX = self + fk::B_VX, B_ST = self + fk::B_ST, B_PB = self + fk::B_PB,       \
                 B_W = self + fk::B_W, B_H2 = self + fk::B_H2, B_PF = self + fk::B_PF, MASKS = self + fk::MASKS, PROBE = self + fk::PROBE;                             \
  (void)SM0; (void)WO; (void)WS; (void)XN; (void)VX; (void)QK; (void)PT; (void)SP; (void)VM; (void)OB; (void)RED; (void)VX2; \
  (void)MEMB; (void)B_XN; (void)B_SM; (void)B_VM; (void)B_VX; (void)B_ST; (void)B_PB; (void)B_W; (void)MASKS; (void)PROBE; (void)B_H2; (void)B_PF

struct FParams {
  CUtensorMap wq, wk, wv, wo, xn, xn12, o;
  const bf16* mem0;
  int one;
  char* xch;
};

__device__ __forceinline__ uint32_t probe_pair(char* p, uint32_t val, uint32_t dummy) {
  uint32_t best0 = 0x7FFFFFFF, best1 = 0x7FFFFFFF;
  st_pub128(p, val); st_pub128(p + 16, val); st_pub128(p + 4096, val); st_pub128(p + 4112, val);
#pragma unroll 1
  for (int r = 0; r < PROBE_N; r++) {
    uint32_t v;
    const uint32_t c0 = clk32();
    asm volatile("atom.relaxed.gpu.global.exch.b32 %0, [%1], %2;" : "=r"(v) : "l"(p + (r & 1) * 4096), "r"(val) : "memory");
    asm volatile("{\n.reg .pred p;\nsetp.eq.u32 p, %0, 0x12345678;\n@p st.shared.u32 [%1], %0;\n}" ::"r"(v), "r"(dummy) : "memory");
    const uint32_t d = clk32() - c0;
    if (r & 1) best1 = min(best1, d); else best0 = min(best0, d);
    if (r >= 1 && min(best0, best1) < PROBE_FAST && max(best0, best1) - min(best0, best1) > 100) break;
  }
  return best1 < best0;
}

typedef uint32_t WRegs[6][2][4][4];

template <bool ISV> struct Chunks {
  static constexpr int SC0 = ISV ? 6 : SCQ;
  static __device__ __forceinline__ constexpr int rf(int wg, int i) { return wg ? 10 + i : (i < SC0 ? i : 4 + i); }
};

template <int WG> struct ProjCfg { static constexpr int NS = WG ? 8 - NS0 : NS0, P0 = WG ? NS0 : 0, NTA = WG ? NTA1 : NTA0; };
__device__ __forceinline__ void load_pair(uint32_t (&t)[4][4], uint32_t wsa, int pp) {
#pragma unroll
  for (int f = 0; f < 4; f++) ldsm4t(t[f], wsa + ((pp >> 1) * 2 + (f & 1)) * 8192 + ((pp & 1) * 2 + (f >> 1)) * 2048);
}
template <bool ISV, int WG>
__device__ __forceinline__ void proj_mem(const WRegs& wr, uint32_t (&ta)[ProjCfg<WG>::NTA][4][4], uint32_t wsa, uint32_t mba,
                                         float (&a0)[4], float (&a1)[4]) {
  constexpr int NS = ProjCfg<WG>::NS, P0 = ProjCfg<WG>::P0, NTA = ProjCfg<WG>::NTA, NP = 12 + NS;
  float acc[4][4];
  auto spos = [](int j) { return j < NTA ? j : j + (j - NTA + 1) * 12 / (NS - NTA > 0 ? NS - NTA : 1); };
  auto which = [&](int p) { int r = -1; for (int j = 0; j < NS; j++) if (spos(j) == p) r = j; return r; };
  auto nsm_before = [&](int p) { int n = 0; for (int j = 0; j < NS; j++) if (spos(j) < p) n++; return n; };
#pragma unroll
  for (int p = 0; p < NP; p++) {
    const int j = which(p), r = j >= 0 ? 0 : p - nsm_before(p);
    uint32_t bp[4], tl[4][4];
    ldsm4(bp, mba + (j >= 0 ? (Chunks<ISV>::SC0 + ((P0 + j) >> 1)) * 1024 + ((P0 + j) & 1) * 512 : Chunks<ISV>::rf(WG, r >> 1) * 1024 + (r & 1) * 512));
    if (j >= NTA) load_pair(tl, wsa, P0 + j);
#pragma unroll
    for (int u = 0; u < 2; u++)
#pragma unroll
      for (int T = 0; T < 2; T++) {
        const uint32_t* a = j >= NTA ? tl[u * 2 + T] : j >= 0 ? ta[j >= 0 ? j % NTA : 0][u * 2 + T] : wr[r >> 1][T][(r & 1) * 2 + u];
        if (p == 0) mma16816z(acc[u * 2 + T], a, bp[2 * u], bp[2 * u + 1]);
        else mma16816(acc[u * 2 + T], a, bp[2 * u], bp[2 * u + 1]);
      }
  }
#pragma unroll
  for (int i = 0; i < 4; i++) { a0[i] = acc[0][i] + acc[2][i]; a1[i] = acc[1][i] + acc[3][i]; }
}
template <int WG>
__device__ __forceinline__ void proj_mem_prefetch(uint32_t (&ta)[ProjCfg<WG>::NTA][4][4], uint32_t wsa) {
#pragma unroll
  for (int j = 0; j < ProjCfg<WG>::NTA; j++) load_pair(ta[j], wsa, ProjCfg<WG>::P0 + j);
}

template <bool ISV, int WG>
__device__ __forceinline__ void proj_finish(const float (&a0)[4], const float (&a1)[4], uint32_t peer0, uint32_t peer1, uint32_t self, int tid,
                                            uint32_t (&vmo)[2][2]) {
  using namespace fk;
  SMAP;
  OPQ;
  if (!ISV) {
    stsm4(PT + (mi >> 1) * 2048 + w * 512 + (mi & 1) * 256 + WG * 128 + mr * 16,
          pack_bf16(a0[0], a0[1]), pack_bf16(a0[2], a0[3]), pack_bf16(a1[0], a1[1]), pack_bf16(a1[2], a1[3]));
    named_bar_sync(NB_C, 256);
  } else {
    if (WG == 0) sts128f(RED + t7 * 16, a1[0], a1[1], a1[2], a1[3]);
    else sts128f(RED + 2048 + t7 * 16, a0[0], a0[1], a0[2], a0[3]);
    if (WG == 1) { lds64(vmo[0], VM + t7 * 8); lds64(vmo[1], VM + 1024 + t7 * 8); }
    named_bar_sync(NB_C, 256);
    const float4 p = lds128f(RED + (1 - WG) * 2048 + t7 * 16);
    const float* k = WG == 0 ? a0 : a1;
    const uint32_t v0 = pack_bf16(k[0] + p.x, k[1] + p.y), v1 = pack_bf16(k[2] + p.z, k[3] + p.w);
    const uint32_t off = VM + WG * 1024 + t7 * 8;
    st_async64(peer0 + off, v0, v1, peer0 + B_VM);
    st_async64(peer1 + off, v0, v1, peer1 + B_VM);
    sts64(off, v0, v1);
    __syncwarp();
    if (lane == 0) mbar_arrive(B_VM);
  }
}

__device__ __forceinline__ void send_scores(float s0, float s1, uint32_t off, uint32_t peer0, uint32_t peer1, uint32_t bar, int lane) {
  if (SPACK) {
    const uint32_t v = pack_bf16(s0, s1);
    st_async32(peer0 + off, v, peer0 + bar);
    st_async32(peer1 + off, v, peer1 + bar);
    sts32(off, v);
  } else {
    st_async64f(peer0 + off, s0, s1, peer0 + bar);
    st_async64f(peer1 + off, s0, s1, peer1 + bar);
    sts64f(off, s0, s1);
  }
  __syncwarp();
  if (lane == 0) mbar_arrive(bar);
}

template <int NT, int PF, int PFA>
__device__ __forceinline__ void wo_phase(uint32_t (&wf)[PFA][4], uint32_t woa, uint32_t oba, char* h1p, uint32_t sel, uint32_t tag) {
  float c[NT][4];
  uint32_t of[2][4];
  ldsm4t(of[0], oba);
#pragma unroll
  for (int k = 0; k < 8; k++) {
    if ((k & 1) == 0 && k + 2 < 8) ldsm4t(of[((k >> 1) + 1) & 1], oba + ((k >> 1) + 1) * 512);
#pragma unroll
    for (int i = 0; i < NT; i++) {
      const int f = k * NT + i;
      const uint32_t b0 = of[(k >> 1) & 1][2 * (k & 1)], b1 = of[(k >> 1) & 1][2 * (k & 1) + 1];
      if (k == 0) mma16816z(c[i], wf[f % PF], b0, b1); else mma16816(c[i], wf[f % PF], b0, b1);
      if (f + PF < 8 * NT) ldsm4t(wf[f % PF], woa + ((f + PF) % NT) * 32768 + ((f + PF) / NT) * 512);
    }
  }
#pragma unroll
  for (int i = 0; i < NT; i++)
    st_pub64(h1p + i * (8 * 32768) + ((sel >> (2 * i)) & 3) * 2048, (pack_bf16(c[i][0], c[i][1]) & ~1u) | tag, pack_bf16(c[i][2], c[i][3]));
}
template <int NT, int F0, int F1, int PFA>
__device__ __forceinline__ void wo_prefetch(uint32_t (&wf)[PFA][4], uint32_t woa) {
#pragma unroll
  for (int f = F0; f < F1; f++) ldsm4t(wf[f], woa + (f % NT) * 32768 + (f / NT) * 512);
}

template <bool ISV, int T, bool ADD>
__device__ __forceinline__ void tok_store(const float (&x)[16], uint32_t base, int tid) {
  OPQ;
  const uint32_t a = ISV ? base + T * 4096 + w * 1024 + lane * 16
                   : T == 0 ? base + w * 512 + (mi & 1) * 256 + (mi >> 1) * 128 + mr * 16
                            : base + 4096 + (mi >> 1) * 1024 + w * 256 + (mi & 1) * 128 + mr * 16;
  constexpr uint32_t STR = ISV ? 512 : 2048;
  uint32_t p[2][4];
  if (ADD) {
#pragma unroll
    for (int i = 0; i < 2; i++) { if (ISV) lds128(p[i], a + i * STR); else ldsm4(p[i], a + i * STR); }
  }
#pragma unroll
  for (int i = 0; i < 2; i++) {
#pragma unroll
    for (int k = 0; k < 4; k++)
      p[i][k] = ADD ? pack_bf16(x[8 * i + 2 * k] + bf_lo(p[i][k]), x[8 * i + 2 * k + 1] + bf_hi(p[i][k]))
                    : pack_bf16(x[8 * i + 2 * k], x[8 * i + 2 * k + 1]);
    if (ISV) sts128(a + i * STR, p[i][0], p[i][1], p[i][2], p[i][3]); else stsm4(a + i * STR, p[i][0], p[i][1], p[i][2], p[i][3]);
  }
}

__device__ __forceinline__ void load_xn(const FParams& P, int seg, uint32_t self) {
  SMAP;
  mbar_expect_tx(B_XN, 49152);
  tma_load_3d(XN, &P.xn12, 0, seg * 32, 0, B_XN);
}

__device__ __forceinline__ uint64_t xn_desc(int slot, int u) { return make_desc(fk::XN + slot * 4096 + u * 32, 16, 1024); }

template <bool ISV>
__device__ __forceinline__ void f_wg0(const FParams& P, const WRegs& wr, const int h, const int rank, uint32_t sel, const int tid) {
  using namespace fk;
  const uint32_t self = mapa(0, rank), peer0 = mapa(0, ISV ? 0 : rank ^ 1) - self, peer1 = mapa(0, ISV ? 1 : 2) - self;
  SMAP;
  const int tile0 = rank * 22;
  const int warp = __shfl_sync(0xffffffffu, threadIdx.x >> 5, 0);
  const bool three = !ISV && warp < 2;
  uint32_t ta[NTA0][4][4], wsa = 0, mba = 0, h2ph = 0;
#pragma unroll 1
  for (int s = -1; s < cfg::NSEG; s++) {
    uint32_t t_pub = 0;
    sel ^= 0x55;
    if (s >= 0) {
      PROF(0, 1);
      float a0[4], a1[4];
      proj_mem<ISV, 0>(wr, ta, wsa, mba, a0, a1);
      PROF(0, 2);
      uint32_t unused[2][2];
      proj_finish<ISV, 0>(a0, a1, peer0, peer1, self, tid, unused);
      PROF(0, 3);
      if (s + 1 == cfg::NSEG) break;
      uint32_t wf[PF0][4], woa;
      {
        OPQ;
        if (!ISV) {
          uint32_t qf[4][4], kf[2][4];
          const uint32_t qa = PT + lane * 16, ka = QK + 4096 + w * 1024 + lane * 16;
          ldsm4t(qf[0], qa); ldsm4t(kf[0], ka); ldsm4t(qf[1], qa + 512);
          ldsm4t(qf[2], qa + 1024); ldsm4t(kf[1], ka + 512); ldsm4t(qf[3], qa + 1536);
          float c0[4], c1[4];
          mma16816z(c0, qf[0], kf[0][0], kf[0][1]);
          mma16816z(c1, qf[1], kf[0][2], kf[0][3]);
          mma16816(c0, qf[2], kf[1][0], kf[1][1]);
          mma16816(c1, qf[3], kf[1][2], kf[1][3]);
          const float s0 = (c0[0] + c0[2]) + (c1[0] + c1[2]), s1 = (c0[1] + c0[3]) + (c1[1] + c1[3]);
          send_scores(s0, s1, SP + rank * SP_SRC + t7 * SPW, peer0, peer1, B_SM, lane);
        }
        PROF(0, 4);
        woa = WO + (w + 4) * 4096 + ((mi >> 1) * 8 + mr) * 32 + (((mi & 1) ^ (mr >> 2)) << 4);
        PIN(woa);
        uint32_t vf[2][2][4], vm[2][2];
        if (!ISV) mbar_spin(B_VX, s & 1);
        PROF(0, 14);
#pragma unroll
        for (int T = 0; T < 2; T++)
#pragma unroll
          for (int kk = 0; kk < 2; kk++) lds128(vf[T][kk], ((ISV && (s & 1)) ? VX2 : VX) + T * 4096 + w * 1024 + kk * 512 + lane * 16);
        if (three) wo_prefetch<3, 0, PF0A>(wf, woa); else wo_prefetch<2, 0, PF0A>(wf, woa);
        uint32_t spa = SP + lane * SPW, vma = VM + t7 * 8, oa = OB + (mi >> 1) * 1024 + w * 256 + (mi & 1) * 128 + mr * 16;
        PIN(spa); PIN(vma); PIN(oa);
        mbar_spin(B_SM, s & 1);
        PROF(0, 5);
        float sc[10];
#pragma unroll
        for (int j = 0; j < 5; j++) {
          if (SPACK) {
            const uint32_t x = lds32(spa + j * 128), y = lds32(spa + SP_SRC + j * 128);
            sc[2 * j] = bf_lo(x) + bf_lo(y); sc[2 * j + 1] = bf_hi(x) + bf_hi(y);
          } else {
            const float2 x = lds64f(spa + j * 256), y = lds64f(spa + SP_SRC + j * 256);
            sc[2 * j] = x.x + y.x; sc[2 * j + 1] = x.y + y.y;
          }
        }
        float m = fmaxf(fmaxf(fmaxf(sc[0], sc[1]), fmaxf(sc[2], sc[3])), fmaxf(fmaxf(sc[4], sc[5]), fmaxf(sc[6], sc[7])));
        m = fmaxf(m, fmaxf(sc[8], sc[9]));
        const bool vm_ok = mbar_test(B_VM, s & 1);
        m = fmaxf(m, __shfl_xor_sync(0xffffffffu, m, 1));
        m = fmaxf(m, __shfl_xor_sync(0xffffffffu, m, 2));
        PROF(0, 15);
        if (!vm_ok) mbar_spin(B_VM, s & 1);
        PROF(0, 0);
        lds64(vm[0], vma); lds64(vm[1], vma + 1024);
        const float cs = 0.08838834764831845f * 1.4426950408889634f;
        const float mc = -m * cs;
        uint32_t pb[5];
#pragma unroll
        for (int j = 0; j < 5; j++) pb[j] = pack_bf16(ex2_approx(fmaf(sc[2 * j], cs, mc)), ex2_approx(fmaf(sc[2 * j + 1], cs, mc)));
        PROF(0, 6);
        float o0[4], o1[4], rs[4];
        const uint32_t ones[4] = {0x3F803F80u, 0x3F803F80u, 0x3F803F80u, 0x3F803F80u};
        mma16816z(rs, ones, pb[0], pb[1]);
        mma16816z(o0, vf[0][0], pb[0], pb[1]);
        mma16816z(o1, vf[1][0], pb[0], pb[1]);
        mma16816(rs, ones, pb[2], pb[3]);
        mma16816(o0, vf[0][1], pb[2], pb[3]);
        mma16816(o1, vf[1][1], pb[2], pb[3]);
        mma1688(rs, ones[0], ones[0], pb[4]);
        mma1688(o0, vm[0][0], vm[0][1], pb[4]);
        mma1688(o1, vm[1][0], vm[1][1], pb[4]);
        const float i0 = rcp_approx(rs[0]), i1 = rcp_approx(rs[1]);
        stsm4(oa, pack_bf16(o0[0] * i0, o0[1] * i1), pack_bf16(o0[2] * i0, o0[3] * i1),
              pack_bf16(o1[0] * i0, o1[1] * i1), pack_bf16(o1[2] * i0, o1[3] * i1));
      }
      {
        OPQ;
        named_bar_arrive(NB_O, 256);
        if (three) wo_prefetch<3, PF0A, PF0>(wf, woa); else wo_prefetch<2, PF0A, PF0>(wf, woa);
        char* h1p = P.xch + (tile0 + 4 + w) * 32768 + (h >> 3) * 8192 + (h & 7) * 256 + lane * 8;
        uint32_t oba = OB + lane * 16;
        PIN(oba);
        PROF(0, 7);
        named_bar_sync(NB_O0, 128);
        PROF(0, 8);
        const uint32_t tag = ((s >> 1) & 1) ^ 1;
        if (three) wo_phase<3, PF0>(wf, woa, oba, h1p, sel, tag); else wo_phase<2, PF0>(wf, woa, oba, h1p, sel, tag);
        t_pub = clk32();
        PROF(0, 9);
        named_bar_sync(NB_HD, 256);
      }
    }
    auto h2_src = [&]() { return P.xch + H1_BYTES + ((s & 1) * 4 + warp) * 8192 + ((sel >> (8 + (s & 1))) & 1) * 4096; };
    {
      const uint32_t ph = (s + 1) & 1;
      float x0[16], x1[16];
      mbar_spin(B_XN, ph);
      wg_fence();
#pragma unroll
      for (int c = 0; c < 10; c++) {
        if (PAUSE && !ISV && c == SCQ + 4) { uint32_t t_; named_bar_and(NB_PZ, 256, 1, t_); wg_fence(); }
        if (c == 9) named_bar_arrive(NB_ST, 256);
#pragma unroll
        for (int u = 0; u < 4; u++) {
          constexpr int SC0 = Chunks<ISV>::SC0;
          if (c >= SC0 && c < SC0 + 4) {
            wgmma_ss_n32_ta(x0, make_desc(fk::WS + (c - SC0) * 16384 + u * 2048, 8192, 1024), xn_desc(c, u), 1);
            wgmma_ss_n32_ta(x1, make_desc(fk::WS + (c - SC0) * 16384 + 8192 + u * 2048, 8192, 1024), xn_desc(c, u), 1);
          } else {
            wgmma_rs_n32(x0, wr[c < SC0 ? c : c >= SC0 + 4 ? c - 4 : 0][0][u], xn_desc(c, u), (c | u) != 0);
            wgmma_rs_n32(x1, wr[c < SC0 ? c : c >= SC0 + 4 ? c - 4 : 0][1][u], xn_desc(c, u), (c | u) != 0);
          }
          if (c == 4 && u == 1) { wg_commit(); wg_wait<1>(); named_bar_arrive(NB_XE, 160); wg_fence(); }
        }
        if (c == 3) wg_commit();
      }
      wg_commit();
      wg_wait<0>();
      PROF(0, 10);
      if (ISV) named_bar_sync(NB_CF, 160);
      const uint32_t tb = ISV ? (ph ? VX2 : VX) : QK;
      tok_store<ISV, 0, false>(x0, tb, tid);
      tok_store<ISV, 1, false>(x1, tb, tid);
      named_bar_arrive(NB_DU, 256);
    }
    {
      OPQ;
      wsa = WS + ((mi >> 1) * 8 + mr) * 128 + (((2 * w + (mi & 1)) ^ mr) << 4);
      mba = MEMB + lane * 16;
      PIN(wsa); PIN(mba);
      if (s >= 0) {
        const char* src = h2_src();
        const uint32_t chk = MEMB + w * 4096 + lane * 32 + lg * 4, bar = B_H2 + 8 * warp;
        PROF(0, 11);
        if (FLAGS) {
          const char* fp = P.xch + FL_OFF + ((sel >> 10) & 1) * 4096 + (h & 3) * 128 + w * 32 + mr * 4;
          const uint32_t want = (s + 1) * 0x10001;
          spin_until(t_pub + D_H2);
          uint32_t f0 = ld_strong4(fp);
          spin_until(clk32() + D_FS);
          uint32_t f1 = ld_strong4(fp);
          spin_until(clk32() + D_FS);
          uint32_t f2 = ld_strong4(fp);
#pragma unroll 1
          for (int tries = 0; tries < POLL_TRIES; tries++) {
            if (__all_sync(0xffffffffu, f0 == want)) break;
            f0 = ld_strong4(fp);
            if (__all_sync(0xffffffffu, f1 == want)) break;
            f1 = ld_strong4(fp);
            if (__all_sync(0xffffffffu, f2 == want)) break;
            f2 = ld_strong4(fp);
          }
          if (D_F) spin_until(clk32() + D_F);
        } else {
          spin_until(t_pub + D_H2);
        }
        PROF(0, 13);
        if (elect_one()) { mbar_expect_tx(bar, 4096); bulk_g2s(MEMB + warp * 4096, src, 4096, bar); }
        proj_mem_prefetch<0>(ta, wsa);
#pragma unroll 1
        for (int tries = 0; tries < POLL_TRIES; tries++) {
          mbar_spin(bar, h2ph);
          h2ph ^= 1;
          const uint32_t mx = max(max(lds32(chk), lds32(chk + 1024)), max(lds32(chk + 2048), lds32(chk + 3072)));
          if (__all_sync(0xffffffffu, mx != EMPTY)) break;
          RETRY(1);
          if (elect_one()) { mbar_expect_tx(bar, 4096); bulk_g2s(MEMB + warp * 4096, src, 4096, bar); }
        }
      } else {
        const bf16* m0 = P.mem0 + mr * cfg::D + w * 256 + mi * 8;
#pragma unroll
        for (int i = 0; i < 8; i++) {
          const uint4 v = *reinterpret_cast<const uint4*>(m0 + i * 32);
          sts128(mba + w * 4096 + i * 512, v.x, v.y, v.z, v.w);
        }
        proj_mem_prefetch<0>(ta, wsa);
      }
      PROF(0, 12);
      named_bar_arrive(NB_M1, 256);
      named_bar_sync(NB_M0, 128);
    }
  }
}

template <bool ISV>
__device__ __forceinline__ void f_wg1(const FParams& P, const WRegs& wr, const int h, const int rank, uint32_t sel, const int tid) {
  using namespace fk;
  const uint32_t self = mapa(0, rank), peer0 = mapa(0, ISV ? 0 : rank ^ 1) - self, peer1 = mapa(0, ISV ? 1 : 2) - self;
  SMAP;
  const int tile0 = rank * 22;
  const int warp = __shfl_sync(0xffffffffu, (threadIdx.x >> 5) & 3, 0);
  uint32_t ta[NTA1][4][4], wsa = 0, mba = 0;
  auto tok_pv = [&](int seg, const uint32_t (&vm)[2][2]) {
    OPQ;
    const int s = seg + 1; (void)s;
    const uint32_t vb = (seg & 1) ? VX2 : VX;
    uint32_t vf[2][2][4];
#pragma unroll
    for (int T = 0; T < 2; T++)
#pragma unroll
      for (int kk = 0; kk < 2; kk++) lds128(vf[T][kk], vb + T * 4096 + w * 1024 + kk * 512 + lane * 16);
    const uint32_t stg = vb + (mi >> 1) * 4096 + mr * 128 + (((2 * w + (mi & 1)) ^ mr) << 4);
    uint32_t pm[4], r[4][4];
    lds128(pm, PT + 2048 + lane * 16);
#pragma unroll
    for (int g2 = 0; g2 < 4; g2 += 2) {
      uint32_t p[2][4];
      lds128(p[0], PT + g2 * 512 + lane * 16);
      lds128(p[1], PT + g2 * 512 + 512 + lane * 16);
      float o[4][4];
#pragma unroll
      for (int i = 0; i < 4; i++) mma16816z(o[i], vf[i & 1][0], p[i >> 1][0], p[i >> 1][1]);
#pragma unroll
      for (int i = 0; i < 4; i++) mma16816(o[i], vf[i & 1][1], p[i >> 1][2], p[i >> 1][3]);
#pragma unroll
      for (int i = 0; i < 4; i++) mma1688(o[i], vm[i & 1][0], vm[i & 1][1], pm[g2 + (i >> 1)]);
#pragma unroll
      for (int i = 0; i < 4; i++) {
        r[g2 + (i >> 1)][2 * (i & 1)] = pack_bf16(o[i][0], o[i][1]);
        r[g2 + (i >> 1)][2 * (i & 1) + 1] = pack_bf16(o[i][2], o[i][3]);
      }
      if (g2 == 0) named_bar_sync(NB_W1, 128);
    }
    PROF(1, 6);
#pragma unroll
    for (int gq = 0; gq < 4; gq++) stsm4t(stg + gq * 1024, r[gq][0], r[gq][1], r[gq][2], r[gq][3]);
  };
  auto o_store = [&](int seg) { tma_store_3d(&P.o, (seg & 1) ? VX2 : VX, 0, seg * 32, 2 * h); tma_store_commit(); };
  auto o_done = [&](int seg) {
    tma_store_wait_all();
    if ((seg & 3) == 3) {
      asm volatile("fence.proxy.async;" ::: "memory");
      asm volatile("red.release.gpu.global.add.u32 [%0], 1;" ::"l"(&g_oflag[seg >> 2]) : "memory");
    }
  };
#pragma unroll 1
  for (int s = -1; s < cfg::NSEG; s++) {
    uint32_t t_pub = 0;
    sel ^= 0x55;
    const bool last = s + 1 == cfg::NSEG;
    if (s >= 0) {
      PROF(1, 1);
      float a0[4], a1[4];
      proj_mem<ISV, 1>(wr, ta, wsa, mba, a0, a1);
      PROF(1, 2);
      uint32_t vmo[2][2];
      proj_finish<ISV, 1>(a0, a1, peer0, peer1, self, tid, vmo);
      PROF(1, 3);
      uint32_t wf[PF1][4], woa;
      if (ISV) {
        if (warp == 3 && !last) {
          mbar_spin(B_VM, s & 1);
          if (elect_one()) load_xn(P, s + 1, self);
        }
        if (s > 0) tok_pv(s - 1, vmo);
        OPQ;
        woa = WO + w * 4096 + ((mi >> 1) * 8 + mr) * 32 + (((mi & 1) ^ (mr >> 2)) << 4);
      } else {
        float c0[4], c1[4];
        if (warp == 0) {
          OPQ;
          uint32_t kf[4][4], qf[4][4];
          float d0[4], d1[4];
          const uint32_t ka = PT + 2048 + (mi & 1) * 256 + (mi >> 1) * 128 + mr * 16;
#pragma unroll
          for (int k = 0; k < 4; k++) { ldsm4t(qf[k], PT + k * 512 + lane * 16); ldsm4t(kf[k], ka + k * 512); }
          mma16816z(c0, qf[0], kf[0][0], kf[0][1]); mma16816z(c1, qf[0], kf[0][2], kf[0][3]);
          mma16816z(d0, qf[1], kf[1][0], kf[1][1]); mma16816z(d1, qf[1], kf[1][2], kf[1][3]);
          mma16816(c0, qf[2], kf[2][0], kf[2][1]); mma16816(c1, qf[2], kf[2][2], kf[2][3]);
          mma16816(d0, qf[3], kf[3][0], kf[3][1]); mma16816(d1, qf[3], kf[3][2], kf[3][3]);
          const float s0 = ((c0[0] + c0[2]) + (c1[0] + c1[2])) + ((d0[0] + d0[2]) + (d1[0] + d1[2]));
          const float s1 = ((c0[1] + c0[3]) + (c1[1] + c1[3])) + ((d0[1] + d0[3]) + (d1[1] + d1[3]));
          if (!last) send_scores(s0, s1, SP + rank * SP_SRC + (128 + lane) * SPW, peer0, peer1, B_SM, lane);
          PROF(1, 5);
#pragma unroll
          for (int mt = 0; mt < 2; mt++) {
            float* c = mt ? c1 : c0;
#pragma unroll
            for (int k = 0; k < 4; k++) ldsm4t(qf[k], QK + mt * 2048 + k * 512 + lane * 16);
            mma16816z(c, qf[0], kf[0][0], kf[0][1]); mma16816z(d0, qf[0], kf[0][2], kf[0][3]);
#pragma unroll
            for (int k = 1; k < 4; k++) { mma16816(c, qf[k], kf[k][0], kf[k][1]); mma16816(d0, qf[k], kf[k][2], kf[k][3]); }
#pragma unroll
            for (int i = 0; i < 4; i++) c[i] += d0[i];
          }
        } else {
          const uint32_t t_c = clk32();
          if (warp == 3 && !last) { if (elect_one()) load_xn(P, s + 1, self); }
          spin_until(t_c + D_ST);
          OPQ;
          const int mt = w >> 1, j0 = w == 3 ? 2 : 0;
          uint32_t qf[4][4], kf[4][4];
#pragma unroll
          for (int k = 0; k < 4; k++) { ldsm4t(qf[k], QK + mt * 2048 + k * 512 + lane * 16); ldsm4t(kf[k], QK + 4096 + j0 * 1024 + k * 512 + lane * 16); }
          mma16816z(c0, qf[0], kf[0][0], kf[0][1]); mma16816z(c1, qf[0], kf[2][0], kf[2][1]);
          mma16816(c0, qf[1], kf[0][2], kf[0][3]); mma16816(c1, qf[1], kf[2][2], kf[2][3]);
          mma16816(c0, qf[2], kf[1][0], kf[1][1]); mma16816(c1, qf[2], kf[3][0], kf[3][1]);
          mma16816(c0, qf[3], kf[1][2], kf[1][3]); mma16816(c1, qf[3], kf[3][2], kf[3][3]);
        }
        OPQ;
        const uint32_t dst = peer1 + QK + rank * 3584 + lane * 8, dbar = peer1 + B_ST;
        woa = WO + w * 4096 + ((mi >> 1) * 8 + mr) * 32 + (((mi & 1) ^ (mr >> 2)) << 4);
        const uint32_t tbl = w == 0 ? 0x9520u : w == 1 ? 0x4F31u : w == 2 ? 0xB7A6u : 0xDFC8u;
        PROF(1, 6);
        mbar_spin(last ? B_VM : B_VX, s & 1);
        st_async64f(dst + (tbl & 15) * 256, c0[0], c0[1], dbar);
        st_async64f(dst + ((tbl >> 4) & 15) * 256, c0[2], c0[3], dbar);
        if ((w & 1) == 0) st_async64f(dst + ((tbl >> 8) & 15) * 256, c1[0], c1[1], dbar);
        st_async64f(dst + (tbl >> 12) * 256, c1[2], c1[3], dbar);
      }
      PROF(1, 4);
      if (!last) {
        OPQ;
        uint32_t oba = OB + lane * 16;
        PIN(oba);
        wo_prefetch<3, 0, PF1>(wf, woa);
        char* h1p = P.xch + (tile0 + w) * 32768 + (h >> 3) * 8192 + (h & 7) * 256 + lane * 8;
        if (ISV) fence_proxy_async_smem();
        PROF(1, 7);
        named_bar_sync(NB_O, 256);
        PROF(1, 8);
        wo_phase<3, PF1>(wf, woa, oba, h1p, sel, ((s >> 1) & 1) ^ 1);
        t_pub = clk32();
        named_bar_arrive(NB_HD, 256);
        PROF(1, 9);
        if (ISV && warp == 0 && s > 0) { if (elect_one()) o_store(s - 1); }
        if (!ISV && tid == 192) mbar_arrive_remote(peer1 + B_PF);
        if (tid == 160) {
          if (s + 2 < cfg::NSEG) { mbar_expect_tx(B_SM, ISV ? 2 * SP_SRC : SP_SRC); if (!ISV) mbar_expect_tx(B_VX, 8192); }
          if (!ISV) mbar_expect_tx(B_VM, 2048);
        }
        __syncwarp();
      }
    }
    auto refill = [&]() {
      if (warp == 3) {
        named_bar_sync(NB_XE, 160);
        if (elect_one()) {
          mbar_expect_tx(B_XN + 8, 16384);
          tma_load_3d(XN, &P.xn, 0, (s + 1) * 32, 12, B_XN + 8);
        }
      }
    };
    if (s < 0) {
      if (ISV && warp == 0) named_bar_arrive(NB_CF, 160);
      refill();
      if (PAUSE && !ISV) { uint32_t t_; named_bar_and(NB_PZ, 256, 1, t_); }
    } else if (!ISV) {
      if (last) break;
      OPQ;
      const int j = 2 * h + rank;
      const char* src = P.xch + j * 32768 + w * 8192 + ((sel >> 6) & 3) * 2048 + lane * 8;
      char* dst = P.xch + H1_BYTES + (j >> 4) * 8192 + (j & 15) * 256 + (w & 1) * 128 + lane * 4;
      const uint32_t tmask = (s >> 1) & 1;
      const bool sw = lq >= 2;
      uint32_t rw = PT + w * 512 + (2 * lq + sw) * 32 + lg * 4, rr = PT + (w & 1) * 256 + lane * 8;
      PIN(rw); PIN(rr);
      uint2 v[8];
      spin_until(t_pub + D_H1);
#pragma unroll
      for (int i = 0; i < 8; i++) v[i] = ld_poll8(src + i * 256);
      refill();
      auto partial = [&]() {
        float f[4];
        f[0] = ((bf_lo(v[0].x) + bf_lo(v[1].x)) + (bf_lo(v[2].x) + bf_lo(v[3].x))) + ((bf_lo(v[4].x) + bf_lo(v[5].x)) + (bf_lo(v[6].x) + bf_lo(v[7].x)));
        f[1] = ((bf_hi(v[0].x) + bf_hi(v[1].x)) + (bf_hi(v[2].x) + bf_hi(v[3].x))) + ((bf_hi(v[4].x) + bf_hi(v[5].x)) + (bf_hi(v[6].x) + bf_hi(v[7].x)));
        f[2] = ((bf_lo(v[0].y) + bf_lo(v[1].y)) + (bf_lo(v[2].y) + bf_lo(v[3].y))) + ((bf_lo(v[4].y) + bf_lo(v[5].y)) + (bf_lo(v[6].y) + bf_lo(v[7].y)));
        f[3] = ((bf_hi(v[0].y) + bf_hi(v[1].y)) + (bf_hi(v[2].y) + bf_hi(v[3].y))) + ((bf_hi(v[4].y) + bf_hi(v[5].y)) + (bf_hi(v[6].y) + bf_hi(v[7].y)));
        sts32(rw, __float_as_uint(sw ? f[1] : f[0]));
        sts32(rw ^ 32, __float_as_uint(sw ? f[0] : f[1]));
        sts32(rw + 256, __float_as_uint(sw ? f[3] : f[2]));
        sts32((rw ^ 32) + 256, __float_as_uint(sw ? f[2] : f[3]));
        uint32_t t0, t1, t2, t3;
        asm("lop3.b32 %0, %1, %2, %3, 0x42;" : "=r"(t0) : "r"(v[0].x), "r"(v[1].x), "r"(tmask));
        asm("lop3.b32 %0, %1, %2, %3, 0x42;" : "=r"(t1) : "r"(v[2].x), "r"(v[3].x), "r"(tmask));
        asm("lop3.b32 %0, %1, %2, %3, 0x42;" : "=r"(t2) : "r"(v[4].x), "r"(v[5].x), "r"(tmask));
        asm("lop3.b32 %0, %1, %2, %3, 0x42;" : "=r"(t3) : "r"(v[6].x), "r"(v[7].x), "r"(tmask));
        return t0 & t1 & t2 & t3 & 1;
      };
      uint32_t ok = partial();
      PROF(1, 10);
      if (PAUSE) named_bar_and(NB_PZ, 256, ok, ok); else named_bar_and(NB_W1, 128, ok, ok);
      if (!ok) {
#pragma unroll 1
        for (int tries = 0; tries < POLL_TRIES; tries++) {
#pragma unroll
          for (int i = 0; i < 8; i++) v[i] = ld_strong8(src + i * 256);
          RETRY(0);
          ok = partial();
          named_bar_and(NB_W1, 128, ok, ok);
          if (ok) break;
        }
      }
      if (FLAGS && warp == 2 && lane < 8) st_pub16(P.xch + FL_OFF + (lane & 1) * 4096 + (lane >> 1) * 128 + j * 2, s + 1);
      if (warp < 2) {
        const float2 y0 = lds64f(rr), y1 = lds64f(rr + 512), y2 = lds64f(rr + 1024), y3 = lds64f(rr + 1536);
        const uint32_t r = pack_bf16((y0.x + y1.x) + (y2.x + y3.x), (y0.y + y1.y) + (y2.y + y3.y));
        st_pub32(dst + (s & 1) * 32768, r);
        st_pub32(dst + (s & 1) * 32768 + 4096, r);
        st_pub32(dst + ((s & 1) ^ 1) * 32768, EMPTY);
        st_pub32(dst + ((s & 1) ^ 1) * 32768 + 4096, EMPTY);
      }
      if (s == 0 && t7 == 0) st_pub32(&g_mask[j], 0);
      PROF(1, 11);
    } else {
      {
        OPQ;
        const uint32_t sa = QK + ((w * (w + 3)) >> 1) * 256 + lane * 8;
        mbar_spin(B_ST, s & 1);
        if (tid == 160 && !last) mbar_expect_tx(B_ST, 7168);
        float sc[10];
        const float scale = 0.08838834764831845f, NEG = -1000000000.0f;
#pragma unroll
        for (int b = 0; b < 5; b++) {
          sc[2 * b] = NEG; sc[2 * b + 1] = NEG;
          if (b <= warp + 1) {
            const float2 x = lds64f(sa + b * 256), y = lds64f(sa + 3584 + b * 256);
            const bool diag = b == warp + 1;
            if (!(diag && 2 * lq > lg)) sc[2 * b] = (x.x + y.x) * scale;
            if (!(diag && 2 * lq + 1 > lg)) sc[2 * b + 1] = (x.y + y.y) * scale;
          }
        }
        float m = fmaxf(fmaxf(fmaxf(sc[0], sc[1]), fmaxf(sc[2], sc[3])), fmaxf(fmaxf(sc[4], sc[5]), fmaxf(sc[6], sc[7])));
        m = fmaxf(m, fmaxf(sc[8], sc[9]));
        m = fmaxf(m, __shfl_xor_sync(0xffffffffu, m, 1));
        m = fmaxf(m, __shfl_xor_sync(0xffffffffu, m, 2));
        float sum = 0.f;
#pragma unroll
        for (int i = 0; i < 10; i++) { sc[i] = ex2_approx((sc[i] - m) * 1.4426950408889634f); sum += sc[i]; }
        sum += __shfl_xor_sync(0xffffffffu, sum, 1);
        sum += __shfl_xor_sync(0xffffffffu, sum, 2);
        const float inv = rcp_approx(sum);
        sts128(PT + w * 512 + lane * 16, pack_bf16(sc[2] * inv, sc[3] * inv), pack_bf16(sc[4] * inv, sc[5] * inv),
               pack_bf16(sc[6] * inv, sc[7] * inv), pack_bf16(sc[8] * inv, sc[9] * inv));
        sts32(PT + 2048 + lane * 16 + w * 4, pack_bf16(sc[0] * inv, sc[1] * inv));
        PROF(1, 10);
        if (last) {
          uint32_t vm[2][2];
          mbar_spin(B_VM, s & 1);
          lds64(vm[0], VM + t7 * 8); lds64(vm[1], VM + 1024 + t7 * 8);
          named_bar_sync(NB_W1, 128);
          tok_pv(s, vm);
          fence_proxy_async_smem();
          named_bar_sync(NB_W1, 128);
          if (warp == 0) { if (elect_one()) { o_store(s - 1); o_store(s); o_done(s); } }
          break;
        }
      }
      if (warp == 0) {
        if (s > 0) { if (elect_one()) o_done(s - 1); }
        __syncwarp();
        named_bar_arrive(NB_CF, 160);
      }
      refill();
      PROF(1, 11);
    }
    {
      const uint32_t ph = (s + 1) & 1;
      float x0[16], x1[16];
      mbar_spin(B_XN, ph);
      named_bar_sync(NB_ST, 256);
      PROF(1, 12);
      wg_fence();
#pragma unroll
      for (int c = 0; c < 6; c++) {
        if (c == 2) { mbar_spin(B_XN + 8, ph); wg_fence(); }
#pragma unroll
        for (int u = 0; u < 4; u++) {
          wgmma_rs_n32(x0, wr[c][0][u], xn_desc(c < 2 ? 10 + c : c - 2, u), (c | u) != 0);
          wgmma_rs_n32(x1, wr[c][1][u], xn_desc(c < 2 ? 10 + c : c - 2, u), (c | u) != 0);
        }
      }
      wg_commit();
      OPQ;
      named_bar_sync(NB_DU, 256);
      wg_wait<0>();
      PROF(1, 13);
      const uint32_t tb = ISV ? (ph ? VX2 : VX) : QK;
      tok_store<ISV, 1, true>(x1, tb, tid);
      tok_store<ISV, 0, true>(x0, tb, tid);
      if (ISV && s + 2 < cfg::NSEG) {
        fence_proxy_async_smem();
        named_bar_sync(NB_W1, 128);
        if (warp >= 2) {
          if (s >= 0) mbar_spin(B_PF, s & 1);
          const uint32_t peer = warp == 2 ? peer0 : peer1;
          if (elect_one()) bulk_s2s(peer + VX, tb, 8192, peer + B_VX);
        }
      }
      wsa = WS + ((mi >> 1) * 8 + mr) * 128 + (((2 * w + (mi & 1)) ^ mr) << 4);
      mba = MEMB + lane * 16;
      PIN(wsa); PIN(mba);
      proj_mem_prefetch<1>(ta, wsa);
      PROF(1, 14);
      named_bar_sync(NB_M1, 256);
    }
  }
}

template <bool ISV, int WG>
__device__ __forceinline__ void f_main(const FParams& P, const int h, const int rank) {
  using namespace fk;
  const uint32_t self = mapa(0, rank);
  SMAP;
  const int tid = __shfl_sync(0xffffffffu, threadIdx.x, threadIdx.x & 31);
  const int tile0 = rank * 22, ntile = ISV ? 20 : 22;
  const CUtensorMap* m0 = ISV ? &P.wv : &P.wq;
  const CUtensorMap* m1 = ISV ? &P.wv : &P.wk;
  const int col0 = h * 128 + (ISV ? 0 : 64 * rank), col1 = h * 128 + (ISV ? 64 : 64 * rank);
  if (threadIdx.x == 0) {
#pragma unroll 1
    for (int i = 0; i < 6; i++) {
      mbar_expect_tx(B_PB + 8 * i, 32768);
#pragma unroll
      for (int g = 0; g < 2; g++) {
        const int row = Chunks<ISV>::rf(g, i) * 64;
        tma_load_2d(SM0 + i * 32768 + g * 16384, m0, col0, row, B_PB + 8 * i);
        tma_load_2d(SM0 + i * 32768 + g * 16384 + 8192, m1, col1, row, B_PB + 8 * i);
      }
    }
  }
  __syncwarp();
  WRegs wr;
  {
    OPQ;
    const uint32_t a = SM0 + WG * 16384 + ((mi >> 1) * 8 + mr) * 128 + (((2 * w + (mi & 1)) ^ mr) << 4);
#pragma unroll
    for (int i = 0; i < 6; i++) {
      mbar_wait(B_PB + 8 * i, 0);
#pragma unroll
      for (int T = 0; T < 2; T++)
#pragma unroll
        for (int u = 0; u < 4; u++) ldsm4t(wr[i][T][u], a + i * 32768 + T * 8192 + u * 2048);
      named_bar_sync(NB_C, 256);
      if (WG == 1 && i < 5 && threadIdx.x == 128 + 32 * (i & 3)) {
        const int t0 = 8 * i, t1 = i < 3 ? min(8 * i + 8, ntile) : t0, p0 = i == 2 ? 0 : i == 3 ? 1 : 5, p1 = i < 2 ? p0 : i == 2 ? 1 : i == 3 ? 5 : 8;
        mbar_expect_tx(B_W, (t1 - t0) * 4096 + (p1 - p0) * 8192);
#pragma unroll 1
        for (int p = p0; p < p1; p++) tma_load_2d(WS + p * 8192, (p & 1) ? m1 : m0, (p & 1) ? col1 : col0, (Chunks<ISV>::SC0 + (p >> 1)) * 64, B_W);
#pragma unroll 1
        for (int t = t0; t < t1; t++) tma_load_2d(WO + t * 4096, &P.wo, (tile0 + t) * 16, h * 128, B_W);
      }
      __syncwarp();
    }
  }
  PROF2(1);
  pdl_wait();
  pdl_launch_dependents();
  if (threadIdx.x == 224) load_xn(P, 0, self);
  __syncwarp();
  mbar_wait(B_W, 0);
  PROF2(4);
  GTSYNC(0);
  uint32_t sel = 0;
  {
    OPQ;
    const int j = 2 * h + rank;
    if (WG == 0) {
      if (lane == 0) {
        char* p = P.xch + H1_BYTES + w * 8192 + (blockIdx.x & 31) * 128;
        sel = (probe_pair(p, EMPTY, PROBE + 32) << 8) | (probe_pair(p + 32768, EMPTY, PROBE + 32) << 9);
      }
    } else if (!ISV) {
      char* p = P.xch + j * 32768 + w * 8192;
      if (lane == 0) sel = probe_pair(p, 0, PROBE + 32) << 7;
      sel = __shfl_sync(0xffffffffu, sel, 0);
#pragma unroll
      for (int i = 0; i < 8; i++) st_pub128(p + (sel >> 7) * 4096 + i * 512 + lane * 16, 0);
      st_pub64(P.xch + H1_BYTES + (w >> 1) * 32768 + (j >> 4) * 8192 + (w & 1) * 4096 + (j & 15) * 256 + lane * 8, EMPTY, EMPTY);
      if (t7 < 8) st_pub16(P.xch + FL_OFF + (lane & 1) * 4096 + (lane >> 1) * 128 + j * 2, 0);
      if (lane == 0) sts32(PROBE + w * 4, sel >> 7);
      __threadfence();
      named_bar_sync(NB_W1, 128);
      if (t7 == 0) {
        const uint32_t m = 0x10 | lds32(PROBE) | (lds32(PROBE + 4) << 1) | (lds32(PROBE + 8) << 2) | (lds32(PROBE + 12) << 3);
        asm volatile("st.release.gpu.global.u32 [%0], %1;" ::"l"(&g_mask[j]), "r"(m) : "memory");
      }
    }
    sel = __shfl_sync(0xffffffffu, sel, 0);
  }
  PROF2(3);
  {
    OPQ;
    if (WG == 1 && w == 1) {
      uint2 v;
#pragma unroll 1
      for (int tries = 0; tries < POLL_TRIES; tries++) {
        v = ld_strong8(&g_mask[2 * lane]);
        if (__all_sync(0xffffffffu, v.x & v.y & 0x10)) break;
        __nanosleep(100);
      }
      __threadfence();
      sts64(MASKS + lane * 8, v.x, v.y);
    }
    named_bar_sync(NB_C, 256);
#pragma unroll
    for (int i = 0; i < 3; i++) {
      const int t = min(tile0 + 8 * i + w + (WG ? 0 : 4), 63);
      sel |= ((lds32(MASKS + t * 4) >> (h >> 3)) & 1) << (2 * i + 1);
    }
  }
  PROF2(2);
  KT_END(8);
  if (WG == 0) f_wg0<ISV>(P, wr, h, rank, sel, tid); else f_wg1<ISV>(P, wr, h, rank, sel, tid);
}

__global__ void __launch_bounds__(256, 1) f_kernel(const __grid_constant__ FParams P) {
  using namespace fk;
  extern __shared__ __align__(1024) uint8_t smem_f[];
  uint32_t rank;
  asm("mov.u32 %0, %%cluster_ctarank;" : "=r"(rank));
  const int h = blockIdx.x / 3;
  if (smem_u32(smem_f) != mapa(0, rank) + SM0) return;
  SCHED_DECL(threadIdx.x * P.one);
  PROF2(0);
  KT_START(1);
  if (threadIdx.x == 0) {
    const bool isv = rank == 2;
    const uint32_t self = mapa(0, rank);
    SMAP;
    for (int i = 0; i < 2; i++) mbar_init(B_XN + 8 * i, 1);
    for (int i = 0; i < 4; i++) mbar_init(B_H2 + 8 * i, 1);
    mbar_init(B_SM, isv ? 1 : 6);
    mbar_init(B_VM, isv ? 8 : 1);
    mbar_init(B_VX, 1);
    mbar_init(B_ST, 1);
    mbar_init(B_PF, 2);
    for (int i = 0; i < 6; i++) mbar_init(B_PB + 8 * i, 1);
    mbar_init(B_W, 5);
    fence_barrier_init();
    mbar_expect_tx(B_SM, isv ? 2 * SP_SRC : SP_SRC);
    if (isv) mbar_expect_tx(B_ST, 7168);
    else { mbar_expect_tx(B_VM, 2048); mbar_expect_tx(B_VX, 8192); }
  }
  __syncthreads();
  cluster_sync();
  const int wg = __shfl_sync(0xffffffffu, threadIdx.x >> 7, 0);
  if (rank == 2) { if (wg == 0) f_main<true, 0>(P, h, 2); else f_main<true, 1>(P, h, 2); }
  else { if (wg == 0) f_main<false, 0>(P, h, rank); else f_main<false, 1>(P, h, rank); }
  PROF2(5);
  GTSYNC(1);
  KT_END(1);
  __syncwarp();
  cluster_sync();
}

__device__ void reset_exchange(int gtid, int nthreads) {
  if (gtid < 16) g_oflag[gtid] = 0;
  if (gtid < 64) g_gflag[gtid] = 0;
}

__device__ bf16 g_xn[cfg::S * cfg::D];
__device__ bf16 g_xn2[cfg::S * cfg::D];
__device__ bf16 g_h[cfg::S * cfg::D];
__device__ bf16 g_x1[cfg::S * cfg::D];
__device__ bf16 g_x1n[cfg::S * cfg::D];
__device__ bf16 g_u[cfg::S * cfg::F];
__device__ bf16 g_g[cfg::S * cfg::D];
__device__ bf16 g_o[cfg::S * cfg::HD];

typedef CUresult (*PFN_encodeTiled)(CUtensorMap*, CUtensorMapDataType, cuuint32_t, void*, const cuuint64_t*,
                                    const cuuint64_t*, const cuuint32_t*, const cuuint32_t*, CUtensorMapInterleave,
                                    CUtensorMapSwizzle, CUtensorMapL2promotion, CUtensorMapFloatOOBfill);

static PFN_encodeTiled get_encoder() {
  static PFN_encodeTiled fn = nullptr;
  if (!fn) {
    void* p = nullptr;
    cudaDriverEntryPointQueryResult st;
    cudaGetDriverEntryPoint("cuTensorMapEncodeTiled", &p, cudaEnableDefault, &st);
    fn = (PFN_encodeTiled)p;
  }
  return fn;
}
static CUtensorMap make_map(const void* ptr, int rows, int cols, int box_rows, int box_cols, int swizzle_bytes) {
  CUtensorMap m;
  cuuint64_t dims[2] = {(cuuint64_t)cols, (cuuint64_t)rows};
  cuuint64_t strides[1] = {(cuuint64_t)cols * 2};
  cuuint32_t box[2] = {(cuuint32_t)box_cols, (cuuint32_t)box_rows};
  cuuint32_t estr[2] = {1, 1};
  CUtensorMapSwizzle sw = swizzle_bytes == 128 ? CU_TENSOR_MAP_SWIZZLE_128B
                        : swizzle_bytes == 64 ? CU_TENSOR_MAP_SWIZZLE_64B
                        : swizzle_bytes == 32 ? CU_TENSOR_MAP_SWIZZLE_32B : CU_TENSOR_MAP_SWIZZLE_NONE;
  get_encoder()(&m, CU_TENSOR_MAP_DATA_TYPE_BFLOAT16, 2, const_cast<void*>(ptr), dims, strides, box, estr,
                CU_TENSOR_MAP_INTERLEAVE_NONE, sw, CU_TENSOR_MAP_L2_PROMOTION_L2_128B, CU_TENSOR_MAP_FLOAT_OOB_FILL_NONE);
  return m;
}
static CUtensorMap make_map3(const void* ptr, int rows, int cols, int box_rows, int nblk) {
  CUtensorMap m;
  cuuint64_t dims[3] = {64, (cuuint64_t)rows, (cuuint64_t)(cols / 64)};
  cuuint64_t strides[2] = {(cuuint64_t)cols * 2, 128};
  cuuint32_t box[3] = {64, (cuuint32_t)box_rows, (cuuint32_t)nblk};
  cuuint32_t estr[3] = {1, 1, 1};
  get_encoder()(&m, CU_TENSOR_MAP_DATA_TYPE_BFLOAT16, 3, const_cast<void*>(ptr), dims, strides, box, estr,
                CU_TENSOR_MAP_INTERLEAVE_NONE, CU_TENSOR_MAP_SWIZZLE_128B, CU_TENSOR_MAP_L2_PROMOTION_L2_128B,
                CU_TENSOR_MAP_FLOAT_OOB_FILL_NONE);
  return m;
}
template <class T> static T* sym(T& s) { void* p = nullptr; cudaGetSymbolAddress(&p, s); return (T*)p; }
#define SYM(name) ((bf16*)[] { void* p = nullptr; cudaGetSymbolAddress(&p, name); return p; }())

template <class... KArgs, class... Args>
static void launch_pdl(void (*kern)(KArgs...), dim3 grid, dim3 block, int smem, cudaStream_t st, Args... args) {
  cudaLaunchConfig_t cfg = {};
  cfg.gridDim = grid; cfg.blockDim = block; cfg.dynamicSmemBytes = smem; cfg.stream = st;
  cudaLaunchAttribute at[1];
  at[0].id = cudaLaunchAttributeProgrammaticStreamSerialization;
  at[0].val.programmaticStreamSerializationAllowed = 1;
  cfg.attrs = at; cfg.numAttrs = 1;
  cudaLaunchKernelEx(&cfg, kern, KArgs(args)...);
}

template <class... KArgs, class... Args>
static void launch_cluster2(void (*kern)(KArgs...), int grid, int smem, cudaStream_t st, Args... args) {
  cudaFuncSetAttribute(kern, cudaFuncAttributeMaxDynamicSharedMemorySize, smem);
  cudaLaunchConfig_t cfg = {};
  cfg.gridDim = dim3(grid); cfg.blockDim = dim3(288); cfg.dynamicSmemBytes = smem; cfg.stream = st;
  cudaLaunchAttribute at[2];
  at[0].id = cudaLaunchAttributeClusterDimension;
  at[0].val.clusterDim.x = 2; at[0].val.clusterDim.y = 1; at[0].val.clusterDim.z = 1;
  at[1].id = cudaLaunchAttributeProgrammaticStreamSerialization;
  at[1].val.programmaticStreamSerializationAllowed = 1;
  cfg.attrs = at; cfg.numAttrs = 2;
  cudaLaunchKernelEx(&cfg, kern, KArgs(args)...);
}
template <int BN, int STAGES, int EPI, bool SHIFT>
static void launch_gemm(cudaStream_t st, const bf16* A, const bf16* B, bf16* Cp, const bf16* R0, int M, int N, int K) {
  using C = GemmCfg<BN, STAGES, EPI, false>;
  CUtensorMap tA = make_map(A, M, K, 128, 64, 128);
  CUtensorMap tB = make_map(B, K, N, 64, 64, 128);
  CUtensorMap tC = make_map(Cp, M, N, 64, 64, 128);
  CUtensorMap tR0 = R0 ? make_map(R0, M, N, 64, 64, 128) : make_map(Cp, M, N, 64, 32, 64);
  launch_cluster2(gemm_kernel<BN, STAGES, EPI, SHIFT>, (N / BN) * (M / 128), C::SMEM, st, tA, tB, tC, tR0, K, N / BN);
}
static void launch_gate_out(cudaStream_t st, const bf16* u, const bf16* w4, bf16* g, const bf16* x1, const bf16* o,
                            const bf16* Wo, bf16* out, const bf16* x) {
  using namespace cfg;
  using C = GemmCfg<256, 4, EPI_FINAL, true>;
  launch_cluster2(gemm_gate_out_kernel, 128, C::SMEM, st, make_map(u, S, F, 128, 64, 128), make_map(w4, F, D, 64, 64, 128),
                  make_map(g, S, D, 64, 64, 128), make_map(x1, S, D, 64, 64, 128), make_map(o, S, HD, 128, 64, 128),
                  make_map(Wo, HD, D, 64, 64, 128), make_map(out, S, D, 64, 64, 128), make_map(x, S, D, 64, 64, 128));
}

#define GEMM_B1 launch_gemm<128, 6, EPI_GELU, false>(st, xn2, w1, hb, nullptr, S, D, D)
#define GEMM_B2 launch_gemm<128, 5, EPI_RES, true>(st, hb, w2, x1, xn, S, D, D)
#define GEMM_B3 launch_gemm<224, 4, EPI_GELU, false>(st, x1n, w3, u, nullptr, S, F, D)
#define GEMM_GO launch_gate_out(st, u, w4, g, x1, o, Wo, out, x)
__global__ void reset_flags() { if (threadIdx.x < 64) g_gflag[threadIdx.x] = 0; }

extern "C" void kernel_launch(void* const* d_in, const int* in_sizes, int n_in, void* d_out, int out_size) {
  using namespace cfg;
  const bf16* x = (const bf16*)d_in[0];
  const bf16* mem0 = (const bf16*)d_in[1];
  const bf16* Wq = (const bf16*)d_in[2];
  const bf16* Wk = (const bf16*)d_in[3];
  const bf16* Wv = (const bf16*)d_in[4];
  const bf16* Wo = (const bf16*)d_in[5];
  const bf16* w1 = (const bf16*)d_in[8];
  const bf16* w2 = (const bf16*)d_in[9];
  const bf16* w3 = (const bf16*)d_in[10];
  const bf16* w4 = (const bf16*)d_in[11];
  bf16* out = (bf16*)d_out;
  cudaStream_t st = cudaStreamPerThread;

  bf16 *xn = SYM(g_xn), *xn2 = SYM(g_xn2), *hb = SYM(g_h), *x1 = SYM(g_x1), *x1n = SYM(g_x1n), *u = SYM(g_u),
       *g = SYM(g_g), *o = SYM(g_o);

  static cudaStream_t st2 = nullptr;
  static cudaEvent_t ev_fork = nullptr, ev_join = nullptr;
  if (!st2) {
    cudaStreamCreateWithFlags(&st2, cudaStreamNonBlocking);
    cudaEventCreateWithFlags(&ev_fork, cudaEventDisableTiming);
    cudaEventCreateWithFlags(&ev_join, cudaEventDisableTiming);
  }

  launch_pdl(ln_kernel<true>, dim3(S / 8), dim3(256), 0, st, x, xn, xn2);
  cudaEventRecord(ev_fork, st);
  cudaStreamWaitEvent(st2, ev_fork, 0);
  {
    cudaFuncSetAttribute(f_kernel, cudaFuncAttributeMaxDynamicSharedMemorySize, fk::SMEM);
    FParams P;
    P.wq = make_map(Wq, D, HD, 64, 64, 128); P.wk = make_map(Wk, D, HD, 64, 64, 128); P.wv = make_map(Wv, D, HD, 64, 64, 128);
    P.wo = make_map(Wo, HD, D, 128, 16, 32); P.xn = make_map3(xn, S, D, 32, 4); P.xn12 = make_map3(xn, S, D, 32, 12); P.o = make_map3(o, S, HD, 32, 2);
    P.mem0 = mem0;
    P.one = 1;
    P.xch = (char*)(((uintptr_t)SYM(g_xch) + 8191) & ~(uintptr_t)8191);
    cudaLaunchConfig_t cfg = {};
    cfg.gridDim = dim3(96); cfg.blockDim = dim3(256); cfg.dynamicSmemBytes = fk::SMEM; cfg.stream = st;
    cudaLaunchAttribute at[2];
    at[0].id = cudaLaunchAttributeClusterDimension;
    at[0].val.clusterDim.x = 3; at[0].val.clusterDim.y = 1; at[0].val.clusterDim.z = 1;
    at[1].id = cudaLaunchAttributeProgrammaticStreamSerialization;
    at[1].val.programmaticStreamSerializationAllowed = 1;
    cfg.attrs = at; cfg.numAttrs = 2;
    cudaLaunchKernelEx(&cfg, f_kernel, P);
  }
  cudaFuncSetAttribute(gemm_bg_gelu_kernel, cudaFuncAttributeMaxDynamicSharedMemorySize, BG_SMEM);
  gemm_bg_gelu_kernel<<<36, 288, BG_SMEM, st2>>>(make_map(xn2, S, D, 128, 64, 128), make_map(w1, D, D, 64, 64, 128),
                                                make_map(hb, S, D, 64, 64, 128), D / 64, D / 128, (S / 128) * (D / 128));
  {
    cudaStream_t st = st2;
    GEMM_B2;
    launch_pdl(ln_kernel<false>, dim3(S / 8), dim3(256), 0, st, x1, x1n, nullptr);
    GEMM_B3;
  }
  cudaEventRecord(ev_join, st2);
  cudaStreamWaitEvent(st, ev_join, 0);
  GEMM_GO;
}
```

```cpp
#include <cuda_runtime.h>
#include <cuda_bf16.h>
#include <cuda.h>
#include <stdint.h>

typedef __nv_bfloat16 bf16;

namespace cfg {
constexpr int S = 2048;
constexpr int D = 1024;
constexpr int H = 32;
constexpr int DH = 128;
constexpr int HD = H * DH;
constexpr int M = 8;
constexpr int SEG = 32;
constexpr int NSEG = S / SEG;
constexpr int F = 3584;
}

__device__ __forceinline__ uint32_t smem_u32(const void* p) { return (uint32_t)__cvta_generic_to_shared(p); }

__device__ __forceinline__ void mbar_init(uint32_t bar, uint32_t count) {
  asm volatile("mbarrier.init.shared::cta.b64 [%0], %1;" ::"r"(bar), "r"(count) : "memory");
}
__device__ __forceinline__ void mbar_expect_tx(uint32_t bar, uint32_t bytes) {
  asm volatile("mbarrier.arrive.expect_tx.shared::cta.b64 _, [%0], %1;" ::"r"(bar), "r"(bytes) : "memory");
}
__device__ __forceinline__ void mbar_arrive(uint32_t bar) {
  asm volatile("mbarrier.arrive.shared::cta.b64 _, [%0];" ::"r"(bar) : "memory");
}
__device__ __forceinline__ bool mbar_try(uint32_t bar, uint32_t parity) {
  uint32_t done;
  asm volatile("{\n.reg .pred p;\nmbarrier.try_wait.parity.shared::cta.b64 p, [%1], %2, 20000;\nselp.u32 %0, 1, 0, p;\n}"
               : "=r"(done) : "r"(bar), "r"(parity) : "memory");
  return done != 0;
}
__device__ __forceinline__ bool mbar_try_nohint(uint32_t bar, uint32_t parity) {
  uint32_t done;
  asm volatile("{\n.reg .pred p;\nmbarrier.try_wait.parity.shared::cta.b64 p, [%1], %2;\nselp.u32 %0, 1, 0, p;\n}"
               : "=r"(done) : "r"(bar), "r"(parity) : "memory");
  return done != 0;
}
constexpr int MBAR_TRIES = 4096;
constexpr int POLL_TRIES = 1 << 16;
__device__ __forceinline__ void mbar_wait(uint32_t bar, uint32_t parity) {
#pragma unroll 1
  for (int n = 0; n < MBAR_TRIES; n++)
    if (mbar_try(bar, parity)) break;
}
__device__ __forceinline__ void mbar_wait_fast(uint32_t bar, uint32_t parity) {
#pragma unroll 1
  for (int n = 0; n < (POLL_TRIES << 4); n++)
    if (mbar_try_nohint(bar, parity)) break;
}
__device__ __forceinline__ void fence_barrier_init() { asm volatile("fence.mbarrier_init.release.cluster;" ::: "memory"); }
__device__ __forceinline__ void fence_proxy_async_smem() { asm volatile("fence.proxy.async.shared::cta;" ::: "memory"); }

__device__ __forceinline__ void tma_load_2d(uint32_t dst, const CUtensorMap* map, int x, int y, uint32_t bar) {
  asm volatile("cp.async.bulk.tensor.2d.shared::cluster.global.mbarrier::complete_tx::bytes [%0], [%1, {%3, %4}], [%2];"
               ::"r"(dst), "l"(map), "r"(bar), "r"(x), "r"(y) : "memory");
}
__device__ __forceinline__ void tma_load_3d(uint32_t dst, const CUtensorMap* map, int x, int y, int z, uint32_t bar) {
  asm volatile("cp.async.bulk.tensor.3d.shared::cluster.global.mbarrier::complete_tx::bytes [%0], [%1, {%3, %4, %5}], [%2];"
               ::"r"(dst), "l"(map), "r"(bar), "r"(x), "r"(y), "r"(z) : "memory");
}
__device__ __forceinline__ void tma_store_2d(const CUtensorMap* map, uint32_t src, int x, int y) {
  asm volatile("cp.async.bulk.tensor.2d.global.shared::cta.bulk_group [%0, {%2, %3}], [%1];"
               ::"l"(map), "r"(src), "r"(x), "r"(y) : "memory");
}
__device__ __forceinline__ void tma_store_commit() { asm volatile("cp.async.bulk.commit_group;" ::: "memory"); }
__device__ __forceinline__ void tma_store_wait_all() { asm volatile("cp.async.bulk.wait_group 0;" ::: "memory"); }
__device__ __forceinline__ void tma_store_wait_read() { asm volatile("cp.async.bulk.wait_group.read 0;" ::: "memory"); }
__device__ __forceinline__ void prefetch_tmap(const CUtensorMap* map) {
  asm volatile("prefetch.tensormap [%0];" ::"l"(map) : "memory");
}

__device__ __forceinline__ void wg_fence() { asm volatile("wgmma.fence.sync.aligned;" ::: "memory"); }
__device__ __forceinline__ void wg_commit() { asm volatile("wgmma.commit_group.sync.aligned;" ::: "memory"); }
template <int N> __device__ __forceinline__ void wg_wait() { asm volatile("wgmma.wait_group.sync.aligned %0;" ::"n"(N) : "memory"); }

#define named_bar_sync(id, n) asm volatile("bar.sync %0, %1;" ::"n"(id), "n"(n) : "memory")
#define named_bar_arrive(id, n) asm volatile("bar.arrive %0, %1;" ::"n"(id), "n"(n) : "memory")

__device__ __forceinline__ uint64_t make_desc(uint32_t addr, uint32_t lbo, uint32_t sbo) {
  return (uint64_t)((addr & 0x3FFFF) >> 4) | ((uint64_t)(lbo >> 4) << 16) | ((uint64_t)(sbo >> 4) << 32) | (1ull << 62);
}

__device__ __forceinline__ uint32_t pack_bf16(float lo, float hi) {
  uint32_t r;
  asm("cvt.rn.bf16x2.f32 %0, %1, %2;" : "=r"(r) : "f"(hi), "f"(lo));
  return r;
}
__device__ __forceinline__ float bf_lo(uint32_t v) { return __uint_as_float(v << 16); }
__device__ __forceinline__ float bf_hi(uint32_t v) { return __uint_as_float(v & 0xFFFF0000u); }
__device__ __forceinline__ float rbf(float v) { return __bfloat162float(__float2bfloat16_rn(v)); }

__device__ __forceinline__ void pdl_launch_dependents() { asm volatile("griddepcontrol.launch_dependents;" ::: "memory"); }
__device__ __forceinline__ void pdl_wait() { asm volatile("griddepcontrol.wait;" ::: "memory"); }

__device__ __forceinline__ float ex2_approx(float x) { float y; asm("ex2.approx.ftz.f32 %0, %1;" : "=f"(y) : "f"(x)); return y; }
__device__ __forceinline__ float rcp_approx(float x) { float y; asm("rcp.approx.ftz.f32 %0, %1;" : "=f"(y) : "f"(x)); return y; }

__device__ __forceinline__ void mul_sigmoid4(float (&v)[4], const float (&t)[4]) {
#pragma unroll
  for (int i = 0; i < 4; i += 2) {
    const float a = 1.0f + ex2_approx(fminf(t[i], 60.0f)), b = 1.0f + ex2_approx(fminf(t[i + 1], 60.0f));
    const float r = rcp_approx(a * b);
    v[i] *= b * r;
    v[i + 1] *= a * r;
  }
}
__device__ __forceinline__ void gelu4(float (&v)[4]) {
  float t[4];
#pragma unroll
  for (int i = 0; i < 4; i++) t[i] = v[i] * fmaf(v[i] * v[i], -0.10294324f, -2.30220819f);
  mul_sigmoid4(v, t);
}
__device__ __forceinline__ void silu4(float (&v)[4]) {
  float t[4];
#pragma unroll
  for (int i = 0; i < 4; i++) t[i] = v[i] * -1.4426950408889634f;
  mul_sigmoid4(v, t);
}

#define KT_START(id)
#define KT_END(id)

__device__ __forceinline__ void wgmma_ss_n128_tb(float (&d)[64], uint64_t da, uint64_t db, int scale_d) {
  asm volatile("{\n.reg .pred p;\nsetp.ne.b32 p, %66, 0;\n"
    "wgmma.mma_async.sync.aligned.m64n128k16.f32.bf16.bf16 "
    "{%0, %1, %2, %3, %4, %5, %6, %7, %8, %9, %10, %11, %12, %13, %14, %15, "
    "%16, %17, %18, %19, %20, %21, %22, %23, %24, %25, %26, %27, %28, %29, %30, %31, "
    "%32, %33, %34, %35, %36, %37, %38, %39, %40, %41, %42, %43, %44, %45, %46, %47, "
    "%48, %49, %50, %51, %52, %53, %54, %55, %56, %57, %58, %59, %60, %61, %62, %63}, "
    "%64, %65, p, 1, 1, 0, 1;\n}\n"
    : "+f"(d[0]), "+f"(d[1]), "+f"(d[2]), "+f"(d[3]), "+f"(d[4]), "+f"(d[5]), "+f"(d[6]), "+f"(d[7]),
      "+f"(d[8]), "+f"(d[9]), "+f"(d[10]), "+f"(d[11]), "+f"(d[12]), "+f"(d[13]), "+f"(d[14]), "+f"(d[15]),
      "+f"(d[16]), "+f"(d[17]), "+f"(d[18]), "+f"(d[19]), "+f"(d[20]), "+f"(d[21]), "+f"(d[22]), "+f"(d[23]),
      "+f"(d[24]), "+f"(d[25]), "+f"(d[26]), "+f"(d[27]), "+f"(d[28]), "+f"(d[29]), "+f"(d[30]), "+f"(d[31]),
      "+f"(d[32]), "+f"(d[33]), "+f"(d[34]), "+f"(d[35]), "+f"(d[36]), "+f"(d[37]), "+f"(d[38]), "+f"(d[39]),
      "+f"(d[40]), "+f"(d[41]), "+f"(d[42]), "+f"(d[43]), "+f"(d[44]), "+f"(d[45]), "+f"(d[46]), "+f"(d[47]),
      "+f"(d[48]), "+f"(d[49]), "+f"(d[50]), "+f"(d[51]), "+f"(d[52]), "+f"(d[53]), "+f"(d[54]), "+f"(d[55]),
      "+f"(d[56]), "+f"(d[57]), "+f"(d[58]), "+f"(d[59]), "+f"(d[60]), "+f"(d[61]), "+f"(d[62]), "+f"(d[63])
    : "l"(da), "l"(db), "r"(scale_d));
}
__device__ __forceinline__ void wgmma_ss_n224_tb(float (&d)[112], uint64_t da, uint64_t db, int scale_d) {
  asm volatile("{\n.reg .pred p;\nsetp.ne.b32 p, %114, 0;\n"
    "wgmma.mma_async.sync.aligned.m64n224k16.f32.bf16.bf16 "
    "{%0, %1, %2, %3, %4, %5, %6, %7, %8, %9, %10, %11, %12, %13, %14, %15, "
    "%16, %17, %18, %19, %20, %21, %22, %23, %24, %25, %26, %27, %28, %29, %30, %31, "
    "%32, %33, %34, %35, %36, %37, %38, %39, %40, %41, %42, %43, %44, %45, %46, %47, "
    "%48, %49, %50, %51, %52, %53, %54, %55, %56, %57, %58, %59, %60, %61, %62, %63, "
    "%64, %65, %66, %67, %68, %69, %70, %71, %72, %73, %74, %75, %76, %77, %78, %79, "
    "%80, %81, %82, %83, %84, %85, %86, %87, %88, %89, %90, %91, %92, %93, %94, %95, "
    "%96, %97, %98, %99, %100, %101, %102, %103, %104, %105, %106, %107, %108, %109, %110, %111}, "
    "%112, %113, p, 1, 1, 0, 1;\n}\n"
    : "+f"(d[0]), "+f"(d[1]), "+f"(d[2]), "+f"(d[3]), "+f"(d[4]), "+f"(d[5]), "+f"(d[6]), "+f"(d[7]),
      "+f"(d[8]), "+f"(d[9]), "+f"(d[10]), "+f"(d[11]), "+f"(d[12]), "+f"(d[13]), "+f"(d[14]), "+f"(d[15]),
      "+f"(d[16]), "+f"(d[17]), "+f"(d[18]), "+f"(d[19]), "+f"(d[20]), "+f"(d[21]), "+f"(d[22]), "+f"(d[23]),
      "+f"(d[24]), "+f"(d[25]), "+f"(d[26]), "+f"(d[27]), "+f"(d[28]), "+f"(d[29]), "+f"(d[30]), "+f"(d[31]),
      "+f"(d[32]), "+f"(d[33]), "+f"(d[34]), "+f"(d[35]), "+f"(d[36]), "+f"(d[37]), "+f"(d[38]), "+f"(d[39]),
      "+f"(d[40]), "+f"(d[41]), "+f"(d[42]), "+f"(d[43]), "+f"(d[44]), "+f"(d[45]), "+f"(d[46]), "+f"(d[47]),
      "+f"(d[48]), "+f"(d[49]), "+f"(d[50]), "+f"(d[51]), "+f"(d[52]), "+f"(d[53]), "+f"(d[54]), "+f"(d[55]),
      "+f"(d[56]), "+f"(d[57]), "+f"(d[58]), "+f"(d[59]), "+f"(d[60]), "+f"(d[61]), "+f"(d[62]), "+f"(d[63]),
      "+f"(d[64]), "+f"(d[65]), "+f"(d[66]), "+f"(d[67]), "+f"(d[68]), "+f"(d[69]), "+f"(d[70]), "+f"(d[71]),
      "+f"(d[72]), "+f"(d[73]), "+f"(d[74]), "+f"(d[75]), "+f"(d[76]), "+f"(d[77]), "+f"(d[78]), "+f"(d[79]),
      "+f"(d[80]), "+f"(d[81]), "+f"(d[82]), "+f"(d[83]), "+f"(d[84]), "+f"(d[85]), "+f"(d[86]), "+f"(d[87]),
      "+f"(d[88]), "+f"(d[89]), "+f"(d[90]), "+f"(d[91]), "+f"(d[92]), "+f"(d[93]), "+f"(d[94]), "+f"(d[95]),
      "+f"(d[96]), "+f"(d[97]), "+f"(d[98]), "+f"(d[99]), "+f"(d[100]), "+f"(d[101]), "+f"(d[102]), "+f"(d[103]),
      "+f"(d[104]), "+f"(d[105]), "+f"(d[106]), "+f"(d[107]), "+f"(d[108]), "+f"(d[109]), "+f"(d[110]), "+f"(d[111])
    : "l"(da), "l"(db), "r"(scale_d));
}
__device__ __forceinline__ void wgmma_ss_n256_tb(float (&d)[128], uint64_t da, uint64_t db, int scale_d) {
  asm volatile("{\n.reg .pred p;\nsetp.ne.b32 p, %130, 0;\n"
    "wgmma.mma_async.sync.aligned.m64n256k16.f32.bf16.bf16 "
    "{%0, %1, %2, %3, %4, %5, %6, %7, %8, %9, %10, %11, %12, %13, %14, %15, "
    "%16, %17, %18, %19, %20, %21, %22, %23, %24, %25, %26, %27, %28, %29, %30, %31, "
    "%32, %33, %34, %35, %36, %37, %38, %39, %40, %41, %42, %43, %44, %45, %46, %47, "
    "%48, %49, %50, %51, %52, %53, %54, %55, %56, %57, %58, %59, %60, %61, %62, %63, "
    "%64, %65, %66, %67, %68, %69, %70, %71, %72, %73, %74, %75, %76, %77, %78, %79, "
    "%80, %81, %82, %83, %84, %85, %86, %87, %88, %89, %90, %91, %92, %93, %94, %95, "
    "%96, %97, %98, %99, %100, %101, %102, %103, %104, %105, %106, %107, %108, %109, %110, %111, "
    "%112, %113, %114, %115, %116, %117, %118, %119, %120, %121, %122, %123, %124, %125, %126, %127}, "
    "%128, %129, p, 1, 1, 0, 1;\n}\n"
    : "+f"(d[0]), "+f"(d[1]), "+f"(d[2]), "+f"(d[3]), "+f"(d[4]), "+f"(d[5]), "+f"(d[6]), "+f"(d[7]),
      "+f"(d[8]), "+f"(d[9]), "+f"(d[10]), "+f"(d[11]), "+f"(d[12]), "+f"(d[13]), "+f"(d[14]), "+f"(d[15]),
      "+f"(d[16]), "+f"(d[17]), "+f"(d[18]), "+f"(d[19]), "+f"(d[20]), "+f"(d[21]), "+f"(d[22]), "+f"(d[23]),
      "+f"(d[24]), "+f"(d[25]), "+f"(d[26]), "+f"(d[27]), "+f"(d[28]), "+f"(d[29]), "+f"(d[30]), "+f"(d[31]),
      "+f"(d[32]), "+f"(d[33]), "+f"(d[34]), "+f"(d[35]), "+f"(d[36]), "+f"(d[37]), "+f"(d[38]), "+f"(d[39]),
      "+f"(d[40]), "+f"(d[41]), "+f"(d[42]), "+f"(d[43]), "+f"(d[44]), "+f"(d[45]), "+f"(d[46]), "+f"(d[47]),
      "+f"(d[48]), "+f"(d[49]), "+f"(d[50]), "+f"(d[51]), "+f"(d[52]), "+f"(d[53]), "+f"(d[54]), "+f"(d[55]),
      "+f"(d[56]), "+f"(d[57]), "+f"(d[58]), "+f"(d[59]), "+f"(d[60]), "+f"(d[61]), "+f"(d[62]), "+f"(d[63]),
      "+f"(d[64]), "+f"(d[65]), "+f"(d[66]), "+f"(d[67]), "+f"(d[68]), "+f"(d[69]), "+f"(d[70]), "+f"(d[71]),
      "+f"(d[72]), "+f"(d[73]), "+f"(d[74]), "+f"(d[75]), "+f"(d[76]), "+f"(d[77]), "+f"(d[78]), "+f"(d[79]),
      "+f"(d[80]), "+f"(d[81]), "+f"(d[82]), "+f"(d[83]), "+f"(d[84]), "+f"(d[85]), "+f"(d[86]), "+f"(d[87]),
      "+f"(d[88]), "+f"(d[89]), "+f"(d[90]), "+f"(d[91]), "+f"(d[92]), "+f"(d[93]), "+f"(d[94]), "+f"(d[95]),
      "+f"(d[96]), "+f"(d[97]), "+f"(d[98]), "+f"(d[99]), "+f"(d[100]), "+f"(d[101]), "+f"(d[102]), "+f"(d[103]),
      "+f"(d[104]), "+f"(d[105]), "+f"(d[106]), "+f"(d[107]), "+f"(d[108]), "+f"(d[109]), "+f"(d[110]), "+f"(d[111]),
      "+f"(d[112]), "+f"(d[113]), "+f"(d[114]), "+f"(d[115]), "+f"(d[116]), "+f"(d[117]), "+f"(d[118]), "+f"(d[119]),
      "+f"(d[120]), "+f"(d[121]), "+f"(d[122]), "+f"(d[123]), "+f"(d[124]), "+f"(d[125]), "+f"(d[126]), "+f"(d[127])
    : "l"(da), "l"(db), "r"(scale_d));
}
__device__ __forceinline__ void wgmma_rs_n32(float (&d)[16], const uint32_t* a, uint64_t db, int scale_d) {
  asm volatile("{\n.reg .pred p;\nsetp.ne.b32 p, %21, 0;\n"
    "wgmma.mma_async.sync.aligned.m64n32k16.f32.bf16.bf16 "
    "{%0, %1, %2, %3, %4, %5, %6, %7, %8, %9, %10, %11, %12, %13, %14, %15}, "
    "{%16, %17, %18, %19}, %20, p, 1, 1, 0;\n}\n"
    : "+f"(d[0]), "+f"(d[1]), "+f"(d[2]), "+f"(d[3]), "+f"(d[4]), "+f"(d[5]), "+f"(d[6]), "+f"(d[7]),
      "+f"(d[8]), "+f"(d[9]), "+f"(d[10]), "+f"(d[11]), "+f"(d[12]), "+f"(d[13]), "+f"(d[14]), "+f"(d[15])
    : "r"(a[0]), "r"(a[1]), "r"(a[2]), "r"(a[3]), "l"(db), "r"(scale_d));
}
__device__ __forceinline__ void wgmma_ss_n32_ta(float (&d)[16], uint64_t da, uint64_t db, int scale_d) {
  asm volatile("{\n.reg .pred p;\nsetp.ne.b32 p, %18, 0;\n"
    "wgmma.mma_async.sync.aligned.m64n32k16.f32.bf16.bf16 "
    "{%0, %1, %2, %3, %4, %5, %6, %7, %8, %9, %10, %11, %12, %13, %14, %15}, "
    "%16, %17, p, 1, 1, 1, 0;\n}\n"
    : "+f"(d[0]), "+f"(d[1]), "+f"(d[2]), "+f"(d[3]), "+f"(d[4]), "+f"(d[5]), "+f"(d[6]), "+f"(d[7]),
      "+f"(d[8]), "+f"(d[9]), "+f"(d[10]), "+f"(d[11]), "+f"(d[12]), "+f"(d[13]), "+f"(d[14]), "+f"(d[15])
    : "l"(da), "l"(db), "r"(scale_d));
}

#define gwait mbar_wait_fast
enum { EPI_PLAIN = 0, EPI_GELU = 1, EPI_RES = 2, EPI_RES_SILU = 3, EPI_FINAL = 4 };

template <int BN> struct WgAcc;
template <> struct WgAcc<128> { static __device__ __forceinline__ void mma(float (&d)[64], uint64_t a, uint64_t b, int s) { wgmma_ss_n128_tb(d, a, b, s); } };
template <> struct WgAcc<256> { static __device__ __forceinline__ void mma(float (&d)[128], uint64_t a, uint64_t b, int s) { wgmma_ss_n256_tb(d, a, b, s); } };

template <int BN, int STAGES, int EPI, bool ALIAS>
struct GemmCfg {
  static constexpr int NBOX = (BN + 63) / 64;
  static constexpr int A_BYTES = 128 * 128;
  static constexpr int B_BYTES = NBOX * 64 * 128;
  static constexpr int STAGE_BYTES = A_BYTES + B_BYTES;
  static constexpr int NRES = (EPI == EPI_FINAL) ? 2 : (EPI == EPI_RES || EPI == EPI_RES_SILU) ? 1 : 0;
  static constexpr int TILE_BYTES = NBOX * 128 * 128;
  static constexpr int SMEM = STAGES * STAGE_BYTES + (ALIAS ? 0 : NRES * TILE_BYTES) + 1024 + 256;
  static __device__ __forceinline__ constexpr uint32_t piece(int p) {
    return ALIAS ? (p / 3) * STAGE_BYTES + (p % 3) * 16384 : STAGES * STAGE_BYTES + p * 16384;
  }
};

#define GPROF(i)

__device__ __forceinline__ void tma_load_2d_mc(uint32_t dst, const CUtensorMap* map, int x, int y, uint32_t bar) {
  asm volatile("cp.async.bulk.tensor.2d.shared::cluster.global.mbarrier::complete_tx::bytes.multicast::cluster "
               "[%0], [%1, {%3, %4}], [%2], %5;"
               ::"r"(dst), "l"(map), "r"(bar), "r"(x), "r"(y), "h"((uint16_t)3) : "memory");
}
__device__ __forceinline__ void mbar_arrive_cluster(uint32_t bar, uint32_t cta) {
  asm volatile("{\n.reg .b32 r;\nmapa.shared::cluster.u32 r, %0, %1;\nmbarrier.arrive.shared::cluster.b64 _, [r];\n}"
               ::"r"(bar), "r"(cta) : "memory");
}
__device__ __forceinline__ void cluster_sync() {
  asm volatile("barrier.cluster.arrive.release.aligned;\nbarrier.cluster.wait.acquire.aligned;" ::: "memory");
}

template <int BN, int STAGES, int EPI, bool SHIFT_A, bool ALIAS, int FLAG>
__device__ __forceinline__ void gemm_body(const CUtensorMap* tmA, const CUtensorMap* tmB, const CUtensorMap* tmC,
                                          const CUtensorMap* tmC2, const CUtensorMap* tmR0, const CUtensorMap* tmR1,
                                          int K, int mt, int nt, unsigned* gflag) {
  using C = GemmCfg<BN, STAGES, EPI, ALIAS>;
  extern __shared__ uint8_t smem_raw[];
  const uint32_t base = (smem_u32(smem_raw) + 1023u) & ~1023u;
  const uint32_t bar_base = base + STAGES * C::STAGE_BYTES + (ALIAS ? 0 : C::NRES * C::TILE_BYTES);
  auto full = [&](int s) { return bar_base + 8 * s; };
  auto empty = [&](int s) { return bar_base + 8 * (STAGES + s); };
  const uint32_t res_bar = bar_base + 8 * 2 * STAGES;

  const int tid = threadIdx.x, warp = tid >> 5, lane = tid & 31;
  const int rank = blockIdx.x & 1;
  const int n0 = nt * BN, m0 = mt * 128;
  const int nkb = K >> 6;

  GPROF(0);
  KT_START(EPI == EPI_RES ? 3 : EPI == EPI_GELU ? 5 : EPI == EPI_RES_SILU ? 6 : 7);
  if (tid == 0) {
    for (int s = 0; s < STAGES; s++) { mbar_init(full(s), 1); mbar_init(empty(s), 4); }
    mbar_init(res_bar, 1);
    fence_barrier_init();
  }
  __syncthreads();
  cluster_sync();
  pdl_launch_dependents();

  if (warp == 8) {
    if (lane == 0) {
      prefetch_tmap(tmA); prefetch_tmap(tmB); prefetch_tmap(tmC);
      pdl_wait();
      auto load_piece = [&](int p) {
        const CUtensorMap* m = p < C::NBOX ? tmR0 : tmR1;
        const int col = n0 + (p % C::NBOX) * 64;
        tma_load_2d(base + C::piece(p), m, col, m0, res_bar);
        tma_load_2d(base + C::piece(p) + 8192, m, col, m0 + 64, res_bar);
      };
      for (int kb = 0; kb < nkb; kb++) {
        const int s = kb % STAGES;
        if (kb >= STAGES) gwait(empty(s), ((kb / STAGES) - 1) & 1);
        const uint32_t sa = base + s * C::STAGE_BYTES, sb = sa + C::A_BYTES;
        mbar_expect_tx(full(s), C::STAGE_BYTES);
        int arow = m0;
        if (SHIFT_A) { const int q = kb >> 2; arow += (q == 0) ? -1 : (q == 1) ? 1 : (q == 2) ? -2 : 2; }
        tma_load_2d(sa, tmA, kb * 64, arow, full(s));
#pragma unroll
        for (int j = 0; j < C::NBOX / 2; j++) {
          const int jj = rank * (C::NBOX / 2) + j;
          tma_load_2d_mc(sb + jj * 8192, tmB, n0 + jj * 64, kb * 64, full(s));
        }
        if (C::NRES > 0 && !ALIAS && kb == STAGES - 1) {
          mbar_expect_tx(res_bar, C::NRES * C::TILE_BYTES);
#pragma unroll
          for (int p = 0; p < C::NRES * C::NBOX; p++) load_piece(p);
        }
      }
      if (C::NRES > 0 && ALIAS) {
        mbar_expect_tx(res_bar, C::NRES * C::TILE_BYTES);
#pragma unroll
        for (int p = 0; p < C::NRES * C::NBOX; p++) {
          if (p % 3 == 0) gwait(empty(p / 3), ((nkb / STAGES) - 1) & 1);
          if (FLAG == 2 && p == C::NBOX) {
#pragma unroll 1
            for (int tries = 0; tries < (POLL_TRIES << 4); tries++) {
              unsigned v;
              asm volatile("ld.acquire.gpu.global.u32 %0, [%1];" : "=r"(v) : "l"(gflag) : "memory");
              if (v >= 2) break;
            }
            asm volatile("fence.proxy.async;" ::: "memory");
          }
          load_piece(p);
        }
      }
    }
  } else {
    const int wg = warp >> 2;
    float acc[BN / 2];
    pdl_wait();
    for (int kb = 0; kb < nkb; kb++) {
      const int s = kb % STAGES;
      gwait(full(s), (kb / STAGES) & 1);
      if (kb == 0) GPROF(1);
      const uint32_t sa = base + s * C::STAGE_BYTES + wg * 8192, sb = base + s * C::STAGE_BYTES + C::A_BYTES;
      wg_fence();
#pragma unroll
      for (int k = 0; k < 4; k++)
        WgAcc<BN>::mma(acc, make_desc(sa + k * 32, 16, 1024), make_desc(sb + k * 2048, 8192, 1024), (kb | k) != 0);
      wg_commit();
      if (kb > 0) {
        wg_wait<1>();
        if ((tid & 127) < 2) mbar_arrive_cluster(empty((kb - 1) % STAGES), tid & 1);
      }
    }
    wg_wait<0>();
    GPROF(2);
    GPROF(3);
    if (C::NRES > 0) gwait(res_bar, 0);
    else named_bar_sync(1, 256);
    const int r0 = wg * 64 + (warp & 3) * 16 + (lane >> 2);
    const int q = lane & 3;
#pragma unroll
    for (int box = 0; box < C::NBOX; box++) {
      constexpr int NB = C::NBOX;
      const bool half = (BN % 64 != 0) && box == NB - 1;
      const uint32_t pbase = base + (C::NRES > 0 ? C::piece(box) : box * 16384);
#pragma unroll
      for (int grp = 0; grp < (half ? 1 : 2); grp++) {
        uint32_t off[4][2], ra[4][2], rb[4][2];
#pragma unroll
        for (int jj = 0; jj < 4; jj++)
#pragma unroll
          for (int h = 0; h < 2; h++) {
            const int r = r0 + h * 8, unit = grp * 4 + jj;
            off[jj][h] = half ? pbase + r * 64 + ((unit ^ ((r >> 1) & 3)) << 4) + q * 4
                              : pbase + r * 128 + ((unit ^ (r & 7)) << 4) + q * 4;
            if (C::NRES > 0) asm volatile("ld.shared.u32 %0, [%1];" : "=r"(ra[jj][h]) : "r"(off[jj][h]));
            if (C::NRES > 1)
              asm volatile("ld.shared.u32 %0, [%1];" : "=r"(rb[jj][h]) : "r"(off[jj][h] + (C::piece(NB + box) - C::piece(box))));
          }
#pragma unroll
        for (int jj = 0; jj < 4; jj++) {
          const int j = box * 8 + grp * 4 + jj;
          const uint32_t s0 = pack_bf16(acc[j * 4], acc[j * 4 + 1]), s1 = pack_bf16(acc[j * 4 + 2], acc[j * 4 + 3]);
          float v[4] = {bf_lo(s0), bf_hi(s0), bf_lo(s1), bf_hi(s1)};
          if (EPI == EPI_GELU) gelu4(v);
          if (EPI == EPI_RES || EPI == EPI_RES_SILU) {
            v[0] += bf_lo(ra[jj][0]); v[1] += bf_hi(ra[jj][0]); v[2] += bf_lo(ra[jj][1]); v[3] += bf_hi(ra[jj][1]);
            if (EPI == EPI_RES_SILU) {
              const uint32_t y0 = pack_bf16(v[0], v[1]), y1 = pack_bf16(v[2], v[3]);
              v[0] = bf_lo(y0); v[1] = bf_hi(y0); v[2] = bf_lo(y1); v[3] = bf_hi(y1);
              silu4(v);
            }
          }
          if (EPI == EPI_FINAL) {
#pragma unroll
            for (int h = 0; h < 2; h++) {
              const uint32_t t = pack_bf16(v[2 * h] * bf_lo(rb[jj][h]), v[2 * h + 1] * bf_hi(rb[jj][h]));
              v[2 * h] = bf_lo(ra[jj][h]) + bf_lo(t);
              v[2 * h + 1] = bf_hi(ra[jj][h]) + bf_hi(t);
            }
          }
          asm volatile("st.shared.u32 [%0], %1;" ::"r"(off[jj][0]), "r"(pack_bf16(v[0], v[1])) : "memory");
          asm volatile("st.shared.u32 [%0], %1;" ::"r"(off[jj][1]), "r"(pack_bf16(v[2], v[3])) : "memory");
        }
      }
      fence_proxy_async_smem();
      if (wg == 0) named_bar_sync(2, 128); else named_bar_sync(3, 128);
      if ((tid & 127) == 0) {
        if (half) tma_store_2d(tmC2, pbase + wg * 4096, n0 + box * 64, m0 + wg * 64);
        else tma_store_2d(tmC, pbase + wg * 8192, n0 + box * 64, m0 + wg * 64);
        tma_store_commit();
      }
    }
    GPROF(4);
    if ((tid & 127) == 0) {
      if (FLAG == 1) {
        tma_store_wait_all();
        asm volatile("fence.proxy.async;" ::: "memory");
        asm volatile("red.release.gpu.global.add.u32 [%0], 1;" ::"l"(gflag) : "memory");
      } else {
        tma_store_wait_read();
      }
    }
  }
  GPROF(5);
  KT_END(EPI == EPI_RES ? 3 : EPI == EPI_GELU ? 5 : EPI == EPI_RES_SILU ? 6 : 7);
  __syncwarp();
  cluster_sync();
}

__device__ __forceinline__ float warp_sum(float v) {
#pragma unroll
  for (int o = 16; o > 0; o >>= 1) v += __shfl_xor_sync(0xffffffffu, v, o);
  return v;
}
__device__ __forceinline__ void ln_row(float (&v)[32]) {
  float s = 0.f;
#pragma unroll
  for (int i = 0; i < 32; i++) s += v[i];
  const float mean = warp_sum(s) * (1.0f / 1024.0f);
  float q = 0.f;
#pragma unroll
  for (int i = 0; i < 32; i++) { const float d = v[i] - mean; q += d * d; }
  const float var = warp_sum(q) * (1.0f / 1024.0f);
  const float mb = rbf(mean);
  const float sd = rbf(sqrtf(rbf(rbf(var) + 1e-5f)));
  const float inv = __fdiv_rn(1.0f, sd);
#pragma unroll
  for (int i = 0; i < 32; i += 2) {
    const uint32_t d = pack_bf16(v[i] - mb, v[i + 1] - mb);
    const uint32_t y = pack_bf16(bf_lo(d) * inv, bf_hi(d) * inv);
    v[i] = bf_lo(y); v[i + 1] = bf_hi(y);
  }
}
__device__ __forceinline__ void load_row(const bf16* p, int lane, float (&v)[32]) {
#pragma unroll
  for (int j = 0; j < 4; j++) {
    const uint4 u = *reinterpret_cast<const uint4*>(p + j * 256 + lane * 8);
    v[j * 8 + 0] = bf_lo(u.x); v[j * 8 + 1] = bf_hi(u.x); v[j * 8 + 2] = bf_lo(u.y); v[j * 8 + 3] = bf_hi(u.y);
    v[j * 8 + 4] = bf_lo(u.z); v[j * 8 + 5] = bf_hi(u.z); v[j * 8 + 6] = bf_lo(u.w); v[j * 8 + 7] = bf_hi(u.w);
  }
}
__device__ __forceinline__ void store_row(bf16* p, int lane, const float (&v)[32]) {
#pragma unroll
  for (int j = 0; j < 4; j++) {
    uint4 u;
    u.x = pack_bf16(v[j * 8 + 0], v[j * 8 + 1]); u.y = pack_bf16(v[j * 8 + 2], v[j * 8 + 3]);
    u.z = pack_bf16(v[j * 8 + 4], v[j * 8 + 5]); u.w = pack_bf16(v[j * 8 + 6], v[j * 8 + 7]);
    *reinterpret_cast<uint4*>(p + j * 256 + lane * 8) = u;
  }
}
__device__ void reset_exchange(int gtid, int nthreads);
template <bool TWICE>
__global__ void __launch_bounds__(256) ln_kernel(const bf16* __restrict__ x, bf16* __restrict__ y1, bf16* __restrict__ y2) {
  const int row = blockIdx.x * 8 + (threadIdx.x >> 5), lane = threadIdx.x & 31;
  KT_START(TWICE ? 0 : 4);
  pdl_launch_dependents();
  pdl_wait();
  if (TWICE) reset_exchange(blockIdx.x * 256 + threadIdx.x, gridDim.x * 256);
  float v[32];
  load_row(x + (size_t)row * cfg::D, lane, v);
  ln_row(v);
  store_row(y1 + (size_t)row * cfg::D, lane, v);
  if (TWICE) {
    ln_row(v);
    store_row(y2 + (size_t)row * cfg::D, lane, v);
  }
  KT_END(TWICE ? 0 : 4);
}

namespace fk {
constexpr uint32_t SM0 = 1024;
constexpr uint32_t WO = SM0, WS = WO + 90112, XN = WS + 65536, VX = XN + 49152, QK = VX + 8192, PT = QK + 8192,
                   SP = PT + 4096, VM = SP + 2560, OB = VM + 2048, BAR = OB + 2048;
constexpr uint32_t MEMB = XN + 16384, RED = XN + 32768, VX2 = WO + 81920;
constexpr int SMEM = 232448;
static_assert(BAR + 512 == SM0 + SMEM, "shared memory layout");
constexpr uint32_t B_XN = BAR, B_H2 = BAR + 448, B_PF = BAR + 16, B_SM = BAR + 32, B_VM = BAR + 40, B_VX = BAR + 48, B_ST = BAR + 56, B_PB = BAR + 64, B_W = BAR + 112,
                   MASKS = BAR + 128, PROBE = BAR + 384;
constexpr int NB_M0 = 1, NB_M1 = 2, NB_C = 3, NB_O = 4, NB_ST = 5, NB_DU = 6, NB_CF = 7, NB_W1 = 8, NB_XE = 9, NB_HD = 10, NB_PZ = 11, NB_O0 = 12;
#define D_H1 850
#define D_H2 1750
#define D_ST 100
#define SCQ 2
#define FLAGS 0
#define D_F 0
#define D_FS 70
#define NS0 4
#define NTA0 2
#define NTA1 2
#define PF0A 3
#define PF0 10
#define PF1A 9
#define PF1 11
#define PAUSE 1
#define PROBE_N 6
#define PROBE_FAST 0
#define SPACK 0
constexpr uint32_t SPW = SPACK ? 4 : 8, SP_SRC = 160 * SPW;
constexpr int H1_BYTES = 64 * 32768, H2_BYTES = 8 * 8192, FL_OFF = H1_BYTES + H2_BYTES, FL_BYTES = 8192;
}

#define PROF(wg, i)
#define PROF2(i)
#define RETRY(i)
#define GTSYNC(i)

__device__ uint4 g_xch[(fk::H1_BYTES + fk::H2_BYTES + fk::FL_BYTES + 8192) / 16];
__device__ unsigned g_mask[64];
__device__ unsigned g_oflag[16];

#define LD_POLL "ld.global.L1::no_allocate"
__device__ __forceinline__ uint4 ld_poll16(const void* p) {
  uint4 v;
  asm volatile(LD_POLL ".v4.u32 {%0,%1,%2,%3}, [%4];" : "=r"(v.x), "=r"(v.y), "=r"(v.z), "=r"(v.w) : "l"(p) : "memory");
  return v;
}
__device__ __forceinline__ uint2 ld_poll8(const void* p) {
  uint2 v;
  asm volatile(LD_POLL ".v2.u32 {%0,%1}, [%2];" : "=r"(v.x), "=r"(v.y) : "l"(p) : "memory");
  return v;
}
__device__ __forceinline__ uint4 ld_strong16(const void* p) {
  uint4 v;
  asm volatile("ld.relaxed.gpu.global.v4.u32 {%0,%1,%2,%3}, [%4];" : "=r"(v.x), "=r"(v.y), "=r"(v.z), "=r"(v.w) : "l"(p) : "memory");
  return v;
}
__device__ __forceinline__ uint2 ld_strong8(const void* p) {
  uint2 v;
  asm volatile("ld.relaxed.gpu.global.v2.u32 {%0,%1}, [%2];" : "=r"(v.x), "=r"(v.y) : "l"(p) : "memory");
  return v;
}
__device__ __forceinline__ void st_pub32(void* p, uint32_t v) { asm volatile("st.relaxed.gpu.global.u32 [%0], %1;" ::"l"(p), "r"(v) : "memory"); }
__device__ __forceinline__ void st_pub16(void* p, uint32_t v) {
  asm volatile("st.relaxed.gpu.global.u16 [%0], %1;" ::"l"(p), "h"((uint16_t)v) : "memory");
}
__device__ __forceinline__ uint32_t ld_strong4(const void* p) {
  uint32_t v;
  asm volatile("ld.relaxed.gpu.global.u32 %0, [%1];" : "=r"(v) : "l"(p) : "memory");
  return v;
}
__device__ __forceinline__ void st_pub64(void* p, uint32_t a, uint32_t b) {
  asm volatile("st.relaxed.gpu.global.v2.u32 [%0], {%1,%2};" ::"l"(p), "r"(a), "r"(b) : "memory");
}
__device__ __forceinline__ void st_pub128(void* p, uint32_t a) {
  asm volatile("st.relaxed.gpu.global.v4.u32 [%0], {%1,%1,%1,%1};" ::"l"(p), "r"(a) : "memory");
}
constexpr uint32_t EMPTY = 0xFFFFFFFFu;
__device__ __forceinline__ uint32_t umax4(const uint4& v) { return max(max(v.x, v.y), max(v.z, v.w)); }
__device__ __forceinline__ void sts128(uint32_t a, uint32_t x, uint32_t y, uint32_t z, uint32_t w) {
  asm volatile("st.shared.v4.u32 [%0], {%1,%2,%3,%4};" ::"r"(a), "r"(x), "r"(y), "r"(z), "r"(w) : "memory");
}
__device__ __forceinline__ void sts64(uint32_t a, uint32_t x, uint32_t y) {
  asm volatile("st.shared.v2.u32 [%0], {%1,%2};" ::"r"(a), "r"(x), "r"(y) : "memory");
}
__device__ __forceinline__ void sts32(uint32_t a, uint32_t x) { asm volatile("st.shared.u32 [%0], %1;" ::"r"(a), "r"(x) : "memory"); }
__device__ __forceinline__ void sts128f(uint32_t a, float x, float y, float z, float w) {
  asm volatile("st.shared.v4.f32 [%0], {%1,%2,%3,%4};" ::"r"(a), "f"(x), "f"(y), "f"(z), "f"(w) : "memory");
}
__device__ __forceinline__ void sts64f(uint32_t a, float x, float y) {
  asm volatile("st.shared.v2.f32 [%0], {%1,%2};" ::"r"(a), "f"(x), "f"(y) : "memory");
}
__device__ __forceinline__ float4 lds128f(uint32_t a) {
  float4 v;
  asm volatile("ld.shared.v4.f32 {%0,%1,%2,%3}, [%4];" : "=f"(v.x), "=f"(v.y), "=f"(v.z), "=f"(v.w) : "r"(a) : "memory");
  return v;
}
__device__ __forceinline__ float2 lds64f(uint32_t a) {
  float2 v;
  asm volatile("ld.shared.v2.f32 {%0,%1}, [%2];" : "=f"(v.x), "=f"(v.y) : "r"(a) : "memory");
  return v;
}
__device__ __forceinline__ void lds128(uint32_t* r, uint32_t a) {
  asm volatile("ld.shared.v4.u32 {%0,%1,%2,%3}, [%4];" : "=r"(r[0]), "=r"(r[1]), "=r"(r[2]), "=r"(r[3]) : "r"(a) : "memory");
}
__device__ __forceinline__ void lds64(uint32_t* r, uint32_t a) {
  asm volatile("ld.shared.v2.u32 {%0,%1}, [%2];" : "=r"(r[0]), "=r"(r[1]) : "r"(a) : "memory");
}
__device__ __forceinline__ uint32_t lds32(uint32_t a) {
  uint32_t v;
  asm volatile("ld.shared.u32 %0, [%1];" : "=r"(v) : "r"(a) : "memory");
  return v;
}
__device__ __forceinline__ void ldsm4(uint32_t* r, uint32_t a) {
  asm volatile("ldmatrix.sync.aligned.m8n8.x4.shared.b16 {%0,%1,%2,%3}, [%4];"
               : "=r"(r[0]), "=r"(r[1]), "=r"(r[2]), "=r"(r[3]) : "r"(a) : "memory");
}
__device__ __forceinline__ void ldsm4t(uint32_t* r, uint32_t a) {
  asm volatile("ldmatrix.sync.aligned.m8n8.x4.trans.shared.b16 {%0,%1,%2,%3}, [%4];"
               : "=r"(r[0]), "=r"(r[1]), "=r"(r[2]), "=r"(r[3]) : "r"(a) : "memory");
}
__device__ __forceinline__ void stsm4(uint32_t a, uint32_t r0, uint32_t r1, uint32_t r2, uint32_t r3) {
  asm volatile("stmatrix.sync.aligned.m8n8.x4.shared.b16 [%0], {%1,%2,%3,%4};"
               ::"r"(a), "r"(r0), "r"(r1), "r"(r2), "r"(r3) : "memory");
}
__device__ __forceinline__ void stsm4t(uint32_t a, uint32_t r0, uint32_t r1, uint32_t r2, uint32_t r3) {
  asm volatile("stmatrix.sync.aligned.m8n8.x4.trans.shared.b16 [%0], {%1,%2,%3,%4};"
               ::"r"(a), "r"(r0), "r"(r1), "r"(r2), "r"(r3) : "memory");
}
__device__ __forceinline__ void mma16816(float* d, const uint32_t* a, uint32_t b0, uint32_t b1) {
  asm volatile("mma.sync.aligned.m16n8k16.row.col.f32.bf16.bf16.f32 {%0,%1,%2,%3}, {%4,%5,%6,%7}, {%8,%9}, {%0,%1,%2,%3};"
               : "+f"(d[0]), "+f"(d[1]), "+f"(d[2]), "+f"(d[3])
               : "r"(a[0]), "r"(a[1]), "r"(a[2]), "r"(a[3]), "r"(b0), "r"(b1));
}
__device__ __forceinline__ void mma16816z(float* d, const uint32_t* a, uint32_t b0, uint32_t b1) {
  asm volatile("mma.sync.aligned.m16n8k16.row.col.f32.bf16.bf16.f32 {%0,%1,%2,%3}, {%4,%5,%6,%7}, {%8,%9}, {%10,%10,%10,%10};"
               : "=f"(d[0]), "=f"(d[1]), "=f"(d[2]), "=f"(d[3])
               : "r"(a[0]), "r"(a[1]), "r"(a[2]), "r"(a[3]), "r"(b0), "r"(b1), "f"(0.f));
}
__device__ __forceinline__ void mma1688(float* d, uint32_t a0, uint32_t a1, uint32_t b0) {
  asm volatile("mma.sync.aligned.m16n8k8.row.col.f32.bf16.bf16.f32 {%0,%1,%2,%3}, {%4,%5}, {%6}, {%0,%1,%2,%3};"
               : "+f"(d[0]), "+f"(d[1]), "+f"(d[2]), "+f"(d[3]) : "r"(a0), "r"(a1), "r"(b0));
}
__device__ __forceinline__ uint32_t movtrans(uint32_t a) {
  uint32_t d;
  asm volatile("movmatrix.sync.aligned.m8n8.trans.b16 %0, %1;" : "=r"(d) : "r"(a));
  return d;
}
__device__ __forceinline__ uint32_t mapa(uint32_t a, uint32_t rank) {
  uint32_t d;
  asm("mapa.shared::cluster.u32 %0, %1, %2;" : "=r"(d) : "r"(a), "r"(rank));
  return d;
}
__device__ __forceinline__ void st_async64(uint32_t a, uint32_t x, uint32_t y, uint32_t bar) {
  asm volatile("st.async.weak.shared::cluster.mbarrier::complete_tx::bytes.v2.b32 [%0], {%1,%2}, [%3];"
               ::"r"(a), "r"(x), "r"(y), "r"(bar) : "memory");
}
__device__ __forceinline__ void st_async64f(uint32_t a, float x, float y, uint32_t bar) {
  st_async64(a, __float_as_uint(x), __float_as_uint(y), bar);
}
__device__ __forceinline__ void bulk_s2s(uint32_t dst, uint32_t src, uint32_t bytes, uint32_t bar) {
  asm volatile("cp.async.bulk.shared::cluster.shared::cta.mbarrier::complete_tx::bytes [%0], [%1], %2, [%3];"
               ::"r"(dst), "r"(src), "r"(bytes), "r"(bar) : "memory");
}
__device__ __forceinline__ void tma_store_3d(const CUtensorMap* map, uint32_t src, int x, int y, int z) {
  asm volatile("cp.async.bulk.tensor.3d.global.shared::cta.bulk_group [%0, {%2, %3, %4}], [%1];"
               ::"l"(map), "r"(src), "r"(x), "r"(y), "r"(z) : "memory");
}
__device__ __forceinline__ void mbar_spin(uint32_t bar, uint32_t parity) {
  asm volatile("{\n.reg .pred p;\n.reg .b32 n;\nmov.u32 n, 0x100000;\nMW_L:\n"
               "mbarrier.try_wait.parity.shared::cta.b64 p, [%0], %1;\n@p bra.uni MW_D;\n"
               "add.s32 n, n, -1;\nsetp.ne.u32 p, n, 0;\n@p bra.uni MW_L;\nMW_D:\n}" ::"r"(bar), "r"(parity) : "memory");
}
__device__ __forceinline__ bool mbar_test(uint32_t bar, uint32_t parity) {
  uint32_t done;
  asm volatile("{\n.reg .pred p;\nmbarrier.test_wait.parity.shared::cta.b64 p, [%1], %2;\nselp.u32 %0, 1, 0, p;\n}"
               : "=r"(done) : "r"(bar), "r"(parity) : "memory");
  return done != 0;
}
__device__ __forceinline__ void mbar_arrive_remote(uint32_t bar) {
  asm volatile("mbarrier.arrive.shared::cluster.b64 _, [%0];" ::"r"(bar) : "memory");
}
__device__ __forceinline__ bool elect_one() {
  uint32_t r;
  asm volatile("{\n.reg .pred p;\nelect.sync _|p, 0xffffffff;\nselp.u32 %0, 1, 0, p;\n}" : "=r"(r));
  return r != 0;
}
__device__ __forceinline__ void st_async32(uint32_t a, uint32_t x, uint32_t bar) {
  asm volatile("st.async.weak.shared::cluster.mbarrier::complete_tx::bytes.b32 [%0], %1, [%2];" ::"r"(a), "r"(x), "r"(bar) : "memory");
}
#define named_bar_and(id, n, in, out) \
  asm volatile("{\n.reg .pred p, q;\nsetp.ne.u32 p, %1, 0;\nbar.red.and.pred q, %2, %3, p;\nselp.u32 %0, 1, 0, q;\n}" \
               : "=r"(out) : "r"(in), "n"(id), "n"(n) : "memory")
__device__ __forceinline__ void bulk_g2s(uint32_t dst, const void* src, uint32_t bytes, uint32_t bar) {
  asm volatile("cp.async.bulk.shared::cluster.global.mbarrier::complete_tx::bytes [%0], [%1], %2, [%3];"
               ::"r"(dst), "l"(src), "r"(bytes), "r"(bar) : "memory");
}
__device__ __forceinline__ uint32_t clk32() { uint32_t c; asm volatile("mov.u32 %0, %%clock;" : "=r"(c)::"memory"); return c; }
__device__ __forceinline__ void spin_until(uint32_t t) { while ((int32_t)(clk32() - t) < 0) {} }
#define PIN(x) asm volatile("" : "+r"(x))
#define MEM_FENCE(addr) \
  asm volatile("{\n.reg .pred p;\nsetp.eq.u32 p, %0, 0xFFFFFFF1;\n@p st.shared.u32 [%0], %0;\n}" ::"r"(addr) : "memory")
#define SCHED_DECL(x) \
  asm volatile(".reg .pred p_never;\n{\n.reg .pred q;\nsetp.eq.u32 q, %0, 0xFFFFFFF1;\nvote.sync.any.pred p_never, q, 0xffffffff;\n}" ::"r"(x))
#define SCHED_FENCE(addr) \
  asm volatile("{\nSF_L:\n@p_never st.volatile.shared.u32 [%0], %0;\n@p_never bra.uni SF_L;\n}" ::"r"(addr) : "memory")
#define OPQ                                                                                     \
  int tid_o = tid;                                                                              \
  asm volatile("" : "+r"(tid_o));                                                               \
  const int lane = tid_o & 31, w = (tid_o >> 5) & 3, t7 = tid_o & 127, lg = lane >> 2,          \
            lq = lane & 3, mi = lane >> 3, mr = lane & 7;                                       \
  (void)w; (void)t7; (void)lg; (void)lq; (void)mi; (void)mr; (void)lane

#define SMAP                                                                                                          \
  const uint32_t SM0 = self + fk::SM0, WO = self + fk::WO, WS = self + fk::WS, XN = self + fk::XN, VX = self + fk::VX, \
                 QK = self + fk::QK, PT = self + fk::PT, SP = self + fk::SP, VM = self + fk::VM, OB = self + fk::OB,   \
                 RED = self + fk::RED, VX2 = self + fk::VX2, MEMB = self + fk::MEMB, B_XN = self + fk::B_XN, B_SM = self + fk::B_SM,       \
                 B_VM = self + fk::B_VM, B_VX = self + fk::B_VX, B_ST = self + fk::B_ST, B_PB = self + fk::B_PB,       \
                 B_W = self + fk::B_W, B_H2 = self + fk::B_H2, B_PF = self + fk::B_PF, MASKS = self + fk::MASKS, PROBE = self + fk::PROBE;                             \
  (void)SM0; (void)WO; (void)WS; (void)XN; (void)VX; (void)QK; (void)PT; (void)SP; (void)VM; (void)OB; (void)RED; (void)VX2; \
  (void)MEMB; (void)B_XN; (void)B_SM; (void)B_VM; (void)B_VX; (void)B_ST; (void)B_PB; (void)B_W; (void)MASKS; (void)PROBE; (void)B_H2; (void)B_PF

struct FParams {
  CUtensorMap wq, wk, wv, wo, xn, xn12, o;
  const bf16* mem0;
  int one;
  char* xch;
};

__device__ __forceinline__ uint32_t probe_pair(char* p, uint32_t val, uint32_t dummy) {
  uint32_t best0 = 0x7FFFFFFF, best1 = 0x7FFFFFFF;
  st_pub128(p, val); st_pub128(p + 16, val); st_pub128(p + 4096, val); st_pub128(p + 4112, val);
#pragma unroll 1
  for (int r = 0; r < PROBE_N; r++) {
    uint32_t v;
    const uint32_t c0 = clk32();
    asm volatile("atom.relaxed.gpu.global.exch.b32 %0, [%1], %2;" : "=r"(v) : "l"(p + (r & 1) * 4096), "r"(val) : "memory");
    asm volatile("{\n.reg .pred p;\nsetp.eq.u32 p, %0, 0x12345678;\n@p st.shared.u32 [%1], %0;\n}" ::"r"(v), "r"(dummy) : "memory");
    const uint32_t d = clk32() - c0;
    if (r & 1) best1 = min(best1, d); else best0 = min(best0, d);
    if (r >= 1 && min(best0, best1) < PROBE_FAST && max(best0, best1) - min(best0, best1) > 100) break;
  }
  return best1 < best0;
}

typedef uint32_t WRegs[6][2][4][4];

template <bool ISV> struct Chunks {
  static constexpr int SC0 = ISV ? 6 : SCQ;
  static __device__ __forceinline__ constexpr int rf(int wg, int i) { return wg ? 10 + i : (i < SC0 ? i : 4 + i); }
};

template <int WG> struct ProjCfg { static constexpr int NS = WG ? 8 - NS0 : NS0, P0 = WG ? NS0 : 0, NTA = WG ? NTA1 : NTA0; };
__device__ __forceinline__ void load_pair(uint32_t (&t)[4][4], uint32_t wsa, int pp) {
#pragma unroll
  for (int f = 0; f < 4; f++) ldsm4t(t[f], wsa + ((pp >> 1) * 2 + (f & 1)) * 8192 + ((pp & 1) * 2 + (f >> 1)) * 2048);
}
template <bool ISV, int WG>
__device__ __forceinline__ void proj_mem(const WRegs& wr, uint32_t (&ta)[ProjCfg<WG>::NTA][4][4], uint32_t wsa, uint32_t mba,
                                         float (&a0)[4], float (&a1)[4]) {
  constexpr int NS = ProjCfg<WG>::NS, P0 = ProjCfg<WG>::P0, NTA = ProjCfg<WG>::NTA, NP = 12 + NS;
  float acc[4][4];
  auto spos = [](int j) { return j < NTA ? j : j + (j - NTA + 1) * 12 / (NS - NTA > 0 ? NS - NTA : 1); };
  auto which = [&](int p) { int r = -1; for (int j = 0; j < NS; j++) if (spos(j) == p) r = j; return r; };
  auto nsm_before = [&](int p) { int n = 0; for (int j = 0; j < NS; j++) if (spos(j) < p) n++; return n; };
#pragma unroll
  for (int p = 0; p < NP; p++) {
    const int j = which(p), r = j >= 0 ? 0 : p - nsm_before(p);
    uint32_t bp[4], tl[4][4];
    ldsm4(bp, mba + (j >= 0 ? (Chunks<ISV>::SC0 + ((P0 + j) >> 1)) * 1024 + ((P0 + j) & 1) * 512 : Chunks<ISV>::rf(WG, r >> 1) * 1024 + (r & 1) * 512));
    if (j >= NTA) load_pair(tl, wsa, P0 + j);
#pragma unroll
    for (int u = 0; u < 2; u++)
#pragma unroll
      for (int T = 0; T < 2; T++) {
        const uint32_t* a = j >= NTA ? tl[u * 2 + T] : j >= 0 ? ta[j >= 0 ? j % NTA : 0][u * 2 + T] : wr[r >> 1][T][(r & 1) * 2 + u];
        if (p == 0) mma16816z(acc[u * 2 + T], a, bp[2 * u], bp[2 * u + 1]);
        else mma16816(acc[u * 2 + T], a, bp[2 * u], bp[2 * u + 1]);
      }
  }
#pragma unroll
  for (int i = 0; i < 4; i++) { a0[i] = acc[0][i] + acc[2][i]; a1[i] = acc[1][i] + acc[3][i]; }
}
template <int WG>
__device__ __forceinline__ void proj_mem_prefetch(uint32_t (&ta)[ProjCfg<WG>::NTA][4][4], uint32_t wsa) {
#pragma unroll
  for (int j = 0; j < ProjCfg<WG>::NTA; j++) load_pair(ta[j], wsa, ProjCfg<WG>::P0 + j);
}

template <bool ISV, int WG>
__device__ __forceinline__ void proj_finish(const float (&a0)[4], const float (&a1)[4], uint32_t peer0, uint32_t peer1, uint32_t self, int tid,
                                            uint32_t (&vmo)[2][2]) {
  using namespace fk;
  SMAP;
  OPQ;
  if (!ISV) {
    stsm4(PT + (mi >> 1) * 2048 + w * 512 + (mi & 1) * 256 + WG * 128 + mr * 16,
          pack_bf16(a0[0], a0[1]), pack_bf16(a0[2], a0[3]), pack_bf16(a1[0], a1[1]), pack_bf16(a1[2], a1[3]));
    named_bar_sync(NB_C, 256);
  } else {
    if (WG == 0) sts128f(RED + t7 * 16, a1[0], a1[1], a1[2], a1[3]);
    else sts128f(RED + 2048 + t7 * 16, a0[0], a0[1], a0[2], a0[3]);
    if (WG == 1) { lds64(vmo[0], VM + t7 * 8); lds64(vmo[1], VM + 1024 + t7 * 8); }
    named_bar_sync(NB_C, 256);
    const float4 p = lds128f(RED + (1 - WG) * 2048 + t7 * 16);
    const float* k = WG == 0 ? a0 : a1;
    const uint32_t v0 = pack_bf16(k[0] + p.x, k[1] + p.y), v1 = pack_bf16(k[2] + p.z, k[3] + p.w);
    const uint32_t off = VM + WG * 1024 + t7 * 8;
    st_async64(peer0 + off, v0, v1, peer0 + B_VM);
    st_async64(peer1 + off, v0, v1, peer1 + B_VM);
    sts64(off, v0, v1);
    __syncwarp();
    if (lane == 0) mbar_arrive(B_VM);
  }
}

__device__ __forceinline__ void send_scores(float s0, float s1, uint32_t off, uint32_t peer0, uint32_t peer1, uint32_t bar, int lane) {
  if (SPACK) {
    const uint32_t v = pack_bf16(s0, s1);
    st_async32(peer0 + off, v, peer0 + bar);
    st_async32(peer1 + off, v, peer1 + bar);
    sts32(off, v);
  } else {
    st_async64f(peer0 + off, s0, s1, peer0 + bar);
    st_async64f(peer1 + off, s0, s1, peer1 + bar);
    sts64f(off, s0, s1);
  }
  __syncwarp();
  if (lane == 0) mbar_arrive(bar);
}

template <int NT, int PF, int PFA>
__device__ __forceinline__ void wo_phase(uint32_t (&wf)[PFA][4], uint32_t woa, uint32_t oba, char* h1p, uint32_t sel, uint32_t tag) {
  float c[NT][4];
  uint32_t of[2][4];
  ldsm4t(of[0], oba);
#pragma unroll
  for (int k = 0; k < 8; k++) {
    if ((k & 1) == 0 && k + 2 < 8) ldsm4t(of[((k >> 1) + 1) & 1], oba + ((k >> 1) + 1) * 512);
#pragma unroll
    for (int i = 0; i < NT; i++) {
      const int f = k * NT + i;
      const uint32_t b0 = of[(k >> 1) & 1][2 * (k & 1)], b1 = of[(k >> 1) & 1][2 * (k & 1) + 1];
      if (k == 0) mma16816z(c[i], wf[f % PF], b0, b1); else mma16816(c[i], wf[f % PF], b0, b1);
      if (f + PF < 8 * NT) ldsm4t(wf[f % PF], woa + ((f + PF) % NT) * 32768 + ((f + PF) / NT) * 512);
    }
  }
#pragma unroll
  for (int i = 0; i < NT; i++)
    st_pub64(h1p + i * (8 * 32768) + ((sel >> (2 * i)) & 3) * 2048, (pack_bf16(c[i][0], c[i][1]) & ~1u) | tag, pack_bf16(c[i][2], c[i][3]));
}
template <int NT, int F0, int F1, int PFA>
__device__ __forceinline__ void wo_prefetch(uint32_t (&wf)[PFA][4], uint32_t woa) {
#pragma unroll
  for (int f = F0; f < F1; f++) ldsm4t(wf[f], woa + (f % NT) * 32768 + (f / NT) * 512);
}

template <bool ISV, int T, bool ADD>
__device__ __forceinline__ void tok_store(const float (&x)[16], uint32_t base, int tid) {
  OPQ;
  const uint32_t a = ISV ? base + T * 4096 + w * 1024 + lane * 16
                   : T == 0 ? base + w * 512 + (mi & 1) * 256 + (mi >> 1) * 128 + mr * 16
                            : base + 4096 + (mi >> 1) * 1024 + w * 256 + (mi & 1) * 128 + mr * 16;
  constexpr uint32_t STR = ISV ? 512 : 2048;
  uint32_t p[2][4];
  if (ADD) {
#pragma unroll
    for (int i = 0; i < 2; i++) { if (ISV) lds128(p[i], a + i * STR); else ldsm4(p[i], a + i * STR); }
  }
#pragma unroll
  for (int i = 0; i < 2; i++) {
#pragma unroll
    for (int k = 0; k < 4; k++)
      p[i][k] = ADD ? pack_bf16(x[8 * i + 2 * k] + bf_lo(p[i][k]), x[8 * i + 2 * k + 1] + bf_hi(p[i][k]))
                    : pack_bf16(x[8 * i + 2 * k], x[8 * i + 2 * k + 1]);
    if (ISV) sts128(a + i * STR, p[i][0], p[i][1], p[i][2], p[i][3]); else stsm4(a + i * STR, p[i][0], p[i][1], p[i][2], p[i][3]);
  }
}

__device__ __forceinline__ void load_xn(const FParams& P, int seg, uint32_t self) {
  SMAP;
  mbar_expect_tx(B_XN, 49152);
  tma_load_3d(XN, &P.xn12, 0, seg * 32, 0, B_XN);
}

__device__ __forceinline__ uint64_t xn_desc(int slot, int u) { return make_desc(fk::XN + slot * 4096 + u * 32, 16, 1024); }

template <bool ISV>
__device__ __forceinline__ void f_wg0(const FParams& P, const WRegs& wr, const int h, const int rank, uint32_t sel, const int tid) {
  using namespace fk;
  const uint32_t self = mapa(0, rank), peer0 = mapa(0, ISV ? 0 : rank ^ 1) - self, peer1 = mapa(0, ISV ? 1 : 2) - self;
  SMAP;
  const int tile0 = rank * 22;
  const int warp = __shfl_sync(0xffffffffu, threadIdx.x >> 5, 0);
  const bool three = !ISV && warp < 2;
  uint32_t ta[NTA0][4][4], wsa = 0, mba = 0, h2ph = 0;
#pragma unroll 1
  for (int s = -1; s < cfg::NSEG; s++) {
    uint32_t t_pub = 0;
    sel ^= 0x55;
    if (s >= 0) {
      PROF(0, 1);
      float a0[4], a1[4];
      proj_mem<ISV, 0>(wr, ta, wsa, mba, a0, a1);
      PROF(0, 2);
      uint32_t unused[2][2];
      proj_finish<ISV, 0>(a0, a1, peer0, peer1, self, tid, unused);
      PROF(0, 3);
      if (s + 1 == cfg::NSEG) break;
      uint32_t wf[PF0][4], woa;
      {
        OPQ;
        if (!ISV) {
          uint32_t qf[4][4], kf[2][4];
          const uint32_t qa = PT + lane * 16, ka = QK + 4096 + w * 1024 + lane * 16;
          ldsm4t(qf[0], qa); ldsm4t(kf[0], ka); ldsm4t(qf[1], qa + 512);
          ldsm4t(qf[2], qa + 1024); ldsm4t(kf[1], ka + 512); ldsm4t(qf[3], qa + 1536);
          float c0[4], c1[4];
          mma16816z(c0, qf[0], kf[0][0], kf[0][1]);
          mma16816z(c1, qf[1], kf[0][2], kf[0][3]);
          mma16816(c0, qf[2], kf[1][0], kf[1][1]);
          mma16816(c1, qf[3], kf[1][2], kf[1][3]);
          const float s0 = (c0[0] + c0[2]) + (c1[0] + c1[2]), s1 = (c0[1] + c0[3]) + (c1[1] + c1[3]);
          send_scores(s0, s1, SP + rank * SP_SRC + t7 * SPW, peer0, peer1, B_SM, lane);
        }
        PROF(0, 4);
        woa = WO + (w + 4) * 4096 + ((mi >> 1) * 8 + mr) * 32 + (((mi & 1) ^ (mr >> 2)) << 4);
        PIN(woa);
        uint32_t vf[2][2][4], vm[2][2];
        if (!ISV) mbar_spin(B_VX, s & 1);
        PROF(0, 14);
#pragma unroll
        for (int T = 0; T < 2; T++)
#pragma unroll
          for (int kk = 0; kk < 2; kk++) lds128(vf[T][kk], ((ISV && (s & 1)) ? VX2 : VX) + T * 4096 + w * 1024 + kk * 512 + lane * 16);
        if (three) wo_prefetch<3, 0, PF0A>(wf, woa); else wo_prefetch<2, 0, PF0A>(wf, woa);
        uint32_t spa = SP + lane * SPW, vma = VM + t7 * 8, oa = OB + (mi >> 1) * 1024 + w * 256 + (mi & 1) * 128 + mr * 16;
        PIN(spa); PIN(vma); PIN(oa);
        mbar_spin(B_SM, s & 1);
        PROF(0, 5);
        float sc[10];
#pragma unroll
        for (int j = 0; j < 5; j++) {
          if (SPACK) {
            const uint32_t x = lds32(spa + j * 128), y = lds32(spa + SP_SRC + j * 128);
            sc[2 * j] = bf_lo(x) + bf_lo(y); sc[2 * j + 1] = bf_hi(x) + bf_hi(y);
          } else {
            const float2 x = lds64f(spa + j * 256), y = lds64f(spa + SP_SRC + j * 256);
            sc[2 * j] = x.x + y.x; sc[2 * j + 1] = x.y + y.y;
          }
        }
        float m = fmaxf(fmaxf(fmaxf(sc[0], sc[1]), fmaxf(sc[2], sc[3])), fmaxf(fmaxf(sc[4], sc[5]), fmaxf(sc[6], sc[7])));
        m = fmaxf(m, fmaxf(sc[8], sc[9]));
        const bool vm_ok = mbar_test(B_VM, s & 1);
        m = fmaxf(m, __shfl_xor_sync(0xffffffffu, m, 1));
        m = fmaxf(m, __shfl_xor_sync(0xffffffffu, m, 2));
        PROF(0, 15);
        if (!vm_ok) mbar_spin(B_VM, s & 1);
        PROF(0, 0);
        lds64(vm[0], vma); lds64(vm[1], vma + 1024);
        const float cs = 0.08838834764831845f * 1.4426950408889634f;
        const float mc = -m * cs;
        uint32_t pb[5];
#pragma unroll
        for (int j = 0; j < 5; j++) pb[j] = pack_bf16(ex2_approx(fmaf(sc[2 * j], cs, mc)), ex2_approx(fmaf(sc[2 * j + 1], cs, mc)));
        PROF(0, 6);
        float o0[4], o1[4], rs[4];
        const uint32_t ones[4] = {0x3F803F80u, 0x3F803F80u, 0x3F803F80u, 0x3F803F80u};
        mma16816z(rs, ones, pb[0], pb[1]);
        mma16816z(o0, vf[0][0], pb[0], pb[1]);
        mma16816z(o1, vf[1][0], pb[0], pb[1]);
        mma16816(rs, ones, pb[2], pb[3]);
        mma16816(o0, vf[0][1], pb[2], pb[3]);
        mma16816(o1, vf[1][1], pb[2], pb[3]);
        mma1688(rs, ones[0], ones[0], pb[4]);
        mma1688(o0, vm[0][0], vm[0][1], pb[4]);
        mma1688(o1, vm[1][0], vm[1][1], pb[4]);
        const float i0 = rcp_approx(rs[0]), i1 = rcp_approx(rs[1]);
        stsm4(oa, pack_bf16(o0[0] * i0, o0[1] * i1), pack_bf16(o0[2] * i0, o0[3] * i1),
              pack_bf16(o1[0] * i0, o1[1] * i1), pack_bf16(o1[2] * i0, o1[3] * i1));
      }
      {
        OPQ;
        named_bar_arrive(NB_O, 256);
        if (three) wo_prefetch<3, PF0A, PF0>(wf, woa); else wo_prefetch<2, PF0A, PF0>(wf, woa);
        char* h1p = P.xch + (tile0 + 4 + w) * 32768 + (h >> 3) * 8192 + (h & 7) * 256 + lane * 8;
        uint32_t oba = OB + lane * 16;
        PIN(oba);
        PROF(0, 7);
        named_bar_sync(NB_O0, 128);
        PROF(0, 8);
        const uint32_t tag = ((s >> 1) & 1) ^ 1;
        if (three) wo_phase<3, PF0>(wf, woa, oba, h1p, sel, tag); else wo_phase<2, PF0>(wf, woa, oba, h1p, sel, tag);
        t_pub = clk32();
        PROF(0, 9);
        named_bar_sync(NB_HD, 256);
      }
    }
    auto h2_src = [&]() { return P.xch + H1_BYTES + ((s & 1) * 4 + warp) * 8192 + ((sel >> (8 + (s & 1))) & 1) * 4096; };
    {
      const uint32_t ph = (s + 1) & 1;
      float x0[16], x1[16];
      mbar_spin(B_XN, ph);
      wg_fence();
#pragma unroll
      for (int c = 0; c < 10; c++) {
        if (PAUSE && !ISV && c == SCQ + 4) { uint32_t t_; named_bar_and(NB_PZ, 256, 1, t_); wg_fence(); }
        if (c == 9) named_bar_arrive(NB_ST, 256);
#pragma unroll
        for (int u = 0; u < 4; u++) {
          constexpr int SC0 = Chunks<ISV>::SC0;
          if (c >= SC0 && c < SC0 + 4) {
            wgmma_ss_n32_ta(x0, make_desc(fk::WS + (c - SC0) * 16384 + u * 2048, 8192, 1024), xn_desc(c, u), 1);
            wgmma_ss_n32_ta(x1, make_desc(fk::WS + (c - SC0) * 16384 + 8192 + u * 2048, 8192, 1024), xn_desc(c, u), 1);
          } else {
            wgmma_rs_n32(x0, wr[c < SC0 ? c : c >= SC0 + 4 ? c - 4 : 0][0][u], xn_desc(c, u), (c | u) != 0);
            wgmma_rs_n32(x1, wr[c < SC0 ? c : c >= SC0 + 4 ? c - 4 : 0][1][u], xn_desc(c, u), (c | u) != 0);
          }
          if (c == 4 && u == 1) { wg_commit(); wg_wait<1>(); named_bar_arrive(NB_XE, 160); wg_fence(); }
        }
        if (c == 3) wg_commit();
      }
      wg_commit();
      wg_wait<0>();
      PROF(0, 10);
      if (ISV) named_bar_sync(NB_CF, 160);
      const uint32_t tb = ISV ? (ph ? VX2 : VX) : QK;
      tok_store<ISV, 0, false>(x0, tb, tid);
      tok_store<ISV, 1, false>(x1, tb, tid);
      named_bar_arrive(NB_DU, 256);
    }
    {
      OPQ;
      wsa = WS + ((mi >> 1) * 8 + mr) * 128 + (((2 * w + (mi & 1)) ^ mr) << 4);
      mba = MEMB + lane * 16;
      PIN(wsa); PIN(mba);
      if (s >= 0) {
        const char* src = h2_src();
        const uint32_t chk = MEMB + w * 4096 + lane * 32 + lg * 4, bar = B_H2 + 8 * warp;
        PROF(0, 11);
        if (FLAGS) {
          const char* fp = P.xch + FL_OFF + ((sel >> 10) & 1) * 4096 + (h & 3) * 128 + w * 32 + mr * 4;
          const uint32_t want = (s + 1) * 0x10001;
          spin_until(t_pub + D_H2);
          uint32_t f0 = ld_strong4(fp);
          spin_until(clk32() + D_FS);
          uint32_t f1 = ld_strong4(fp);
          spin_until(clk32() + D_FS);
          uint32_t f2 = ld_strong4(fp);
#pragma unroll 1
          for (int tries = 0; tries < POLL_TRIES; tries++) {
            if (__all_sync(0xffffffffu, f0 == want)) break;
            f0 = ld_strong4(fp);
            if (__all_sync(0xffffffffu, f1 == want)) break;
            f1 = ld_strong4(fp);
            if (__all_sync(0xffffffffu, f2 == want)) break;
            f2 = ld_strong4(fp);
          }
          if (D_F) spin_until(clk32() + D_F);
        } else {
          spin_until(t_pub + D_H2);
        }
        PROF(0, 13);
        if (elect_one()) { mbar_expect_tx(bar, 4096); bulk_g2s(MEMB + warp * 4096, src, 4096, bar); }
        proj_mem_prefetch<0>(ta, wsa);
#pragma unroll 1
        for (int tries = 0; tries < POLL_TRIES; tries++) {
          mbar_spin(bar, h2ph);
          h2ph ^= 1;
          const uint32_t mx = max(max(lds32(chk), lds32(chk + 1024)), max(lds32(chk + 2048), lds32(chk + 3072)));
          if (__all_sync(0xffffffffu, mx != EMPTY)) break;
          RETRY(1);
          if (elect_one()) { mbar_expect_tx(bar, 4096); bulk_g2s(MEMB + warp * 4096, src, 4096, bar); }
        }
      } else {
        const bf16* m0 = P.mem0 + mr * cfg::D + w * 256 + mi * 8;
#pragma unroll
        for (int i = 0; i < 8; i++) {
          const uint4 v = *reinterpret_cast<const uint4*>(m0 + i * 32);
          sts128(mba + w * 4096 + i * 512, v.x, v.y, v.z, v.w);
        }
        proj_mem_prefetch<0>(ta, wsa);
      }
      PROF(0, 12);
      named_bar_arrive(NB_M1, 256);
      named_bar_sync(NB_M0, 128);
    }
  }
}

template <bool ISV>
__device__ __forceinline__ void f_wg1(const FParams& P, const WRegs& wr, const int h, const int rank, uint32_t sel, const int tid) {
  using namespace fk;
  const uint32_t self = mapa(0, rank), peer0 = mapa(0, ISV ? 0 : rank ^ 1) - self, peer1 = mapa(0, ISV ? 1 : 2) - self;
  SMAP;
  const int tile0 = rank * 22;
  const int warp = __shfl_sync(0xffffffffu, (threadIdx.x >> 5) & 3, 0);
  uint32_t ta[NTA1][4][4], wsa = 0, mba = 0;
  auto tok_pv = [&](int seg, const uint32_t (&vm)[2][2]) {
    OPQ;
    const int s = seg + 1; (void)s;
    const uint32_t vb = (seg & 1) ? VX2 : VX;
    uint32_t vf[2][2][4];
#pragma unroll
    for (int T = 0; T < 2; T++)
#pragma unroll
      for (int kk = 0; kk < 2; kk++) lds128(vf[T][kk], vb + T * 4096 + w * 1024 + kk * 512 + lane * 16);
    const uint32_t stg = vb + (mi >> 1) * 4096 + mr * 128 + (((2 * w + (mi & 1)) ^ mr) << 4);
    uint32_t pm[4], r[4][4];
    lds128(pm, PT + 2048 + lane * 16);
#pragma unroll
    for (int g2 = 0; g2 < 4; g2 += 2) {
      uint32_t p[2][4];
      lds128(p[0], PT + g2 * 512 + lane * 16);
      lds128(p[1], PT + g2 * 512 + 512 + lane * 16);
      float o[4][4];
#pragma unroll
      for (int i = 0; i < 4; i++) mma16816z(o[i], vf[i & 1][0], p[i >> 1][0], p[i >> 1][1]);
#pragma unroll
      for (int i = 0; i < 4; i++) mma16816(o[i], vf[i & 1][1], p[i >> 1][2], p[i >> 1][3]);
#pragma unroll
      for (int i = 0; i < 4; i++) mma1688(o[i], vm[i & 1][0], vm[i & 1][1], pm[g2 + (i >> 1)]);
#pragma unroll
      for (int i = 0; i < 4; i++) {
        r[g2 + (i >> 1)][2 * (i & 1)] = pack_bf16(o[i][0], o[i][1]);
        r[g2 + (i >> 1)][2 * (i & 1) + 1] = pack_bf16(o[i][2], o[i][3]);
      }
      if (g2 == 0) named_bar_sync(NB_W1, 128);
    }
    PROF(1, 6);
#pragma unroll
    for (int gq = 0; gq < 4; gq++) stsm4t(stg + gq * 1024, r[gq][0], r[gq][1], r[gq][2], r[gq][3]);
  };
  auto o_store = [&](int seg) { tma_store_3d(&P.o, (seg & 1) ? VX2 : VX, 0, seg * 32, 2 * h); tma_store_commit(); };
  auto o_done = [&](int seg) {
    tma_store_wait_all();
    if ((seg & 3) == 3) {
      asm volatile("fence.proxy.async;" ::: "memory");
      asm volatile("red.release.gpu.global.add.u32 [%0], 1;" ::"l"(&g_oflag[seg >> 2]) : "memory");
    }
  };
#pragma unroll 1
  for (int s = -1; s < cfg::NSEG; s++) {
    uint32_t t_pub = 0;
    sel ^= 0x55;
    const bool last = s + 1 == cfg::NSEG;
    if (s >= 0) {
      PROF(1, 1);
      float a0[4], a1[4];
      proj_mem<ISV, 1>(wr, ta, wsa, mba, a0, a1);
      PROF(1, 2);
      uint32_t vmo[2][2];
      proj_finish<ISV, 1>(a0, a1, peer0, peer1, self, tid, vmo);
      PROF(1, 3);
      uint32_t wf[PF1][4], woa;
      if (ISV) {
        if (warp == 3 && !last) {
          mbar_spin(B_VM, s & 1);
          if (elect_one()) load_xn(P, s + 1, self);
        }
        if (s > 0) tok_pv(s - 1, vmo);
        OPQ;
        woa = WO + w * 4096 + ((mi >> 1) * 8 + mr) * 32 + (((mi & 1) ^ (mr >> 2)) << 4);
      } else {
        float c0[4], c1[4];
        if (warp == 0) {
          OPQ;
          uint32_t kf[4][4], qf[4][4];
          float d0[4], d1[4];
          const uint32_t ka = PT + 2048 + (mi & 1) * 256 + (mi >> 1) * 128 + mr * 16;
#pragma unroll
          for (int k = 0; k < 4; k++) { ldsm4t(qf[k], PT + k * 512 + lane * 16); ldsm4t(kf[k], ka + k * 512); }
          mma16816z(c0, qf[0], kf[0][0], kf[0][1]); mma16816z(c1, qf[0], kf[0][2], kf[0][3]);
          mma16816z(d0, qf[1], kf[1][0], kf[1][1]); mma16816z(d1, qf[1], kf[1][2], kf[1][3]);
          mma16816(c0, qf[2], kf[2][0], kf[2][1]); mma16816(c1, qf[2], kf[2][2], kf[2][3]);
          mma16816(d0, qf[3], kf[3][0], kf[3][1]); mma16816(d1, qf[3], kf[3][2], kf[3][3]);
          const float s0 = ((c0[0] + c0[2]) + (c1[0] + c1[2])) + ((d0[0] + d0[2]) + (d1[0] + d1[2]));
          const float s1 = ((c0[1] + c0[3]) + (c1[1] + c1[3])) + ((d0[1] + d0[3]) + (d1[1] + d1[3]));
          if (!last) send_scores(s0, s1, SP + rank * SP_SRC + (128 + lane) * SPW, peer0, peer1, B_SM, lane);
          PROF(1, 5);
#pragma unroll
          for (int mt = 0; mt < 2; mt++) {
            float* c = mt ? c1 : c0;
#pragma unroll
            for (int k = 0; k < 4; k++) ldsm4t(qf[k], QK + mt * 2048 + k * 512 + lane * 16);
            mma16816z(c, qf[0], kf[0][0], kf[0][1]); mma16816z(d0, qf[0], kf[0][2], kf[0][3]);
#pragma unroll
            for (int k = 1; k < 4; k++) { mma16816(c, qf[k], kf[k][0], kf[k][1]); mma16816(d0, qf[k], kf[k][2], kf[k][3]); }
#pragma unroll
            for (int i = 0; i < 4; i++) c[i] += d0[i];
          }
        } else {
          const uint32_t t_c = clk32();
          if (warp == 3 && !last) { if (elect_one()) load_xn(P, s + 1, self); }
          spin_until(t_c + D_ST);
          OPQ;
          const int mt = w >> 1, j0 = w == 3 ? 2 : 0;
          uint32_t qf[4][4], kf[4][4];
#pragma unroll
          for (int k = 0; k < 4; k++) { ldsm4t(qf[k], QK + mt * 2048 + k * 512 + lane * 16); ldsm4t(kf[k], QK + 4096 + j0 * 1024 + k * 512 + lane * 16); }
          mma16816z(c0, qf[0], kf[0][0], kf[0][1]); mma16816z(c1, qf[0], kf[2][0], kf[2][1]);
          mma16816(c0, qf[1], kf[0][2], kf[0][3]); mma16816(c1, qf[1], kf[2][2], kf[2][3]);
          mma16816(c0, qf[2], kf[1][0], kf[1][1]); mma16816(c1, qf[2], kf[3][0], kf[3][1]);
          mma16816(c0, qf[3], kf[1][2], kf[1][3]); mma16816(c1, qf[3], kf[3][2], kf[3][3]);
        }
        OPQ;
        const uint32_t dst = peer1 + QK + rank * 3584 + lane * 8, dbar = peer1 + B_ST;
        woa = WO + w * 4096 + ((mi >> 1) * 8 + mr) * 32 + (((mi & 1) ^ (mr >> 2)) << 4);
        const uint32_t tbl = w == 0 ? 0x9520u : w == 1 ? 0x4F31u : w == 2 ? 0xB7A6u : 0xDFC8u;
        PROF(1, 6);
        mbar_spin(last ? B_VM : B_VX, s & 1);
        st_async64f(dst + (tbl & 15) * 256, c0[0], c0[1], dbar);
        st_async64f(dst + ((tbl >> 4) & 15) * 256, c0[2], c0[3], dbar);
        if ((w & 1) == 0) st_async64f(dst + ((tbl >> 8) & 15) * 256, c1[0], c1[1], dbar);
        st_async64f(dst + (tbl >> 12) * 256, c1[2], c1[3], dbar);
      }
      PROF(1, 4);
      if (!last) {
        OPQ;
        uint32_t oba = OB + lane * 16;
        PIN(oba);
        wo_prefetch<3, 0, PF1>(wf, woa);
        char* h1p = P.xch + (tile0 + w) * 32768 + (h >> 3) * 8192 + (h & 7) * 256 + lane * 8;
        if (ISV) fence_proxy_async_smem();
        PROF(1, 7);
        named_bar_sync(NB_O, 256);
        PROF(1, 8);
        wo_phase<3, PF1>(wf, woa, oba, h1p, sel, ((s >> 1) & 1) ^ 1);
        t_pub = clk32();
        named_bar_arrive(NB_HD, 256);
        PROF(1, 9);
        if (ISV && warp == 0 && s > 0) { if (elect_one()) o_store(s - 1); }
        if (!ISV && tid == 192) mbar_arrive_remote(peer1 + B_PF);
        if (tid == 160) {
          if (s + 2 < cfg::NSEG) { mbar_expect_tx(B_SM, ISV ? 2 * SP_SRC : SP_SRC); if (!ISV) mbar_expect_tx(B_VX, 8192); }
          if (!ISV) mbar_expect_tx(B_VM, 2048);
        }
        __syncwarp();
      }
    }
    auto refill = [&]() {
      if (warp == 3) {
        named_bar_sync(NB_XE, 160);
        if (elect_one()) {
          mbar_expect_tx(B_XN + 8, 16384);
          tma_load_3d(XN, &P.xn, 0, (s + 1) * 32, 12, B_XN + 8);
        }
      }
    };
    if (s < 0) {
      if (ISV && warp == 0) named_bar_arrive(NB_CF, 160);
      refill();
      if (PAUSE && !ISV) { uint32_t t_; named_bar_and(NB_PZ, 256, 1, t_); }
    } else if (!ISV) {
      if (last) break;
      OPQ;
      const int j = 2 * h + rank;
      const char* src = P.xch + j * 32768 + w * 8192 + ((sel >> 6) & 3) * 2048 + lane * 8;
      char* dst = P.xch + H1_BYTES + (j >> 4) * 8192 + (j & 15) * 256 + (w & 1) * 128 + lane * 4;
      const uint32_t tmask = (s >> 1) & 1;
      const bool sw = lq >= 2;
      uint32_t rw = PT + w * 512 + (2 * lq + sw) * 32 + lg * 4, rr = PT + (w & 1) * 256 + lane * 8;
      PIN(rw); PIN(rr);
      uint2 v[8];
      spin_until(t_pub + D_H1);
#pragma unroll
      for (int i = 0; i < 8; i++) v[i] = ld_poll8(src + i * 256);
      refill();
      auto partial = [&]() {
        float f[4];
        f[0] = ((bf_lo(v[0].x) + bf_lo(v[1].x)) + (bf_lo(v[2].x) + bf_lo(v[3].x))) + ((bf_lo(v[4].x) + bf_lo(v[5].x)) + (bf_lo(v[6].x) + bf_lo(v[7].x)));
        f[1] = ((bf_hi(v[0].x) + bf_hi(v[1].x)) + (bf_hi(v[2].x) + bf_hi(v[3].x))) + ((bf_hi(v[4].x) + bf_hi(v[5].x)) + (bf_hi(v[6].x) + bf_hi(v[7].x)));
        f[2] = ((bf_lo(v[0].y) + bf_lo(v[1].y)) + (bf_lo(v[2].y) + bf_lo(v[3].y))) + ((bf_lo(v[4].y) + bf_lo(v[5].y)) + (bf_lo(v[6].y) + bf_lo(v[7].y)));
        f[3] = ((bf_hi(v[0].y) + bf_hi(v[1].y)) + (bf_hi(v[2].y) + bf_hi(v[3].y))) + ((bf_hi(v[4].y) + bf_hi(v[5].y)) + (bf_hi(v[6].y) + bf_hi(v[7].y)));
        sts32(rw, __float_as_uint(sw ? f[1] : f[0]));
        sts32(rw ^ 32, __float_as_uint(sw ? f[0] : f[1]));
        sts32(rw + 256, __float_as_uint(sw ? f[3] : f[2]));
        sts32((rw ^ 32) + 256, __float_as_uint(sw ? f[2] : f[3]));
        uint32_t t0, t1, t2, t3;
        asm("lop3.b32 %0, %1, %2, %3, 0x42;" : "=r"(t0) : "r"(v[0].x), "r"(v[1].x), "r"(tmask));
        asm("lop3.b32 %0, %1, %2, %3, 0x42;" : "=r"(t1) : "r"(v[2].x), "r"(v[3].x), "r"(tmask));
        asm("lop3.b32 %0, %1, %2, %3, 0x42;" : "=r"(t2) : "r"(v[4].x), "r"(v[5].x), "r"(tmask));
        asm("lop3.b32 %0, %1, %2, %3, 0x42;" : "=r"(t3) : "r"(v[6].x), "r"(v[7].x), "r"(tmask));
        return t0 & t1 & t2 & t3 & 1;
      };
      uint32_t ok = partial();
      PROF(1, 10);
      if (PAUSE) named_bar_and(NB_PZ, 256, ok, ok); else named_bar_and(NB_W1, 128, ok, ok);
      if (!ok) {
#pragma unroll 1
        for (int tries = 0; tries < POLL_TRIES; tries++) {
#pragma unroll
          for (int i = 0; i < 8; i++) v[i] = ld_strong8(src + i * 256);
          RETRY(0);
          ok = partial();
          named_bar_and(NB_W1, 128, ok, ok);
          if (ok) break;
        }
      }
      if (FLAGS && warp == 2 && lane < 8) st_pub16(P.xch + FL_OFF + (lane & 1) * 4096 + (lane >> 1) * 128 + j * 2, s + 1);
      if (warp < 2) {
        const float2 y0 = lds64f(rr), y1 = lds64f(rr + 512), y2 = lds64f(rr + 1024), y3 = lds64f(rr + 1536);
        const uint32_t r = pack_bf16((y0.x + y1.x) + (y2.x + y3.x), (y0.y + y1.y) + (y2.y + y3.y));
        st_pub32(dst + (s & 1) * 32768, r);
        st_pub32(dst + (s & 1) * 32768 + 4096, r);
        st_pub32(dst + ((s & 1) ^ 1) * 32768, EMPTY);
        st_pub32(dst + ((s & 1) ^ 1) * 32768 + 4096, EMPTY);
      }
      if (s == 0 && t7 == 0) st_pub32(&g_mask[j], 0);
      PROF(1, 11);
    } else {
      {
        OPQ;
        const uint32_t sa = QK + ((w * (w + 3)) >> 1) * 256 + lane * 8;
        mbar_spin(B_ST, s & 1);
        if (tid == 160 && !last) mbar_expect_tx(B_ST, 7168);
        float sc[10];
        const float scale = 0.08838834764831845f, NEG = -1000000000.0f;
#pragma unroll
        for (int b = 0; b < 5; b++) {
          sc[2 * b] = NEG; sc[2 * b + 1] = NEG;
          if (b <= warp + 1) {
            const float2 x = lds64f(sa + b * 256), y = lds64f(sa + 3584 + b * 256);
            const bool diag = b == warp + 1;
            if (!(diag && 2 * lq > lg)) sc[2 * b] = (x.x + y.x) * scale;
            if (!(diag && 2 * lq + 1 > lg)) sc[2 * b + 1] = (x.y + y.y) * scale;
          }
        }
        float m = fmaxf(fmaxf(fmaxf(sc[0], sc[1]), fmaxf(sc[2], sc[3])), fmaxf(fmaxf(sc[4], sc[5]), fmaxf(sc[6], sc[7])));
        m = fmaxf(m, fmaxf(sc[8], sc[9]));
        m = fmaxf(m, __shfl_xor_sync(0xffffffffu, m, 1));
        m = fmaxf(m, __shfl_xor_sync(0xffffffffu, m, 2));
        float sum = 0.f;
#pragma unroll
        for (int i = 0; i < 10; i++) { sc[i] = ex2_approx((sc[i] - m) * 1.4426950408889634f); sum += sc[i]; }
        sum += __shfl_xor_sync(0xffffffffu, sum, 1);
        sum += __shfl_xor_sync(0xffffffffu, sum, 2);
        const float inv = rcp_approx(sum);
        sts128(PT + w * 512 + lane * 16, pack_bf16(sc[2] * inv, sc[3] * inv), pack_bf16(sc[4] * inv, sc[5] * inv),
               pack_bf16(sc[6] * inv, sc[7] * inv), pack_bf16(sc[8] * inv, sc[9] * inv));
        sts32(PT + 2048 + lane * 16 + w * 4, pack_bf16(sc[0] * inv, sc[1] * inv));
        PROF(1, 10);
        if (last) {
          uint32_t vm[2][2];
          mbar_spin(B_VM, s & 1);
          lds64(vm[0], VM + t7 * 8); lds64(vm[1], VM + 1024 + t7 * 8);
          named_bar_sync(NB_W1, 128);
          tok_pv(s, vm);
          fence_proxy_async_smem();
          named_bar_sync(NB_W1, 128);
          if (warp == 0) { if (elect_one()) { o_store(s - 1); o_store(s); o_done(s); } }
          break;
        }
      }
      if (warp == 0) {
        if (s > 0) { if (elect_one()) o_done(s - 1); }
        __syncwarp();
        named_bar_arrive(NB_CF, 160);
      }
      refill();
      PROF(1, 11);
    }
    {
      const uint32_t ph = (s + 1) & 1;
      float x0[16], x1[16];
      mbar_spin(B_XN, ph);
      named_bar_sync(NB_ST, 256);
      PROF(1, 12);
      wg_fence();
#pragma unroll
      for (int c = 0; c < 6; c++) {
        if (c == 2) { mbar_spin(B_XN + 8, ph); wg_fence(); }
#pragma unroll
        for (int u = 0; u < 4; u++) {
          wgmma_rs_n32(x0, wr[c][0][u], xn_desc(c < 2 ? 10 + c : c - 2, u), (c | u) != 0);
          wgmma_rs_n32(x1, wr[c][1][u], xn_desc(c < 2 ? 10 + c : c - 2, u), (c | u) != 0);
        }
      }
      wg_commit();
      OPQ;
      named_bar_sync(NB_DU, 256);
      wg_wait<0>();
      PROF(1, 13);
      const uint32_t tb = ISV ? (ph ? VX2 : VX) : QK;
      tok_store<ISV, 1, true>(x1, tb, tid);
      tok_store<ISV, 0, true>(x0, tb, tid);
      if (ISV && s + 2 < cfg::NSEG) {
        fence_proxy_async_smem();
        named_bar_sync(NB_W1, 128);
        if (warp >= 2) {
          if (s >= 0) mbar_spin(B_PF, s & 1);
          const uint32_t peer = warp == 2 ? peer0 : peer1;
          if (elect_one()) bulk_s2s(peer + VX, tb, 8192, peer + B_VX);
        }
      }
      wsa = WS + ((mi >> 1) * 8 + mr) * 128 + (((2 * w + (mi & 1)) ^ mr) << 4);
      mba = MEMB + lane * 16;
      PIN(wsa); PIN(mba);
      proj_mem_prefetch<1>(ta, wsa);
      PROF(1, 14);
      named_bar_sync(NB_M1, 256);
    }
  }
}

template <bool ISV, int WG>
__device__ __forceinline__ void f_main(const FParams& P, const int h, const int rank) {
  using namespace fk;
  const uint32_t self = mapa(0, rank);
  SMAP;
  const int tid = __shfl_sync(0xffffffffu, threadIdx.x, threadIdx.x & 31);
  const int tile0 = rank * 22, ntile = ISV ? 20 : 22;
  const CUtensorMap* m0 = ISV ? &P.wv : &P.wq;
  const CUtensorMap* m1 = ISV ? &P.wv : &P.wk;
  const int col0 = h * 128 + (ISV ? 0 : 64 * rank), col1 = h * 128 + (ISV ? 64 : 64 * rank);
  if (threadIdx.x == 0) {
#pragma unroll 1
    for (int i = 0; i < 6; i++) {
      mbar_expect_tx(B_PB + 8 * i, 32768);
#pragma unroll
      for (int g = 0; g < 2; g++) {
        const int row = Chunks<ISV>::rf(g, i) * 64;
        tma_load_2d(SM0 + i * 32768 + g * 16384, m0, col0, row, B_PB + 8 * i);
        tma_load_2d(SM0 + i * 32768 + g * 16384 + 8192, m1, col1, row, B_PB + 8 * i);
      }
    }
  }
  __syncwarp();
  pdl_wait();
  pdl_launch_dependents();
  WRegs wr;
  {
    OPQ;
    const uint32_t a = SM0 + WG * 16384 + ((mi >> 1) * 8 + mr) * 128 + (((2 * w + (mi & 1)) ^ mr) << 4);
#pragma unroll
    for (int i = 0; i < 6; i++) {
      mbar_wait(B_PB + 8 * i, 0);
#pragma unroll
      for (int T = 0; T < 2; T++)
#pragma unroll
        for (int u = 0; u < 4; u++) ldsm4t(wr[i][T][u], a + i * 32768 + T * 8192 + u * 2048);
      named_bar_sync(NB_C, 256);
      if (WG == 1 && i < 5 && threadIdx.x == 128 + 32 * (i & 3)) {
        const int t0 = 8 * i, t1 = i < 3 ? min(8 * i + 8, ntile) : t0, p0 = i == 2 ? 0 : i == 3 ? 1 : 5, p1 = i < 2 ? p0 : i == 2 ? 1 : i == 3 ? 5 : 8;
        mbar_expect_tx(B_W, (t1 - t0) * 4096 + (p1 - p0) * 8192);
#pragma unroll 1
        for (int p = p0; p < p1; p++) tma_load_2d(WS + p * 8192, (p & 1) ? m1 : m0, (p & 1) ? col1 : col0, (Chunks<ISV>::SC0 + (p >> 1)) * 64, B_W);
#pragma unroll 1
        for (int t = t0; t < t1; t++) tma_load_2d(WO + t * 4096, &P.wo, (tile0 + t) * 16, h * 128, B_W);
      }
      __syncwarp();
    }
  }
  PROF2(1);
  if (threadIdx.x == 224) load_xn(P, 0, self);
  __syncwarp();
  mbar_wait(B_W, 0);
  PROF2(4);
  GTSYNC(0);
  uint32_t sel = 0;
  {
    OPQ;
    const int j = 2 * h + rank;
    if (WG == 0) {
      if (lane == 0) {
        char* p = P.xch + H1_BYTES + w * 8192 + (blockIdx.x & 31) * 128;
        sel = (probe_pair(p, EMPTY, PROBE + 32) << 8) | (probe_pair(p + 32768, EMPTY, PROBE + 32) << 9);
      }
    } else if (!ISV) {
      char* p = P.xch + j * 32768 + w * 8192;
      if (lane == 0) sel = probe_pair(p, 0, PROBE + 32) << 7;
      sel = __shfl_sync(0xffffffffu, sel, 0);
#pragma unroll
      for (int i = 0; i < 8; i++) st_pub128(p + (sel >> 7) * 4096 + i * 512 + lane * 16, 0);
      st_pub64(P.xch + H1_BYTES + (w >> 1) * 32768 + (j >> 4) * 8192 + (w & 1) * 4096 + (j & 15) * 256 + lane * 8, EMPTY, EMPTY);
      if (t7 < 8) st_pub16(P.xch + FL_OFF + (lane & 1) * 4096 + (lane >> 1) * 128 + j * 2, 0);
      if (lane == 0) sts32(PROBE + w * 4, sel >> 7);
      __threadfence();
      named_bar_sync(NB_W1, 128);
      if (t7 == 0) {
        const uint32_t m = 0x10 | lds32(PROBE) | (lds32(PROBE + 4) << 1) | (lds32(PROBE + 8) << 2) | (lds32(PROBE + 12) << 3);
        asm volatile("st.release.gpu.global.u32 [%0], %1;" ::"l"(&g_mask[j]), "r"(m) : "memory");
      }
    }
    sel = __shfl_sync(0xffffffffu, sel, 0);
  }
  PROF2(3);
  {
    OPQ;
    if (WG == 1 && w == 1) {
      uint2 v;
#pragma unroll 1
      for (int tries = 0; tries < POLL_TRIES; tries++) {
        v = ld_strong8(&g_mask[2 * lane]);
        if (__all_sync(0xffffffffu, v.x & v.y & 0x10)) break;
        __nanosleep(100);
      }
      __threadfence();
      sts64(MASKS + lane * 8, v.x, v.y);
    }
    named_bar_sync(NB_C, 256);
#pragma unroll
    for (int i = 0; i < 3; i++) {
      const int t = min(tile0 + 8 * i + w + (WG ? 0 : 4), 63);
      sel |= ((lds32(MASKS + t * 4) >> (h >> 3)) & 1) << (2 * i + 1);
    }
  }
  PROF2(2);
  KT_END(8);
  if (WG == 0) f_wg0<ISV>(P, wr, h, rank, sel, tid); else f_wg1<ISV>(P, wr, h, rank, sel, tid);
}

__global__ void __launch_bounds__(256, 1) f_kernel(const __grid_constant__ FParams P) {
  using namespace fk;
  extern __shared__ __align__(1024) uint8_t smem_f[];
  uint32_t rank;
  asm("mov.u32 %0, %%cluster_ctarank;" : "=r"(rank));
  const int h = blockIdx.x / 3;
  if (smem_u32(smem_f) != mapa(0, rank) + SM0) return;
  SCHED_DECL(threadIdx.x * P.one);
  PROF2(0);
  KT_START(1);
  if (threadIdx.x == 0) {
    const bool isv = rank == 2;
    const uint32_t self = mapa(0, rank);
    SMAP;
    for (int i = 0; i < 2; i++) mbar_init(B_XN + 8 * i, 1);
    for (int i = 0; i < 4; i++) mbar_init(B_H2 + 8 * i, 1);
    mbar_init(B_SM, isv ? 1 : 6);
    mbar_init(B_VM, isv ? 8 : 1);
    mbar_init(B_VX, 1);
    mbar_init(B_ST, 1);
    mbar_init(B_PF, 2);
    for (int i = 0; i < 6; i++) mbar_init(B_PB + 8 * i, 1);
    mbar_init(B_W, 5);
    fence_barrier_init();
    mbar_expect_tx(B_SM, isv ? 2 * SP_SRC : SP_SRC);
    if (isv) mbar_expect_tx(B_ST, 7168);
    else { mbar_expect_tx(B_VM, 2048); mbar_expect_tx(B_VX, 8192); }
  }
  __syncthreads();
  cluster_sync();
  const int wg = __shfl_sync(0xffffffffu, threadIdx.x >> 7, 0);
  if (rank == 2) { if (wg == 0) f_main<true, 0>(P, h, 2); else f_main<true, 1>(P, h, 2); }
  else { if (wg == 0) f_main<false, 0>(P, h, rank); else f_main<false, 1>(P, h, rank); }
  PROF2(5);
  GTSYNC(1);
  KT_END(1);
  __syncwarp();
  cluster_sync();
}

namespace gk {
enum { T_B1 = 0, T_B2 = 1, T_B3 = 2, T_B4 = 3, T_O = 4, T_LN = 5, T_END = 7 };
constexpr int NST = 4, STAGE = 49152, MAXITEMS = 256;
constexpr uint32_t OUTB = NST * STAGE, BARS = OUTB + 32768;
constexpr uint32_t B_FULL = BARS, B_EMPTY = BARS + 32, B_ITEM = BARS + 64, B_FILL = BARS + 128, B_FREE = BARS + 160, ITEMS = BARS + 192;
constexpr int SMEM = BARS + 256;
}
struct GParams {
  CUtensorMap a[5], b[5], c[5], r[4];
  const bf16* x1;
  bf16* x1n;
  int nitems;
  uint16_t items[gk::MAXITEMS];
};
__device__ unsigned g_cnt[6][16];
__device__ unsigned g_next;
#define ILOG(i)

__device__ __forceinline__ void tma_load_3d_mc(uint32_t dst, const CUtensorMap* map, int x, int y, int z, uint32_t bar) {
  asm volatile("cp.async.bulk.tensor.3d.shared::cluster.global.mbarrier::complete_tx::bytes.multicast::cluster "
               "[%0], [%1, {%3, %4, %5}], [%2], %6;"
               ::"r"(dst), "l"(map), "r"(bar), "r"(x), "r"(y), "r"(z), "h"((uint16_t)3) : "memory");
}
__device__ __forceinline__ void wait_count(const unsigned* p, unsigned need) {
#pragma unroll 1
  for (int tries = 0; tries < (1 << 16); tries++) {
    unsigned v;
    asm volatile("ld.acquire.gpu.global.u32 %0, [%1];" : "=r"(v) : "l"(p) : "memory");
    if (v >= need) break;
    __nanosleep(200);
  }
}
__device__ __forceinline__ float tanh_approx(float x) { float y; asm("tanh.approx.f32 %0, %1;" : "=f"(y) : "f"(x)); return y; }

template <int TYPE>
__device__ __forceinline__ void g_piece(const float* acc, uint32_t out, uint32_t r0, uint32_t r1) {
#pragma unroll
  for (int jj = 0; jj < 8; jj += 2) {
    uint32_t ra[4], rb[4], o[4];
    if (TYPE == gk::T_B2 || TYPE == gk::T_B4 || TYPE == gk::T_O) ldsm4(ra, r0 ^ (jj << 4));
    if (TYPE == gk::T_O) ldsm4(rb, r1 ^ (jj << 4));
#pragma unroll
    for (int hh = 0; hh < 2; hh++) {
      const float* a = acc + (jj + hh) * 4;
      const uint32_t s0 = pack_bf16(a[0], a[1]), s1 = pack_bf16(a[2], a[3]);
      float v[4] = {bf_lo(s0), bf_hi(s0), bf_lo(s1), bf_hi(s1)};
      if (TYPE == gk::T_B1) gelu4(v);
      if (TYPE == gk::T_B2 || TYPE == gk::T_B4) {
        v[0] += bf_lo(ra[2 * hh]); v[1] += bf_hi(ra[2 * hh]); v[2] += bf_lo(ra[2 * hh + 1]); v[3] += bf_hi(ra[2 * hh + 1]);
        if (TYPE == gk::T_B4) {
          const uint32_t y0 = pack_bf16(v[0], v[1]), y1 = pack_bf16(v[2], v[3]);
          v[0] = bf_lo(y0); v[1] = bf_hi(y0); v[2] = bf_lo(y1); v[3] = bf_hi(y1);
          silu4(v);
        }
      }
      if (TYPE == gk::T_O) {
#pragma unroll
        for (int k = 0; k < 2; k++) {
          const uint32_t t = pack_bf16(v[2 * k] * bf_lo(rb[2 * hh + k]), v[2 * k + 1] * bf_hi(rb[2 * hh + k]));
          v[2 * k] = bf_lo(ra[2 * hh + k]) + bf_lo(t);
          v[2 * k + 1] = bf_hi(ra[2 * hh + k]) + bf_hi(t);
        }
      }
      o[2 * hh] = pack_bf16(v[0], v[1]);
      o[2 * hh + 1] = pack_bf16(v[2], v[3]);
    }
    stsm4(out ^ (jj << 4), o[0], o[1], o[2], o[3]);
  }
}

template <int TYPE>
__device__ __forceinline__ void g_epilogue(const float (&acc)[128], uint32_t base, int& it, int& np, int wg, int tid) {
  using namespace gk;
  const int lane = tid & 31, mi = lane >> 3, mr = lane & 7;
  const uint32_t rowoff = (((tid >> 5) & 3) * 16 + (mi & 1) * 8 + mr) * 128 + (((mi >> 1) ^ mr) << 4);
  constexpr int NR = TYPE == T_O ? 2 : TYPE == T_B1 ? 0 : 1;
  auto piece = [&](int rho) { return base + ((it + rho / 3) % NST) * STAGE + (rho % 3) * 16384 + wg * 8192 + rowoff; };
#pragma unroll
  for (int p = 0; p < 4; p++, np++) {
    const int b = wg * 2 + (p & 1);
#pragma unroll
    for (int rho = p * NR; rho < (p + 1) * NR; rho++)
      if (rho % 3 == 0) { const int k = it + rho / 3; mbar_spin(base + B_FULL + 8 * (k % NST), (k / NST) & 1); }
    if (np >= 2) mbar_spin(base + B_FREE + 8 * b, ((np >> 1) - 1) & 1);
    g_piece<TYPE>(&acc[p * 32], base + OUTB + b * 8192 + rowoff, piece(p * NR), piece(p * NR + 1));
    fence_proxy_async_smem();
    __syncwarp();
    if (lane == 0) mbar_arrive(base + B_FILL + 8 * b);
#pragma unroll
    for (int rho = p * NR; rho < (p + 1) * NR; rho++)
      if ((rho % 3 == 2 || rho == 4 * NR - 1) && lane < 2) mbar_arrive_cluster(base + B_EMPTY + 8 * ((it + rho / 3) % NST), lane);
  }
  it += (4 * NR + 2) / 3;
}

__global__ void __launch_bounds__(384, 1) g_kernel(const __grid_constant__ GParams P) {
  using namespace gk;
  extern __shared__ __align__(1024) uint8_t smem_g[];
  const uint32_t base = smem_u32(smem_g);
  const int tid = threadIdx.x, warp = __shfl_sync(0xffffffffu, tid >> 5, 0), lane = tid & 31;
  const int rank = blockIdx.x & 1;
  KT_START(2);
  if (tid == 0) {
    for (int s = 0; s < NST; s++) { mbar_init(base + B_FULL + 8 * s, 1); mbar_init(base + B_EMPTY + 8 * s, 16); }
    for (int s = 0; s < 8; s++) mbar_init(base + B_ITEM + 8 * s, 1);
    for (int s = 0; s < 4; s++) { mbar_init(base + B_FILL + 8 * s, 4); mbar_init(base + B_FREE + 8 * s, 1); }
    fence_barrier_init();
  }
  __syncthreads();
  cluster_sync();
  auto get_item = [&](int q) {
    mbar_wait(base + B_ITEM + 8 * (q & 7), (q >> 3) & 1);
    return lds32(base + ITEMS + 4 * (q & 7));
  };

  if (warp >= 8) {
   asm volatile("setmaxnreg.dec.sync.aligned.u32 40;");
   if (warp == 8) {
    if (lane == 0) {
      int it = 0;
      auto acquire = [&]() { if (it >= NST) mbar_wait(base + B_EMPTY + 8 * (it % NST), ((it / NST) - 1) & 1); };
#pragma unroll 1
      for (int q = 0;; q++) {
        mbar_expect_tx(base + B_ITEM + 8 * (q & 7), 4);
        if (rank == 0) {
          const unsigned idx = atomicAdd(&g_next, 1);
          const uint32_t v = idx < (unsigned)P.nitems ? P.items[idx] : T_END;
#pragma unroll
          for (int r = 0; r < 2; r++) st_async32(mapa(base + ITEMS + 4 * (q & 7), r), v, mapa(base + B_ITEM + 8 * (q & 7), r));
        }
        const uint32_t item = get_item(q);
        const int type = item & 7, mb = ((item >> 3) & 7) * 2 + rank, nt = item >> 6;
        ILOG(1);
        if (type == T_END) break;
        if (type == T_B2) {
          wait_count(&g_cnt[T_B1][max(mb - 1, 0)], 8); wait_count(&g_cnt[T_B1][mb], 8); wait_count(&g_cnt[T_B1][min(mb + 1, 15)], 8);
        } else if (type == T_LN) wait_count(&g_cnt[T_B2][mb], 8);
        else if (type == T_B3) wait_count(&g_cnt[T_LN][mb], 8);
        else if (type == T_B4) wait_count(&g_cnt[T_B3][mb], 28);
        else if (type == T_O) wait_count(&g_oflag[mb], 32);
        asm volatile("fence.proxy.async;" ::: "memory");
        ILOG(2);
        if (type == T_LN) {
          acquire();
          mbar_arrive(base + B_FULL + 8 * (it % NST));
          it++;
          continue;
        }
        const CUtensorMap *ma = &P.a[type], *mbm = &P.b[type];
        const int nkb = type == T_B4 ? cfg::F / 64 : type == T_O ? cfg::HD / 64 : cfg::D / 64;
#pragma unroll 1
        for (int kb = 0; kb < nkb; kb++, it++) {
          acquire();
          const uint32_t sa = base + (it % NST) * STAGE, full = base + B_FULL + 8 * (it % NST);
          mbar_expect_tx(full, STAGE);
          int arow = mb * 128;
          if (type == T_B2) { const int qd = kb >> 2; arow += (qd == 0) ? -1 : (qd == 1) ? 1 : (qd == 2) ? -2 : 2; }
          tma_load_3d_mc(sa + 16384 + rank * 16384, mbm, 0, kb * 64, nt * 4 + rank * 2, full);
          tma_load_2d(sa, ma, kb * 64, arow, full);
        }
        const int nres = type == T_O ? 8 : (type == T_B2 || type == T_B4) ? 4 : 0;
        if (type == T_O) { wait_count(&g_cnt[T_B4][mb], 8); asm volatile("fence.proxy.async;" ::: "memory"); }
#pragma unroll 1
        for (int rho = 0; rho < nres; rho += 3, it++) {
          acquire();
          const uint32_t sa = base + (it % NST) * STAGE, full = base + B_FULL + 8 * (it % NST);
          const int n = min(3, nres - rho);
          mbar_expect_tx(full, n * 16384);
          for (int i = 0; i < n; i++) {
            const int rr = rho + i;
            const CUtensorMap* m = type == T_O ? &P.r[2 + (rr & 1)] : &P.r[type == T_B4];
            tma_load_2d(sa + i * 16384, m, nt * 256 + (type == T_O ? rr >> 1 : rr) * 64, mb * 128, full);
          }
        }
      }
    }
   } else {
    if (lane == 0 && warp < 11) {
      const int wg = warp - 9;
      int np = 0;
#pragma unroll 1
      for (int q = 0;; q++) {
        const uint32_t item = get_item(q);
        const int type = item & 7, mb = ((item >> 3) & 7) * 2 + rank, nt = item >> 6;
        if (type == T_END) break;
        if (type == T_LN) continue;
#pragma unroll 1
        for (int p = 0; p < 4; p++, np++) {
          const int b = wg * 2 + (p & 1);
          mbar_wait(base + B_FILL + 8 * b, (np >> 1) & 1);
          tma_store_2d(&P.c[type], base + OUTB + b * 8192, nt * 256 + p * 64, mb * 128 + wg * 64);
          tma_store_commit();
          tma_store_wait_read();
          mbar_arrive(base + B_FREE + 8 * b);
        }
        tma_store_wait_all();
        if (type != T_O) {
          asm volatile("fence.proxy.async;" ::: "memory");
          asm volatile("red.release.gpu.global.add.u32 [%0], 1;" ::"l"(&g_cnt[type][mb]) : "memory");
        }
      }
    }
   }
   __syncwarp();
   pdl_wait();
   cluster_sync();
  } else {
    asm volatile("setmaxnreg.inc.sync.aligned.u32 232;");
    const int wg = warp >> 2;
    int it = 0, np = 0;
#pragma unroll 1
    for (int q = 0;; q++) {
      const uint32_t item = get_item(q);
      const int type = item & 7, mb = ((item >> 3) & 7) * 2 + rank;
      if (type == T_END) break;
      if (type == T_LN) {
        mbar_wait(base + B_FULL + 8 * (it % NST), (it / NST) & 1);
        if (lane < 2) mbar_arrive_cluster(base + B_EMPTY + 8 * (it % NST), lane);
        it++;
#pragma unroll 1
        for (int r4 = 0; r4 < 16; r4 += 4) {
          const size_t row = (size_t)(mb * 128 + warp * 16 + r4) * cfg::D + lane * 8;
          uint4 raw[4][4];
#pragma unroll
          for (int r = 0; r < 4; r++)
#pragma unroll
            for (int j = 0; j < 4; j++) raw[r][j] = __ldcg(reinterpret_cast<const uint4*>(P.x1 + row + r * cfg::D + j * 256));
#pragma unroll
          for (int r = 0; r < 4; r++) {
            float v[32];
#pragma unroll
            for (int j = 0; j < 4; j++) {
              const uint4 u = raw[r][j];
              v[j * 8 + 0] = bf_lo(u.x); v[j * 8 + 1] = bf_hi(u.x); v[j * 8 + 2] = bf_lo(u.y); v[j * 8 + 3] = bf_hi(u.y);
              v[j * 8 + 4] = bf_lo(u.z); v[j * 8 + 5] = bf_hi(u.z); v[j * 8 + 6] = bf_lo(u.w); v[j * 8 + 7] = bf_hi(u.w);
            }
            ln_row(v);
            store_row(P.x1n + (size_t)(mb * 128 + warp * 16 + r4 + r) * cfg::D, lane, v);
          }
        }
        __threadfence();
        __syncwarp();
        if (lane == 0) atomicAdd(&g_cnt[T_LN][mb], 1);
        if (tid == 0) ILOG(5);
        continue;
      }
      const int nkb = type == T_B4 ? cfg::F / 64 : type == T_O ? cfg::HD / 64 : cfg::D / 64;
      float acc[128];
#pragma unroll 1
      for (int kb = 0; kb < nkb; kb++, it++) {
        const int s = it % NST;
        if (kb == 0) mbar_wait(base + B_FULL + 8 * s, (it / NST) & 1); else mbar_spin(base + B_FULL + 8 * s, (it / NST) & 1);
        if (kb == 0 && tid == 0) ILOG(3);
        const uint32_t sa = base + s * STAGE + wg * 8192, sb = base + s * STAGE + 16384;
        wg_fence();
#pragma unroll
        for (int k = 0; k < 4; k++)
          wgmma_ss_n256_tb(acc, make_desc(sa + k * 32, 16, 1024), make_desc(sb + k * 2048, 8192, 1024), (kb | k) != 0);
        wg_commit();
        if (kb > 0) {
          wg_wait<1>();
          if (lane < 2) mbar_arrive_cluster(base + B_EMPTY + 8 * ((it - 1) % NST), lane);
        }
      }
      wg_wait<0>();
      if (tid == 0) ILOG(4);
      if (lane < 2) mbar_arrive_cluster(base + B_EMPTY + 8 * ((it - 1) % NST), lane);
      if (type == T_B1 || type == T_B3) g_epilogue<T_B1>(acc, base, it, np, wg, tid);
      else if (type == T_B2) g_epilogue<T_B2>(acc, base, it, np, wg, tid);
      else if (type == T_B4) g_epilogue<T_B4>(acc, base, it, np, wg, tid);
      else g_epilogue<T_O>(acc, base, it, np, wg, tid);
      if (tid == 0) ILOG(5);
    }
    KT_END(2);
    cluster_sync();
  }
}

__global__ void __launch_bounds__(288, 1)
tail_kernel(const __grid_constant__ CUtensorMap tmO, const __grid_constant__ CUtensorMap tmWo, const __grid_constant__ CUtensorMap tmOut,
            const __grid_constant__ CUtensorMap tmX, const __grid_constant__ CUtensorMap tmG, int mt0) {
  const int pair = blockIdx.x >> 1;
  gemm_body<128, 4, EPI_FINAL, false, false, 0>(&tmO, &tmWo, &tmOut, &tmOut, &tmX, &tmG, cfg::HD, mt0 + (pair >> 3) * 2 + (blockIdx.x & 1),
                                                pair & 7, nullptr);
}

__device__ void reset_exchange(int gtid, int nthreads) {
  if (gtid < 16) g_oflag[gtid] = 0;
  if (gtid < 96) (&g_cnt[0][0])[gtid] = 0;
  if (gtid == 0) g_next = 0;
}

__device__ bf16 g_xn[cfg::S * cfg::D];
__device__ bf16 g_xn2[cfg::S * cfg::D];
__device__ bf16 g_h[cfg::S * cfg::D];
__device__ bf16 g_x1[cfg::S * cfg::D];
__device__ bf16 g_x1n[cfg::S * cfg::D];
__device__ bf16 g_u[cfg::S * cfg::F];
__device__ bf16 g_g[cfg::S * cfg::D];
__device__ bf16 g_o[cfg::S * cfg::HD];

typedef CUresult (*PFN_encodeTiled)(CUtensorMap*, CUtensorMapDataType, cuuint32_t, void*, const cuuint64_t*,
                                    const cuuint64_t*, const cuuint32_t*, const cuuint32_t*, CUtensorMapInterleave,
                                    CUtensorMapSwizzle, CUtensorMapL2promotion, CUtensorMapFloatOOBfill);

static PFN_encodeTiled get_encoder() {
  static PFN_encodeTiled fn = nullptr;
  if (!fn) {
    void* p = nullptr;
    cudaDriverEntryPointQueryResult st;
    cudaGetDriverEntryPoint("cuTensorMapEncodeTiled", &p, cudaEnableDefault, &st);
    fn = (PFN_encodeTiled)p;
  }
  return fn;
}
static CUtensorMap make_map(const void* ptr, int rows, int cols, int box_rows, int box_cols, int swizzle_bytes) {
  CUtensorMap m;
  cuuint64_t dims[2] = {(cuuint64_t)cols, (cuuint64_t)rows};
  cuuint64_t strides[1] = {(cuuint64_t)cols * 2};
  cuuint32_t box[2] = {(cuuint32_t)box_cols, (cuuint32_t)box_rows};
  cuuint32_t estr[2] = {1, 1};
  CUtensorMapSwizzle sw = swizzle_bytes == 128 ? CU_TENSOR_MAP_SWIZZLE_128B
                        : swizzle_bytes == 64 ? CU_TENSOR_MAP_SWIZZLE_64B
                        : swizzle_bytes == 32 ? CU_TENSOR_MAP_SWIZZLE_32B : CU_TENSOR_MAP_SWIZZLE_NONE;
  get_encoder()(&m, CU_TENSOR_MAP_DATA_TYPE_BFLOAT16, 2, const_cast<void*>(ptr), dims, strides, box, estr,
                CU_TENSOR_MAP_INTERLEAVE_NONE, sw, CU_TENSOR_MAP_L2_PROMOTION_L2_128B, CU_TENSOR_MAP_FLOAT_OOB_FILL_NONE);
  return m;
}
static CUtensorMap make_map3(const void* ptr, int rows, int cols, int box_rows, int nblk) {
  CUtensorMap m;
  cuuint64_t dims[3] = {64, (cuuint64_t)rows, (cuuint64_t)(cols / 64)};
  cuuint64_t strides[2] = {(cuuint64_t)cols * 2, 128};
  cuuint32_t box[3] = {64, (cuuint32_t)box_rows, (cuuint32_t)nblk};
  cuuint32_t estr[3] = {1, 1, 1};
  get_encoder()(&m, CU_TENSOR_MAP_DATA_TYPE_BFLOAT16, 3, const_cast<void*>(ptr), dims, strides, box, estr,
                CU_TENSOR_MAP_INTERLEAVE_NONE, CU_TENSOR_MAP_SWIZZLE_128B, CU_TENSOR_MAP_L2_PROMOTION_L2_128B,
                CU_TENSOR_MAP_FLOAT_OOB_FILL_NONE);
  return m;
}
template <class T> static T* sym(T& s) { void* p = nullptr; cudaGetSymbolAddress(&p, s); return (T*)p; }
#define SYM(name) ((bf16*)[] { void* p = nullptr; cudaGetSymbolAddress(&p, name); return p; }())

template <class... KArgs, class... Args>
static void launch_pdl(void (*kern)(KArgs...), dim3 grid, dim3 block, int smem, cudaStream_t st, Args... args) {
  cudaLaunchConfig_t cfg = {};
  cfg.gridDim = grid; cfg.blockDim = block; cfg.dynamicSmemBytes = smem; cfg.stream = st;
  cudaLaunchAttribute at[1];
  at[0].id = cudaLaunchAttributeProgrammaticStreamSerialization;
  at[0].val.programmaticStreamSerializationAllowed = 1;
  cfg.attrs = at; cfg.numAttrs = 1;
  cudaLaunchKernelEx(&cfg, kern, KArgs(args)...);
}

#define G_CTAS 36
#define O_PAIRS 4
static int build_items(uint16_t* it) {
  using namespace gk;
  int n = 0;
  auto add = [&](int type, int mp, int nt) { it[n++] = (uint16_t)(type | mp << 3 | nt << 6); };
  for (int mp = 0; mp < 8; mp++) for (int nt = 0; nt < 4; nt++) add(T_B1, mp, nt);
  for (int mp = 0; mp < 8; mp++) {
    for (int nt = 0; nt < 4; nt++) add(T_B2, mp, nt);
    if (mp >= 5) add(T_LN, mp - 5, 0);
  }
  for (int mp = 0; mp < 8; mp++) {
    for (int nt = 0; nt < 14; nt++) {
      add(T_B3, mp, nt);
      const int k = mp * 14 + nt;
      if (k % 4 == 3 && k / 4 + 3 < 8) add(T_LN, k / 4 + 3, 0);
    }
  }
  for (int mp = 0; mp < 8; mp++) for (int nt = 0; nt < 4; nt++) add(T_B4, mp, nt);
  for (int mp = 0; mp < O_PAIRS; mp++) for (int nt = 0; nt < 4; nt++) add(T_O, mp, nt);
  return n;
}

extern "C" void kernel_launch(void* const* d_in, const int* in_sizes, int n_in, void* d_out, int out_size) {
  using namespace cfg;
  const bf16* x = (const bf16*)d_in[0];
  const bf16* mem0 = (const bf16*)d_in[1];
  const bf16* Wq = (const bf16*)d_in[2];
  const bf16* Wk = (const bf16*)d_in[3];
  const bf16* Wv = (const bf16*)d_in[4];
  const bf16* Wo = (const bf16*)d_in[5];
  const bf16* w1 = (const bf16*)d_in[8];
  const bf16* w2 = (const bf16*)d_in[9];
  const bf16* w3 = (const bf16*)d_in[10];
  const bf16* w4 = (const bf16*)d_in[11];
  bf16* out = (bf16*)d_out;
  cudaStream_t st = cudaStreamPerThread;

  bf16 *xn = SYM(g_xn), *xn2 = SYM(g_xn2), *hb = SYM(g_h), *x1 = SYM(g_x1), *x1n = SYM(g_x1n), *u = SYM(g_u),
       *g = SYM(g_g), *o = SYM(g_o);

  launch_pdl(ln_kernel<true>, dim3(S / 8), dim3(256), 0, st, x, xn, xn2);
  {
    cudaFuncSetAttribute(f_kernel, cudaFuncAttributeMaxDynamicSharedMemorySize, fk::SMEM);
    FParams P;
    P.wq = make_map(Wq, D, HD, 64, 64, 128); P.wk = make_map(Wk, D, HD, 64, 64, 128); P.wv = make_map(Wv, D, HD, 64, 64, 128);
    P.wo = make_map(Wo, HD, D, 128, 16, 32); P.xn = make_map3(xn, S, D, 32, 4); P.xn12 = make_map3(xn, S, D, 32, 12); P.o = make_map3(o, S, HD, 32, 2);
    P.mem0 = mem0;
    P.one = 1;
    P.xch = (char*)(((uintptr_t)SYM(g_xch) + 8191) & ~(uintptr_t)8191);
    cudaLaunchConfig_t cfg = {};
    cfg.gridDim = dim3(96); cfg.blockDim = dim3(256); cfg.dynamicSmemBytes = fk::SMEM; cfg.stream = st;
    cudaLaunchAttribute at[2];
    at[0].id = cudaLaunchAttributeClusterDimension;
    at[0].val.clusterDim.x = 3; at[0].val.clusterDim.y = 1; at[0].val.clusterDim.z = 1;
    at[1].id = cudaLaunchAttributeProgrammaticStreamSerialization;
    at[1].val.programmaticStreamSerializationAllowed = 1;
    cfg.attrs = at; cfg.numAttrs = 2;
    cudaLaunchKernelEx(&cfg, f_kernel, P);
  }
  {
    cudaFuncSetAttribute(g_kernel, cudaFuncAttributeMaxDynamicSharedMemorySize, gk::SMEM);
    GParams G;
    const bf16* as[5] = {xn2, hb, x1n, u, o};
    const bf16* bs[5] = {w1, w2, w3, w4, Wo};
    const bf16* cs[5] = {hb, x1, u, g, out};
    const bf16* rs[4] = {xn, x1, x, g};
    const int ks[5] = {D, D, D, F, HD}, ns[5] = {D, D, F, D, D};
    for (int i = 0; i < 5; i++) {
      G.a[i] = make_map(as[i], S, ks[i], 128, 64, 128);
      G.b[i] = make_map3(bs[i], ks[i], ns[i], 64, 2);
      G.c[i] = make_map(cs[i], S, ns[i], 64, 64, 128);
    }
    for (int i = 0; i < 4; i++) G.r[i] = make_map(rs[i], S, D, 128, 64, 128);
    G.x1 = x1; G.x1n = x1n;
    G.nitems = build_items(G.items);
    cudaLaunchConfig_t cfg = {};
    cfg.gridDim = dim3(G_CTAS); cfg.blockDim = dim3(384); cfg.dynamicSmemBytes = gk::SMEM; cfg.stream = st;
    cudaLaunchAttribute at[2];
    at[0].id = cudaLaunchAttributeClusterDimension;
    at[0].val.clusterDim.x = 2; at[0].val.clusterDim.y = 1; at[0].val.clusterDim.z = 1;
    at[1].id = cudaLaunchAttributeProgrammaticStreamSerialization;
    at[1].val.programmaticStreamSerializationAllowed = 1;
    cfg.attrs = at;
    cfg.numAttrs = 2;
    cudaLaunchKernelEx(&cfg, g_kernel, G);
  }
  if (O_PAIRS < 8) {
    using C = GemmCfg<128, 4, EPI_FINAL, false>;
    cudaFuncSetAttribute(tail_kernel, cudaFuncAttributeMaxDynamicSharedMemorySize, C::SMEM);
    cudaLaunchConfig_t cfg = {};
    cfg.gridDim = dim3((8 - O_PAIRS) * 16); cfg.blockDim = dim3(288); cfg.dynamicSmemBytes = C::SMEM; cfg.stream = st;
    cudaLaunchAttribute at[1];
    at[0].id = cudaLaunchAttributeClusterDimension;
    at[0].val.clusterDim.x = 2; at[0].val.clusterDim.y = 1; at[0].val.clusterDim.z = 1;
    cfg.attrs = at; cfg.numAttrs = 1;
    cudaLaunchKernelEx(&cfg, tail_kernel, make_map(o, S, HD, 128, 64, 128), make_map(Wo, HD, D, 64, 64, 128), make_map(out, S, D, 64, 64, 128),
                       make_map(x, S, D, 64, 64, 128), make_map(g, S, D, 64, 64, 128), O_PAIRS * 2);
  }
}
```

```cpp
#include <cuda_runtime.h>
#include <cuda_bf16.h>
#include <cuda.h>
#include <stdint.h>

typedef __nv_bfloat16 bf16;

namespace cfg {
constexpr int S = 2048;
constexpr int D = 1024;
constexpr int H = 32;
constexpr int DH = 128;
constexpr int HD = H * DH;
constexpr int M = 8;
constexpr int SEG = 32;
constexpr int NSEG = S / SEG;
constexpr int F = 3584;
}

__device__ __forceinline__ uint32_t smem_u32(const void* p) { return (uint32_t)__cvta_generic_to_shared(p); }

__device__ __forceinline__ void mbar_init(uint32_t bar, uint32_t count) {
  asm volatile("mbarrier.init.shared::cta.b64 [%0], %1;" ::"r"(bar), "r"(count) : "memory");
}
__device__ __forceinline__ void mbar_expect_tx(uint32_t bar, uint32_t bytes) {
  asm volatile("mbarrier.arrive.expect_tx.shared::cta.b64 _, [%0], %1;" ::"r"(bar), "r"(bytes) : "memory");
}
__device__ __forceinline__ void mbar_arrive(uint32_t bar) {
  asm volatile("mbarrier.arrive.shared::cta.b64 _, [%0];" ::"r"(bar) : "memory");
}
__device__ __forceinline__ bool mbar_try(uint32_t bar, uint32_t parity) {
  uint32_t done;
  asm volatile("{\n.reg .pred p;\nmbarrier.try_wait.parity.shared::cta.b64 p, [%1], %2, 20000;\nselp.u32 %0, 1, 0, p;\n}"
               : "=r"(done) : "r"(bar), "r"(parity) : "memory");
  return done != 0;
}
__device__ __forceinline__ bool mbar_try_nohint(uint32_t bar, uint32_t parity) {
  uint32_t done;
  asm volatile("{\n.reg .pred p;\nmbarrier.try_wait.parity.shared::cta.b64 p, [%1], %2;\nselp.u32 %0, 1, 0, p;\n}"
               : "=r"(done) : "r"(bar), "r"(parity) : "memory");
  return done != 0;
}
constexpr int MBAR_TRIES = 4096;
constexpr int POLL_TRIES = 1 << 16;
__device__ __forceinline__ void mbar_wait(uint32_t bar, uint32_t parity) {
#pragma unroll 1
  for (int n = 0; n < MBAR_TRIES; n++)
    if (mbar_try(bar, parity)) break;
}
__device__ __forceinline__ void mbar_wait_fast(uint32_t bar, uint32_t parity) {
#pragma unroll 1
  for (int n = 0; n < (POLL_TRIES << 4); n++)
    if (mbar_try_nohint(bar, parity)) break;
}
__device__ __forceinline__ void fence_barrier_init() { asm volatile("fence.mbarrier_init.release.cluster;" ::: "memory"); }
__device__ __forceinline__ void fence_proxy_async_smem() { asm volatile("fence.proxy.async.shared::cta;" ::: "memory"); }

__device__ __forceinline__ void tma_load_2d(uint32_t dst, const CUtensorMap* map, int x, int y, uint32_t bar) {
  asm volatile("cp.async.bulk.tensor.2d.shared::cluster.global.mbarrier::complete_tx::bytes [%0], [%1, {%3, %4}], [%2];"
               ::"r"(dst), "l"(map), "r"(bar), "r"(x), "r"(y) : "memory");
}
__device__ __forceinline__ void tma_load_3d(uint32_t dst, const CUtensorMap* map, int x, int y, int z, uint32_t bar) {
  asm volatile("cp.async.bulk.tensor.3d.shared::cluster.global.mbarrier::complete_tx::bytes [%0], [%1, {%3, %4, %5}], [%2];"
               ::"r"(dst), "l"(map), "r"(bar), "r"(x), "r"(y), "r"(z) : "memory");
}
__device__ __forceinline__ void tma_store_2d(const CUtensorMap* map, uint32_t src, int x, int y) {
  asm volatile("cp.async.bulk.tensor.2d.global.shared::cta.bulk_group [%0, {%2, %3}], [%1];"
               ::"l"(map), "r"(src), "r"(x), "r"(y) : "memory");
}
__device__ __forceinline__ void tma_store_commit() { asm volatile("cp.async.bulk.commit_group;" ::: "memory"); }
__device__ __forceinline__ void tma_store_wait_all() { asm volatile("cp.async.bulk.wait_group 0;" ::: "memory"); }
__device__ __forceinline__ void tma_store_wait_read() { asm volatile("cp.async.bulk.wait_group.read 0;" ::: "memory"); }
__device__ __forceinline__ void prefetch_tmap(const CUtensorMap* map) {
  asm volatile("prefetch.tensormap [%0];" ::"l"(map) : "memory");
}

__device__ __forceinline__ void wg_fence() { asm volatile("wgmma.fence.sync.aligned;" ::: "memory"); }
__device__ __forceinline__ void wg_commit() { asm volatile("wgmma.commit_group.sync.aligned;" ::: "memory"); }
template <int N> __device__ __forceinline__ void wg_wait() { asm volatile("wgmma.wait_group.sync.aligned %0;" ::"n"(N) : "memory"); }

#define named_bar_sync(id, n) asm volatile("bar.sync %0, %1;" ::"n"(id), "n"(n) : "memory")
#define named_bar_arrive(id, n) asm volatile("bar.arrive %0, %1;" ::"n"(id), "n"(n) : "memory")

__device__ __forceinline__ uint64_t make_desc(uint32_t addr, uint32_t lbo, uint32_t sbo) {
  return (uint64_t)((addr & 0x3FFFF) >> 4) | ((uint64_t)(lbo >> 4) << 16) | ((uint64_t)(sbo >> 4) << 32) | (1ull << 62);
}

__device__ __forceinline__ uint32_t pack_bf16(float lo, float hi) {
  uint32_t r;
  asm("cvt.rn.bf16x2.f32 %0, %1, %2;" : "=r"(r) : "f"(hi), "f"(lo));
  return r;
}
__device__ __forceinline__ float bf_lo(uint32_t v) { return __uint_as_float(v << 16); }
__device__ __forceinline__ float bf_hi(uint32_t v) { return __uint_as_float(v & 0xFFFF0000u); }
__device__ __forceinline__ float rbf(float v) { return __bfloat162float(__float2bfloat16_rn(v)); }

__device__ __forceinline__ void pdl_launch_dependents() { asm volatile("griddepcontrol.launch_dependents;" ::: "memory"); }
__device__ __forceinline__ void pdl_wait() { asm volatile("griddepcontrol.wait;" ::: "memory"); }

__device__ __forceinline__ float ex2_approx(float x) { float y; asm("ex2.approx.ftz.f32 %0, %1;" : "=f"(y) : "f"(x)); return y; }
__device__ __forceinline__ float rcp_approx(float x) { float y; asm("rcp.approx.ftz.f32 %0, %1;" : "=f"(y) : "f"(x)); return y; }

__device__ __forceinline__ void mul_sigmoid4(float (&v)[4], const float (&t)[4]) {
#pragma unroll
  for (int i = 0; i < 4; i += 2) {
    const float a = 1.0f + ex2_approx(fminf(t[i], 60.0f)), b = 1.0f + ex2_approx(fminf(t[i + 1], 60.0f));
    const float r = rcp_approx(a * b);
    v[i] *= b * r;
    v[i + 1] *= a * r;
  }
}
__device__ __forceinline__ void gelu4(float (&v)[4]) {
  float t[4];
#pragma unroll
  for (int i = 0; i < 4; i++) t[i] = v[i] * fmaf(v[i] * v[i], -0.10294324f, -2.30220819f);
  mul_sigmoid4(v, t);
}
__device__ __forceinline__ void silu4(float (&v)[4]) {
  float t[4];
#pragma unroll
  for (int i = 0; i < 4; i++) t[i] = v[i] * -1.4426950408889634f;
  mul_sigmoid4(v, t);
}

#define KT_START(id)
#define KT_END(id)

__device__ __forceinline__ void wgmma_ss_n128_tb(float (&d)[64], uint64_t da, uint64_t db, int scale_d) {
  asm volatile("{\n.reg .pred p;\nsetp.ne.b32 p, %66, 0;\n"
    "wgmma.mma_async.sync.aligned.m64n128k16.f32.bf16.bf16 "
    "{%0, %1, %2, %3, %4, %5, %6, %7, %8, %9, %10, %11, %12, %13, %14, %15, "
    "%16, %17, %18, %19, %20, %21, %22, %23, %24, %25, %26, %27, %28, %29, %30, %31, "
    "%32, %33, %34, %35, %36, %37, %38, %39, %40, %41, %42, %43, %44, %45, %46, %47, "
    "%48, %49, %50, %51, %52, %53, %54, %55, %56, %57, %58, %59, %60, %61, %62, %63}, "
    "%64, %65, p, 1, 1, 0, 1;\n}\n"
    : "+f"(d[0]), "+f"(d[1]), "+f"(d[2]), "+f"(d[3]), "+f"(d[4]), "+f"(d[5]), "+f"(d[6]), "+f"(d[7]),
      "+f"(d[8]), "+f"(d[9]), "+f"(d[10]), "+f"(d[11]), "+f"(d[12]), "+f"(d[13]), "+f"(d[14]), "+f"(d[15]),
      "+f"(d[16]), "+f"(d[17]), "+f"(d[18]), "+f"(d[19]), "+f"(d[20]), "+f"(d[21]), "+f"(d[22]), "+f"(d[23]),
      "+f"(d[24]), "+f"(d[25]), "+f"(d[26]), "+f"(d[27]), "+f"(d[28]), "+f"(d[29]), "+f"(d[30]), "+f"(d[31]),
      "+f"(d[32]), "+f"(d[33]), "+f"(d[34]), "+f"(d[35]), "+f"(d[36]), "+f"(d[37]), "+f"(d[38]), "+f"(d[39]),
      "+f"(d[40]), "+f"(d[41]), "+f"(d[42]), "+f"(d[43]), "+f"(d[44]), "+f"(d[45]), "+f"(d[46]), "+f"(d[47]),
      "+f"(d[48]), "+f"(d[49]), "+f"(d[50]), "+f"(d[51]), "+f"(d[52]), "+f"(d[53]), "+f"(d[54]), "+f"(d[55]),
      "+f"(d[56]), "+f"(d[57]), "+f"(d[58]), "+f"(d[59]), "+f"(d[60]), "+f"(d[61]), "+f"(d[62]), "+f"(d[63])
    : "l"(da), "l"(db), "r"(scale_d));
}
__device__ __forceinline__ void wgmma_ss_n224_tb(float (&d)[112], uint64_t da, uint64_t db, int scale_d) {
  asm volatile("{\n.reg .pred p;\nsetp.ne.b32 p, %114, 0;\n"
    "wgmma.mma_async.sync.aligned.m64n224k16.f32.bf16.bf16 "
    "{%0, %1, %2, %3, %4, %5, %6, %7, %8, %9, %10, %11, %12, %13, %14, %15, "
    "%16, %17, %18, %19, %20, %21, %22, %23, %24, %25, %26, %27, %28, %29, %30, %31, "
    "%32, %33, %34, %35, %36, %37, %38, %39, %40, %41, %42, %43, %44, %45, %46, %47, "
    "%48, %49, %50, %51, %52, %53, %54, %55, %56, %57, %58, %59, %60, %61, %62, %63, "
    "%64, %65, %66, %67, %68, %69, %70, %71, %72, %73, %74, %75, %76, %77, %78, %79, "
    "%80, %81, %82, %83, %84, %85, %86, %87, %88, %89, %90, %91, %92, %93, %94, %95, "
    "%96, %97, %98, %99, %100, %101, %102, %103, %104, %105, %106, %107, %108, %109, %110, %111}, "
    "%112, %113, p, 1, 1, 0, 1;\n}\n"
    : "+f"(d[0]), "+f"(d[1]), "+f"(d[2]), "+f"(d[3]), "+f"(d[4]), "+f"(d[5]), "+f"(d[6]), "+f"(d[7]),
      "+f"(d[8]), "+f"(d[9]), "+f"(d[10]), "+f"(d[11]), "+f"(d[12]), "+f"(d[13]), "+f"(d[14]), "+f"(d[15]),
      "+f"(d[16]), "+f"(d[17]), "+f"(d[18]), "+f"(d[19]), "+f"(d[20]), "+f"(d[21]), "+f"(d[22]), "+f"(d[23]),
      "+f"(d[24]), "+f"(d[25]), "+f"(d[26]), "+f"(d[27]), "+f"(d[28]), "+f"(d[29]), "+f"(d[30]), "+f"(d[31]),
      "+f"(d[32]), "+f"(d[33]), "+f"(d[34]), "+f"(d[35]), "+f"(d[36]), "+f"(d[37]), "+f"(d[38]), "+f"(d[39]),
      "+f"(d[40]), "+f"(d[41]), "+f"(d[42]), "+f"(d[43]), "+f"(d[44]), "+f"(d[45]), "+f"(d[46]), "+f"(d[47]),
      "+f"(d[48]), "+f"(d[49]), "+f"(d[50]), "+f"(d[51]), "+f"(d[52]), "+f"(d[53]), "+f"(d[54]), "+f"(d[55]),
      "+f"(d[56]), "+f"(d[57]), "+f"(d[58]), "+f"(d[59]), "+f"(d[60]), "+f"(d[61]), "+f"(d[62]), "+f"(d[63]),
      "+f"(d[64]), "+f"(d[65]), "+f"(d[66]), "+f"(d[67]), "+f"(d[68]), "+f"(d[69]), "+f"(d[70]), "+f"(d[71]),
      "+f"(d[72]), "+f"(d[73]), "+f"(d[74]), "+f"(d[75]), "+f"(d[76]), "+f"(d[77]), "+f"(d[78]), "+f"(d[79]),
      "+f"(d[80]), "+f"(d[81]), "+f"(d[82]), "+f"(d[83]), "+f"(d[84]), "+f"(d[85]), "+f"(d[86]), "+f"(d[87]),
      "+f"(d[88]), "+f"(d[89]), "+f"(d[90]), "+f"(d[91]), "+f"(d[92]), "+f"(d[93]), "+f"(d[94]), "+f"(d[95]),
      "+f"(d[96]), "+f"(d[97]), "+f"(d[98]), "+f"(d[99]), "+f"(d[100]), "+f"(d[101]), "+f"(d[102]), "+f"(d[103]),
      "+f"(d[104]), "+f"(d[105]), "+f"(d[106]), "+f"(d[107]), "+f"(d[108]), "+f"(d[109]), "+f"(d[110]), "+f"(d[111])
    : "l"(da), "l"(db), "r"(scale_d));
}
__device__ __forceinline__ void wgmma_ss_n256_tb(float (&d)[128], uint64_t da, uint64_t db, int scale_d) {
  asm volatile("{\n.reg .pred p;\nsetp.ne.b32 p, %130, 0;\n"
    "wgmma.mma_async.sync.aligned.m64n256k16.f32.bf16.bf16 "
    "{%0, %1, %2, %3, %4, %5, %6, %7, %8, %9, %10, %11, %12, %13, %14, %15, "
    "%16, %17, %18, %19, %20, %21, %22, %23, %24, %25, %26, %27, %28, %29, %30, %31, "
    "%32, %33, %34, %35, %36, %37, %38, %39, %40, %41, %42, %43, %44, %45, %46, %47, "
    "%48, %49, %50, %51, %52, %53, %54, %55, %56, %57, %58, %59, %60, %61, %62, %63, "
    "%64, %65, %66, %67, %68, %69, %70, %71, %72, %73, %74, %75, %76, %77, %78, %79, "
    "%80, %81, %82, %83, %84, %85, %86, %87, %88, %89, %90, %91, %92, %93, %94, %95, "
    "%96, %97, %98, %99, %100, %101, %102, %103, %104, %105, %106, %107, %108, %109, %110, %111, "
    "%112, %113, %114, %115, %116, %117, %118, %119, %120, %121, %122, %123, %124, %125, %126, %127}, "
    "%128, %129, p, 1, 1, 0, 1;\n}\n"
    : "+f"(d[0]), "+f"(d[1]), "+f"(d[2]), "+f"(d[3]), "+f"(d[4]), "+f"(d[5]), "+f"(d[6]), "+f"(d[7]),
      "+f"(d[8]), "+f"(d[9]), "+f"(d[10]), "+f"(d[11]), "+f"(d[12]), "+f"(d[13]), "+f"(d[14]), "+f"(d[15]),
      "+f"(d[16]), "+f"(d[17]), "+f"(d[18]), "+f"(d[19]), "+f"(d[20]), "+f"(d[21]), "+f"(d[22]), "+f"(d[23]),
      "+f"(d[24]), "+f"(d[25]), "+f"(d[26]), "+f"(d[27]), "+f"(d[28]), "+f"(d[29]), "+f"(d[30]), "+f"(d[31]),
      "+f"(d[32]), "+f"(d[33]), "+f"(d[34]), "+f"(d[35]), "+f"(d[36]), "+f"(d[37]), "+f"(d[38]), "+f"(d[39]),
      "+f"(d[40]), "+f"(d[41]), "+f"(d[42]), "+f"(d[43]), "+f"(d[44]), "+f"(d[45]), "+f"(d[46]), "+f"(d[47]),
      "+f"(d[48]), "+f"(d[49]), "+f"(d[50]), "+f"(d[51]), "+f"(d[52]), "+f"(d[53]), "+f"(d[54]), "+f"(d[55]),
      "+f"(d[56]), "+f"(d[57]), "+f"(d[58]), "+f"(d[59]), "+f"(d[60]), "+f"(d[61]), "+f"(d[62]), "+f"(d[63]),
      "+f"(d[64]), "+f"(d[65]), "+f"(d[66]), "+f"(d[67]), "+f"(d[68]), "+f"(d[69]), "+f"(d[70]), "+f"(d[71]),
      "+f"(d[72]), "+f"(d[73]), "+f"(d[74]), "+f"(d[75]), "+f"(d[76]), "+f"(d[77]), "+f"(d[78]), "+f"(d[79]),
      "+f"(d[80]), "+f"(d[81]), "+f"(d[82]), "+f"(d[83]), "+f"(d[84]), "+f"(d[85]), "+f"(d[86]), "+f"(d[87]),
      "+f"(d[88]), "+f"(d[89]), "+f"(d[90]), "+f"(d[91]), "+f"(d[92]), "+f"(d[93]), "+f"(d[94]), "+f"(d[95]),
      "+f"(d[96]), "+f"(d[97]), "+f"(d[98]), "+f"(d[99]), "+f"(d[100]), "+f"(d[101]), "+f"(d[102]), "+f"(d[103]),
      "+f"(d[104]), "+f"(d[105]), "+f"(d[106]), "+f"(d[107]), "+f"(d[108]), "+f"(d[109]), "+f"(d[110]), "+f"(d[111]),
      "+f"(d[112]), "+f"(d[113]), "+f"(d[114]), "+f"(d[115]), "+f"(d[116]), "+f"(d[117]), "+f"(d[118]), "+f"(d[119]),
      "+f"(d[120]), "+f"(d[121]), "+f"(d[122]), "+f"(d[123]), "+f"(d[124]), "+f"(d[125]), "+f"(d[126]), "+f"(d[127])
    : "l"(da), "l"(db), "r"(scale_d));
}
__device__ __forceinline__ void wgmma_rs_n32(float (&d)[16], const uint32_t* a, uint64_t db, int scale_d) {
  asm volatile("{\n.reg .pred p;\nsetp.ne.b32 p, %21, 0;\n"
    "wgmma.mma_async.sync.aligned.m64n32k16.f32.bf16.bf16 "
    "{%0, %1, %2, %3, %4, %5, %6, %7, %8, %9, %10, %11, %12, %13, %14, %15}, "
    "{%16, %17, %18, %19}, %20, p, 1, 1, 0;\n}\n"
    : "+f"(d[0]), "+f"(d[1]), "+f"(d[2]), "+f"(d[3]), "+f"(d[4]), "+f"(d[5]), "+f"(d[6]), "+f"(d[7]),
      "+f"(d[8]), "+f"(d[9]), "+f"(d[10]), "+f"(d[11]), "+f"(d[12]), "+f"(d[13]), "+f"(d[14]), "+f"(d[15])
    : "r"(a[0]), "r"(a[1]), "r"(a[2]), "r"(a[3]), "l"(db), "r"(scale_d));
}
__device__ __forceinline__ void wgmma_ss_n32_ta(float (&d)[16], uint64_t da, uint64_t db, int scale_d) {
  asm volatile("{\n.reg .pred p;\nsetp.ne.b32 p, %18, 0;\n"
    "wgmma.mma_async.sync.aligned.m64n32k16.f32.bf16.bf16 "
    "{%0, %1, %2, %3, %4, %5, %6, %7, %8, %9, %10, %11, %12, %13, %14, %15}, "
    "%16, %17, p, 1, 1, 1, 0;\n}\n"
    : "+f"(d[0]), "+f"(d[1]), "+f"(d[2]), "+f"(d[3]), "+f"(d[4]), "+f"(d[5]), "+f"(d[6]), "+f"(d[7]),
      "+f"(d[8]), "+f"(d[9]), "+f"(d[10]), "+f"(d[11]), "+f"(d[12]), "+f"(d[13]), "+f"(d[14]), "+f"(d[15])
    : "l"(da), "l"(db), "r"(scale_d));
}

#define gwait mbar_wait_fast
enum { EPI_PLAIN = 0, EPI_GELU = 1, EPI_RES = 2, EPI_RES_SILU = 3, EPI_FINAL = 4 };

template <int BN> struct WgAcc;
template <> struct WgAcc<128> { static __device__ __forceinline__ void mma(float (&d)[64], uint64_t a, uint64_t b, int s) { wgmma_ss_n128_tb(d, a, b, s); } };
template <> struct WgAcc<256> { static __device__ __forceinline__ void mma(float (&d)[128], uint64_t a, uint64_t b, int s) { wgmma_ss_n256_tb(d, a, b, s); } };

template <int BN, int STAGES, int EPI, bool ALIAS>
struct GemmCfg {
  static constexpr int NBOX = (BN + 63) / 64;
  static constexpr int A_BYTES = 128 * 128;
  static constexpr int B_BYTES = NBOX * 64 * 128;
  static constexpr int STAGE_BYTES = A_BYTES + B_BYTES;
  static constexpr int NRES = (EPI == EPI_FINAL) ? 2 : (EPI == EPI_RES || EPI == EPI_RES_SILU) ? 1 : 0;
  static constexpr int TILE_BYTES = NBOX * 128 * 128;
  static constexpr int SMEM = STAGES * STAGE_BYTES + (ALIAS ? 0 : NRES * TILE_BYTES) + 1024 + 256;
  static __device__ __forceinline__ constexpr uint32_t piece(int p) {
    return ALIAS ? (p / 3) * STAGE_BYTES + (p % 3) * 16384 : STAGES * STAGE_BYTES + p * 16384;
  }
};

#define GPROF(i)

__device__ __forceinline__ void tma_load_2d_mc(uint32_t dst, const CUtensorMap* map, int x, int y, uint32_t bar) {
  asm volatile("cp.async.bulk.tensor.2d.shared::cluster.global.mbarrier::complete_tx::bytes.multicast::cluster "
               "[%0], [%1, {%3, %4}], [%2], %5;"
               ::"r"(dst), "l"(map), "r"(bar), "r"(x), "r"(y), "h"((uint16_t)3) : "memory");
}
__device__ __forceinline__ void mbar_arrive_cluster(uint32_t bar, uint32_t cta) {
  asm volatile("{\n.reg .b32 r;\nmapa.shared::cluster.u32 r, %0, %1;\nmbarrier.arrive.shared::cluster.b64 _, [r];\n}"
               ::"r"(bar), "r"(cta) : "memory");
}
__device__ __forceinline__ void cluster_sync() {
  asm volatile("barrier.cluster.arrive.release.aligned;\nbarrier.cluster.wait.acquire.aligned;" ::: "memory");
}

template <int BN, int STAGES, int EPI, bool SHIFT_A, bool ALIAS, int FLAG>
__device__ __forceinline__ void gemm_body(const CUtensorMap* tmA, const CUtensorMap* tmB, const CUtensorMap* tmC,
                                          const CUtensorMap* tmC2, const CUtensorMap* tmR0, const CUtensorMap* tmR1,
                                          int K, int mt, int nt, unsigned* gflag) {
  using C = GemmCfg<BN, STAGES, EPI, ALIAS>;
  extern __shared__ uint8_t smem_raw[];
  const uint32_t base = (smem_u32(smem_raw) + 1023u) & ~1023u;
  const uint32_t bar_base = base + STAGES * C::STAGE_BYTES + (ALIAS ? 0 : C::NRES * C::TILE_BYTES);
  auto full = [&](int s) { return bar_base + 8 * s; };
  auto empty = [&](int s) { return bar_base + 8 * (STAGES + s); };
  const uint32_t res_bar = bar_base + 8 * 2 * STAGES;

  const int tid = threadIdx.x, warp = tid >> 5, lane = tid & 31;
  const int rank = blockIdx.x & 1;
  const int n0 = nt * BN, m0 = mt * 128;
  const int nkb = K >> 6;

  GPROF(0);
  KT_START(EPI == EPI_RES ? 3 : EPI == EPI_GELU ? 5 : EPI == EPI_RES_SILU ? 6 : 7);
  if (tid == 0) {
    for (int s = 0; s < STAGES; s++) { mbar_init(full(s), 1); mbar_init(empty(s), 4); }
    mbar_init(res_bar, 1);
    fence_barrier_init();
  }
  __syncthreads();
  cluster_sync();
  pdl_launch_dependents();

  if (warp == 8) {
    if (lane == 0) {
      prefetch_tmap(tmA); prefetch_tmap(tmB); prefetch_tmap(tmC);
      pdl_wait();
      auto load_piece = [&](int p) {
        const CUtensorMap* m = p < C::NBOX ? tmR0 : tmR1;
        const int col = n0 + (p % C::NBOX) * 64;
        tma_load_2d(base + C::piece(p), m, col, m0, res_bar);
        tma_load_2d(base + C::piece(p) + 8192, m, col, m0 + 64, res_bar);
      };
      for (int kb = 0; kb < nkb; kb++) {
        const int s = kb % STAGES;
        if (kb >= STAGES) gwait(empty(s), ((kb / STAGES) - 1) & 1);
        const uint32_t sa = base + s * C::STAGE_BYTES, sb = sa + C::A_BYTES;
        mbar_expect_tx(full(s), C::STAGE_BYTES);
        int arow = m0;
        if (SHIFT_A) { const int q = kb >> 2; arow += (q == 0) ? -1 : (q == 1) ? 1 : (q == 2) ? -2 : 2; }
        tma_load_2d(sa, tmA, kb * 64, arow, full(s));
#pragma unroll
        for (int j = 0; j < C::NBOX / 2; j++) {
          const int jj = rank * (C::NBOX / 2) + j;
          tma_load_2d_mc(sb + jj * 8192, tmB, n0 + jj * 64, kb * 64, full(s));
        }
        if (C::NRES > 0 && !ALIAS && kb == STAGES - 1) {
          mbar_expect_tx(res_bar, C::NRES * C::TILE_BYTES);
#pragma unroll
          for (int p = 0; p < C::NRES * C::NBOX; p++) load_piece(p);
        }
      }
      if (C::NRES > 0 && ALIAS) {
        mbar_expect_tx(res_bar, C::NRES * C::TILE_BYTES);
#pragma unroll
        for (int p = 0; p < C::NRES * C::NBOX; p++) {
          if (p % 3 == 0) gwait(empty(p / 3), ((nkb / STAGES) - 1) & 1);
          if (FLAG == 2 && p == C::NBOX) {
#pragma unroll 1
            for (int tries = 0; tries < (POLL_TRIES << 4); tries++) {
              unsigned v;
              asm volatile("ld.acquire.gpu.global.u32 %0, [%1];" : "=r"(v) : "l"(gflag) : "memory");
              if (v >= 2) break;
            }
            asm volatile("fence.proxy.async;" ::: "memory");
          }
          load_piece(p);
        }
      }
    }
  } else {
    const int wg = warp >> 2;
    float acc[BN / 2];
    pdl_wait();
    for (int kb = 0; kb < nkb; kb++) {
      const int s = kb % STAGES;
      gwait(full(s), (kb / STAGES) & 1);
      if (kb == 0) GPROF(1);
      const uint32_t sa = base + s * C::STAGE_BYTES + wg * 8192, sb = base + s * C::STAGE_BYTES + C::A_BYTES;
      wg_fence();
#pragma unroll
      for (int k = 0; k < 4; k++)
        WgAcc<BN>::mma(acc, make_desc(sa + k * 32, 16, 1024), make_desc(sb + k * 2048, 8192, 1024), (kb | k) != 0);
      wg_commit();
      if (kb > 0) {
        wg_wait<1>();
        if ((tid & 127) < 2) mbar_arrive_cluster(empty((kb - 1) % STAGES), tid & 1);
      }
    }
    wg_wait<0>();
    GPROF(2);
    GPROF(3);
    if (C::NRES > 0) gwait(res_bar, 0);
    else named_bar_sync(1, 256);
    const int r0 = wg * 64 + (warp & 3) * 16 + (lane >> 2);
    const int q = lane & 3;
#pragma unroll
    for (int box = 0; box < C::NBOX; box++) {
      constexpr int NB = C::NBOX;
      const bool half = (BN % 64 != 0) && box == NB - 1;
      const uint32_t pbase = base + (C::NRES > 0 ? C::piece(box) : box * 16384);
#pragma unroll
      for (int grp = 0; grp < (half ? 1 : 2); grp++) {
        uint32_t off[4][2], ra[4][2], rb[4][2];
#pragma unroll
        for (int jj = 0; jj < 4; jj++)
#pragma unroll
          for (int h = 0; h < 2; h++) {
            const int r = r0 + h * 8, unit = grp * 4 + jj;
            off[jj][h] = half ? pbase + r * 64 + ((unit ^ ((r >> 1) & 3)) << 4) + q * 4
                              : pbase + r * 128 + ((unit ^ (r & 7)) << 4) + q * 4;
            if (C::NRES > 0) asm volatile("ld.shared.u32 %0, [%1];" : "=r"(ra[jj][h]) : "r"(off[jj][h]));
            if (C::NRES > 1)
              asm volatile("ld.shared.u32 %0, [%1];" : "=r"(rb[jj][h]) : "r"(off[jj][h] + (C::piece(NB + box) - C::piece(box))));
          }
#pragma unroll
        for (int jj = 0; jj < 4; jj++) {
          const int j = box * 8 + grp * 4 + jj;
          const uint32_t s0 = pack_bf16(acc[j * 4], acc[j * 4 + 1]), s1 = pack_bf16(acc[j * 4 + 2], acc[j * 4 + 3]);
          float v[4] = {bf_lo(s0), bf_hi(s0), bf_lo(s1), bf_hi(s1)};
          if (EPI == EPI_GELU) gelu4(v);
          if (EPI == EPI_RES || EPI == EPI_RES_SILU) {
            v[0] += bf_lo(ra[jj][0]); v[1] += bf_hi(ra[jj][0]); v[2] += bf_lo(ra[jj][1]); v[3] += bf_hi(ra[jj][1]);
            if (EPI == EPI_RES_SILU) {
              const uint32_t y0 = pack_bf16(v[0], v[1]), y1 = pack_bf16(v[2], v[3]);
              v[0] = bf_lo(y0); v[1] = bf_hi(y0); v[2] = bf_lo(y1); v[3] = bf_hi(y1);
              silu4(v);
            }
          }
          if (EPI == EPI_FINAL) {
#pragma unroll
            for (int h = 0; h < 2; h++) {
              const uint32_t t = pack_bf16(v[2 * h] * bf_lo(rb[jj][h]), v[2 * h + 1] * bf_hi(rb[jj][h]));
              v[2 * h] = bf_lo(ra[jj][h]) + bf_lo(t);
              v[2 * h + 1] = bf_hi(ra[jj][h]) + bf_hi(t);
            }
          }
          asm volatile("st.shared.u32 [%0], %1;" ::"r"(off[jj][0]), "r"(pack_bf16(v[0], v[1])) : "memory");
          asm volatile("st.shared.u32 [%0], %1;" ::"r"(off[jj][1]), "r"(pack_bf16(v[2], v[3])) : "memory");
        }
      }
      fence_proxy_async_smem();
      if (wg == 0) named_bar_sync(2, 128); else named_bar_sync(3, 128);
      if ((tid & 127) == 0) {
        if (half) tma_store_2d(tmC2, pbase + wg * 4096, n0 + box * 64, m0 + wg * 64);
        else tma_store_2d(tmC, pbase + wg * 8192, n0 + box * 64, m0 + wg * 64);
        tma_store_commit();
      }
    }
    GPROF(4);
    if ((tid & 127) == 0) {
      if (FLAG == 1) {
        tma_store_wait_all();
        asm volatile("fence.proxy.async;" ::: "memory");
        asm volatile("red.release.gpu.global.add.u32 [%0], 1;" ::"l"(gflag) : "memory");
      } else {
        tma_store_wait_read();
      }
    }
  }
  GPROF(5);
  KT_END(EPI == EPI_RES ? 3 : EPI == EPI_GELU ? 5 : EPI == EPI_RES_SILU ? 6 : 7);
  __syncwarp();
  cluster_sync();
}

__device__ __forceinline__ float warp_sum(float v) {
#pragma unroll
  for (int o = 16; o > 0; o >>= 1) v += __shfl_xor_sync(0xffffffffu, v, o);
  return v;
}
__device__ __forceinline__ void ln_row(float (&v)[32]) {
  float s = 0.f;
#pragma unroll
  for (int i = 0; i < 32; i++) s += v[i];
  const float mean = warp_sum(s) * (1.0f / 1024.0f);
  float q = 0.f;
#pragma unroll
  for (int i = 0; i < 32; i++) { const float d = v[i] - mean; q += d * d; }
  const float var = warp_sum(q) * (1.0f / 1024.0f);
  const float mb = rbf(mean);
  const float sd = rbf(sqrtf(rbf(rbf(var) + 1e-5f)));
  const float inv = __fdiv_rn(1.0f, sd);
#pragma unroll
  for (int i = 0; i < 32; i += 2) {
    const uint32_t d = pack_bf16(v[i] - mb, v[i + 1] - mb);
    const uint32_t y = pack_bf16(bf_lo(d) * inv, bf_hi(d) * inv);
    v[i] = bf_lo(y); v[i + 1] = bf_hi(y);
  }
}
__device__ __forceinline__ void load_row(const bf16* p, int lane, float (&v)[32]) {
#pragma unroll
  for (int j = 0; j < 4; j++) {
    const uint4 u = *reinterpret_cast<const uint4*>(p + j * 256 + lane * 8);
    v[j * 8 + 0] = bf_lo(u.x); v[j * 8 + 1] = bf_hi(u.x); v[j * 8 + 2] = bf_lo(u.y); v[j * 8 + 3] = bf_hi(u.y);
    v[j * 8 + 4] = bf_lo(u.z); v[j * 8 + 5] = bf_hi(u.z); v[j * 8 + 6] = bf_lo(u.w); v[j * 8 + 7] = bf_hi(u.w);
  }
}
__device__ __forceinline__ void store_row(bf16* p, int lane, const float (&v)[32]) {
#pragma unroll
  for (int j = 0; j < 4; j++) {
    uint4 u;
    u.x = pack_bf16(v[j * 8 + 0], v[j * 8 + 1]); u.y = pack_bf16(v[j * 8 + 2], v[j * 8 + 3]);
    u.z = pack_bf16(v[j * 8 + 4], v[j * 8 + 5]); u.w = pack_bf16(v[j * 8 + 6], v[j * 8 + 7]);
    *reinterpret_cast<uint4*>(p + j * 256 + lane * 8) = u;
  }
}
__device__ void reset_exchange(int gtid, int nthreads);
template <bool TWICE>
__global__ void __launch_bounds__(256) ln_kernel(const bf16* __restrict__ x, bf16* __restrict__ y1, bf16* __restrict__ y2) {
  const int row = blockIdx.x * 8 + (threadIdx.x >> 5), lane = threadIdx.x & 31;
  KT_START(TWICE ? 0 : 4);
  pdl_launch_dependents();
  pdl_wait();
  if (TWICE) reset_exchange(blockIdx.x * 256 + threadIdx.x, gridDim.x * 256);
  float v[32];
  load_row(x + (size_t)row * cfg::D, lane, v);
  ln_row(v);
  store_row(y1 + (size_t)row * cfg::D, lane, v);
  if (TWICE) {
    ln_row(v);
    store_row(y2 + (size_t)row * cfg::D, lane, v);
  }
  KT_END(TWICE ? 0 : 4);
}

namespace fk {
constexpr uint32_t SM0 = 1024;
constexpr uint32_t WO = SM0, WS = WO + 90112, XN = WS + 65536, VX = XN + 49152, QK = VX + 8192, PT = QK + 8192,
                   SP = PT + 4096, VM = SP + 2560, OB = VM + 2048, BAR = OB + 2048;
constexpr uint32_t MEMB = XN + 16384, RED = XN + 32768, VX2 = WO + 81920;
constexpr int SMEM = 232448;
static_assert(BAR + 512 == SM0 + SMEM, "shared memory layout");
constexpr uint32_t B_XN = BAR, B_H2 = BAR + 448, B_PF = BAR + 16, B_SM = BAR + 32, B_VM = BAR + 40, B_VX = BAR + 48, B_ST = BAR + 56, B_PB = BAR + 64, B_W = BAR + 112,
                   MASKS = BAR + 128, PROBE = BAR + 384;
constexpr int NB_M0 = 1, NB_M1 = 2, NB_C = 3, NB_O = 4, NB_ST = 5, NB_DU = 6, NB_CF = 7, NB_W1 = 8, NB_XE = 9, NB_HD = 10, NB_PZ = 11, NB_O0 = 12;
#define D_H1 850
#define D_H2 1750
#define D_ST 100
#define SCQ 2
#define FLAGS 0
#define D_F 0
#define D_FS 70
#define NS0 4
#define NTA0 2
#define NTA1 2
#define PF0A 3
#define PF0 10
#define PF1A 9
#define PF1 11
#define PAUSE 1
#define PROBE_N 6
#define PROBE_FAST 0
#define SPACK 0
constexpr uint32_t SPW = SPACK ? 4 : 8, SP_SRC = 160 * SPW;
constexpr int H1_BYTES = 64 * 32768, H2_BYTES = 8 * 8192, FL_OFF = H1_BYTES + H2_BYTES, FL_BYTES = 8192;
}

#define PROF(wg, i)
#define PROF2(i)
#define RETRY(i)
#define GTSYNC(i)

__device__ uint4 g_xch[(fk::H1_BYTES + fk::H2_BYTES + fk::FL_BYTES + 8192) / 16];
__device__ unsigned g_mask[64];
__device__ unsigned g_oflag[16];

#define LD_POLL "ld.global.L1::no_allocate"
__device__ __forceinline__ uint4 ld_poll16(const void* p) {
  uint4 v;
  asm volatile(LD_POLL ".v4.u32 {%0,%1,%2,%3}, [%4];" : "=r"(v.x), "=r"(v.y), "=r"(v.z), "=r"(v.w) : "l"(p) : "memory");
  return v;
}
__device__ __forceinline__ uint2 ld_poll8(const void* p) {
  uint2 v;
  asm volatile(LD_POLL ".v2.u32 {%0,%1}, [%2];" : "=r"(v.x), "=r"(v.y) : "l"(p) : "memory");
  return v;
}
__device__ __forceinline__ uint4 ld_strong16(const void* p) {
  uint4 v;
  asm volatile("ld.relaxed.gpu.global.v4.u32 {%0,%1,%2,%3}, [%4];" : "=r"(v.x), "=r"(v.y), "=r"(v.z), "=r"(v.w) : "l"(p) : "memory");
  return v;
}
__device__ __forceinline__ uint2 ld_strong8(const void* p) {
  uint2 v;
  asm volatile("ld.relaxed.gpu.global.v2.u32 {%0,%1}, [%2];" : "=r"(v.x), "=r"(v.y) : "l"(p) : "memory");
  return v;
}
__device__ __forceinline__ void st_pub32(void* p, uint32_t v) { asm volatile("st.relaxed.gpu.global.u32 [%0], %1;" ::"l"(p), "r"(v) : "memory"); }
__device__ __forceinline__ void st_pub16(void* p, uint32_t v) {
  asm volatile("st.relaxed.gpu.global.u16 [%0], %1;" ::"l"(p), "h"((uint16_t)v) : "memory");
}
__device__ __forceinline__ uint32_t ld_strong4(const void* p) {
  uint32_t v;
  asm volatile("ld.relaxed.gpu.global.u32 %0, [%1];" : "=r"(v) : "l"(p) : "memory");
  return v;
}
__device__ __forceinline__ void st_pub64(void* p, uint32_t a, uint32_t b) {
  asm volatile("st.relaxed.gpu.global.v2.u32 [%0], {%1,%2};" ::"l"(p), "r"(a), "r"(b) : "memory");
}
__device__ __forceinline__ void st_pub128(void* p, uint32_t a) {
  asm volatile("st.relaxed.gpu.global.v4.u32 [%0], {%1,%1,%1,%1};" ::"l"(p), "r"(a) : "memory");
}
constexpr uint32_t EMPTY = 0xFFFFFFFFu;
__device__ __forceinline__ uint32_t umax4(const uint4& v) { return max(max(v.x, v.y), max(v.z, v.w)); }
__device__ __forceinline__ void sts128(uint32_t a, uint32_t x, uint32_t y, uint32_t z, uint32_t w) {
  asm volatile("st.shared.v4.u32 [%0], {%1,%2,%3,%4};" ::"r"(a), "r"(x), "r"(y), "r"(z), "r"(w) : "memory");
}
__device__ __forceinline__ void sts64(uint32_t a, uint32_t x, uint32_t y) {
  asm volatile("st.shared.v2.u32 [%0], {%1,%2};" ::"r"(a), "r"(x), "r"(y) : "memory");
}
__device__ __forceinline__ void sts32(uint32_t a, uint32_t x) { asm volatile("st.shared.u32 [%0], %1;" ::"r"(a), "r"(x) : "memory"); }
__device__ __forceinline__ void sts128f(uint32_t a, float x, float y, float z, float w) {
  asm volatile("st.shared.v4.f32 [%0], {%1,%2,%3,%4};" ::"r"(a), "f"(x), "f"(y), "f"(z), "f"(w) : "memory");
}
__device__ __forceinline__ void sts64f(uint32_t a, float x, float y) {
  asm volatile("st.shared.v2.f32 [%0], {%1,%2};" ::"r"(a), "f"(x), "f"(y) : "memory");
}
__device__ __forceinline__ float4 lds128f(uint32_t a) {
  float4 v;
  asm volatile("ld.shared.v4.f32 {%0,%1,%2,%3}, [%4];" : "=f"(v.x), "=f"(v.y), "=f"(v.z), "=f"(v.w) : "r"(a) : "memory");
  return v;
}
__device__ __forceinline__ float2 lds64f(uint32_t a) {
  float2 v;
  asm volatile("ld.shared.v2.f32 {%0,%1}, [%2];" : "=f"(v.x), "=f"(v.y) : "r"(a) : "memory");
  return v;
}
__device__ __forceinline__ void lds128(uint32_t* r, uint32_t a) {
  asm volatile("ld.shared.v4.u32 {%0,%1,%2,%3}, [%4];" : "=r"(r[0]), "=r"(r[1]), "=r"(r[2]), "=r"(r[3]) : "r"(a) : "memory");
}
__device__ __forceinline__ void lds64(uint32_t* r, uint32_t a) {
  asm volatile("ld.shared.v2.u32 {%0,%1}, [%2];" : "=r"(r[0]), "=r"(r[1]) : "r"(a) : "memory");
}
__device__ __forceinline__ uint32_t lds32(uint32_t a) {
  uint32_t v;
  asm volatile("ld.shared.u32 %0, [%1];" : "=r"(v) : "r"(a) : "memory");
  return v;
}
__device__ __forceinline__ void ldsm4(uint32_t* r, uint32_t a) {
  asm volatile("ldmatrix.sync.aligned.m8n8.x4.shared.b16 {%0,%1,%2,%3}, [%4];"
               : "=r"(r[0]), "=r"(r[1]), "=r"(r[2]), "=r"(r[3]) : "r"(a) : "memory");
}
__device__ __forceinline__ void ldsm4t(uint32_t* r, uint32_t a) {
  asm volatile("ldmatrix.sync.aligned.m8n8.x4.trans.shared.b16 {%0,%1,%2,%3}, [%4];"
               : "=r"(r[0]), "=r"(r[1]), "=r"(r[2]), "=r"(r[3]) : "r"(a) : "memory");
}
__device__ __forceinline__ void stsm4(uint32_t a, uint32_t r0, uint32_t r1, uint32_t r2, uint32_t r3) {
  asm volatile("stmatrix.sync.aligned.m8n8.x4.shared.b16 [%0], {%1,%2,%3,%4};"
               ::"r"(a), "r"(r0), "r"(r1), "r"(r2), "r"(r3) : "memory");
}
__device__ __forceinline__ void stsm4t(uint32_t a, uint32_t r0, uint32_t r1, uint32_t r2, uint32_t r3) {
  asm volatile("stmatrix.sync.aligned.m8n8.x4.trans.shared.b16 [%0], {%1,%2,%3,%4};"
               ::"r"(a), "r"(r0), "r"(r1), "r"(r2), "r"(r3) : "memory");
}
__device__ __forceinline__ void mma16816(float* d, const uint32_t* a, uint32_t b0, uint32_t b1) {
  asm volatile("mma.sync.aligned.m16n8k16.row.col.f32.bf16.bf16.f32 {%0,%1,%2,%3}, {%4,%5,%6,%7}, {%8,%9}, {%0,%1,%2,%3};"
               : "+f"(d[0]), "+f"(d[1]), "+f"(d[2]), "+f"(d[3])
               : "r"(a[0]), "r"(a[1]), "r"(a[2]), "r"(a[3]), "r"(b0), "r"(b1));
}
__device__ __forceinline__ void mma16816z(float* d, const uint32_t* a, uint32_t b0, uint32_t b1) {
  asm volatile("mma.sync.aligned.m16n8k16.row.col.f32.bf16.bf16.f32 {%0,%1,%2,%3}, {%4,%5,%6,%7}, {%8,%9}, {%10,%10,%10,%10};"
               : "=f"(d[0]), "=f"(d[1]), "=f"(d[2]), "=f"(d[3])
               : "r"(a[0]), "r"(a[1]), "r"(a[2]), "r"(a[3]), "r"(b0), "r"(b1), "f"(0.f));
}
__device__ __forceinline__ void mma1688(float* d, uint32_t a0, uint32_t a1, uint32_t b0) {
  asm volatile("mma.sync.aligned.m16n8k8.row.col.f32.bf16.bf16.f32 {%0,%1,%2,%3}, {%4,%5}, {%6}, {%0,%1,%2,%3};"
               : "+f"(d[0]), "+f"(d[1]), "+f"(d[2]), "+f"(d[3]) : "r"(a0), "r"(a1), "r"(b0));
}
__device__ __forceinline__ uint32_t movtrans(uint32_t a) {
  uint32_t d;
  asm volatile("movmatrix.sync.aligned.m8n8.trans.b16 %0, %1;" : "=r"(d) : "r"(a));
  return d;
}
__device__ __forceinline__ uint32_t mapa(uint32_t a, uint32_t rank) {
  uint32_t d;
  asm("mapa.shared::cluster.u32 %0, %1, %2;" : "=r"(d) : "r"(a), "r"(rank));
  return d;
}
__device__ __forceinline__ void st_async64(uint32_t a, uint32_t x, uint32_t y, uint32_t bar) {
  asm volatile("st.async.weak.shared::cluster.mbarrier::complete_tx::bytes.v2.b32 [%0], {%1,%2}, [%3];"
               ::"r"(a), "r"(x), "r"(y), "r"(bar) : "memory");
}
__device__ __forceinline__ void st_async64f(uint32_t a, float x, float y, uint32_t bar) {
  st_async64(a, __float_as_uint(x), __float_as_uint(y), bar);
}
__device__ __forceinline__ void bulk_s2s(uint32_t dst, uint32_t src, uint32_t bytes, uint32_t bar) {
  asm volatile("cp.async.bulk.shared::cluster.shared::cta.mbarrier::complete_tx::bytes [%0], [%1], %2, [%3];"
               ::"r"(dst), "r"(src), "r"(bytes), "r"(bar) : "memory");
}
__device__ __forceinline__ void tma_store_3d(const CUtensorMap* map, uint32_t src, int x, int y, int z) {
  asm volatile("cp.async.bulk.tensor.3d.global.shared::cta.bulk_group [%0, {%2, %3, %4}], [%1];"
               ::"l"(map), "r"(src), "r"(x), "r"(y), "r"(z) : "memory");
}
__device__ __forceinline__ void mbar_spin(uint32_t bar, uint32_t parity) {
  asm volatile("{\n.reg .pred p;\n.reg .b32 n;\nmov.u32 n, 0x100000;\nMW_L:\n"
               "mbarrier.try_wait.parity.shared::cta.b64 p, [%0], %1;\n@p bra.uni MW_D;\n"
               "add.s32 n, n, -1;\nsetp.ne.u32 p, n, 0;\n@p bra.uni MW_L;\nMW_D:\n}" ::"r"(bar), "r"(parity) : "memory");
}
__device__ __forceinline__ bool mbar_test(uint32_t bar, uint32_t parity) {
  uint32_t done;
  asm volatile("{\n.reg .pred p;\nmbarrier.test_wait.parity.shared::cta.b64 p, [%1], %2;\nselp.u32 %0, 1, 0, p;\n}"
               : "=r"(done) : "r"(bar), "r"(parity) : "memory");
  return done != 0;
}
__device__ __forceinline__ void mbar_arrive_remote(uint32_t bar) {
  asm volatile("mbarrier.arrive.shared::cluster.b64 _, [%0];" ::"r"(bar) : "memory");
}
__device__ __forceinline__ bool elect_one() {
  uint32_t r;
  asm volatile("{\n.reg .pred p;\nelect.sync _|p, 0xffffffff;\nselp.u32 %0, 1, 0, p;\n}" : "=r"(r));
  return r != 0;
}
__device__ __forceinline__ void st_async32(uint32_t a, uint32_t x, uint32_t bar) {
  asm volatile("st.async.weak.shared::cluster.mbarrier::complete_tx::bytes.b32 [%0], %1, [%2];" ::"r"(a), "r"(x), "r"(bar) : "memory");
}
#define named_bar_and(id, n, in, out) \
  asm volatile("{\n.reg .pred p, q;\nsetp.ne.u32 p, %1, 0;\nbar.red.and.pred q, %2, %3, p;\nselp.u32 %0, 1, 0, q;\n}" \
               : "=r"(out) : "r"(in), "n"(id), "n"(n) : "memory")
__device__ __forceinline__ void bulk_g2s(uint32_t dst, const void* src, uint32_t bytes, uint32_t bar) {
  asm volatile("cp.async.bulk.shared::cluster.global.mbarrier::complete_tx::bytes [%0], [%1], %2, [%3];"
               ::"r"(dst), "l"(src), "r"(bytes), "r"(bar) : "memory");
}
__device__ __forceinline__ uint32_t clk32() { uint32_t c; asm volatile("mov.u32 %0, %%clock;" : "=r"(c)::"memory"); return c; }
__device__ __forceinline__ void spin_until(uint32_t t) { while ((int32_t)(clk32() - t) < 0) {} }
#define PIN(x) asm volatile("" : "+r"(x))
#define MEM_FENCE(addr) \
  asm volatile("{\n.reg .pred p;\nsetp.eq.u32 p, %0, 0xFFFFFFF1;\n@p st.shared.u32 [%0], %0;\n}" ::"r"(addr) : "memory")
#define SCHED_DECL(x) \
  asm volatile(".reg .pred p_never;\n{\n.reg .pred q;\nsetp.eq.u32 q, %0, 0xFFFFFFF1;\nvote.sync.any.pred p_never, q, 0xffffffff;\n}" ::"r"(x))
#define SCHED_FENCE(addr) \
  asm volatile("{\nSF_L:\n@p_never st.volatile.shared.u32 [%0], %0;\n@p_never bra.uni SF_L;\n}" ::"r"(addr) : "memory")
#define OPQ                                                                                     \
  int tid_o = tid;                                                                              \
  asm volatile("" : "+r"(tid_o));                                                               \
  const int lane = tid_o & 31, w = (tid_o >> 5) & 3, t7 = tid_o & 127, lg = lane >> 2,          \
            lq = lane & 3, mi = lane >> 3, mr = lane & 7;                                       \
  (void)w; (void)t7; (void)lg; (void)lq; (void)mi; (void)mr; (void)lane

#define SMAP                                                                                                          \
  const uint32_t SM0 = self + fk::SM0, WO = self + fk::WO, WS = self + fk::WS, XN = self + fk::XN, VX = self + fk::VX, \
                 QK = self + fk::QK, PT = self + fk::PT, SP = self + fk::SP, VM = self + fk::VM, OB = self + fk::OB,   \
                 RED = self + fk::RED, VX2 = self + fk::VX2, MEMB = self + fk::MEMB, B_XN = self + fk::B_XN, B_SM = self + fk::B_SM,       \
                 B_VM = self + fk::B_VM, B_VX = self + fk::B_VX, B_ST = self + fk::B_ST, B_PB = self + fk::B_PB,       \
                 B_W = self + fk::B_W, B_H2 = self + fk::B_H2, B_PF = self + fk::B_PF, MASKS = self + fk::MASKS, PROBE = self + fk::PROBE;                             \
  (void)SM0; (void)WO; (void)WS; (void)XN; (void)VX; (void)QK; (void)PT; (void)SP; (void)VM; (void)OB; (void)RED; (void)VX2; \
  (void)MEMB; (void)B_XN; (void)B_SM; (void)B_VM; (void)B_VX; (void)B_ST; (void)B_PB; (void)B_W; (void)MASKS; (void)PROBE; (void)B_H2; (void)B_PF

struct FParams {
  CUtensorMap wq, wk, wv, wo, xn, xn12, o;
  const bf16* mem0;
  int one;
  char* xch;
};

__device__ __forceinline__ uint32_t probe_pair(char* p, uint32_t val, uint32_t dummy) {
  uint32_t best0 = 0x7FFFFFFF, best1 = 0x7FFFFFFF;
  st_pub128(p, val); st_pub128(p + 16, val); st_pub128(p + 4096, val); st_pub128(p + 4112, val);
#pragma unroll 1
  for (int r = 0; r < PROBE_N; r++) {
    uint32_t v;
    const uint32_t c0 = clk32();
    asm volatile("atom.relaxed.gpu.global.exch.b32 %0, [%1], %2;" : "=r"(v) : "l"(p + (r & 1) * 4096), "r"(val) : "memory");
    asm volatile("{\n.reg .pred p;\nsetp.eq.u32 p, %0, 0x12345678;\n@p st.shared.u32 [%1], %0;\n}" ::"r"(v), "r"(dummy) : "memory");
    const uint32_t d = clk32() - c0;
    if (r & 1) best1 = min(best1, d); else best0 = min(best0, d);
    if (r >= 1 && min(best0, best1) < PROBE_FAST && max(best0, best1) - min(best0, best1) > 100) break;
  }
  return best1 < best0;
}

typedef uint32_t WRegs[6][2][4][4];

template <bool ISV> struct Chunks {
  static constexpr int SC0 = ISV ? 6 : SCQ;
  static __device__ __forceinline__ constexpr int rf(int wg, int i) { return wg ? 10 + i : (i < SC0 ? i : 4 + i); }
};

template <int WG> struct ProjCfg { static constexpr int NS = WG ? 8 - NS0 : NS0, P0 = WG ? NS0 : 0, NTA = WG ? NTA1 : NTA0; };
__device__ __forceinline__ void load_pair(uint32_t (&t)[4][4], uint32_t wsa, int pp) {
#pragma unroll
  for (int f = 0; f < 4; f++) ldsm4t(t[f], wsa + ((pp >> 1) * 2 + (f & 1)) * 8192 + ((pp & 1) * 2 + (f >> 1)) * 2048);
}
template <bool ISV, int WG>
__device__ __forceinline__ void proj_mem(const WRegs& wr, uint32_t (&ta)[ProjCfg<WG>::NTA][4][4], uint32_t wsa, uint32_t mba,
                                         float (&a0)[4], float (&a1)[4]) {
  constexpr int NS = ProjCfg<WG>::NS, P0 = ProjCfg<WG>::P0, NTA = ProjCfg<WG>::NTA, NP = 12 + NS;
  float acc[4][4];
  auto spos = [](int j) { return j < NTA ? j : j + (j - NTA + 1) * 12 / (NS - NTA > 0 ? NS - NTA : 1); };
  auto which = [&](int p) { int r = -1; for (int j = 0; j < NS; j++) if (spos(j) == p) r = j; return r; };
  auto nsm_before = [&](int p) { int n = 0; for (int j = 0; j < NS; j++) if (spos(j) < p) n++; return n; };
#pragma unroll
  for (int p = 0; p < NP; p++) {
    const int j = which(p), r = j >= 0 ? 0 : p - nsm_before(p);
    uint32_t bp[4], tl[4][4];
    ldsm4(bp, mba + (j >= 0 ? (Chunks<ISV>::SC0 + ((P0 + j) >> 1)) * 1024 + ((P0 + j) & 1) * 512 : Chunks<ISV>::rf(WG, r >> 1) * 1024 + (r & 1) * 512));
    if (j >= NTA) load_pair(tl, wsa, P0 + j);
#pragma unroll
    for (int u = 0; u < 2; u++)
#pragma unroll
      for (int T = 0; T < 2; T++) {
        const uint32_t* a = j >= NTA ? tl[u * 2 + T] : j >= 0 ? ta[j >= 0 ? j % NTA : 0][u * 2 + T] : wr[r >> 1][T][(r & 1) * 2 + u];
        if (p == 0) mma16816z(acc[u * 2 + T], a, bp[2 * u], bp[2 * u + 1]);
        else mma16816(acc[u * 2 + T], a, bp[2 * u], bp[2 * u + 1]);
      }
  }
#pragma unroll
  for (int i = 0; i < 4; i++) { a0[i] = acc[0][i] + acc[2][i]; a1[i] = acc[1][i] + acc[3][i]; }
}
template <int WG>
__device__ __forceinline__ void proj_mem_prefetch(uint32_t (&ta)[ProjCfg<WG>::NTA][4][4], uint32_t wsa) {
#pragma unroll
  for (int j = 0; j < ProjCfg<WG>::NTA; j++) load_pair(ta[j], wsa, ProjCfg<WG>::P0 + j);
}

template <bool ISV, int WG>
__device__ __forceinline__ void proj_finish(const float (&a0)[4], const float (&a1)[4], uint32_t peer0, uint32_t peer1, uint32_t self, int tid,
                                            uint32_t (&vmo)[2][2]) {
  using namespace fk;
  SMAP;
  OPQ;
  if (!ISV) {
    stsm4(PT + (mi >> 1) * 2048 + w * 512 + (mi & 1) * 256 + WG * 128 + mr * 16,
          pack_bf16(a0[0], a0[1]), pack_bf16(a0[2], a0[3]), pack_bf16(a1[0], a1[1]), pack_bf16(a1[2], a1[3]));
    named_bar_sync(NB_C, 256);
  } else {
    if (WG == 0) sts128f(RED + t7 * 16, a1[0], a1[1], a1[2], a1[3]);
    else sts128f(RED + 2048 + t7 * 16, a0[0], a0[1], a0[2], a0[3]);
    if (WG == 1) { lds64(vmo[0], VM + t7 * 8); lds64(vmo[1], VM + 1024 + t7 * 8); }
    named_bar_sync(NB_C, 256);
    const float4 p = lds128f(RED + (1 - WG) * 2048 + t7 * 16);
    const float* k = WG == 0 ? a0 : a1;
    const uint32_t v0 = pack_bf16(k[0] + p.x, k[1] + p.y), v1 = pack_bf16(k[2] + p.z, k[3] + p.w);
    const uint32_t off = VM + WG * 1024 + t7 * 8;
    st_async64(peer0 + off, v0, v1, peer0 + B_VM);
    st_async64(peer1 + off, v0, v1, peer1 + B_VM);
    sts64(off, v0, v1);
    __syncwarp();
    if (lane == 0) mbar_arrive(B_VM);
  }
}

__device__ __forceinline__ void send_scores(float s0, float s1, uint32_t off, uint32_t peer0, uint32_t peer1, uint32_t bar, int lane) {
  if (SPACK) {
    const uint32_t v = pack_bf16(s0, s1);
    st_async32(peer0 + off, v, peer0 + bar);
    st_async32(peer1 + off, v, peer1 + bar);
    sts32(off, v);
  } else {
    st_async64f(peer0 + off, s0, s1, peer0 + bar);
    st_async64f(peer1 + off, s0, s1, peer1 + bar);
    sts64f(off, s0, s1);
  }
  __syncwarp();
  if (lane == 0) mbar_arrive(bar);
}

template <int NT, int PF, int PFA>
__device__ __forceinline__ void wo_phase(uint32_t (&wf)[PFA][4], uint32_t woa, uint32_t oba, char* h1p, uint32_t sel, uint32_t tag) {
  float c[NT][4];
  uint32_t of[2][4];
  ldsm4t(of[0], oba);
#pragma unroll
  for (int k = 0; k < 8; k++) {
    if ((k & 1) == 0 && k + 2 < 8) ldsm4t(of[((k >> 1) + 1) & 1], oba + ((k >> 1) + 1) * 512);
#pragma unroll
    for (int i = 0; i < NT; i++) {
      const int f = k * NT + i;
      const uint32_t b0 = of[(k >> 1) & 1][2 * (k & 1)], b1 = of[(k >> 1) & 1][2 * (k & 1) + 1];
      if (k == 0) mma16816z(c[i], wf[f % PF], b0, b1); else mma16816(c[i], wf[f % PF], b0, b1);
      if (f + PF < 8 * NT) ldsm4t(wf[f % PF], woa + ((f + PF) % NT) * 32768 + ((f + PF) / NT) * 512);
    }
  }
#pragma unroll
  for (int i = 0; i < NT; i++)
    st_pub64(h1p + i * (8 * 32768) + ((sel >> (2 * i)) & 3) * 2048, (pack_bf16(c[i][0], c[i][1]) & ~1u) | tag, pack_bf16(c[i][2], c[i][3]));
}
template <int NT, int F0, int F1, int PFA>
__device__ __forceinline__ void wo_prefetch(uint32_t (&wf)[PFA][4], uint32_t woa) {
#pragma unroll
  for (int f = F0; f < F1; f++) ldsm4t(wf[f], woa + (f % NT) * 32768 + (f / NT) * 512);
}

template <bool ISV, int T, bool ADD>
__device__ __forceinline__ void tok_store(const float (&x)[16], uint32_t base, int tid) {
  OPQ;
  const uint32_t a = ISV ? base + T * 4096 + w * 1024 + lane * 16
                   : T == 0 ? base + w * 512 + (mi & 1) * 256 + (mi >> 1) * 128 + mr * 16
                            : base + 4096 + (mi >> 1) * 1024 + w * 256 + (mi & 1) * 128 + mr * 16;
  constexpr uint32_t STR = ISV ? 512 : 2048;
  uint32_t p[2][4];
  if (ADD) {
#pragma unroll
    for (int i = 0; i < 2; i++) { if (ISV) lds128(p[i], a + i * STR); else ldsm4(p[i], a + i * STR); }
  }
#pragma unroll
  for (int i = 0; i < 2; i++) {
#pragma unroll
    for (int k = 0; k < 4; k++)
      p[i][k] = ADD ? pack_bf16(x[8 * i + 2 * k] + bf_lo(p[i][k]), x[8 * i + 2 * k + 1] + bf_hi(p[i][k]))
                    : pack_bf16(x[8 * i + 2 * k], x[8 * i + 2 * k + 1]);
    if (ISV) sts128(a + i * STR, p[i][0], p[i][1], p[i][2], p[i][3]); else stsm4(a + i * STR, p[i][0], p[i][1], p[i][2], p[i][3]);
  }
}

__device__ __forceinline__ void load_xn(const FParams& P, int seg, uint32_t self) {
  SMAP;
  mbar_expect_tx(B_XN, 49152);
  tma_load_3d(XN, &P.xn12, 0, seg * 32, 0, B_XN);
}

__device__ __forceinline__ uint64_t xn_desc(int slot, int u) { return make_desc(fk::XN + slot * 4096 + u * 32, 16, 1024); }

template <bool ISV>
__device__ __forceinline__ void f_wg0(const FParams& P, const WRegs& wr, const int h, const int rank, uint32_t sel, const int tid) {
  using namespace fk;
  const uint32_t self = mapa(0, rank), peer0 = mapa(0, ISV ? 0 : rank ^ 1) - self, peer1 = mapa(0, ISV ? 1 : 2) - self;
  SMAP;
  const int tile0 = rank * 22;
  const int warp = __shfl_sync(0xffffffffu, threadIdx.x >> 5, 0);
  const bool three = !ISV && warp < 2;
  uint32_t ta[NTA0][4][4], wsa = 0, mba = 0, h2ph = 0;
#pragma unroll 1
  for (int s = -1; s < cfg::NSEG; s++) {
    uint32_t t_pub = 0;
    sel ^= 0x55;
    if (s >= 0) {
      PROF(0, 1);
      float a0[4], a1[4];
      proj_mem<ISV, 0>(wr, ta, wsa, mba, a0, a1);
      PROF(0, 2);
      uint32_t unused[2][2];
      proj_finish<ISV, 0>(a0, a1, peer0, peer1, self, tid, unused);
      PROF(0, 3);
      if (s + 1 == cfg::NSEG) break;
      uint32_t wf[PF0][4], woa;
      {
        OPQ;
        if (!ISV) {
          uint32_t qf[4][4], kf[2][4];
          const uint32_t qa = PT + lane * 16, ka = QK + 4096 + w * 1024 + lane * 16;
          ldsm4t(qf[0], qa); ldsm4t(kf[0], ka); ldsm4t(qf[1], qa + 512);
          ldsm4t(qf[2], qa + 1024); ldsm4t(kf[1], ka + 512); ldsm4t(qf[3], qa + 1536);
          float c0[4], c1[4];
          mma16816z(c0, qf[0], kf[0][0], kf[0][1]);
          mma16816z(c1, qf[1], kf[0][2], kf[0][3]);
          mma16816(c0, qf[2], kf[1][0], kf[1][1]);
          mma16816(c1, qf[3], kf[1][2], kf[1][3]);
          const float s0 = (c0[0] + c0[2]) + (c1[0] + c1[2]), s1 = (c0[1] + c0[3]) + (c1[1] + c1[3]);
          send_scores(s0, s1, SP + rank * SP_SRC + t7 * SPW, peer0, peer1, B_SM, lane);
        }
        PROF(0, 4);
        woa = WO + (w + 4) * 4096 + ((mi >> 1) * 8 + mr) * 32 + (((mi & 1) ^ (mr >> 2)) << 4);
        PIN(woa);
        uint32_t vf[2][2][4], vm[2][2];
        if (!ISV) mbar_spin(B_VX, s & 1);
        PROF(0, 14);
#pragma unroll
        for (int T = 0; T < 2; T++)
#pragma unroll
          for (int kk = 0; kk < 2; kk++) lds128(vf[T][kk], ((ISV && (s & 1)) ? VX2 : VX) + T * 4096 + w * 1024 + kk * 512 + lane * 16);
        if (three) wo_prefetch<3, 0, PF0A>(wf, woa); else wo_prefetch<2, 0, PF0A>(wf, woa);
        uint32_t spa = SP + lane * SPW, vma = VM + t7 * 8, oa = OB + (mi >> 1) * 1024 + w * 256 + (mi & 1) * 128 + mr * 16;
        PIN(spa); PIN(vma); PIN(oa);
        mbar_spin(B_SM, s & 1);
        PROF(0, 5);
        float sc[10];
#pragma unroll
        for (int j = 0; j < 5; j++) {
          if (SPACK) {
            const uint32_t x = lds32(spa + j * 128), y = lds32(spa + SP_SRC + j * 128);
            sc[2 * j] = bf_lo(x) + bf_lo(y); sc[2 * j + 1] = bf_hi(x) + bf_hi(y);
          } else {
            const float2 x = lds64f(spa + j * 256), y = lds64f(spa + SP_SRC + j * 256);
            sc[2 * j] = x.x + y.x; sc[2 * j + 1] = x.y + y.y;
          }
        }
        float m = fmaxf(fmaxf(fmaxf(sc[0], sc[1]), fmaxf(sc[2], sc[3])), fmaxf(fmaxf(sc[4], sc[5]), fmaxf(sc[6], sc[7])));
        m = fmaxf(m, fmaxf(sc[8], sc[9]));
        const bool vm_ok = mbar_test(B_VM, s & 1);
        m = fmaxf(m, __shfl_xor_sync(0xffffffffu, m, 1));
        m = fmaxf(m, __shfl_xor_sync(0xffffffffu, m, 2));
        PROF(0, 15);
        if (!vm_ok) mbar_spin(B_VM, s & 1);
        PROF(0, 0);
        lds64(vm[0], vma); lds64(vm[1], vma + 1024);
        const float cs = 0.08838834764831845f * 1.4426950408889634f;
        const float mc = -m * cs;
        uint32_t pb[5];
#pragma unroll
        for (int j = 0; j < 5; j++) pb[j] = pack_bf16(ex2_approx(fmaf(sc[2 * j], cs, mc)), ex2_approx(fmaf(sc[2 * j + 1], cs, mc)));
        PROF(0, 6);
        float o0[4], o1[4], rs[4];
        const uint32_t ones[4] = {0x3F803F80u, 0x3F803F80u, 0x3F803F80u, 0x3F803F80u};
        mma16816z(rs, ones, pb[0], pb[1]);
        mma16816z(o0, vf[0][0], pb[0], pb[1]);
        mma16816z(o1, vf[1][0], pb[0], pb[1]);
        mma16816(rs, ones, pb[2], pb[3]);
        mma16816(o0, vf[0][1], pb[2], pb[3]);
        mma16816(o1, vf[1][1], pb[2], pb[3]);
        mma1688(rs, ones[0], ones[0], pb[4]);
        mma1688(o0, vm[0][0], vm[0][1], pb[4]);
        mma1688(o1, vm[1][0], vm[1][1], pb[4]);
        const float i0 = rcp_approx(rs[0]), i1 = rcp_approx(rs[1]);
        stsm4(oa, pack_bf16(o0[0] * i0, o0[1] * i1), pack_bf16(o0[2] * i0, o0[3] * i1),
              pack_bf16(o1[0] * i0, o1[1] * i1), pack_bf16(o1[2] * i0, o1[3] * i1));
      }
      {
        OPQ;
        named_bar_arrive(NB_O, 256);
        if (three) wo_prefetch<3, PF0A, PF0>(wf, woa); else wo_prefetch<2, PF0A, PF0>(wf, woa);
        char* h1p = P.xch + (tile0 + 4 + w) * 32768 + (h >> 3) * 8192 + (h & 7) * 256 + lane * 8;
        uint32_t oba = OB + lane * 16;
        PIN(oba);
        PROF(0, 7);
        named_bar_sync(NB_O0, 128);
        PROF(0, 8);
        const uint32_t tag = ((s >> 1) & 1) ^ 1;
        if (three) wo_phase<3, PF0>(wf, woa, oba, h1p, sel, tag); else wo_phase<2, PF0>(wf, woa, oba, h1p, sel, tag);
        t_pub = clk32();
        PROF(0, 9);
        named_bar_sync(NB_HD, 256);
      }
    }
    auto h2_src = [&]() { return P.xch + H1_BYTES + ((s & 1) * 4 + warp) * 8192 + ((sel >> (8 + (s & 1))) & 1) * 4096; };
    {
      const uint32_t ph = (s + 1) & 1;
      float x0[16], x1[16];
      mbar_spin(B_XN, ph);
      wg_fence();
#pragma unroll
      for (int c = 0; c < 10; c++) {
        if (PAUSE && !ISV && c == SCQ + 4) { uint32_t t_; named_bar_and(NB_PZ, 256, 1, t_); wg_fence(); }
        if (c == 9) named_bar_arrive(NB_ST, 256);
#pragma unroll
        for (int u = 0; u < 4; u++) {
          constexpr int SC0 = Chunks<ISV>::SC0;
          if (c >= SC0 && c < SC0 + 4) {
            wgmma_ss_n32_ta(x0, make_desc(fk::WS + (c - SC0) * 16384 + u * 2048, 8192, 1024), xn_desc(c, u), 1);
            wgmma_ss_n32_ta(x1, make_desc(fk::WS + (c - SC0) * 16384 + 8192 + u * 2048, 8192, 1024), xn_desc(c, u), 1);
          } else {
            wgmma_rs_n32(x0, wr[c < SC0 ? c : c >= SC0 + 4 ? c - 4 : 0][0][u], xn_desc(c, u), (c | u) != 0);
            wgmma_rs_n32(x1, wr[c < SC0 ? c : c >= SC0 + 4 ? c - 4 : 0][1][u], xn_desc(c, u), (c | u) != 0);
          }
          if (c == 4 && u == 1) { wg_commit(); wg_wait<1>(); named_bar_arrive(NB_XE, 160); wg_fence(); }
        }
        if (c == 3) wg_commit();
      }
      wg_commit();
      wg_wait<0>();
      PROF(0, 10);
      if (ISV) named_bar_sync(NB_CF, 160);
      const uint32_t tb = ISV ? (ph ? VX2 : VX) : QK;
      tok_store<ISV, 0, false>(x0, tb, tid);
      tok_store<ISV, 1, false>(x1, tb, tid);
      named_bar_arrive(NB_DU, 256);
    }
    {
      OPQ;
      wsa = WS + ((mi >> 1) * 8 + mr) * 128 + (((2 * w + (mi & 1)) ^ mr) << 4);
      mba = MEMB + lane * 16;
      PIN(wsa); PIN(mba);
      if (s >= 0) {
        const char* src = h2_src();
        const uint32_t chk = MEMB + w * 4096 + lane * 32 + lg * 4, bar = B_H2 + 8 * warp;
        PROF(0, 11);
        if (FLAGS) {
          const char* fp = P.xch + FL_OFF + ((sel >> 10) & 1) * 4096 + (h & 3) * 128 + w * 32 + mr * 4;
          const uint32_t want = (s + 1) * 0x10001;
          spin_until(t_pub + D_H2);
          uint32_t f0 = ld_strong4(fp);
          spin_until(clk32() + D_FS);
          uint32_t f1 = ld_strong4(fp);
          spin_until(clk32() + D_FS);
          uint32_t f2 = ld_strong4(fp);
#pragma unroll 1
          for (int tries = 0; tries < POLL_TRIES; tries++) {
            if (__all_sync(0xffffffffu, f0 == want)) break;
            f0 = ld_strong4(fp);
            if (__all_sync(0xffffffffu, f1 == want)) break;
            f1 = ld_strong4(fp);
            if (__all_sync(0xffffffffu, f2 == want)) break;
            f2 = ld_strong4(fp);
          }
          if (D_F) spin_until(clk32() + D_F);
        } else {
          spin_until(t_pub + D_H2);
        }
        PROF(0, 13);
        if (elect_one()) { mbar_expect_tx(bar, 4096); bulk_g2s(MEMB + warp * 4096, src, 4096, bar); }
        proj_mem_prefetch<0>(ta, wsa);
#pragma unroll 1
        for (int tries = 0; tries < POLL_TRIES; tries++) {
          mbar_spin(bar, h2ph);
          h2ph ^= 1;
          const uint32_t mx = max(max(lds32(chk), lds32(chk + 1024)), max(lds32(chk + 2048), lds32(chk + 3072)));
          if (__all_sync(0xffffffffu, mx != EMPTY)) break;
          RETRY(1);
          if (elect_one()) { mbar_expect_tx(bar, 4096); bulk_g2s(MEMB + warp * 4096, src, 4096, bar); }
        }
      } else {
        const bf16* m0 = P.mem0 + mr * cfg::D + w * 256 + mi * 8;
#pragma unroll
        for (int i = 0; i < 8; i++) {
          const uint4 v = *reinterpret_cast<const uint4*>(m0 + i * 32);
          sts128(mba + w * 4096 + i * 512, v.x, v.y, v.z, v.w);
        }
        proj_mem_prefetch<0>(ta, wsa);
      }
      PROF(0, 12);
      named_bar_arrive(NB_M1, 256);
      named_bar_sync(NB_M0, 128);
    }
  }
}

template <bool ISV>
__device__ __forceinline__ void f_wg1(const FParams& P, const WRegs& wr, const int h, const int rank, uint32_t sel, const int tid) {
  using namespace fk;
  const uint32_t self = mapa(0, rank), peer0 = mapa(0, ISV ? 0 : rank ^ 1) - self, peer1 = mapa(0, ISV ? 1 : 2) - self;
  SMAP;
  const int tile0 = rank * 22;
  const int warp = __shfl_sync(0xffffffffu, (threadIdx.x >> 5) & 3, 0);
  uint32_t ta[NTA1][4][4], wsa = 0, mba = 0;
  auto tok_pv = [&](int seg, const uint32_t (&vm)[2][2]) {
    OPQ;
    const int s = seg + 1; (void)s;
    const uint32_t vb = (seg & 1) ? VX2 : VX;
    uint32_t vf[2][2][4];
#pragma unroll
    for (int T = 0; T < 2; T++)
#pragma unroll
      for (int kk = 0; kk < 2; kk++) lds128(vf[T][kk], vb + T * 4096 + w * 1024 + kk * 512 + lane * 16);
    const uint32_t stg = vb + (mi >> 1) * 4096 + mr * 128 + (((2 * w + (mi & 1)) ^ mr) << 4);
    uint32_t pm[4], r[4][4];
    lds128(pm, PT + 2048 + lane * 16);
#pragma unroll
    for (int g2 = 0; g2 < 4; g2 += 2) {
      uint32_t p[2][4];
      lds128(p[0], PT + g2 * 512 + lane * 16);
      lds128(p[1], PT + g2 * 512 + 512 + lane * 16);
      float o[4][4];
#pragma unroll
      for (int i = 0; i < 4; i++) mma16816z(o[i], vf[i & 1][0], p[i >> 1][0], p[i >> 1][1]);
#pragma unroll
      for (int i = 0; i < 4; i++) mma16816(o[i], vf[i & 1][1], p[i >> 1][2], p[i >> 1][3]);
#pragma unroll
      for (int i = 0; i < 4; i++) mma1688(o[i], vm[i & 1][0], vm[i & 1][1], pm[g2 + (i >> 1)]);
#pragma unroll
      for (int i = 0; i < 4; i++) {
        r[g2 + (i >> 1)][2 * (i & 1)] = pack_bf16(o[i][0], o[i][1]);
        r[g2 + (i >> 1)][2 * (i & 1) + 1] = pack_bf16(o[i][2], o[i][3]);
      }
      if (g2 == 0) named_bar_sync(NB_W1, 128);
    }
    PROF(1, 6);
#pragma unroll
    for (int gq = 0; gq < 4; gq++) stsm4t(stg + gq * 1024, r[gq][0], r[gq][1], r[gq][2], r[gq][3]);
  };
  auto o_store = [&](int seg) { tma_store_3d(&P.o, (seg & 1) ? VX2 : VX, 0, seg * 32, 2 * h); tma_store_commit(); };
  auto o_done = [&](int seg) {
    tma_store_wait_all();
    if ((seg & 3) == 3) {
      asm volatile("fence.proxy.async;" ::: "memory");
      asm volatile("red.release.gpu.global.add.u32 [%0], 1;" ::"l"(&g_oflag[seg >> 2]) : "memory");
    }
  };
#pragma unroll 1
  for (int s = -1; s < cfg::NSEG; s++) {
    uint32_t t_pub = 0;
    sel ^= 0x55;
    const bool last = s + 1 == cfg::NSEG;
    if (s >= 0) {
      PROF(1, 1);
      float a0[4], a1[4];
      proj_mem<ISV, 1>(wr, ta, wsa, mba, a0, a1);
      PROF(1, 2);
      uint32_t vmo[2][2];
      proj_finish<ISV, 1>(a0, a1, peer0, peer1, self, tid, vmo);
      PROF(1, 3);
      uint32_t wf[PF1][4], woa;
      if (ISV) {
        if (warp == 3 && !last) {
          mbar_spin(B_VM, s & 1);
          if (elect_one()) load_xn(P, s + 1, self);
        }
        if (s > 0) tok_pv(s - 1, vmo);
        OPQ;
        woa = WO + w * 4096 + ((mi >> 1) * 8 + mr) * 32 + (((mi & 1) ^ (mr >> 2)) << 4);
      } else {
        float c0[4], c1[4];
        if (warp == 0) {
          OPQ;
          uint32_t kf[4][4], qf[4][4];
          float d0[4], d1[4];
          const uint32_t ka = PT + 2048 + (mi & 1) * 256 + (mi >> 1) * 128 + mr * 16;
#pragma unroll
          for (int k = 0; k < 4; k++) { ldsm4t(qf[k], PT + k * 512 + lane * 16); ldsm4t(kf[k], ka + k * 512); }
          mma16816z(c0, qf[0], kf[0][0], kf[0][1]); mma16816z(c1, qf[0], kf[0][2], kf[0][3]);
          mma16816z(d0, qf[1], kf[1][0], kf[1][1]); mma16816z(d1, qf[1], kf[1][2], kf[1][3]);
          mma16816(c0, qf[2], kf[2][0], kf[2][1]); mma16816(c1, qf[2], kf[2][2], kf[2][3]);
          mma16816(d0, qf[3], kf[3][0], kf[3][1]); mma16816(d1, qf[3], kf[3][2], kf[3][3]);
          const float s0 = ((c0[0] + c0[2]) + (c1[0] + c1[2])) + ((d0[0] + d0[2]) + (d1[0] + d1[2]));
          const float s1 = ((c0[1] + c0[3]) + (c1[1] + c1[3])) + ((d0[1] + d0[3]) + (d1[1] + d1[3]));
          if (!last) send_scores(s0, s1, SP + rank * SP_SRC + (128 + lane) * SPW, peer0, peer1, B_SM, lane);
          PROF(1, 5);
#pragma unroll
          for (int mt = 0; mt < 2; mt++) {
            float* c = mt ? c1 : c0;
#pragma unroll
            for (int k = 0; k < 4; k++) ldsm4t(qf[k], QK + mt * 2048 + k * 512 + lane * 16);
            mma16816z(c, qf[0], kf[0][0], kf[0][1]); mma16816z(d0, qf[0], kf[0][2], kf[0][3]);
#pragma unroll
            for (int k = 1; k < 4; k++) { mma16816(c, qf[k], kf[k][0], kf[k][1]); mma16816(d0, qf[k], kf[k][2], kf[k][3]); }
#pragma unroll
            for (int i = 0; i < 4; i++) c[i] += d0[i];
          }
        } else {
          const uint32_t t_c = clk32();
          if (warp == 3 && !last) { if (elect_one()) load_xn(P, s + 1, self); }
          spin_until(t_c + D_ST);
          OPQ;
          const int mt = w >> 1, j0 = w == 3 ? 2 : 0;
          uint32_t qf[4][4], kf[4][4];
#pragma unroll
          for (int k = 0; k < 4; k++) { ldsm4t(qf[k], QK + mt * 2048 + k * 512 + lane * 16); ldsm4t(kf[k], QK + 4096 + j0 * 1024 + k * 512 + lane * 16); }
          mma16816z(c0, qf[0], kf[0][0], kf[0][1]); mma16816z(c1, qf[0], kf[2][0], kf[2][1]);
          mma16816(c0, qf[1], kf[0][2], kf[0][3]); mma16816(c1, qf[1], kf[2][2], kf[2][3]);
          mma16816(c0, qf[2], kf[1][0], kf[1][1]); mma16816(c1, qf[2], kf[3][0], kf[3][1]);
          mma16816(c0, qf[3], kf[1][2], kf[1][3]); mma16816(c1, qf[3], kf[3][2], kf[3][3]);
        }
        OPQ;
        const uint32_t dst = peer1 + QK + rank * 3584 + lane * 8, dbar = peer1 + B_ST;
        woa = WO + w * 4096 + ((mi >> 1) * 8 + mr) * 32 + (((mi & 1) ^ (mr >> 2)) << 4);
        const uint32_t tbl = w == 0 ? 0x9520u : w == 1 ? 0x4F31u : w == 2 ? 0xB7A6u : 0xDFC8u;
        PROF(1, 6);
        mbar_spin(last ? B_VM : B_VX, s & 1);
        st_async64f(dst + (tbl & 15) * 256, c0[0], c0[1], dbar);
        st_async64f(dst + ((tbl >> 4) & 15) * 256, c0[2], c0[3], dbar);
        if ((w & 1) == 0) st_async64f(dst + ((tbl >> 8) & 15) * 256, c1[0], c1[1], dbar);
        st_async64f(dst + (tbl >> 12) * 256, c1[2], c1[3], dbar);
      }
      PROF(1, 4);
      if (!last) {
        OPQ;
        uint32_t oba = OB + lane * 16;
        PIN(oba);
        wo_prefetch<3, 0, PF1>(wf, woa);
        char* h1p = P.xch + (tile0 + w) * 32768 + (h >> 3) * 8192 + (h & 7) * 256 + lane * 8;
        if (ISV) fence_proxy_async_smem();
        PROF(1, 7);
        named_bar_sync(NB_O, 256);
        PROF(1, 8);
        wo_phase<3, PF1>(wf, woa, oba, h1p, sel, ((s >> 1) & 1) ^ 1);
        t_pub = clk32();
        named_bar_arrive(NB_HD, 256);
        PROF(1, 9);
        if (ISV && warp == 0 && s > 0) { if (elect_one()) o_store(s - 1); }
        if (!ISV && tid == 192) mbar_arrive_remote(peer1 + B_PF);
        if (tid == 160) {
          if (s + 2 < cfg::NSEG) { mbar_expect_tx(B_SM, ISV ? 2 * SP_SRC : SP_SRC); if (!ISV) mbar_expect_tx(B_VX, 8192); }
          if (!ISV) mbar_expect_tx(B_VM, 2048);
        }
        __syncwarp();
      }
    }
    auto refill = [&]() {
      if (warp == 3) {
        named_bar_sync(NB_XE, 160);
        if (elect_one()) {
          mbar_expect_tx(B_XN + 8, 16384);
          tma_load_3d(XN, &P.xn, 0, (s + 1) * 32, 12, B_XN + 8);
        }
      }
    };
    if (s < 0) {
      if (ISV && warp == 0) named_bar_arrive(NB_CF, 160);
      refill();
      if (PAUSE && !ISV) { uint32_t t_; named_bar_and(NB_PZ, 256, 1, t_); }
    } else if (!ISV) {
      if (last) break;
      OPQ;
      const int j = 2 * h + rank;
      const char* src = P.xch + j * 32768 + w * 8192 + ((sel >> 6) & 3) * 2048 + lane * 8;
      char* dst = P.xch + H1_BYTES + (j >> 4) * 8192 + (j & 15) * 256 + (w & 1) * 128 + lane * 4;
      const uint32_t tmask = (s >> 1) & 1;
      const bool sw = lq >= 2;
      uint32_t rw = PT + w * 512 + (2 * lq + sw) * 32 + lg * 4, rr = PT + (w & 1) * 256 + lane * 8;
      PIN(rw); PIN(rr);
      uint2 v[8];
      spin_until(t_pub + D_H1);
#pragma unroll
      for (int i = 0; i < 8; i++) v[i] = ld_poll8(src + i * 256);
      refill();
      auto partial = [&]() {
        float f[4];
        f[0] = ((bf_lo(v[0].x) + bf_lo(v[1].x)) + (bf_lo(v[2].x) + bf_lo(v[3].x))) + ((bf_lo(v[4].x) + bf_lo(v[5].x)) + (bf_lo(v[6].x) + bf_lo(v[7].x)));
        f[1] = ((bf_hi(v[0].x) + bf_hi(v[1].x)) + (bf_hi(v[2].x) + bf_hi(v[3].x))) + ((bf_hi(v[4].x) + bf_hi(v[5].x)) + (bf_hi(v[6].x) + bf_hi(v[7].x)));
        f[2] = ((bf_lo(v[0].y) + bf_lo(v[1].y)) + (bf_lo(v[2].y) + bf_lo(v[3].y))) + ((bf_lo(v[4].y) + bf_lo(v[5].y)) + (bf_lo(v[6].y) + bf_lo(v[7].y)));
        f[3] = ((bf_hi(v[0].y) + bf_hi(v[1].y)) + (bf_hi(v[2].y) + bf_hi(v[3].y))) + ((bf_hi(v[4].y) + bf_hi(v[5].y)) + (bf_hi(v[6].y) + bf_hi(v[7].y)));
        sts32(rw, __float_as_uint(sw ? f[1] : f[0]));
        sts32(rw ^ 32, __float_as_uint(sw ? f[0] : f[1]));
        sts32(rw + 256, __float_as_uint(sw ? f[3] : f[2]));
        sts32((rw ^ 32) + 256, __float_as_uint(sw ? f[2] : f[3]));
        uint32_t t0, t1, t2, t3;
        asm("lop3.b32 %0, %1, %2, %3, 0x42;" : "=r"(t0) : "r"(v[0].x), "r"(v[1].x), "r"(tmask));
        asm("lop3.b32 %0, %1, %2, %3, 0x42;" : "=r"(t1) : "r"(v[2].x), "r"(v[3].x), "r"(tmask));
        asm("lop3.b32 %0, %1, %2, %3, 0x42;" : "=r"(t2) : "r"(v[4].x), "r"(v[5].x), "r"(tmask));
        asm("lop3.b32 %0, %1, %2, %3, 0x42;" : "=r"(t3) : "r"(v[6].x), "r"(v[7].x), "r"(tmask));
        return t0 & t1 & t2 & t3 & 1;
      };
      uint32_t ok = partial();
      PROF(1, 10);
      if (PAUSE) named_bar_and(NB_PZ, 256, ok, ok); else named_bar_and(NB_W1, 128, ok, ok);
      if (!ok) {
#pragma unroll 1
        for (int tries = 0; tries < POLL_TRIES; tries++) {
#pragma unroll
          for (int i = 0; i < 8; i++) v[i] = ld_strong8(src + i * 256);
          RETRY(0);
          ok = partial();
          named_bar_and(NB_W1, 128, ok, ok);
          if (ok) break;
        }
      }
      if (FLAGS && warp == 2 && lane < 8) st_pub16(P.xch + FL_OFF + (lane & 1) * 4096 + (lane >> 1) * 128 + j * 2, s + 1);
      if (warp < 2) {
        const float2 y0 = lds64f(rr), y1 = lds64f(rr + 512), y2 = lds64f(rr + 1024), y3 = lds64f(rr + 1536);
        const uint32_t r = pack_bf16((y0.x + y1.x) + (y2.x + y3.x), (y0.y + y1.y) + (y2.y + y3.y));
        st_pub32(dst + (s & 1) * 32768, r);
        st_pub32(dst + (s & 1) * 32768 + 4096, r);
        st_pub32(dst + ((s & 1) ^ 1) * 32768, EMPTY);
        st_pub32(dst + ((s & 1) ^ 1) * 32768 + 4096, EMPTY);
      }
      if (s == 0 && t7 == 0) st_pub32(&g_mask[j], 0);
      PROF(1, 11);
    } else {
      {
        OPQ;
        const uint32_t sa = QK + ((w * (w + 3)) >> 1) * 256 + lane * 8;
        mbar_spin(B_ST, s & 1);
        if (tid == 160 && !last) mbar_expect_tx(B_ST, 7168);
        float sc[10];
        const float scale = 0.08838834764831845f, NEG = -1000000000.0f;
#pragma unroll
        for (int b = 0; b < 5; b++) {
          sc[2 * b] = NEG; sc[2 * b + 1] = NEG;
          if (b <= warp + 1) {
            const float2 x = lds64f(sa + b * 256), y = lds64f(sa + 3584 + b * 256);
            const bool diag = b == warp + 1;
            if (!(diag && 2 * lq > lg)) sc[2 * b] = (x.x + y.x) * scale;
            if (!(diag && 2 * lq + 1 > lg)) sc[2 * b + 1] = (x.y + y.y) * scale;
          }
        }
        float m = fmaxf(fmaxf(fmaxf(sc[0], sc[1]), fmaxf(sc[2], sc[3])), fmaxf(fmaxf(sc[4], sc[5]), fmaxf(sc[6], sc[7])));
        m = fmaxf(m, fmaxf(sc[8], sc[9]));
        m = fmaxf(m, __shfl_xor_sync(0xffffffffu, m, 1));
        m = fmaxf(m, __shfl_xor_sync(0xffffffffu, m, 2));
        float sum = 0.f;
#pragma unroll
        for (int i = 0; i < 10; i++) { sc[i] = ex2_approx((sc[i] - m) * 1.4426950408889634f); sum += sc[i]; }
        sum += __shfl_xor_sync(0xffffffffu, sum, 1);
        sum += __shfl_xor_sync(0xffffffffu, sum, 2);
        const float inv = rcp_approx(sum);
        sts128(PT + w * 512 + lane * 16, pack_bf16(sc[2] * inv, sc[3] * inv), pack_bf16(sc[4] * inv, sc[5] * inv),
               pack_bf16(sc[6] * inv, sc[7] * inv), pack_bf16(sc[8] * inv, sc[9] * inv));
        sts32(PT + 2048 + lane * 16 + w * 4, pack_bf16(sc[0] * inv, sc[1] * inv));
        PROF(1, 10);
        if (last) {
          uint32_t vm[2][2];
          mbar_spin(B_VM, s & 1);
          lds64(vm[0], VM + t7 * 8); lds64(vm[1], VM + 1024 + t7 * 8);
          named_bar_sync(NB_W1, 128);
          tok_pv(s, vm);
          fence_proxy_async_smem();
          named_bar_sync(NB_W1, 128);
          if (warp == 0) { if (elect_one()) { o_store(s - 1); o_store(s); o_done(s); } }
          break;
        }
      }
      if (warp == 0) {
        if (s > 0) { if (elect_one()) o_done(s - 1); }
        __syncwarp();
        named_bar_arrive(NB_CF, 160);
      }
      refill();
      PROF(1, 11);
    }
    {
      const uint32_t ph = (s + 1) & 1;
      float x0[16], x1[16];
      mbar_spin(B_XN, ph);
      named_bar_sync(NB_ST, 256);
      PROF(1, 12);
      wg_fence();
#pragma unroll
      for (int c = 0; c < 6; c++) {
        if (c == 2) { mbar_spin(B_XN + 8, ph); wg_fence(); }
#pragma unroll
        for (int u = 0; u < 4; u++) {
          wgmma_rs_n32(x0, wr[c][0][u], xn_desc(c < 2 ? 10 + c : c - 2, u), (c | u) != 0);
          wgmma_rs_n32(x1, wr[c][1][u], xn_desc(c < 2 ? 10 + c : c - 2, u), (c | u) != 0);
        }
      }
      wg_commit();
      OPQ;
      named_bar_sync(NB_DU, 256);
      wg_wait<0>();
      PROF(1, 13);
      const uint32_t tb = ISV ? (ph ? VX2 : VX) : QK;
      tok_store<ISV, 1, true>(x1, tb, tid);
      tok_store<ISV, 0, true>(x0, tb, tid);
      if (ISV && s + 2 < cfg::NSEG) {
        fence_proxy_async_smem();
        named_bar_sync(NB_W1, 128);
        if (warp >= 2) {
          if (s >= 0) mbar_spin(B_PF, s & 1);
          const uint32_t peer = warp == 2 ? peer0 : peer1;
          if (elect_one()) bulk_s2s(peer + VX, tb, 8192, peer + B_VX);
        }
      }
      wsa = WS + ((mi >> 1) * 8 + mr) * 128 + (((2 * w + (mi & 1)) ^ mr) << 4);
      mba = MEMB + lane * 16;
      PIN(wsa); PIN(mba);
      proj_mem_prefetch<1>(ta, wsa);
      PROF(1, 14);
      named_bar_sync(NB_M1, 256);
    }
  }
}

template <bool ISV, int WG>
__device__ __forceinline__ void f_main(const FParams& P, const int h, const int rank) {
  using namespace fk;
  const uint32_t self = mapa(0, rank);
  SMAP;
  const int tid = __shfl_sync(0xffffffffu, threadIdx.x, threadIdx.x & 31);
  const int tile0 = rank * 22, ntile = ISV ? 20 : 22;
  const CUtensorMap* m0 = ISV ? &P.wv : &P.wq;
  const CUtensorMap* m1 = ISV ? &P.wv : &P.wk;
  const int col0 = h * 128 + (ISV ? 0 : 64 * rank), col1 = h * 128 + (ISV ? 64 : 64 * rank);
  if (threadIdx.x == 0) {
#pragma unroll 1
    for (int i = 0; i < 6; i++) {
      mbar_expect_tx(B_PB + 8 * i, 32768);
#pragma unroll
      for (int g = 0; g < 2; g++) {
        const int row = Chunks<ISV>::rf(g, i) * 64;
        tma_load_2d(SM0 + i * 32768 + g * 16384, m0, col0, row, B_PB + 8 * i);
        tma_load_2d(SM0 + i * 32768 + g * 16384 + 8192, m1, col1, row, B_PB + 8 * i);
      }
    }
  }
  __syncwarp();
  pdl_wait();
  pdl_launch_dependents();
  WRegs wr;
  {
    OPQ;
    const uint32_t a = SM0 + WG * 16384 + ((mi >> 1) * 8 + mr) * 128 + (((2 * w + (mi & 1)) ^ mr) << 4);
#pragma unroll
    for (int i = 0; i < 6; i++) {
      mbar_wait(B_PB + 8 * i, 0);
#pragma unroll
      for (int T = 0; T < 2; T++)
#pragma unroll
        for (int u = 0; u < 4; u++) ldsm4t(wr[i][T][u], a + i * 32768 + T * 8192 + u * 2048);
      named_bar_sync(NB_C, 256);
      if (WG == 1 && i < 5 && threadIdx.x == 128 + 32 * (i & 3)) {
        const int t0 = 8 * i, t1 = i < 3 ? min(8 * i + 8, ntile) : t0, p0 = i == 2 ? 0 : i == 3 ? 1 : 5, p1 = i < 2 ? p0 : i == 2 ? 1 : i == 3 ? 5 : 8;
        mbar_expect_tx(B_W, (t1 - t0) * 4096 + (p1 - p0) * 8192);
#pragma unroll 1
        for (int p = p0; p < p1; p++) tma_load_2d(WS + p * 8192, (p & 1) ? m1 : m0, (p & 1) ? col1 : col0, (Chunks<ISV>::SC0 + (p >> 1)) * 64, B_W);
#pragma unroll 1
        for (int t = t0; t < t1; t++) tma_load_2d(WO + t * 4096, &P.wo, (tile0 + t) * 16, h * 128, B_W);
      }
      __syncwarp();
    }
  }
  PROF2(1);
  if (threadIdx.x == 224) load_xn(P, 0, self);
  __syncwarp();
  mbar_wait(B_W, 0);
  PROF2(4);
  GTSYNC(0);
  uint32_t sel = 0;
  {
    OPQ;
    const int j = 2 * h + rank;
    if (WG == 0) {
      if (lane == 0) {
        char* p = P.xch + H1_BYTES + w * 8192 + (blockIdx.x & 31) * 128;
        sel = (probe_pair(p, EMPTY, PROBE + 32) << 8) | (probe_pair(p + 32768, EMPTY, PROBE + 32) << 9);
      }
    } else if (!ISV) {
      char* p = P.xch + j * 32768 + w * 8192;
      if (lane == 0) sel = probe_pair(p, 0, PROBE + 32) << 7;
      sel = __shfl_sync(0xffffffffu, sel, 0);
#pragma unroll
      for (int i = 0; i < 8; i++) st_pub128(p + (sel >> 7) * 4096 + i * 512 + lane * 16, 0);
      st_pub64(P.xch + H1_BYTES + (w >> 1) * 32768 + (j >> 4) * 8192 + (w & 1) * 4096 + (j & 15) * 256 + lane * 8, EMPTY, EMPTY);
      if (t7 < 8) st_pub16(P.xch + FL_OFF + (lane & 1) * 4096 + (lane >> 1) * 128 + j * 2, 0);
      if (lane == 0) sts32(PROBE + w * 4, sel >> 7);
      __threadfence();
      named_bar_sync(NB_W1, 128);
      if (t7 == 0) {
        const uint32_t m = 0x10 | lds32(PROBE) | (lds32(PROBE + 4) << 1) | (lds32(PROBE + 8) << 2) | (lds32(PROBE + 12) << 3);
        asm volatile("st.release.gpu.global.u32 [%0], %1;" ::"l"(&g_mask[j]), "r"(m) : "memory");
      }
    }
    sel = __shfl_sync(0xffffffffu, sel, 0);
  }
  PROF2(3);
  {
    OPQ;
    if (WG == 1 && w == 1) {
      uint2 v;
#pragma unroll 1
      for (int tries = 0; tries < POLL_TRIES; tries++) {
        v = ld_strong8(&g_mask[2 * lane]);
        if (__all_sync(0xffffffffu, v.x & v.y & 0x10)) break;
        __nanosleep(100);
      }
      __threadfence();
      sts64(MASKS + lane * 8, v.x, v.y);
    }
    named_bar_sync(NB_C, 256);
#pragma unroll
    for (int i = 0; i < 3; i++) {
      const int t = min(tile0 + 8 * i + w + (WG ? 0 : 4), 63);
      sel |= ((lds32(MASKS + t * 4) >> (h >> 3)) & 1) << (2 * i + 1);
    }
  }
  PROF2(2);
  KT_END(8);
  if (WG == 0) f_wg0<ISV>(P, wr, h, rank, sel, tid); else f_wg1<ISV>(P, wr, h, rank, sel, tid);
}

__global__ void __launch_bounds__(256, 1) f_kernel(const __grid_constant__ FParams P) {
  using namespace fk;
  extern __shared__ __align__(1024) uint8_t smem_f[];
  uint32_t rank;
  asm("mov.u32 %0, %%cluster_ctarank;" : "=r"(rank));
  const int h = blockIdx.x / 3;
  if (smem_u32(smem_f) != mapa(0, rank) + SM0) return;
  SCHED_DECL(threadIdx.x * P.one);
  PROF2(0);
  KT_START(1);
  if (threadIdx.x == 0) {
    const bool isv = rank == 2;
    const uint32_t self = mapa(0, rank);
    SMAP;
    for (int i = 0; i < 2; i++) mbar_init(B_XN + 8 * i, 1);
    for (int i = 0; i < 4; i++) mbar_init(B_H2 + 8 * i, 1);
    mbar_init(B_SM, isv ? 1 : 6);
    mbar_init(B_VM, isv ? 8 : 1);
    mbar_init(B_VX, 1);
    mbar_init(B_ST, 1);
    mbar_init(B_PF, 2);
    for (int i = 0; i < 6; i++) mbar_init(B_PB + 8 * i, 1);
    mbar_init(B_W, 5);
    fence_barrier_init();
    mbar_expect_tx(B_SM, isv ? 2 * SP_SRC : SP_SRC);
    if (isv) mbar_expect_tx(B_ST, 7168);
    else { mbar_expect_tx(B_VM, 2048); mbar_expect_tx(B_VX, 8192); }
  }
  __syncthreads();
  cluster_sync();
  const int wg = __shfl_sync(0xffffffffu, threadIdx.x >> 7, 0);
  if (rank == 2) { if (wg == 0) f_main<true, 0>(P, h, 2); else f_main<true, 1>(P, h, 2); }
  else { if (wg == 0) f_main<false, 0>(P, h, rank); else f_main<false, 1>(P, h, rank); }
  PROF2(5);
  GTSYNC(1);
  KT_END(1);
  __syncwarp();
  cluster_sync();
}

#define GCL 2
namespace gk {
enum { T_B1 = 0, T_B2 = 1, T_B3 = 2, T_B4 = 3, T_O = 4, T_LN = 5, T_END = 7 };
constexpr int NST = 3, STAGE = 49152, MAXITEMS = 512, NEW = 3;
constexpr uint32_t OUTB = NST * STAGE, BARS = OUTB + 65536;
constexpr uint32_t B_FULL = BARS, B_EMPTY = BARS + 32, B_ITEM = BARS + 64, B_FILL = BARS + 128, B_FREE = BARS + 160, ITEMS = BARS + 192;
constexpr int SMEM = BARS + 256;
}
struct GParams {
  CUtensorMap a[5], b[5];
  bf16* c[5];
  const bf16* r[5];
  bf16* x1n;
  int nitems, lnpos;
  uint16_t items[gk::MAXITEMS];
};
__device__ unsigned g_cnt[6][16];
__device__ unsigned g_next;
#define ILOG(i)

__device__ __forceinline__ void tma_load_3d_mc(uint32_t dst, const CUtensorMap* map, int x, int y, int z, uint32_t bar) {
  asm volatile("cp.async.bulk.tensor.3d.shared::cluster.global.mbarrier::complete_tx::bytes.multicast::cluster "
               "[%0], [%1, {%3, %4, %5}], [%2], %6;"
               ::"r"(dst), "l"(map), "r"(bar), "r"(x), "r"(y), "r"(z), "h"((uint16_t)3) : "memory");
}
__device__ __forceinline__ void wait_count(const unsigned* p, unsigned need) {
#pragma unroll 1
  for (int tries = 0; tries < (1 << 16); tries++) {
    unsigned v;
    asm volatile("ld.acquire.gpu.global.u32 %0, [%1];" : "=r"(v) : "l"(p) : "memory");
    if (v >= need) break;
    __nanosleep(200);
  }
}
__device__ __forceinline__ float tanh_approx(float x) { float y; asm("tanh.approx.f32 %0, %1;" : "=f"(y) : "f"(x)); return y; }
__device__ __forceinline__ uint32_t sub_bf16x2(uint32_t a, uint32_t b) {
  uint32_t d;
  asm("sub.rn.bf16x2 %0, %1, %2;" : "=r"(d) : "r"(a), "r"(b));
  return d;
}
__device__ __forceinline__ uint32_t add_bf16x2(uint32_t a, uint32_t b) {
  uint32_t d;
  asm("add.rn.bf16x2 %0, %1, %2;" : "=r"(d) : "r"(a), "r"(b));
  return d;
}
__device__ __forceinline__ uint32_t mul_bf16x2(uint32_t a, uint32_t b) {
  uint32_t d;
  asm("mul.rn.bf16x2 %0, %1, %2;" : "=r"(d) : "r"(a), "r"(b));
  return d;
}

template <int NR>
__device__ __forceinline__ void ln_regs(uint32_t (&raw)[NR][16]) {
  float m[NR], q[NR];
#pragma unroll
  for (int r = 0; r < NR; r++) {
    float s0 = 0.f, s1 = 0.f;
#pragma unroll
    for (int i = 0; i < 16; i++) { s0 += bf_lo(raw[r][i]); s1 += bf_hi(raw[r][i]); }
    m[r] = s0 + s1;
  }
#pragma unroll
  for (int o = 16; o > 0; o >>= 1)
#pragma unroll
    for (int r = 0; r < NR; r++) m[r] += __shfl_xor_sync(0xffffffffu, m[r], o);
#pragma unroll
  for (int r = 0; r < NR; r++) {
    m[r] *= 1.0f / 1024.0f;
    float s0 = 0.f, s1 = 0.f;
#pragma unroll
    for (int i = 0; i < 16; i++) {
      const float d0 = bf_lo(raw[r][i]) - m[r], d1 = bf_hi(raw[r][i]) - m[r];
      s0 = fmaf(d0, d0, s0); s1 = fmaf(d1, d1, s1);
    }
    q[r] = s0 + s1;
  }
#pragma unroll
  for (int o = 16; o > 0; o >>= 1)
#pragma unroll
    for (int r = 0; r < NR; r++) q[r] += __shfl_xor_sync(0xffffffffu, q[r], o);
#pragma unroll
  for (int r = 0; r < NR; r++) {
    const uint32_t mb = pack_bf16(m[r], m[r]);
    const float sd = rbf(sqrtf(rbf(rbf(q[r] * (1.0f / 1024.0f)) + 1e-5f)));
    const float inv = __fdiv_rn(1.0f, sd);
#pragma unroll
    for (int i = 0; i < 16; i++) {
      const uint32_t d = sub_bf16x2(raw[r][i], mb);
      raw[r][i] = pack_bf16(bf_lo(d) * inv, bf_hi(d) * inv);
    }
  }
}
template <int NR>
__device__ __forceinline__ void load_rows(uint32_t (&raw)[NR][16], const bf16* src, int lane) {
#pragma unroll
  for (int r = 0; r < NR; r++)
#pragma unroll
    for (int j = 0; j < 4; j++) {
      const uint4 u = __ldcg(reinterpret_cast<const uint4*>(src + r * cfg::D + j * 256 + lane * 8));
      raw[r][4 * j] = u.x; raw[r][4 * j + 1] = u.y; raw[r][4 * j + 2] = u.z; raw[r][4 * j + 3] = u.w;
    }
}
template <int NR>
__device__ __forceinline__ void store_rows(const uint32_t (&raw)[NR][16], bf16* dst, int lane) {
#pragma unroll
  for (int r = 0; r < NR; r++)
#pragma unroll
    for (int j = 0; j < 4; j++)
      *reinterpret_cast<uint4*>(dst + r * cfg::D + j * 256 + lane * 8) = make_uint4(raw[r][4 * j], raw[r][4 * j + 1], raw[r][4 * j + 2], raw[r][4 * j + 3]);
}

__global__ void __launch_bounds__(384, 1) g_kernel(const __grid_constant__ GParams P) {
  using namespace gk;
  extern __shared__ __align__(1024) uint8_t smem_g[];
  const uint32_t base = smem_u32(smem_g);
  const int tid = threadIdx.x, warp = __shfl_sync(0xffffffffu, tid >> 5, 0), lane = tid & 31;
  const int rank = blockIdx.x % GCL;
  KT_START(2);
  if (tid == 0) {
    for (int s = 0; s < NST; s++) { mbar_init(base + B_FULL + 8 * s, 1); mbar_init(base + B_EMPTY + 8 * s, 8 * GCL); }
    for (int s = 0; s < 8; s++) mbar_init(base + B_ITEM + 8 * s, 1);
    for (int s = 0; s < 2; s++) { mbar_init(base + B_FILL + 8 * s, 4); mbar_init(base + B_FREE + 8 * s, NEW); }
    fence_barrier_init();
  }
  __syncthreads();
  if (GCL > 1) cluster_sync();
  auto release = [&](uint32_t st) {
    if (GCL > 1) { if (lane < GCL) mbar_arrive_cluster(base + B_EMPTY + 8 * st, lane); }
    else if (lane == 0) mbar_arrive(base + B_EMPTY + 8 * st);
  };
  auto get_item = [&](int q) {
    mbar_wait(base + B_ITEM + 8 * (q & 7), (q >> 3) & 1);
    return lds32(base + ITEMS + 4 * (q & 7));
  };

  if (warp >= 8) {
   if (warp == 8) {
    if (lane == 0) {
      uint32_t st = 0, ph = 1;
#pragma unroll 1
      for (int q = 0;; q++) {
        if (GCL > 1) mbar_expect_tx(base + B_ITEM + 8 * (q & 7), 4);
        if (rank == 0) {
          const unsigned idx = atomicAdd(&g_next, 1), ln = idx - P.lnpos;
          const uint32_t v = (idx < (unsigned)P.nitems ? P.items[idx] : T_END) | (ln < 64 / GCL ? (ln + 1) << 16 : 0);
          if (GCL > 1) {
#pragma unroll
            for (int r = 0; r < GCL; r++) st_async32(mapa(base + ITEMS + 4 * (q & 7), r), v, mapa(base + B_ITEM + 8 * (q & 7), r));
          } else {
            sts32(base + ITEMS + 4 * (q & 7), v);
            mbar_arrive(base + B_ITEM + 8 * (q & 7));
          }
        }
        const uint32_t item = get_item(q);
        const int type = item & 7, mb = ((item >> 3) & 15) + rank, nt = (item >> 7) & 15;
        ILOG(1);
        if (type == T_END) break;
        if (type == T_B2) {
          wait_count(&g_cnt[T_B1][max(mb - 1, 0)], 4 * NEW); wait_count(&g_cnt[T_B1][mb], 4 * NEW); wait_count(&g_cnt[T_B1][min(mb + 1, 15)], 4 * NEW);
        } else if (type == T_B3) wait_count(&g_cnt[T_LN][mb], 32);
        else if (type == T_B4) wait_count(&g_cnt[T_B3][mb], 14 * NEW);
        else if (type == T_O) wait_count(&g_oflag[mb], 32);
        asm volatile("fence.proxy.async.global;" ::: "memory");
        ILOG(2);
        const CUtensorMap *ma = &P.a[type], *mbm = &P.b[type];
        const int nkb = type == T_B4 ? cfg::F / 64 : type == T_O ? cfg::HD / 64 : cfg::D / 64;
#pragma unroll 1
        for (int kb = 0; kb < nkb; kb++) {
          mbar_wait(base + B_EMPTY + 8 * st, ph);
          const uint32_t sa = base + st * STAGE, full = base + B_FULL + 8 * st;
          mbar_expect_tx(full, STAGE);
          int arow = mb * 128;
          if (type == T_B2) { const int qd = kb >> 2; arow += (qd == 0) ? -1 : (qd == 1) ? 1 : (qd == 2) ? -2 : 2; }
          if (GCL > 1) tma_load_3d_mc(sa + 16384 + rank * 16384, mbm, 0, kb * 64, nt * 4 + rank * 2, full);
          else tma_load_3d(sa + 16384, mbm, 0, kb * 64, nt * 4, full);
          tma_load_2d(sa, ma, kb * 64, arow, full);
          if (++st == NST) { st = 0; ph ^= 1; }
        }
      }
    }
   } else {
    const int ew = warp - 9;
#pragma unroll 1
    for (int q = 0;; q++) {
      const uint32_t item = get_item(q);
      const int type = item & 7, mb = ((item >> 3) & 15) + rank, nt = (item >> 7) & 15;
      if (type == T_END) break;
      if (type == T_O) wait_count(&g_cnt[T_B4][mb], 4 * NEW);
      const int ldc = type == T_B3 ? cfg::F : cfg::D;
      bf16* cp = P.c[type] + (size_t)mb * 128 * ldc + nt * 256 + lane * 8;
      const size_t roff = (size_t)mb * 128 * cfg::D + nt * 256 + lane * 8;
      const bf16 *rp = P.r[type] + roff, *gp = P.c[T_B4] + roff;
      const bool res = type == T_B2 || type >= T_B4, act = type != T_B2 && type != T_O;
      const float c1 = type == T_B4 ? 0.f : 0.035677408136300125f, c0 = type == T_B4 ? 0.5f : 0.7978845608028654f;
      uint32_t yn[4][4];
      uint4 rn[4], gn[4];
      auto fetch_res = [&](int grp) {
#pragma unroll
        for (int i = 0; i < 4; i++) {
          if (res) rn[i] = __ldcg(reinterpret_cast<const uint4*>(rp + (grp * 4 + i) * cfg::D));
          if (type == T_O) gn[i] = __ldcg(reinterpret_cast<const uint4*>(gp + (grp * 4 + i) * cfg::D));
        }
      };
      auto fetch_y = [&](int grp) {
#pragma unroll
        for (int i = 0; i < 4; i++) lds128(yn[i], base + OUTB + (grp * 4 + i) * 512 + ((lane ^ ((grp * 4 + i) & 7)) << 4));
      };
      if (type == T_B4) wait_count(&g_cnt[T_B2][mb], 4 * NEW);
      fetch_res(ew);
      mbar_wait(base + B_FILL, q & 1);
      fetch_y(ew);
#pragma unroll 1
      for (int grp = ew; grp < 32; grp += NEW) {
        uint32_t y[4][4];
#pragma unroll
        for (int i = 0; i < 4; i++) {
#pragma unroll
          for (int k = 0; k < 4; k++) y[i][k] = yn[i][k];
          if (type == T_O) {
            y[i][0] = mul_bf16x2(y[i][0], gn[i].x); y[i][1] = mul_bf16x2(y[i][1], gn[i].y);
            y[i][2] = mul_bf16x2(y[i][2], gn[i].z); y[i][3] = mul_bf16x2(y[i][3], gn[i].w);
          }
          if (res) {
            y[i][0] = add_bf16x2(y[i][0], rn[i].x); y[i][1] = add_bf16x2(y[i][1], rn[i].y);
            y[i][2] = add_bf16x2(y[i][2], rn[i].z); y[i][3] = add_bf16x2(y[i][3], rn[i].w);
          }
        }
        const int nx = grp + NEW;
        if (nx < 32) {
          fetch_res(nx);
          if (nx >= 16 && grp < 16) {
            __syncwarp();
            if (lane == 0) mbar_arrive(base + B_FREE);
            mbar_wait(base + B_FILL + 8, q & 1);
          }
          fetch_y(nx);
        }
        if (act) {
#pragma unroll
          for (int i = 0; i < 4; i++)
#pragma unroll
            for (int k = 0; k < 4; k++) {
              const float v0 = bf_lo(y[i][k]), v1 = bf_hi(y[i][k]);
              const float t0 = tanh_approx(v0 * fmaf(v0 * c1, v0, c0)), t1 = tanh_approx(v1 * fmaf(v1 * c1, v1, c0));
              const float h0 = 0.5f * v0, h1 = 0.5f * v1;
              y[i][k] = pack_bf16(fmaf(h0, t0, h0), fmaf(h1, t1, h1));
            }
        }
#pragma unroll
        for (int i = 0; i < 4; i++)
          *reinterpret_cast<uint4*>(cp + (size_t)(grp * 4 + i) * ldc) = make_uint4(y[i][0], y[i][1], y[i][2], y[i][3]);
      }
      __syncwarp();
      if (lane == 0) mbar_arrive(base + B_FREE + 8);
      if (type != T_O) {
        __threadfence();
        __syncwarp();
        if (lane == 0) atomicAdd(&g_cnt[type][mb], 1);
      }
      if (tid == 288) ILOG(7);
    }
   }
   __syncwarp();
   pdl_wait();
   if (GCL > 1) cluster_sync();
  } else {
    const int wg = warp >> 2;
    const uint32_t outa = base + OUTB + (warp * 16 + ((lane >> 3) & 1) * 8 + (lane & 7)) * 512 + (((lane >> 4) ^ (lane & 7)) << 4);
    uint32_t st = 0, ph = 0;
    float acc[128];
#pragma unroll 1
    for (int q = 0;; q++) {
      const uint32_t item = get_item(q);
      const int type = item & 7;
      if (type == T_END) break;
      if (item >> 16) {
        const int ln = (item >> 16) - 1, lb = (ln >> 2) * GCL + rank;
        const size_t row = (size_t)(lb * 128 + (ln & 3) * 32 + warp * 4) * cfg::D;
        wait_count(&g_cnt[T_B2][lb], 4 * NEW);
        uint32_t raw[4][16];
        load_rows<4>(raw, P.c[T_B2] + row, lane);
        ln_regs<4>(raw);
        store_rows<4>(raw, P.x1n + row, lane);
        __threadfence();
        __syncwarp();
        if (lane == 0) atomicAdd(&g_cnt[T_LN][lb], 1);
        if (tid == 0) ILOG(6);
#pragma unroll
        for (int i = 0; i < 128; i++) acc[i] = 0.f;
      }
      const int nkb = type == T_B4 ? cfg::F / 64 : type == T_O ? cfg::HD / 64 : cfg::D / 64;
      uint32_t prev = 0;
#pragma unroll 1
      for (int kb = 0; kb < nkb; kb++) {
        if (kb == 0) mbar_wait(base + B_FULL + 8 * st, ph); else mbar_spin(base + B_FULL + 8 * st, ph);
        if (kb == 0 && tid == 0) ILOG(3);
        const uint32_t sa = base + st * STAGE + wg * 8192, sb = base + st * STAGE + 16384;
        wg_fence();
#pragma unroll
        for (int k = 0; k < 4; k++) {
          wgmma_ss_n256_tb(acc, make_desc(sa + k * 32, 16, 1024), make_desc(sb + k * 2048, 8192, 1024), (kb | k) != 0);
          if (k == 0) {
            wg_commit();
            wg_wait<1>();
            if (kb > 0) release(prev);
            wg_fence();
          }
        }
        wg_commit();
        prev = st;
        if (++st == NST) { st = 0; ph ^= 1; }
      }
      if (q > 0) mbar_wait(base + B_FREE + 8 * wg, (q - 1) & 1);
      wg_wait<0>();
      if (tid == 0) ILOG(4);
      release(prev);
#pragma unroll
      for (int j = 0; j < 16; j++)
        stsm4((outa ^ ((j & 3) << 5)) + (j >> 2) * 128, pack_bf16(acc[8 * j], acc[8 * j + 1]), pack_bf16(acc[8 * j + 2], acc[8 * j + 3]),
              pack_bf16(acc[8 * j + 4], acc[8 * j + 5]), pack_bf16(acc[8 * j + 6], acc[8 * j + 7]));
      __syncwarp();
      if (lane == 0) mbar_arrive(base + B_FILL + 8 * wg);
      if (tid == 0) ILOG(5);
    }
    KT_END(2);
    if (GCL > 1) cluster_sync();
  }
}

__global__ void __launch_bounds__(288, 1)
tail_kernel(const __grid_constant__ CUtensorMap tmO, const __grid_constant__ CUtensorMap tmWo, const __grid_constant__ CUtensorMap tmOut,
            const __grid_constant__ CUtensorMap tmX, const __grid_constant__ CUtensorMap tmG, int mt0) {
  const int pair = blockIdx.x >> 1;
  gemm_body<128, 4, EPI_FINAL, false, false, 0>(&tmO, &tmWo, &tmOut, &tmOut, &tmX, &tmG, cfg::HD, mt0 + (pair >> 3) * 2 + (blockIdx.x & 1),
                                                pair & 7, nullptr);
}

__device__ void reset_exchange(int gtid, int nthreads) {
  if (gtid < 16) g_oflag[gtid] = 0;
  if (gtid < 96) (&g_cnt[0][0])[gtid] = 0;
  if (gtid == 0) g_next = 0;
}

__device__ bf16 g_xn[cfg::S * cfg::D];
__device__ bf16 g_xn2[cfg::S * cfg::D];
__device__ bf16 g_h[cfg::S * cfg::D];
__device__ bf16 g_x1[cfg::S * cfg::D];
__device__ bf16 g_x1n[cfg::S * cfg::D];
__device__ bf16 g_u[cfg::S * cfg::F];
__device__ bf16 g_g[cfg::S * cfg::D];
__device__ bf16 g_o[cfg::S * cfg::HD];

typedef CUresult (*PFN_encodeTiled)(CUtensorMap*, CUtensorMapDataType, cuuint32_t, void*, const cuuint64_t*,
                                    const cuuint64_t*, const cuuint32_t*, const cuuint32_t*, CUtensorMapInterleave,
                                    CUtensorMapSwizzle, CUtensorMapL2promotion, CUtensorMapFloatOOBfill);

static PFN_encodeTiled get_encoder() {
  static PFN_encodeTiled fn = nullptr;
  if (!fn) {
    void* p = nullptr;
    cudaDriverEntryPointQueryResult st;
    cudaGetDriverEntryPoint("cuTensorMapEncodeTiled", &p, cudaEnableDefault, &st);
    fn = (PFN_encodeTiled)p;
  }
  return fn;
}
static CUtensorMap make_map(const void* ptr, int rows, int cols, int box_rows, int box_cols, int swizzle_bytes) {
  CUtensorMap m;
  cuuint64_t dims[2] = {(cuuint64_t)cols, (cuuint64_t)rows};
  cuuint64_t strides[1] = {(cuuint64_t)cols * 2};
  cuuint32_t box[2] = {(cuuint32_t)box_cols, (cuuint32_t)box_rows};
  cuuint32_t estr[2] = {1, 1};
  CUtensorMapSwizzle sw = swizzle_bytes == 128 ? CU_TENSOR_MAP_SWIZZLE_128B
                        : swizzle_bytes == 64 ? CU_TENSOR_MAP_SWIZZLE_64B
                        : swizzle_bytes == 32 ? CU_TENSOR_MAP_SWIZZLE_32B : CU_TENSOR_MAP_SWIZZLE_NONE;
  get_encoder()(&m, CU_TENSOR_MAP_DATA_TYPE_BFLOAT16, 2, const_cast<void*>(ptr), dims, strides, box, estr,
                CU_TENSOR_MAP_INTERLEAVE_NONE, sw, CU_TENSOR_MAP_L2_PROMOTION_L2_128B, CU_TENSOR_MAP_FLOAT_OOB_FILL_NONE);
  return m;
}
static CUtensorMap make_map3(const void* ptr, int rows, int cols, int box_rows, int nblk) {
  CUtensorMap m;
  cuuint64_t dims[3] = {64, (cuuint64_t)rows, (cuuint64_t)(cols / 64)};
  cuuint64_t strides[2] = {(cuuint64_t)cols * 2, 128};
  cuuint32_t box[3] = {64, (cuuint32_t)box_rows, (cuuint32_t)nblk};
  cuuint32_t estr[3] = {1, 1, 1};
  get_encoder()(&m, CU_TENSOR_MAP_DATA_TYPE_BFLOAT16, 3, const_cast<void*>(ptr), dims, strides, box, estr,
                CU_TENSOR_MAP_INTERLEAVE_NONE, CU_TENSOR_MAP_SWIZZLE_128B, CU_TENSOR_MAP_L2_PROMOTION_L2_128B,
                CU_TENSOR_MAP_FLOAT_OOB_FILL_NONE);
  return m;
}
template <class T> static T* sym(T& s) { void* p = nullptr; cudaGetSymbolAddress(&p, s); return (T*)p; }
#define SYM(name) ((bf16*)[] { void* p = nullptr; cudaGetSymbolAddress(&p, name); return p; }())

template <class... KArgs, class... Args>
static void launch_pdl(void (*kern)(KArgs...), dim3 grid, dim3 block, int smem, cudaStream_t st, Args... args) {
  cudaLaunchConfig_t cfg = {};
  cfg.gridDim = grid; cfg.blockDim = block; cfg.dynamicSmemBytes = smem; cfg.stream = st;
  cudaLaunchAttribute at[1];
  at[0].id = cudaLaunchAttributeProgrammaticStreamSerialization;
  at[0].val.programmaticStreamSerializationAllowed = 1;
  cfg.attrs = at; cfg.numAttrs = 1;
  cudaLaunchKernelEx(&cfg, kern, KArgs(args)...);
}

#define G_CTAS 36
#define LN_POS 60
#define O_PAIRS 4
static int build_items(uint16_t* it) {
  using namespace gk;
  int n = 0;
  auto add = [&](int type, int nrows, int ncols) {
    for (int mb = 0; mb < nrows; mb += GCL) for (int nt = 0; nt < ncols; nt++) it[n++] = (uint16_t)(type | mb << 3 | nt << 7);
  };
  add(T_B1, 16, 4); add(T_B2, 16, 4); add(T_B3, 16, 14); add(T_B4, 16, 4); add(T_O, 2 * O_PAIRS, 4);
  return n;
}

extern "C" void kernel_launch(void* const* d_in, const int* in_sizes, int n_in, void* d_out, int out_size) {
  using namespace cfg;
  const bf16* x = (const bf16*)d_in[0];
  const bf16* mem0 = (const bf16*)d_in[1];
  const bf16* Wq = (const bf16*)d_in[2];
  const bf16* Wk = (const bf16*)d_in[3];
  const bf16* Wv = (const bf16*)d_in[4];
  const bf16* Wo = (const bf16*)d_in[5];
  const bf16* w1 = (const bf16*)d_in[8];
  const bf16* w2 = (const bf16*)d_in[9];
  const bf16* w3 = (const bf16*)d_in[10];
  const bf16* w4 = (const bf16*)d_in[11];
  bf16* out = (bf16*)d_out;
  cudaStream_t st = cudaStreamPerThread;

  bf16 *xn = SYM(g_xn), *xn2 = SYM(g_xn2), *hb = SYM(g_h), *x1 = SYM(g_x1), *x1n = SYM(g_x1n), *u = SYM(g_u),
       *g = SYM(g_g), *o = SYM(g_o);

  launch_pdl(ln_kernel<true>, dim3(S / 8), dim3(256), 0, st, x, xn, xn2);
  {
    cudaFuncSetAttribute(f_kernel, cudaFuncAttributeMaxDynamicSharedMemorySize, fk::SMEM);
    FParams P;
    P.wq = make_map(Wq, D, HD, 64, 64, 128); P.wk = make_map(Wk, D, HD, 64, 64, 128); P.wv = make_map(Wv, D, HD, 64, 64, 128);
    P.wo = make_map(Wo, HD, D, 128, 16, 32); P.xn = make_map3(xn, S, D, 32, 4); P.xn12 = make_map3(xn, S, D, 32, 12); P.o = make_map3(o, S, HD, 32, 2);
    P.mem0 = mem0;
    P.one = 1;
    P.xch = (char*)(((uintptr_t)SYM(g_xch) + 8191) & ~(uintptr_t)8191);
    cudaLaunchConfig_t cfg = {};
    cfg.gridDim = dim3(96); cfg.blockDim = dim3(256); cfg.dynamicSmemBytes = fk::SMEM; cfg.stream = st;
    cudaLaunchAttribute at[2];
    at[0].id = cudaLaunchAttributeClusterDimension;
    at[0].val.clusterDim.x = 3; at[0].val.clusterDim.y = 1; at[0].val.clusterDim.z = 1;
    at[1].id = cudaLaunchAttributeProgrammaticStreamSerialization;
    at[1].val.programmaticStreamSerializationAllowed = 1;
    cfg.attrs = at; cfg.numAttrs = 2;
    cudaLaunchKernelEx(&cfg, f_kernel, P);
  }
  {
    cudaFuncSetAttribute(g_kernel, cudaFuncAttributeMaxDynamicSharedMemorySize, gk::SMEM);
    GParams G;
    const bf16* as[5] = {xn2, hb, x1n, u, o};
    const bf16* bs[5] = {w1, w2, w3, w4, Wo};
    bf16* cs[5] = {hb, x1, u, g, out};
    const bf16* rs[5] = {xn, xn, xn, x1, x};
    const int ks[5] = {D, D, D, F, HD}, ns[5] = {D, D, F, D, D};
    for (int i = 0; i < 5; i++) {
      G.a[i] = make_map(as[i], S, ks[i], 128, 64, 128);
      G.b[i] = make_map3(bs[i], ks[i], ns[i], 64, 4 / GCL);
      G.c[i] = cs[i];
      G.r[i] = rs[i];
    }
    G.x1n = x1n;
    G.nitems = build_items(G.items);
    G.lnpos = LN_POS * 2 / GCL;
    cudaLaunchConfig_t cfg = {};
    cfg.gridDim = dim3(G_CTAS); cfg.blockDim = dim3(384); cfg.dynamicSmemBytes = gk::SMEM; cfg.stream = st;
    cudaLaunchAttribute at[2];
    at[0].id = cudaLaunchAttributeClusterDimension;
    at[0].val.clusterDim.x = GCL; at[0].val.clusterDim.y = 1; at[0].val.clusterDim.z = 1;
    at[1].id = cudaLaunchAttributeProgrammaticStreamSerialization;
    at[1].val.programmaticStreamSerializationAllowed = 1;
    cfg.attrs = at;
    cfg.numAttrs = 2;
    cudaLaunchKernelEx(&cfg, g_kernel, G);
  }
  if (O_PAIRS < 8) {
    using C = GemmCfg<128, 4, EPI_FINAL, false>;
    cudaFuncSetAttribute(tail_kernel, cudaFuncAttributeMaxDynamicSharedMemorySize, C::SMEM);
    cudaLaunchConfig_t cfg = {};
    cfg.gridDim = dim3((8 - O_PAIRS) * 16); cfg.blockDim = dim3(288); cfg.dynamicSmemBytes = C::SMEM; cfg.stream = st;
    cudaLaunchAttribute at[1];
    at[0].id = cudaLaunchAttributeClusterDimension;
    at[0].val.clusterDim.x = 2; at[0].val.clusterDim.y = 1; at[0].val.clusterDim.z = 1;
    cfg.attrs = at; cfg.numAttrs = 1;
    cudaLaunchKernelEx(&cfg, tail_kernel, make_map(o, S, HD, 128, 64, 128), make_map(Wo, HD, D, 64, 64, 128), make_map(out, S, D, 64, 64, 128),
                       make_map(x, S, D, 64, 64, 128), make_map(g, S, D, 64, 64, 128), O_PAIRS * 2);
  }
}
```

```cpp
#include <cuda_runtime.h>
#include <cuda_bf16.h>
#include <cuda.h>
#include <stdint.h>

typedef __nv_bfloat16 bf16;

namespace cfg {
constexpr int S = 2048;
constexpr int D = 1024;
constexpr int H = 32;
constexpr int DH = 128;
constexpr int HD = H * DH;
constexpr int M = 8;
constexpr int SEG = 32;
constexpr int NSEG = S / SEG;
constexpr int F = 3584;
}

__device__ __forceinline__ uint32_t smem_u32(const void* p) { return (uint32_t)__cvta_generic_to_shared(p); }

__device__ __forceinline__ void mbar_init(uint32_t bar, uint32_t count) {
  asm volatile("mbarrier.init.shared::cta.b64 [%0], %1;" ::"r"(bar), "r"(count) : "memory");
}
__device__ __forceinline__ void mbar_expect_tx(uint32_t bar, uint32_t bytes) {
  asm volatile("mbarrier.arrive.expect_tx.shared::cta.b64 _, [%0], %1;" ::"r"(bar), "r"(bytes) : "memory");
}
__device__ __forceinline__ void mbar_arrive(uint32_t bar) {
  asm volatile("mbarrier.arrive.shared::cta.b64 _, [%0];" ::"r"(bar) : "memory");
}
__device__ __forceinline__ bool mbar_try(uint32_t bar, uint32_t parity) {
  uint32_t done;
  asm volatile("{\n.reg .pred p;\nmbarrier.try_wait.parity.shared::cta.b64 p, [%1], %2, 20000;\nselp.u32 %0, 1, 0, p;\n}"
               : "=r"(done) : "r"(bar), "r"(parity) : "memory");
  return done != 0;
}
__device__ __forceinline__ bool mbar_try_nohint(uint32_t bar, uint32_t parity) {
  uint32_t done;
  asm volatile("{\n.reg .pred p;\nmbarrier.try_wait.parity.shared::cta.b64 p, [%1], %2;\nselp.u32 %0, 1, 0, p;\n}"
               : "=r"(done) : "r"(bar), "r"(parity) : "memory");
  return done != 0;
}
constexpr int MBAR_TRIES = 4096;
constexpr int POLL_TRIES = 1 << 16;
__device__ __forceinline__ void mbar_wait(uint32_t bar, uint32_t parity) {
#pragma unroll 1
  for (int n = 0; n < MBAR_TRIES; n++)
    if (mbar_try(bar, parity)) break;
}
__device__ __forceinline__ void mbar_wait_fast(uint32_t bar, uint32_t parity) {
#pragma unroll 1
  for (int n = 0; n < (POLL_TRIES << 4); n++)
    if (mbar_try_nohint(bar, parity)) break;
}
__device__ __forceinline__ void fence_barrier_init() { asm volatile("fence.mbarrier_init.release.cluster;" ::: "memory"); }
__device__ __forceinline__ void fence_proxy_async_smem() { asm volatile("fence.proxy.async.shared::cta;" ::: "memory"); }

__device__ __forceinline__ void tma_load_2d(uint32_t dst, const CUtensorMap* map, int x, int y, uint32_t bar) {
  asm volatile("cp.async.bulk.tensor.2d.shared::cluster.global.mbarrier::complete_tx::bytes [%0], [%1, {%3, %4}], [%2];"
               ::"r"(dst), "l"(map), "r"(bar), "r"(x), "r"(y) : "memory");
}
__device__ __forceinline__ void tma_load_3d(uint32_t dst, const CUtensorMap* map, int x, int y, int z, uint32_t bar) {
  asm volatile("cp.async.bulk.tensor.3d.shared::cluster.global.mbarrier::complete_tx::bytes [%0], [%1, {%3, %4, %5}], [%2];"
               ::"r"(dst), "l"(map), "r"(bar), "r"(x), "r"(y), "r"(z) : "memory");
}
__device__ __forceinline__ void tma_store_2d(const CUtensorMap* map, uint32_t src, int x, int y) {
  asm volatile("cp.async.bulk.tensor.2d.global.shared::cta.bulk_group [%0, {%2, %3}], [%1];"
               ::"l"(map), "r"(src), "r"(x), "r"(y) : "memory");
}
__device__ __forceinline__ void tma_store_commit() { asm volatile("cp.async.bulk.commit_group;" ::: "memory"); }
__device__ __forceinline__ void tma_store_wait_all() { asm volatile("cp.async.bulk.wait_group 0;" ::: "memory"); }
__device__ __forceinline__ void tma_store_wait_read() { asm volatile("cp.async.bulk.wait_group.read 0;" ::: "memory"); }
__device__ __forceinline__ void prefetch_tmap(const CUtensorMap* map) {
  asm volatile("prefetch.tensormap [%0];" ::"l"(map) : "memory");
}

__device__ __forceinline__ void wg_fence() { asm volatile("wgmma.fence.sync.aligned;" ::: "memory"); }
__device__ __forceinline__ void wg_commit() { asm volatile("wgmma.commit_group.sync.aligned;" ::: "memory"); }
template <int N> __device__ __forceinline__ void wg_wait() { asm volatile("wgmma.wait_group.sync.aligned %0;" ::"n"(N) : "memory"); }

#define named_bar_sync(id, n) asm volatile("bar.sync %0, %1;" ::"n"(id), "n"(n) : "memory")
#define named_bar_arrive(id, n) asm volatile("bar.arrive %0, %1;" ::"n"(id), "n"(n) : "memory")

__device__ __forceinline__ uint64_t make_desc(uint32_t addr, uint32_t lbo, uint32_t sbo) {
  return (uint64_t)((addr & 0x3FFFF) >> 4) | ((uint64_t)(lbo >> 4) << 16) | ((uint64_t)(sbo >> 4) << 32) | (1ull << 62);
}

__device__ __forceinline__ uint32_t pack_bf16(float lo, float hi) {
  uint32_t r;
  asm("cvt.rn.bf16x2.f32 %0, %1, %2;" : "=r"(r) : "f"(hi), "f"(lo));
  return r;
}
__device__ __forceinline__ float bf_lo(uint32_t v) { return __uint_as_float(v << 16); }
__device__ __forceinline__ float bf_hi(uint32_t v) { return __uint_as_float(v & 0xFFFF0000u); }
__device__ __forceinline__ float rbf(float v) { return __bfloat162float(__float2bfloat16_rn(v)); }

__device__ __forceinline__ void pdl_launch_dependents() { asm volatile("griddepcontrol.launch_dependents;" ::: "memory"); }
__device__ __forceinline__ void pdl_wait() { asm volatile("griddepcontrol.wait;" ::: "memory"); }

__device__ __forceinline__ float ex2_approx(float x) { float y; asm("ex2.approx.ftz.f32 %0, %1;" : "=f"(y) : "f"(x)); return y; }
__device__ __forceinline__ float rcp_approx(float x) { float y; asm("rcp.approx.ftz.f32 %0, %1;" : "=f"(y) : "f"(x)); return y; }

__device__ __forceinline__ void mul_sigmoid4(float (&v)[4], const float (&t)[4]) {
#pragma unroll
  for (int i = 0; i < 4; i += 2) {
    const float a = 1.0f + ex2_approx(fminf(t[i], 60.0f)), b = 1.0f + ex2_approx(fminf(t[i + 1], 60.0f));
    const float r = rcp_approx(a * b);
    v[i] *= b * r;
    v[i + 1] *= a * r;
  }
}
__device__ __forceinline__ void gelu4(float (&v)[4]) {
  float t[4];
#pragma unroll
  for (int i = 0; i < 4; i++) t[i] = v[i] * fmaf(v[i] * v[i], -0.10294324f, -2.30220819f);
  mul_sigmoid4(v, t);
}
__device__ __forceinline__ void silu4(float (&v)[4]) {
  float t[4];
#pragma unroll
  for (int i = 0; i < 4; i++) t[i] = v[i] * -1.4426950408889634f;
  mul_sigmoid4(v, t);
}

#define KT_START(id)
#define KT_END(id)

__device__ __forceinline__ void wgmma_ss_n256_tb(float (&d)[128], uint64_t da, uint64_t db, int scale_d) {
  asm volatile("{\n.reg .pred p;\nsetp.ne.b32 p, %130, 0;\n"
    "wgmma.mma_async.sync.aligned.m64n256k16.f32.bf16.bf16 "
    "{%0, %1, %2, %3, %4, %5, %6, %7, %8, %9, %10, %11, %12, %13, %14, %15, "
    "%16, %17, %18, %19, %20, %21, %22, %23, %24, %25, %26, %27, %28, %29, %30, %31, "
    "%32, %33, %34, %35, %36, %37, %38, %39, %40, %41, %42, %43, %44, %45, %46, %47, "
    "%48, %49, %50, %51, %52, %53, %54, %55, %56, %57, %58, %59, %60, %61, %62, %63, "
    "%64, %65, %66, %67, %68, %69, %70, %71, %72, %73, %74, %75, %76, %77, %78, %79, "
    "%80, %81, %82, %83, %84, %85, %86, %87, %88, %89, %90, %91, %92, %93, %94, %95, "
    "%96, %97, %98, %99, %100, %101, %102, %103, %104, %105, %106, %107, %108, %109, %110, %111, "
    "%112, %113, %114, %115, %116, %117, %118, %119, %120, %121, %122, %123, %124, %125, %126, %127}, "
    "%128, %129, p, 1, 1, 0, 1;\n}\n"
    : "+f"(d[0]), "+f"(d[1]), "+f"(d[2]), "+f"(d[3]), "+f"(d[4]), "+f"(d[5]), "+f"(d[6]), "+f"(d[7]),
      "+f"(d[8]), "+f"(d[9]), "+f"(d[10]), "+f"(d[11]), "+f"(d[12]), "+f"(d[13]), "+f"(d[14]), "+f"(d[15]),
      "+f"(d[16]), "+f"(d[17]), "+f"(d[18]), "+f"(d[19]), "+f"(d[20]), "+f"(d[21]), "+f"(d[22]), "+f"(d[23]),
      "+f"(d[24]), "+f"(d[25]), "+f"(d[26]), "+f"(d[27]), "+f"(d[28]), "+f"(d[29]), "+f"(d[30]), "+f"(d[31]),
      "+f"(d[32]), "+f"(d[33]), "+f"(d[34]), "+f"(d[35]), "+f"(d[36]), "+f"(d[37]), "+f"(d[38]), "+f"(d[39]),
      "+f"(d[40]), "+f"(d[41]), "+f"(d[42]), "+f"(d[43]), "+f"(d[44]), "+f"(d[45]), "+f"(d[46]), "+f"(d[47]),
      "+f"(d[48]), "+f"(d[49]), "+f"(d[50]), "+f"(d[51]), "+f"(d[52]), "+f"(d[53]), "+f"(d[54]), "+f"(d[55]),
      "+f"(d[56]), "+f"(d[57]), "+f"(d[58]), "+f"(d[59]), "+f"(d[60]), "+f"(d[61]), "+f"(d[62]), "+f"(d[63]),
      "+f"(d[64]), "+f"(d[65]), "+f"(d[66]), "+f"(d[67]), "+f"(d[68]), "+f"(d[69]), "+f"(d[70]), "+f"(d[71]),
      "+f"(d[72]), "+f"(d[73]), "+f"(d[74]), "+f"(d[75]), "+f"(d[76]), "+f"(d[77]), "+f"(d[78]), "+f"(d[79]),
      "+f"(d[80]), "+f"(d[81]), "+f"(d[82]), "+f"(d[83]), "+f"(d[84]), "+f"(d[85]), "+f"(d[86]), "+f"(d[87]),
      "+f"(d[88]), "+f"(d[89]), "+f"(d[90]), "+f"(d[91]), "+f"(d[92]), "+f"(d[93]), "+f"(d[94]), "+f"(d[95]),
      "+f"(d[96]), "+f"(d[97]), "+f"(d[98]), "+f"(d[99]), "+f"(d[100]), "+f"(d[101]), "+f"(d[102]), "+f"(d[103]),
      "+f"(d[104]), "+f"(d[105]), "+f"(d[106]), "+f"(d[107]), "+f"(d[108]), "+f"(d[109]), "+f"(d[110]), "+f"(d[111]),
      "+f"(d[112]), "+f"(d[113]), "+f"(d[114]), "+f"(d[115]), "+f"(d[116]), "+f"(d[117]), "+f"(d[118]), "+f"(d[119]),
      "+f"(d[120]), "+f"(d[121]), "+f"(d[122]), "+f"(d[123]), "+f"(d[124]), "+f"(d[125]), "+f"(d[126]), "+f"(d[127])
    : "l"(da), "l"(db), "r"(scale_d));
}
__device__ __forceinline__ void wgmma_rs_n32(float (&d)[16], const uint32_t* a, uint64_t db, int scale_d) {
  asm volatile("{\n.reg .pred p;\nsetp.ne.b32 p, %21, 0;\n"
    "wgmma.mma_async.sync.aligned.m64n32k16.f32.bf16.bf16 "
    "{%0, %1, %2, %3, %4, %5, %6, %7, %8, %9, %10, %11, %12, %13, %14, %15}, "
    "{%16, %17, %18, %19}, %20, p, 1, 1, 0;\n}\n"
    : "+f"(d[0]), "+f"(d[1]), "+f"(d[2]), "+f"(d[3]), "+f"(d[4]), "+f"(d[5]), "+f"(d[6]), "+f"(d[7]),
      "+f"(d[8]), "+f"(d[9]), "+f"(d[10]), "+f"(d[11]), "+f"(d[12]), "+f"(d[13]), "+f"(d[14]), "+f"(d[15])
    : "r"(a[0]), "r"(a[1]), "r"(a[2]), "r"(a[3]), "l"(db), "r"(scale_d));
}
__device__ __forceinline__ void wgmma_ss_n32_ta(float (&d)[16], uint64_t da, uint64_t db, int scale_d) {
  asm volatile("{\n.reg .pred p;\nsetp.ne.b32 p, %18, 0;\n"
    "wgmma.mma_async.sync.aligned.m64n32k16.f32.bf16.bf16 "
    "{%0, %1, %2, %3, %4, %5, %6, %7, %8, %9, %10, %11, %12, %13, %14, %15}, "
    "%16, %17, p, 1, 1, 1, 0;\n}\n"
    : "+f"(d[0]), "+f"(d[1]), "+f"(d[2]), "+f"(d[3]), "+f"(d[4]), "+f"(d[5]), "+f"(d[6]), "+f"(d[7]),
      "+f"(d[8]), "+f"(d[9]), "+f"(d[10]), "+f"(d[11]), "+f"(d[12]), "+f"(d[13]), "+f"(d[14]), "+f"(d[15])
    : "l"(da), "l"(db), "r"(scale_d));
}

__device__ __forceinline__ void tma_load_2d_mc(uint32_t dst, const CUtensorMap* map, int x, int y, uint32_t bar, uint16_t mask) {
  asm volatile("cp.async.bulk.tensor.2d.shared::cluster.global.mbarrier::complete_tx::bytes.multicast::cluster "
               "[%0], [%1, {%3, %4}], [%2], %5;"
               ::"r"(dst), "l"(map), "r"(bar), "r"(x), "r"(y), "h"(mask) : "memory");
}
__device__ __forceinline__ void mbar_arrive_cluster(uint32_t bar, uint32_t cta) {
  asm volatile("{\n.reg .b32 r;\nmapa.shared::cluster.u32 r, %0, %1;\nmbarrier.arrive.shared::cluster.b64 _, [r];\n}"
               ::"r"(bar), "r"(cta) : "memory");
}
__device__ __forceinline__ void cluster_sync() {
  asm volatile("barrier.cluster.arrive.release.aligned;\nbarrier.cluster.wait.acquire.aligned;" ::: "memory");
}
__device__ __forceinline__ void wait_count(const unsigned* p, unsigned need) {
#pragma unroll 1
  for (int tries = 0; tries < (1 << 16); tries++) {
    unsigned v;
    asm volatile("ld.acquire.gpu.global.u32 %0, [%1];" : "=r"(v) : "l"(p) : "memory");
    if (v >= need) break;
    __nanosleep(200);
  }
}
__device__ __forceinline__ uint32_t sub_bf16x2(uint32_t a, uint32_t b) {
  uint32_t d;
  asm("sub.rn.bf16x2 %0, %1, %2;" : "=r"(d) : "r"(a), "r"(b));
  return d;
}
__device__ __forceinline__ uint32_t add_bf16x2(uint32_t a, uint32_t b) {
  uint32_t d;
  asm("add.rn.bf16x2 %0, %1, %2;" : "=r"(d) : "r"(a), "r"(b));
  return d;
}
__device__ __forceinline__ uint32_t mul_bf16x2(uint32_t a, uint32_t b) {
  uint32_t d;
  asm("mul.rn.bf16x2 %0, %1, %2;" : "=r"(d) : "r"(a), "r"(b));
  return d;
}

template <int NR>
__device__ __forceinline__ void ln_regs(uint32_t (&raw)[NR][16]) {
  float m[NR], q[NR];
#pragma unroll
  for (int r = 0; r < NR; r++) {
    float s0 = 0.f, s1 = 0.f;
#pragma unroll
    for (int i = 0; i < 16; i++) { s0 += bf_lo(raw[r][i]); s1 += bf_hi(raw[r][i]); }
    m[r] = s0 + s1;
  }
#pragma unroll
  for (int o = 16; o > 0; o >>= 1)
#pragma unroll
    for (int r = 0; r < NR; r++) m[r] += __shfl_xor_sync(0xffffffffu, m[r], o);
#pragma unroll
  for (int r = 0; r < NR; r++) {
    m[r] *= 1.0f / 1024.0f;
    float s0 = 0.f, s1 = 0.f;
#pragma unroll
    for (int i = 0; i < 16; i++) {
      const float d0 = bf_lo(raw[r][i]) - m[r], d1 = bf_hi(raw[r][i]) - m[r];
      s0 = fmaf(d0, d0, s0); s1 = fmaf(d1, d1, s1);
    }
    q[r] = s0 + s1;
  }
#pragma unroll
  for (int o = 16; o > 0; o >>= 1)
#pragma unroll
    for (int r = 0; r < NR; r++) q[r] += __shfl_xor_sync(0xffffffffu, q[r], o);
#pragma unroll
  for (int r = 0; r < NR; r++) {
    const uint32_t mb = pack_bf16(m[r], m[r]);
    float sq;
    asm("sqrt.approx.f32 %0, %1;" : "=f"(sq) : "f"(rbf(rbf(q[r] * (1.0f / 1024.0f)) + 1e-5f)));
    const float inv = rcp_approx(rbf(sq));
#pragma unroll
    for (int i = 0; i < 16; i++) {
      const uint32_t d = sub_bf16x2(raw[r][i], mb);
      raw[r][i] = pack_bf16(bf_lo(d) * inv, bf_hi(d) * inv);
    }
  }
}
__device__ __forceinline__ void load_row16(uint32_t (&raw)[16], const bf16* src, int lane) {
#pragma unroll
  for (int j = 0; j < 4; j++) {
    const uint4 u = __ldcg(reinterpret_cast<const uint4*>(src + j * 256 + lane * 8));
    raw[4 * j] = u.x; raw[4 * j + 1] = u.y; raw[4 * j + 2] = u.z; raw[4 * j + 3] = u.w;
  }
}
__device__ __forceinline__ void store_row16(const uint32_t (&raw)[16], bf16* dst, int lane) {
#pragma unroll
  for (int j = 0; j < 4; j++)
    *reinterpret_cast<uint4*>(dst + j * 256 + lane * 8) = make_uint4(raw[4 * j], raw[4 * j + 1], raw[4 * j + 2], raw[4 * j + 3]);
}

namespace fk {
constexpr uint32_t SM0 = 1024;
constexpr uint32_t WO = SM0, WS = WO + 90112, XN = WS + 65536, VX = XN + 49152, QK = VX + 8192, PT = QK + 8192,
                   SP = PT + 4096, VM = SP + 2560, OB = VM + 2048, BAR = OB + 2048;
constexpr uint32_t MEMB = XN + 16384, RED = XN + 32768, VX2 = WO + 81920;
constexpr int SMEM = 232448;
static_assert(BAR + 512 == SM0 + SMEM, "shared memory layout");
constexpr uint32_t B_XN = BAR, B_H2 = BAR + 480, B_PF = BAR + 16, B_WO = BAR + 24, B_SM = BAR + 32, B_VM = BAR + 40, B_VX = BAR + 48, B_ST = BAR + 56, B_PB = BAR + 64, B_W = BAR + 112,
                   MASKS = BAR + 128, PROBE = BAR + 384;
constexpr int NB_M0 = 1, NB_M1 = 2, NB_C = 3, NB_O = 4, NB_ST = 5, NB_DU = 6, NB_CF = 7, NB_W1 = 8, NB_XE = 9, NB_HD = 10, NB_PZ = 11, NB_O0 = 12;
#define D_H1 850
#define D_H2 1750
#define D_ST 100
#define SCQ 2
#define PRE_G 5
#define WO_AT 4
#define NS0 4
#define NTA0 2
#define NTA1 2
#define PF0A 3
#define PF0 10
#define PF1A 9
#define PF1 11
#define PAUSE 1
#define PROBE_N 4
#define SPACK 0
constexpr uint32_t SPW = SPACK ? 4 : 8, SP_SRC = 160 * SPW;
constexpr int H1_BYTES = 64 * 32768, H2_BYTES = 8 * 8192;
}

#define PROF(wg, i)
#define PROF2(i)
#define RETRY(i)
#define GTSYNC(i)
#define PRO(i)

__device__ uint4 g_xch[(fk::H1_BYTES + fk::H2_BYTES + 8192) / 16];
__device__ __align__(16) unsigned g_mask[128];
__device__ unsigned g_cnt[6][16];
__device__ unsigned g_next;
constexpr int TAIL_MB0 = 10, GATE_CNT = 12;
__device__ unsigned g_tflag[96], g_tfix[96];
__device__ uint4 g_tpart[96][3][4][256];
__device__ unsigned g_oflag[16];

#define LD_POLL "ld.global.L1::no_allocate"
__device__ __forceinline__ uint4 ld_poll16(const void* p) {
  uint4 v;
  asm volatile(LD_POLL ".v4.u32 {%0,%1,%2,%3}, [%4];" : "=r"(v.x), "=r"(v.y), "=r"(v.z), "=r"(v.w) : "l"(p) : "memory");
  return v;
}
__device__ __forceinline__ uint2 ld_poll8(const void* p) {
  uint2 v;
  asm volatile(LD_POLL ".v2.u32 {%0,%1}, [%2];" : "=r"(v.x), "=r"(v.y) : "l"(p) : "memory");
  return v;
}
__device__ __forceinline__ uint4 ld_strong16(const void* p) {
  uint4 v;
  asm volatile("ld.relaxed.gpu.global.v4.u32 {%0,%1,%2,%3}, [%4];" : "=r"(v.x), "=r"(v.y), "=r"(v.z), "=r"(v.w) : "l"(p) : "memory");
  return v;
}
__device__ __forceinline__ uint2 ld_strong8(const void* p) {
  uint2 v;
  asm volatile("ld.relaxed.gpu.global.v2.u32 {%0,%1}, [%2];" : "=r"(v.x), "=r"(v.y) : "l"(p) : "memory");
  return v;
}
__device__ __forceinline__ void st_pub32(void* p, uint32_t v) { asm volatile("st.relaxed.gpu.global.u32 [%0], %1;" ::"l"(p), "r"(v) : "memory"); }
__device__ __forceinline__ void st_pub16(void* p, uint32_t v) {
  asm volatile("st.relaxed.gpu.global.u16 [%0], %1;" ::"l"(p), "h"((uint16_t)v) : "memory");
}
__device__ __forceinline__ uint32_t ld_strong4(const void* p) {
  uint32_t v;
  asm volatile("ld.relaxed.gpu.global.u32 %0, [%1];" : "=r"(v) : "l"(p) : "memory");
  return v;
}
__device__ __forceinline__ void st_pub64(void* p, uint32_t a, uint32_t b) {
  asm volatile("st.relaxed.gpu.global.v2.u32 [%0], {%1,%2};" ::"l"(p), "r"(a), "r"(b) : "memory");
}
__device__ __forceinline__ void st_pub128(void* p, uint32_t a) {
  asm volatile("st.relaxed.gpu.global.v4.u32 [%0], {%1,%1,%1,%1};" ::"l"(p), "r"(a) : "memory");
}
constexpr uint32_t EMPTY = 0xFFFFFFFFu;
__device__ __forceinline__ uint32_t umax4(const uint4& v) { return max(max(v.x, v.y), max(v.z, v.w)); }
__device__ __forceinline__ void sts128(uint32_t a, uint32_t x, uint32_t y, uint32_t z, uint32_t w) {
  asm volatile("st.shared.v4.u32 [%0], {%1,%2,%3,%4};" ::"r"(a), "r"(x), "r"(y), "r"(z), "r"(w) : "memory");
}
__device__ __forceinline__ void sts64(uint32_t a, uint32_t x, uint32_t y) {
  asm volatile("st.shared.v2.u32 [%0], {%1,%2};" ::"r"(a), "r"(x), "r"(y) : "memory");
}
__device__ __forceinline__ void sts32(uint32_t a, uint32_t x) { asm volatile("st.shared.u32 [%0], %1;" ::"r"(a), "r"(x) : "memory"); }
__device__ __forceinline__ void sts128f(uint32_t a, float x, float y, float z, float w) {
  asm volatile("st.shared.v4.f32 [%0], {%1,%2,%3,%4};" ::"r"(a), "f"(x), "f"(y), "f"(z), "f"(w) : "memory");
}
__device__ __forceinline__ void sts64f(uint32_t a, float x, float y) {
  asm volatile("st.shared.v2.f32 [%0], {%1,%2};" ::"r"(a), "f"(x), "f"(y) : "memory");
}
__device__ __forceinline__ float4 lds128f(uint32_t a) {
  float4 v;
  asm volatile("ld.shared.v4.f32 {%0,%1,%2,%3}, [%4];" : "=f"(v.x), "=f"(v.y), "=f"(v.z), "=f"(v.w) : "r"(a) : "memory");
  return v;
}
__device__ __forceinline__ float2 lds64f(uint32_t a) {
  float2 v;
  asm volatile("ld.shared.v2.f32 {%0,%1}, [%2];" : "=f"(v.x), "=f"(v.y) : "r"(a) : "memory");
  return v;
}
__device__ __forceinline__ void lds128(uint32_t* r, uint32_t a) {
  asm volatile("ld.shared.v4.u32 {%0,%1,%2,%3}, [%4];" : "=r"(r[0]), "=r"(r[1]), "=r"(r[2]), "=r"(r[3]) : "r"(a) : "memory");
}
__device__ __forceinline__ void lds64(uint32_t* r, uint32_t a) {
  asm volatile("ld.shared.v2.u32 {%0,%1}, [%2];" : "=r"(r[0]), "=r"(r[1]) : "r"(a) : "memory");
}
__device__ __forceinline__ uint32_t lds32(uint32_t a) {
  uint32_t v;
  asm volatile("ld.shared.u32 %0, [%1];" : "=r"(v) : "r"(a) : "memory");
  return v;
}
__device__ __forceinline__ void ldsm4(uint32_t* r, uint32_t a) {
  asm volatile("ldmatrix.sync.aligned.m8n8.x4.shared.b16 {%0,%1,%2,%3}, [%4];"
               : "=r"(r[0]), "=r"(r[1]), "=r"(r[2]), "=r"(r[3]) : "r"(a) : "memory");
}
__device__ __forceinline__ void ldsm4t(uint32_t* r, uint32_t a) {
  asm volatile("ldmatrix.sync.aligned.m8n8.x4.trans.shared.b16 {%0,%1,%2,%3}, [%4];"
               : "=r"(r[0]), "=r"(r[1]), "=r"(r[2]), "=r"(r[3]) : "r"(a) : "memory");
}
__device__ __forceinline__ void stsm4(uint32_t a, uint32_t r0, uint32_t r1, uint32_t r2, uint32_t r3) {
  asm volatile("stmatrix.sync.aligned.m8n8.x4.shared.b16 [%0], {%1,%2,%3,%4};"
               ::"r"(a), "r"(r0), "r"(r1), "r"(r2), "r"(r3) : "memory");
}
__device__ __forceinline__ void stsm4t(uint32_t a, uint32_t r0, uint32_t r1, uint32_t r2, uint32_t r3) {
  asm volatile("stmatrix.sync.aligned.m8n8.x4.trans.shared.b16 [%0], {%1,%2,%3,%4};"
               ::"r"(a), "r"(r0), "r"(r1), "r"(r2), "r"(r3) : "memory");
}
__device__ __forceinline__ void mma16816(float* d, const uint32_t* a, uint32_t b0, uint32_t b1) {
  asm volatile("mma.sync.aligned.m16n8k16.row.col.f32.bf16.bf16.f32 {%0,%1,%2,%3}, {%4,%5,%6,%7}, {%8,%9}, {%0,%1,%2,%3};"
               : "+f"(d[0]), "+f"(d[1]), "+f"(d[2]), "+f"(d[3])
               : "r"(a[0]), "r"(a[1]), "r"(a[2]), "r"(a[3]), "r"(b0), "r"(b1));
}
__device__ __forceinline__ void mma16816z(float* d, const uint32_t* a, uint32_t b0, uint32_t b1) {
  asm volatile("mma.sync.aligned.m16n8k16.row.col.f32.bf16.bf16.f32 {%0,%1,%2,%3}, {%4,%5,%6,%7}, {%8,%9}, {%10,%10,%10,%10};"
               : "=f"(d[0]), "=f"(d[1]), "=f"(d[2]), "=f"(d[3])
               : "r"(a[0]), "r"(a[1]), "r"(a[2]), "r"(a[3]), "r"(b0), "r"(b1), "f"(0.f));
}
__device__ __forceinline__ void mma1688(float* d, uint32_t a0, uint32_t a1, uint32_t b0) {
  asm volatile("mma.sync.aligned.m16n8k8.row.col.f32.bf16.bf16.f32 {%0,%1,%2,%3}, {%4,%5}, {%6}, {%0,%1,%2,%3};"
               : "+f"(d[0]), "+f"(d[1]), "+f"(d[2]), "+f"(d[3]) : "r"(a0), "r"(a1), "r"(b0));
}
__device__ __forceinline__ uint32_t movtrans(uint32_t a) {
  uint32_t d;
  asm volatile("movmatrix.sync.aligned.m8n8.trans.b16 %0, %1;" : "=r"(d) : "r"(a));
  return d;
}
__device__ __forceinline__ uint32_t mapa(uint32_t a, uint32_t rank) {
  uint32_t d;
  asm("mapa.shared::cluster.u32 %0, %1, %2;" : "=r"(d) : "r"(a), "r"(rank));
  return d;
}
__device__ __forceinline__ void st_async64(uint32_t a, uint32_t x, uint32_t y, uint32_t bar) {
  asm volatile("st.async.weak.shared::cluster.mbarrier::complete_tx::bytes.v2.b32 [%0], {%1,%2}, [%3];"
               ::"r"(a), "r"(x), "r"(y), "r"(bar) : "memory");
}
__device__ __forceinline__ void st_async64f(uint32_t a, float x, float y, uint32_t bar) {
  st_async64(a, __float_as_uint(x), __float_as_uint(y), bar);
}
__device__ __forceinline__ void bulk_s2s(uint32_t dst, uint32_t src, uint32_t bytes, uint32_t bar) {
  asm volatile("cp.async.bulk.shared::cluster.shared::cta.mbarrier::complete_tx::bytes [%0], [%1], %2, [%3];"
               ::"r"(dst), "r"(src), "r"(bytes), "r"(bar) : "memory");
}
__device__ __forceinline__ void tma_store_3d(const CUtensorMap* map, uint32_t src, int x, int y, int z) {
  asm volatile("cp.async.bulk.tensor.3d.global.shared::cta.bulk_group [%0, {%2, %3, %4}], [%1];"
               ::"l"(map), "r"(src), "r"(x), "r"(y), "r"(z) : "memory");
}
__device__ __forceinline__ void mbar_spin(uint32_t bar, uint32_t parity) {
  asm volatile("{\n.reg .pred p;\n.reg .b32 n;\nmov.u32 n, 0x100000;\nMW_L:\n"
               "mbarrier.try_wait.parity.shared::cta.b64 p, [%0], %1;\n@p bra.uni MW_D;\n"
               "add.s32 n, n, -1;\nsetp.ne.u32 p, n, 0;\n@p bra.uni MW_L;\nMW_D:\n}" ::"r"(bar), "r"(parity) : "memory");
}
__device__ __forceinline__ bool mbar_test(uint32_t bar, uint32_t parity) {
  uint32_t done;
  asm volatile("{\n.reg .pred p;\nmbarrier.test_wait.parity.shared::cta.b64 p, [%1], %2;\nselp.u32 %0, 1, 0, p;\n}"
               : "=r"(done) : "r"(bar), "r"(parity) : "memory");
  return done != 0;
}
__device__ __forceinline__ void mbar_arrive_remote(uint32_t bar) {
  asm volatile("mbarrier.arrive.shared::cluster.b64 _, [%0];" ::"r"(bar) : "memory");
}
__device__ __forceinline__ bool elect_one() {
  uint32_t r;
  asm volatile("{\n.reg .pred p;\nelect.sync _|p, 0xffffffff;\nselp.u32 %0, 1, 0, p;\n}" : "=r"(r));
  return r != 0;
}
__device__ __forceinline__ void st_async32(uint32_t a, uint32_t x, uint32_t bar) {
  asm volatile("st.async.weak.shared::cluster.mbarrier::complete_tx::bytes.b32 [%0], %1, [%2];" ::"r"(a), "r"(x), "r"(bar) : "memory");
}
#define named_bar_and(id, n, in, out) \
  asm volatile("{\n.reg .pred p, q;\nsetp.ne.u32 p, %1, 0;\nbar.red.and.pred q, %2, %3, p;\nselp.u32 %0, 1, 0, q;\n}" \
               : "=r"(out) : "r"(in), "n"(id), "n"(n) : "memory")
__device__ __forceinline__ void bulk_g2s(uint32_t dst, const void* src, uint32_t bytes, uint32_t bar) {
  asm volatile("cp.async.bulk.shared::cluster.global.mbarrier::complete_tx::bytes [%0], [%1], %2, [%3];"
               ::"r"(dst), "l"(src), "r"(bytes), "r"(bar) : "memory");
}
__device__ __forceinline__ void l2_prefetch(const void* p, uint32_t bytes) {
  asm volatile("cp.async.bulk.prefetch.L2.global [%0], %1;" ::"l"(p), "r"(bytes) : "memory");
}

__device__ __forceinline__ uint32_t clk32() { uint32_t c; asm volatile("mov.u32 %0, %%clock;" : "=r"(c)::"memory"); return c; }
__device__ __forceinline__ void spin_until(uint32_t t) { while ((int32_t)(clk32() - t) < 0) {} }
#define PIN(x) asm volatile("" : "+r"(x))
#define OPQ                                                                                     \
  int tid_o = tid;                                                                              \
  asm volatile("" : "+r"(tid_o));                                                               \
  const int lane = tid_o & 31, w = (tid_o >> 5) & 3, t7 = tid_o & 127, lg = lane >> 2,          \
            lq = lane & 3, mi = lane >> 3, mr = lane & 7;                                       \
  (void)w; (void)t7; (void)lg; (void)lq; (void)mi; (void)mr; (void)lane

#define SMAP                                                                                                          \
  const uint32_t SM0 = self + fk::SM0, WO = self + fk::WO, WS = self + fk::WS, XN = self + fk::XN, VX = self + fk::VX, \
                 QK = self + fk::QK, PT = self + fk::PT, SP = self + fk::SP, VM = self + fk::VM, OB = self + fk::OB,   \
                 RED = self + fk::RED, VX2 = self + fk::VX2, MEMB = self + fk::MEMB, B_XN = self + fk::B_XN, B_SM = self + fk::B_SM,       \
                 B_VM = self + fk::B_VM, B_VX = self + fk::B_VX, B_ST = self + fk::B_ST, B_PB = self + fk::B_PB,       \
                 B_W = self + fk::B_W, B_H2 = self + fk::B_H2, B_PF = self + fk::B_PF, B_WO = self + fk::B_WO, MASKS = self + fk::MASKS, PROBE = self + fk::PROBE;                             \
  (void)SM0; (void)WO; (void)WS; (void)XN; (void)VX; (void)QK; (void)PT; (void)SP; (void)VM; (void)OB; (void)RED; (void)VX2; \
  (void)MEMB; (void)B_XN; (void)B_SM; (void)B_VM; (void)B_VX; (void)B_ST; (void)B_PB; (void)B_W; (void)MASKS; (void)PROBE; (void)B_H2; (void)B_PF; (void)B_WO

struct FParams {
  CUtensorMap wq, wk, wv, wo, wo16, xn, xn12, o;
  CUtensorMap ta, tb, tx, tg, tout;
  const bf16 *mem0, *x, *w1;
  bf16 *xn_ptr, *xn2;
  int nprobe;
  char* xch;
};

__device__ __forceinline__ uint2 probe_pair(char* p, uint32_t val, uint32_t dummy, int n) {
  uint2 best = make_uint2(0x7FFFFFFF, 0x7FFFFFFF);
  st_pub128(p, val); st_pub128(p + 16, val); st_pub128(p + 4096, val); st_pub128(p + 4112, val);
#pragma unroll 1
  for (int r = 0; r < n; r++) {
    uint32_t v;
    const uint32_t c0 = clk32();
    asm volatile("atom.relaxed.gpu.global.exch.b32 %0, [%1], %2;" : "=r"(v) : "l"(p + (r & 1) * 4096), "r"(val) : "memory");
    asm volatile("{\n.reg .pred p;\nsetp.eq.u32 p, %0, 0x12345678;\n@p st.shared.u32 [%1], %0;\n}" ::"r"(v), "r"(dummy) : "memory");
    const uint32_t d = clk32() - c0;
    if (r & 1) best.y = min(best.y, d); else best.x = min(best.x, d);
  }
  return best;
}

typedef uint32_t WRegs[6][2][4][4];

template <bool ISV> struct Chunks {
  static constexpr int SC0 = ISV ? 6 : SCQ;
  static __device__ __forceinline__ constexpr int rf(int wg, int i) { return wg ? 10 + i : (i < SC0 ? i : 4 + i); }
};

template <int WG> struct ProjCfg { static constexpr int NS = WG ? 8 - NS0 : NS0, P0 = WG ? NS0 : 0, NTA = WG ? NTA1 : NTA0; };
__device__ __forceinline__ void load_pair(uint32_t (&t)[4][4], uint32_t wsa, int pp) {
#pragma unroll
  for (int f = 0; f < 4; f++) ldsm4t(t[f], wsa + ((pp >> 1) * 2 + (f & 1)) * 8192 + ((pp & 1) * 2 + (f >> 1)) * 2048);
}
template <bool ISV, int WG>
__device__ __forceinline__ void proj_mem(const WRegs& wr, uint32_t (&ta)[ProjCfg<WG>::NTA][4][4], uint32_t wsa, uint32_t mba,
                                         float (&a0)[4], float (&a1)[4]) {
  constexpr int NS = ProjCfg<WG>::NS, P0 = ProjCfg<WG>::P0, NTA = ProjCfg<WG>::NTA, NP = 12 + NS;
  float acc[4][4];
  auto spos = [](int j) { return j < NTA ? j : j + (j - NTA + 1) * 12 / (NS - NTA > 0 ? NS - NTA : 1); };
  auto which = [&](int p) { int r = -1; for (int j = 0; j < NS; j++) if (spos(j) == p) r = j; return r; };
  auto nsm_before = [&](int p) { int n = 0; for (int j = 0; j < NS; j++) if (spos(j) < p) n++; return n; };
#pragma unroll
  for (int p = 0; p < NP; p++) {
    const int j = which(p), r = j >= 0 ? 0 : p - nsm_before(p);
    uint32_t bp[4], tl[4][4];
    ldsm4(bp, mba + (j >= 0 ? (Chunks<ISV>::SC0 + ((P0 + j) >> 1)) * 1024 + ((P0 + j) & 1) * 512 : Chunks<ISV>::rf(WG, r >> 1) * 1024 + (r & 1) * 512));
    if (j >= NTA) load_pair(tl, wsa, P0 + j);
#pragma unroll
    for (int u = 0; u < 2; u++)
#pragma unroll
      for (int T = 0; T < 2; T++) {
        const uint32_t* a = j >= NTA ? tl[u * 2 + T] : j >= 0 ? ta[j >= 0 ? j % NTA : 0][u * 2 + T] : wr[r >> 1][T][(r & 1) * 2 + u];
        if (p == 0) mma16816z(acc[u * 2 + T], a, bp[2 * u], bp[2 * u + 1]);
        else mma16816(acc[u * 2 + T], a, bp[2 * u], bp[2 * u + 1]);
      }
  }
#pragma unroll
  for (int i = 0; i < 4; i++) { a0[i] = acc[0][i] + acc[2][i]; a1[i] = acc[1][i] + acc[3][i]; }
}
template <int WG>
__device__ __forceinline__ void proj_mem_prefetch(uint32_t (&ta)[ProjCfg<WG>::NTA][4][4], uint32_t wsa) {
#pragma unroll
  for (int j = 0; j < ProjCfg<WG>::NTA; j++) load_pair(ta[j], wsa, ProjCfg<WG>::P0 + j);
}

template <bool ISV, int WG>
__device__ __forceinline__ void proj_finish(const float (&a0)[4], const float (&a1)[4], uint32_t peer0, uint32_t peer1, uint32_t self, int tid,
                                            uint32_t (&vmo)[2][2]) {
  using namespace fk;
  SMAP;
  OPQ;
  if (!ISV) {
    stsm4(PT + (mi >> 1) * 2048 + w * 512 + (mi & 1) * 256 + WG * 128 + mr * 16,
          pack_bf16(a0[0], a0[1]), pack_bf16(a0[2], a0[3]), pack_bf16(a1[0], a1[1]), pack_bf16(a1[2], a1[3]));
    named_bar_sync(NB_C, 256);
  } else {
    if (WG == 0) sts128f(RED + t7 * 16, a1[0], a1[1], a1[2], a1[3]);
    else sts128f(RED + 2048 + t7 * 16, a0[0], a0[1], a0[2], a0[3]);
    if (WG == 1) { lds64(vmo[0], VM + t7 * 8); lds64(vmo[1], VM + 1024 + t7 * 8); }
    named_bar_sync(NB_C, 256);
    const float4 p = lds128f(RED + (1 - WG) * 2048 + t7 * 16);
    const float* k = WG == 0 ? a0 : a1;
    const uint32_t v0 = pack_bf16(k[0] + p.x, k[1] + p.y), v1 = pack_bf16(k[2] + p.z, k[3] + p.w);
    const uint32_t off = VM + WG * 1024 + t7 * 8;
    st_async64(peer0 + off, v0, v1, peer0 + B_VM);
    st_async64(peer1 + off, v0, v1, peer1 + B_VM);
    sts64(off, v0, v1);
    __syncwarp();
    if (lane == 0) mbar_arrive(B_VM);
  }
}

__device__ __forceinline__ void send_scores(float s0, float s1, uint32_t off, uint32_t peer0, uint32_t peer1, uint32_t bar, int lane) {
  if (SPACK) {
    const uint32_t v = pack_bf16(s0, s1);
    st_async32(peer0 + off, v, peer0 + bar);
    st_async32(peer1 + off, v, peer1 + bar);
    sts32(off, v);
  } else {
    st_async64f(peer0 + off, s0, s1, peer0 + bar);
    st_async64f(peer1 + off, s0, s1, peer1 + bar);
    sts64f(off, s0, s1);
  }
  __syncwarp();
  if (lane == 0) mbar_arrive(bar);
}

template <int NT, bool NARROW>
__device__ __forceinline__ uint32_t wo_addr(int f, uint32_t woa, uint32_t wob) {
  return (NARROW && f % NT == 2) ? wob + (f / NT) * 512 : woa + (f % NT) * 32768 + (f / NT) * 2048;
}
template <int NT, bool NARROW, int PF>
__device__ __forceinline__ void wo_phase(uint32_t (&wf)[PF][4], uint32_t woa, uint32_t wob, uint32_t oba, char* h1p, uint32_t sel, uint32_t tag) {
  float c[NT][4];
  uint32_t of[2][4];
  ldsm4t(of[0], oba);
#pragma unroll
  for (int k = 0; k < 8; k++) {
    if ((k & 1) == 0 && k + 2 < 8) ldsm4t(of[((k >> 1) + 1) & 1], oba + ((k >> 1) + 1) * 512);
#pragma unroll
    for (int i = 0; i < NT; i++) {
      const int f = k * NT + i;
      const uint32_t b0 = of[(k >> 1) & 1][2 * (k & 1)], b1 = of[(k >> 1) & 1][2 * (k & 1) + 1];
      if (k == 0) mma16816z(c[i], wf[f % PF], b0, b1); else mma16816(c[i], wf[f % PF], b0, b1);
      if (f + PF < 8 * NT) ldsm4t(wf[f % PF], wo_addr<NT, NARROW>(f + PF, woa, wob));
    }
  }
#pragma unroll
  for (int i = 0; i < NT; i++)
    st_pub64(h1p + i * (8 * 32768) + ((sel >> (2 * i)) & 3) * 2048, (pack_bf16(c[i][0], c[i][1]) & ~1u) | tag, pack_bf16(c[i][2], c[i][3]));
}
template <int NT, bool NARROW, int F0, int F1, int PF>
__device__ __forceinline__ void wo_prefetch(uint32_t (&wf)[PF][4], uint32_t woa, uint32_t wob) {
#pragma unroll
  for (int f = F0; f < F1; f++) ldsm4t(wf[f], wo_addr<NT, NARROW>(f, woa, wob));
}

template <bool ISV, int T, bool ADD>
__device__ __forceinline__ void tok_store(const float (&x)[16], uint32_t base, int tid) {
  OPQ;
  const uint32_t a = ISV ? base + T * 4096 + w * 1024 + lane * 16
                   : T == 0 ? base + w * 512 + (mi & 1) * 256 + (mi >> 1) * 128 + mr * 16
                            : base + 4096 + (mi >> 1) * 1024 + w * 256 + (mi & 1) * 128 + mr * 16;
  constexpr uint32_t STR = ISV ? 512 : 2048;
  uint32_t p[2][4];
  if (ADD) {
#pragma unroll
    for (int i = 0; i < 2; i++) { if (ISV) lds128(p[i], a + i * STR); else ldsm4(p[i], a + i * STR); }
  }
#pragma unroll
  for (int i = 0; i < 2; i++) {
#pragma unroll
    for (int k = 0; k < 4; k++)
      p[i][k] = ADD ? pack_bf16(x[8 * i + 2 * k] + bf_lo(p[i][k]), x[8 * i + 2 * k + 1] + bf_hi(p[i][k]))
                    : pack_bf16(x[8 * i + 2 * k], x[8 * i + 2 * k + 1]);
    if (ISV) sts128(a + i * STR, p[i][0], p[i][1], p[i][2], p[i][3]); else stsm4(a + i * STR, p[i][0], p[i][1], p[i][2], p[i][3]);
  }
}

__device__ __forceinline__ void load_xn(const FParams& P, int seg, uint32_t self) {
  SMAP;
  mbar_expect_tx(B_XN, 49152);
  tma_load_3d(XN, &P.xn12, 0, seg * 32, 0, B_XN);
}

__device__ __forceinline__ uint64_t xn_desc(int slot, int u) { return make_desc(fk::XN + slot * 4096 + u * 32, 16, 1024); }

template <bool ISV>
__device__ __forceinline__ void f_wg0(const FParams& P, const WRegs& wr, const int h, const int rank, uint32_t sel, const int tid) {
  using namespace fk;
  const uint32_t self = mapa(0, rank), peer0 = mapa(0, ISV ? 0 : rank ^ 1) - self, peer1 = mapa(0, ISV ? 1 : 2) - self;
  SMAP;
  const int tile0 = rank * 22;
  const int warp = __shfl_sync(0xffffffffu, threadIdx.x >> 5, 0);
  const bool three = !ISV && warp < 2;
  uint32_t ta[NTA0][4][4], wsa = 0, mba = 0, h2ph = 0;
#pragma unroll 1
  for (int s = -1; s < cfg::NSEG; s++) {
    uint32_t t_pub = 0;
    sel ^= 0x55;
    if (s >= 0) {
      PROF(0, 1);
      float a0[4], a1[4];
      proj_mem<ISV, 0>(wr, ta, wsa, mba, a0, a1);
      PROF(0, 2);
      uint32_t unused[2][2];
      proj_finish<ISV, 0>(a0, a1, peer0, peer1, self, tid, unused);
      PROF(0, 3);
      if (s + 1 == cfg::NSEG) break;
      uint32_t wf[PF0][4], woa, wob;
      {
        OPQ;
        if (!ISV) {
          uint32_t qf[4][4], kf[2][4];
          const uint32_t qa = PT + lane * 16, ka = QK + 4096 + w * 1024 + lane * 16;
          ldsm4t(qf[0], qa); ldsm4t(kf[0], ka); ldsm4t(qf[1], qa + 512);
          ldsm4t(qf[2], qa + 1024); ldsm4t(kf[1], ka + 512); ldsm4t(qf[3], qa + 1536);
          float c0[4], c1[4];
          mma16816z(c0, qf[0], kf[0][0], kf[0][1]);
          mma16816z(c1, qf[1], kf[0][2], kf[0][3]);
          mma16816(c0, qf[2], kf[1][0], kf[1][1]);
          mma16816(c1, qf[3], kf[1][2], kf[1][3]);
          const float s0 = (c0[0] + c0[2]) + (c1[0] + c1[2]), s1 = (c0[1] + c0[3]) + (c1[1] + c1[3]);
          send_scores(s0, s1, SP + rank * SP_SRC + t7 * SPW, peer0, peer1, B_SM, lane);
        }
        PROF(0, 4);
        woa = WO + 16384 + ((mi >> 1) * 8 + mr) * 128 + (((2 * w + (mi & 1)) ^ mr) << 4);
        wob = WO + 81920 + w * 4096 + ((mi >> 1) * 8 + mr) * 32 + (((mi & 1) ^ (mr >> 2)) << 4);
        uint32_t vf[2][2][4], vm[2][2];
        if (!ISV) mbar_spin(B_VX, s & 1);
        PROF(0, 14);
#pragma unroll
        for (int T = 0; T < 2; T++)
#pragma unroll
          for (int kk = 0; kk < 2; kk++) lds128(vf[T][kk], ((ISV && (s & 1)) ? VX2 : VX) + T * 4096 + w * 1024 + kk * 512 + lane * 16);
        if (three) wo_prefetch<3, true, 0, PF0A>(wf, woa, wob); else wo_prefetch<2, false, 0, PF0A>(wf, woa, wob);
        uint32_t spa = SP + lane * SPW, vma = VM + t7 * 8, oa = OB + (mi >> 1) * 1024 + w * 256 + (mi & 1) * 128 + mr * 16;
        PIN(spa); PIN(vma); PIN(oa);
        mbar_spin(B_SM, s & 1);
        PROF(0, 5);
        float sc[10];
#pragma unroll
        for (int j = 0; j < 5; j++) {
          if (SPACK) {
            const uint32_t x = lds32(spa + j * 128), y = lds32(spa + SP_SRC + j * 128);
            sc[2 * j] = bf_lo(x) + bf_lo(y); sc[2 * j + 1] = bf_hi(x) + bf_hi(y);
          } else {
            const float2 x = lds64f(spa + j * 256), y = lds64f(spa + SP_SRC + j * 256);
            sc[2 * j] = x.x + y.x; sc[2 * j + 1] = x.y + y.y;
          }
        }
        float m = fmaxf(fmaxf(fmaxf(sc[0], sc[1]), fmaxf(sc[2], sc[3])), fmaxf(fmaxf(sc[4], sc[5]), fmaxf(sc[6], sc[7])));
        m = fmaxf(m, fmaxf(sc[8], sc[9]));
        const bool vm_ok = mbar_test(B_VM, s & 1);
        m = fmaxf(m, __shfl_xor_sync(0xffffffffu, m, 1));
        m = fmaxf(m, __shfl_xor_sync(0xffffffffu, m, 2));
        PROF(0, 15);
        if (!vm_ok) mbar_spin(B_VM, s & 1);
        PROF(0, 0);
        lds64(vm[0], vma); lds64(vm[1], vma + 1024);
        const float cs = 0.08838834764831845f * 1.4426950408889634f;
        const float mc = -m * cs;
        uint32_t pb[5];
#pragma unroll
        for (int j = 0; j < 5; j++) pb[j] = pack_bf16(ex2_approx(fmaf(sc[2 * j], cs, mc)), ex2_approx(fmaf(sc[2 * j + 1], cs, mc)));
        PROF(0, 6);
        float o0[4], o1[4], rs[4];
        const uint32_t ones[4] = {0x3F803F80u, 0x3F803F80u, 0x3F803F80u, 0x3F803F80u};
        mma16816z(rs, ones, pb[0], pb[1]);
        mma16816z(o0, vf[0][0], pb[0], pb[1]);
        mma16816z(o1, vf[1][0], pb[0], pb[1]);
        mma16816(rs, ones, pb[2], pb[3]);
        mma16816(o0, vf[0][1], pb[2], pb[3]);
        mma16816(o1, vf[1][1], pb[2], pb[3]);
        mma1688(rs, ones[0], ones[0], pb[4]);
        mma1688(o0, vm[0][0], vm[0][1], pb[4]);
        mma1688(o1, vm[1][0], vm[1][1], pb[4]);
        const float i0 = rcp_approx(rs[0]), i1 = rcp_approx(rs[1]);
        stsm4(oa, pack_bf16(o0[0] * i0, o0[1] * i1), pack_bf16(o0[2] * i0, o0[3] * i1),
              pack_bf16(o1[0] * i0, o1[1] * i1), pack_bf16(o1[2] * i0, o1[3] * i1));
      }
      {
        OPQ;
        named_bar_arrive(NB_O, 256);
        if (three) wo_prefetch<3, true, PF0A, PF0>(wf, woa, wob); else wo_prefetch<2, false, PF0A, PF0>(wf, woa, wob);
        char* h1p = P.xch + (tile0 + 4 + w) * 32768 + (h >> 3) * 8192 + (h & 7) * 256 + lane * 8;
        uint32_t oba = OB + lane * 16;
        PIN(oba);
        PROF(0, 7);
        named_bar_sync(NB_O0, 128);
        PROF(0, 8);
        const uint32_t tag = ((s >> 1) & 1) ^ 1;
        if (three) wo_phase<3, true>(wf, woa, wob, oba, h1p, sel, tag); else wo_phase<2, false>(wf, woa, wob, oba, h1p, sel, tag);
        t_pub = clk32();
        PROF(0, 9);
        named_bar_sync(NB_HD, 256);
      }
    }
    auto h2_src = [&]() { return P.xch + H1_BYTES + ((s & 1) * 4 + warp) * 8192 + ((sel >> (8 + (s & 1))) & 1) * 4096; };
    {
      const uint32_t ph = (s + 1) & 1;
      float x0[16], x1[16];
      mbar_spin(B_XN, ph);
      wg_fence();
#pragma unroll
      for (int c = 0; c < 10; c++) {
        if (PAUSE && !ISV && c == SCQ + 4) { uint32_t t_; named_bar_and(NB_PZ, 256, 1, t_); wg_fence(); }
        if (c == 9) named_bar_arrive(NB_ST, 256);
#pragma unroll
        for (int u = 0; u < 4; u++) {
          constexpr int SC0 = Chunks<ISV>::SC0;
          if (c >= SC0 && c < SC0 + 4) {
            wgmma_ss_n32_ta(x0, make_desc(fk::WS + (c - SC0) * 16384 + u * 2048, 8192, 1024), xn_desc(c, u), 1);
            wgmma_ss_n32_ta(x1, make_desc(fk::WS + (c - SC0) * 16384 + 8192 + u * 2048, 8192, 1024), xn_desc(c, u), 1);
          } else {
            wgmma_rs_n32(x0, wr[c < SC0 ? c : c >= SC0 + 4 ? c - 4 : 0][0][u], xn_desc(c, u), (c | u) != 0);
            wgmma_rs_n32(x1, wr[c < SC0 ? c : c >= SC0 + 4 ? c - 4 : 0][1][u], xn_desc(c, u), (c | u) != 0);
          }
          if (c == 4 && u == 1) { wg_commit(); wg_wait<1>(); named_bar_arrive(NB_XE, 160); wg_fence(); }
        }
        if (c == 3) wg_commit();
      }
      wg_commit();
      wg_wait<0>();
      PROF(0, 10);
      if (ISV) named_bar_sync(NB_CF, 160);
      const uint32_t tb = ISV ? (ph ? VX2 : VX) : QK;
      tok_store<ISV, 0, false>(x0, tb, tid);
      tok_store<ISV, 1, false>(x1, tb, tid);
      named_bar_arrive(NB_DU, 256);
    }
    {
      OPQ;
      wsa = WS + ((mi >> 1) * 8 + mr) * 128 + (((2 * w + (mi & 1)) ^ mr) << 4);
      mba = MEMB + lane * 16;
      PIN(wsa); PIN(mba);
      if (s >= 0) {
        const char* src = h2_src();
        const uint32_t chk = MEMB + w * 4096 + lane * 32 + lg * 4, bar = B_H2 + 8 * warp;
        PROF(0, 11);
        spin_until(t_pub + D_H2);
        PROF(0, 13);
        if (elect_one()) { mbar_expect_tx(bar, 4096); bulk_g2s(MEMB + warp * 4096, src, 4096, bar); }
        proj_mem_prefetch<0>(ta, wsa);
#pragma unroll 1
        for (int tries = 0; tries < POLL_TRIES; tries++) {
          mbar_spin(bar, h2ph);
          h2ph ^= 1;
          const uint32_t mx = max(max(lds32(chk), lds32(chk + 1024)), max(lds32(chk + 2048), lds32(chk + 3072)));
          if (__all_sync(0xffffffffu, mx != EMPTY)) break;
          RETRY(1);
          if (elect_one()) { mbar_expect_tx(bar, 4096); bulk_g2s(MEMB + warp * 4096, src, 4096, bar); }
        }
      } else {
        const bf16* m0 = P.mem0 + mr * cfg::D + w * 256 + mi * 8;
#pragma unroll
        for (int i = 0; i < 8; i++) {
          const uint4 v = *reinterpret_cast<const uint4*>(m0 + i * 32);
          sts128(mba + w * 4096 + i * 512, v.x, v.y, v.z, v.w);
        }
        proj_mem_prefetch<0>(ta, wsa);
        mbar_wait(B_WO, 0);
      }
      PROF(0, 12);
      named_bar_arrive(NB_M1, 256);
      named_bar_sync(NB_M0, 128);
    }
  }
}

template <bool ISV>
__device__ __forceinline__ void f_wg1(const FParams& P, const WRegs& wr, const int h, const int rank, uint32_t sel, const int tid) {
  using namespace fk;
  const uint32_t self = mapa(0, rank), peer0 = mapa(0, ISV ? 0 : rank ^ 1) - self, peer1 = mapa(0, ISV ? 1 : 2) - self;
  SMAP;
  const int tile0 = rank * 22;
  const int warp = __shfl_sync(0xffffffffu, (threadIdx.x >> 5) & 3, 0);
  uint32_t ta[NTA1][4][4], wsa = 0, mba = 0;
  auto tok_pv = [&](int seg, const uint32_t (&vm)[2][2]) {
    OPQ;
    const int s = seg + 1; (void)s;
    const uint32_t vb = (seg & 1) ? VX2 : VX;
    uint32_t vf[2][2][4];
#pragma unroll
    for (int T = 0; T < 2; T++)
#pragma unroll
      for (int kk = 0; kk < 2; kk++) lds128(vf[T][kk], vb + T * 4096 + w * 1024 + kk * 512 + lane * 16);
    const uint32_t stg = vb + (mi >> 1) * 4096 + mr * 128 + (((2 * w + (mi & 1)) ^ mr) << 4);
    uint32_t pm[4], r[4][4];
    lds128(pm, PT + 2048 + lane * 16);
#pragma unroll
    for (int g2 = 0; g2 < 4; g2 += 2) {
      uint32_t p[2][4];
      lds128(p[0], PT + g2 * 512 + lane * 16);
      lds128(p[1], PT + g2 * 512 + 512 + lane * 16);
      float o[4][4];
#pragma unroll
      for (int i = 0; i < 4; i++) mma16816z(o[i], vf[i & 1][0], p[i >> 1][0], p[i >> 1][1]);
#pragma unroll
      for (int i = 0; i < 4; i++) mma16816(o[i], vf[i & 1][1], p[i >> 1][2], p[i >> 1][3]);
#pragma unroll
      for (int i = 0; i < 4; i++) mma1688(o[i], vm[i & 1][0], vm[i & 1][1], pm[g2 + (i >> 1)]);
#pragma unroll
      for (int i = 0; i < 4; i++) {
        r[g2 + (i >> 1)][2 * (i & 1)] = pack_bf16(o[i][0], o[i][1]);
        r[g2 + (i >> 1)][2 * (i & 1) + 1] = pack_bf16(o[i][2], o[i][3]);
      }
      if (g2 == 0) named_bar_sync(NB_W1, 128);
    }
    PROF(1, 6);
#pragma unroll
    for (int gq = 0; gq < 4; gq++) stsm4t(stg + gq * 1024, r[gq][0], r[gq][1], r[gq][2], r[gq][3]);
  };
  auto o_store = [&](int seg) { tma_store_3d(&P.o, (seg & 1) ? VX2 : VX, 0, seg * 32, 2 * h); tma_store_commit(); };
  auto o_done = [&](int seg) {
    tma_store_wait_all();
    if ((seg & 3) == 3) {
      asm volatile("fence.proxy.async.global;" ::: "memory");
      asm volatile("red.release.gpu.global.add.u32 [%0], 1;" ::"l"(&g_oflag[seg >> 2]) : "memory");
    }
  };
#pragma unroll 1
  for (int s = -1; s < cfg::NSEG; s++) {
    uint32_t t_pub = 0;
    sel ^= 0x55;
    const bool last = s + 1 == cfg::NSEG;
    if (s >= 0) {
      PROF(1, 1);
      float a0[4], a1[4];
      proj_mem<ISV, 1>(wr, ta, wsa, mba, a0, a1);
      PROF(1, 2);
      uint32_t vmo[2][2];
      proj_finish<ISV, 1>(a0, a1, peer0, peer1, self, tid, vmo);
      PROF(1, 3);
      uint32_t wf[PF1][4], woa;
      if (ISV) {
        if (warp == 3 && !last) {
          mbar_spin(B_VM, s & 1);
          if (elect_one()) load_xn(P, s + 1, self);
        }
        if (s > 0) tok_pv(s - 1, vmo);
        OPQ;
        woa = WO + ((mi >> 1) * 8 + mr) * 128 + (((2 * w + (mi & 1)) ^ mr) << 4);
      } else {
        float c0[4], c1[4];
        if (warp == 0) {
          OPQ;
          uint32_t kf[4][4], qf[4][4];
          float d0[4], d1[4];
          const uint32_t ka = PT + 2048 + (mi & 1) * 256 + (mi >> 1) * 128 + mr * 16;
#pragma unroll
          for (int k = 0; k < 4; k++) { ldsm4t(qf[k], PT + k * 512 + lane * 16); ldsm4t(kf[k], ka + k * 512); }
          mma16816z(c0, qf[0], kf[0][0], kf[0][1]); mma16816z(c1, qf[0], kf[0][2], kf[0][3]);
          mma16816z(d0, qf[1], kf[1][0], kf[1][1]); mma16816z(d1, qf[1], kf[1][2], kf[1][3]);
          mma16816(c0, qf[2], kf[2][0], kf[2][1]); mma16816(c1, qf[2], kf[2][2], kf[2][3]);
          mma16816(d0, qf[3], kf[3][0], kf[3][1]); mma16816(d1, qf[3], kf[3][2], kf[3][3]);
          const float s0 = ((c0[0] + c0[2]) + (c1[0] + c1[2])) + ((d0[0] + d0[2]) + (d1[0] + d1[2]));
          const float s1 = ((c0[1] + c0[3]) + (c1[1] + c1[3])) + ((d0[1] + d0[3]) + (d1[1] + d1[3]));
          if (!last) send_scores(s0, s1, SP + rank * SP_SRC + (128 + lane) * SPW, peer0, peer1, B_SM, lane);
          PROF(1, 5);
#pragma unroll
          for (int mt = 0; mt < 2; mt++) {
            float* c = mt ? c1 : c0;
#pragma unroll
            for (int k = 0; k < 4; k++) ldsm4t(qf[k], QK + mt * 2048 + k * 512 + lane * 16);
            mma16816z(c, qf[0], kf[0][0], kf[0][1]); mma16816z(d0, qf[0], kf[0][2], kf[0][3]);
#pragma unroll
            for (int k = 1; k < 4; k++) { mma16816(c, qf[k], kf[k][0], kf[k][1]); mma16816(d0, qf[k], kf[k][2], kf[k][3]); }
#pragma unroll
            for (int i = 0; i < 4; i++) c[i] += d0[i];
          }
        } else {
          const uint32_t t_c = clk32();
          if (warp == 3 && !last) { if (elect_one()) load_xn(P, s + 1, self); }
          spin_until(t_c + D_ST);
          OPQ;
          const int mt = w >> 1, j0 = w == 3 ? 2 : 0;
          uint32_t qf[4][4], kf[4][4];
#pragma unroll
          for (int k = 0; k < 4; k++) { ldsm4t(qf[k], QK + mt * 2048 + k * 512 + lane * 16); ldsm4t(kf[k], QK + 4096 + j0 * 1024 + k * 512 + lane * 16); }
          mma16816z(c0, qf[0], kf[0][0], kf[0][1]); mma16816z(c1, qf[0], kf[2][0], kf[2][1]);
          mma16816(c0, qf[1], kf[0][2], kf[0][3]); mma16816(c1, qf[1], kf[2][2], kf[2][3]);
          mma16816(c0, qf[2], kf[1][0], kf[1][1]); mma16816(c1, qf[2], kf[3][0], kf[3][1]);
          mma16816(c0, qf[3], kf[1][2], kf[1][3]); mma16816(c1, qf[3], kf[3][2], kf[3][3]);
        }
        OPQ;
        const uint32_t dst = peer1 + QK + rank * 3584 + lane * 8, dbar = peer1 + B_ST;
        woa = WO + ((mi >> 1) * 8 + mr) * 128 + (((2 * w + (mi & 1)) ^ mr) << 4);
        const uint32_t tbl = w == 0 ? 0x9520u : w == 1 ? 0x4F31u : w == 2 ? 0xB7A6u : 0xDFC8u;
        PROF(1, 6);
        mbar_spin(last ? B_VM : B_VX, s & 1);
        st_async64f(dst + (tbl & 15) * 256, c0[0], c0[1], dbar);
        st_async64f(dst + ((tbl >> 4) & 15) * 256, c0[2], c0[3], dbar);
        if ((w & 1) == 0) st_async64f(dst + ((tbl >> 8) & 15) * 256, c1[0], c1[1], dbar);
        st_async64f(dst + (tbl >> 12) * 256, c1[2], c1[3], dbar);
      }
      PROF(1, 4);
      if (!last) {
        OPQ;
        uint32_t oba = OB + lane * 16;
        PIN(oba);
        wo_prefetch<3, false, 0, PF1>(wf, woa, 0);
        char* h1p = P.xch + (tile0 + w) * 32768 + (h >> 3) * 8192 + (h & 7) * 256 + lane * 8;
        if (ISV) fence_proxy_async_smem();
        PROF(1, 7);
        named_bar_sync(NB_O, 256);
        PROF(1, 8);
        wo_phase<3, false>(wf, woa, 0, oba, h1p, sel, ((s >> 1) & 1) ^ 1);
        t_pub = clk32();
        named_bar_arrive(NB_HD, 256);
        PROF(1, 9);
        if (ISV && warp == 0 && s > 0) { if (elect_one()) o_store(s - 1); }
        if (!ISV && tid == 192) mbar_arrive_remote(peer1 + B_PF);
        if (tid == 160) {
          if (s == 1) st_pub32(&g_mask[blockIdx.x], 0);
          if (s + 2 < cfg::NSEG) { mbar_expect_tx(B_SM, ISV ? 2 * SP_SRC : SP_SRC); if (!ISV) mbar_expect_tx(B_VX, 8192); }
          if (!ISV) mbar_expect_tx(B_VM, 2048);
        }
        __syncwarp();
      }
    }
    auto refill = [&]() {
      if (warp == 3) {
        named_bar_sync(NB_XE, 160);
        if (elect_one()) {
          mbar_expect_tx(B_XN + 8, 16384);
          tma_load_3d(XN, &P.xn, 0, (s + 1) * 32, 12, B_XN + 8);
        }
      }
    };
    if (s < 0) {
      if (ISV && warp == 0) named_bar_arrive(NB_CF, 160);
      refill();
      if (PAUSE && !ISV) { uint32_t t_; named_bar_and(NB_PZ, 256, 1, t_); }
    } else if (!ISV) {
      if (last) break;
      OPQ;
      const int j = 2 * h + rank;
      const char* src = P.xch + j * 32768 + w * 8192 + ((sel >> 6) & 3) * 2048 + lane * 8;
      char* dst = P.xch + H1_BYTES + (j >> 4) * 8192 + (j & 15) * 256 + (w & 1) * 128 + lane * 4;
      const uint32_t tmask = (s >> 1) & 1;
      const bool sw = lq >= 2;
      uint32_t rw = PT + w * 512 + (2 * lq + sw) * 32 + lg * 4, rr = PT + (w & 1) * 256 + lane * 8;
      PIN(rw); PIN(rr);
      uint2 v[8];
      spin_until(t_pub + D_H1);
#pragma unroll
      for (int i = 0; i < 8; i++) v[i] = ld_poll8(src + i * 256);
      refill();
      auto partial = [&]() {
        float f[4];
        f[0] = ((bf_lo(v[0].x) + bf_lo(v[1].x)) + (bf_lo(v[2].x) + bf_lo(v[3].x))) + ((bf_lo(v[4].x) + bf_lo(v[5].x)) + (bf_lo(v[6].x) + bf_lo(v[7].x)));
        f[1] = ((bf_hi(v[0].x) + bf_hi(v[1].x)) + (bf_hi(v[2].x) + bf_hi(v[3].x))) + ((bf_hi(v[4].x) + bf_hi(v[5].x)) + (bf_hi(v[6].x) + bf_hi(v[7].x)));
        f[2] = ((bf_lo(v[0].y) + bf_lo(v[1].y)) + (bf_lo(v[2].y) + bf_lo(v[3].y))) + ((bf_lo(v[4].y) + bf_lo(v[5].y)) + (bf_lo(v[6].y) + bf_lo(v[7].y)));
        f[3] = ((bf_hi(v[0].y) + bf_hi(v[1].y)) + (bf_hi(v[2].y) + bf_hi(v[3].y))) + ((bf_hi(v[4].y) + bf_hi(v[5].y)) + (bf_hi(v[6].y) + bf_hi(v[7].y)));
        sts32(rw, __float_as_uint(sw ? f[1] : f[0]));
        sts32(rw ^ 32, __float_as_uint(sw ? f[0] : f[1]));
        sts32(rw + 256, __float_as_uint(sw ? f[3] : f[2]));
        sts32((rw ^ 32) + 256, __float_as_uint(sw ? f[2] : f[3]));
        uint32_t t0, t1, t2, t3;
        asm("lop3.b32 %0, %1, %2, %3, 0x42;" : "=r"(t0) : "r"(v[0].x), "r"(v[1].x), "r"(tmask));
        asm("lop3.b32 %0, %1, %2, %3, 0x42;" : "=r"(t1) : "r"(v[2].x), "r"(v[3].x), "r"(tmask));
        asm("lop3.b32 %0, %1, %2, %3, 0x42;" : "=r"(t2) : "r"(v[4].x), "r"(v[5].x), "r"(tmask));
        asm("lop3.b32 %0, %1, %2, %3, 0x42;" : "=r"(t3) : "r"(v[6].x), "r"(v[7].x), "r"(tmask));
        return t0 & t1 & t2 & t3 & 1;
      };
      uint32_t ok = partial();
      PROF(1, 10);
      if (PAUSE) named_bar_and(NB_PZ, 256, ok, ok); else named_bar_and(NB_W1, 128, ok, ok);
      if (!ok) {
#pragma unroll 1
        for (int tries = 0; tries < POLL_TRIES; tries++) {
#pragma unroll
          for (int i = 0; i < 8; i++) v[i] = ld_strong8(src + i * 256);
          RETRY(0);
          ok = partial();
          named_bar_and(NB_W1, 128, ok, ok);
          if (ok) break;
        }
      }
      if (warp < 2) {
        const float2 y0 = lds64f(rr), y1 = lds64f(rr + 512), y2 = lds64f(rr + 1024), y3 = lds64f(rr + 1536);
        const uint32_t r = pack_bf16((y0.x + y1.x) + (y2.x + y3.x), (y0.y + y1.y) + (y2.y + y3.y));
        st_pub32(dst + (s & 1) * 32768, r);
        st_pub32(dst + (s & 1) * 32768 + 4096, r);
        st_pub32(dst + ((s & 1) ^ 1) * 32768, EMPTY);
        st_pub32(dst + ((s & 1) ^ 1) * 32768 + 4096, EMPTY);
      }
      PROF(1, 11);
    } else {
      {
        OPQ;
        const uint32_t sa = QK + ((w * (w + 3)) >> 1) * 256 + lane * 8;
        mbar_spin(B_ST, s & 1);
        if (tid == 160 && !last) mbar_expect_tx(B_ST, 7168);
        float sc[10];
        const float scale = 0.08838834764831845f, NEG = -1000000000.0f;
#pragma unroll
        for (int b = 0; b < 5; b++) {
          sc[2 * b] = NEG; sc[2 * b + 1] = NEG;
          if (b <= warp + 1) {
            const float2 x = lds64f(sa + b * 256), y = lds64f(sa + 3584 + b * 256);
            const bool diag = b == warp + 1;
            if (!(diag && 2 * lq > lg)) sc[2 * b] = (x.x + y.x) * scale;
            if (!(diag && 2 * lq + 1 > lg)) sc[2 * b + 1] = (x.y + y.y) * scale;
          }
        }
        float m = fmaxf(fmaxf(fmaxf(sc[0], sc[1]), fmaxf(sc[2], sc[3])), fmaxf(fmaxf(sc[4], sc[5]), fmaxf(sc[6], sc[7])));
        m = fmaxf(m, fmaxf(sc[8], sc[9]));
        m = fmaxf(m, __shfl_xor_sync(0xffffffffu, m, 1));
        m = fmaxf(m, __shfl_xor_sync(0xffffffffu, m, 2));
        float sum = 0.f;
#pragma unroll
        for (int i = 0; i < 10; i++) { sc[i] = ex2_approx((sc[i] - m) * 1.4426950408889634f); sum += sc[i]; }
        sum += __shfl_xor_sync(0xffffffffu, sum, 1);
        sum += __shfl_xor_sync(0xffffffffu, sum, 2);
        const float inv = rcp_approx(sum);
        sts128(PT + w * 512 + lane * 16, pack_bf16(sc[2] * inv, sc[3] * inv), pack_bf16(sc[4] * inv, sc[5] * inv),
               pack_bf16(sc[6] * inv, sc[7] * inv), pack_bf16(sc[8] * inv, sc[9] * inv));
        sts32(PT + 2048 + lane * 16 + w * 4, pack_bf16(sc[0] * inv, sc[1] * inv));
        PROF(1, 10);
        if (last) {
          uint32_t vm[2][2];
          mbar_spin(B_VM, s & 1);
          lds64(vm[0], VM + t7 * 8); lds64(vm[1], VM + 1024 + t7 * 8);
          named_bar_sync(NB_W1, 128);
          tok_pv(s, vm);
          fence_proxy_async_smem();
          named_bar_sync(NB_W1, 128);
          if (warp == 0) { if (elect_one()) { o_store(s - 1); o_store(s); o_done(s); } }
          break;
        }
      }
      if (warp == 0) {
        if (elect_one()) tma_store_wait_read();
        __syncwarp();
        named_bar_arrive(NB_CF, 160);
        if (s > 0 && (s & 3) == 0) { if (elect_one()) o_done(s - 1); }
      }
      refill();
      PROF(1, 11);
    }
    {
      const uint32_t ph = (s + 1) & 1;
      float x0[16], x1[16];
      mbar_spin(B_XN, ph);
      named_bar_sync(NB_ST, 256);
      PROF(1, 12);
      wg_fence();
#pragma unroll
      for (int c = 0; c < 6; c++) {
        if (c == 2) { mbar_spin(B_XN + 8, ph); wg_fence(); }
#pragma unroll
        for (int u = 0; u < 4; u++) {
          wgmma_rs_n32(x0, wr[c][0][u], xn_desc(c < 2 ? 10 + c : c - 2, u), (c | u) != 0);
          wgmma_rs_n32(x1, wr[c][1][u], xn_desc(c < 2 ? 10 + c : c - 2, u), (c | u) != 0);
        }
      }
      wg_commit();
      OPQ;
      named_bar_sync(NB_DU, 256);
      wg_wait<0>();
      PROF(1, 13);
      const uint32_t tb = ISV ? (ph ? VX2 : VX) : QK;
      tok_store<ISV, 1, true>(x1, tb, tid);
      tok_store<ISV, 0, true>(x0, tb, tid);
      if (ISV && s + 2 < cfg::NSEG) {
        fence_proxy_async_smem();
        named_bar_sync(NB_W1, 128);
        if (warp >= 2) {
          if (s >= 0) mbar_spin(B_PF, s & 1);
          const uint32_t peer = warp == 2 ? peer0 : peer1;
          if (elect_one()) bulk_s2s(peer + VX, tb, 8192, peer + B_VX);
        }
      }
      wsa = WS + ((mi >> 1) * 8 + mr) * 128 + (((2 * w + (mi & 1)) ^ mr) << 4);
      mba = MEMB + lane * 16;
      PIN(wsa); PIN(mba);
      proj_mem_prefetch<1>(ta, wsa);
      PROF(1, 14);
      if (s < 0) mbar_wait(B_WO, 0);
      named_bar_sync(NB_M1, 256);
    }
  }
}

template <bool ISV, int WG>
__device__ __forceinline__ void f_main(const FParams& P, const int h, const int rank) {
  using namespace fk;
  const uint32_t self = mapa(0, rank);
  SMAP;
  const int tid = __shfl_sync(0xffffffffu, threadIdx.x, threadIdx.x & 31);
  const int tile0 = rank * 22, ntile = ISV ? 20 : 22;
  const CUtensorMap* m0 = ISV ? &P.wv : &P.wq;
  const CUtensorMap* m1 = ISV ? &P.wv : &P.wk;
  const int col0 = h * 128 + (ISV ? 0 : 64 * rank), col1 = h * 128 + (ISV ? 64 : 64 * rank);
  WRegs wr;
  uint32_t sel = 0;
  {
    OPQ;
    const uint32_t a = SM0 + WG * 16384 + ((mi >> 1) * 8 + mr) * 128 + (((2 * w + (mi & 1)) ^ mr) << 4);
#pragma unroll
    for (int i = 0; i < 6; i++) {
      mbar_wait(B_PB + 8 * i, 0);
      PRO(8 + i);
#pragma unroll
      for (int T = 0; T < 2; T++)
#pragma unroll
        for (int u = 0; u < 4; u++) ldsm4t(wr[i][T][u], a + i * 32768 + T * 8192 + u * 2048);
      named_bar_sync(NB_C, 256);
      if (WG == 1 && w == (i & 3)) {
        if (elect_one()) {
          if (i <= 2 && i + PRE_G < 6) {
#pragma unroll 1
            for (int n = 2 * (i + PRE_G); n < (i == 2 ? 12 : 2 * (i + PRE_G) + 2); n++) {
              const int ii = n >> 1, row = Chunks<ISV>::rf(n & 1, ii) * 64;
              if (!(n & 1)) mbar_expect_tx(B_PB + 8 * ii, 32768);
              tma_load_2d(SM0 + n * 16384, m0, col0, row, B_PB + 8 * ii);
              tma_load_2d(SM0 + n * 16384 + 8192, m1, col1, row, B_PB + 8 * ii);
            }
          }
          if (i == 3 || i == 4) {
            const int p0 = i == 3 ? 0 : 5, p1 = i == 3 ? 5 : 8;
            mbar_expect_tx(B_W, (p1 - p0) * 8192);
#pragma unroll 1
            for (int p = p0; p < p1; p++) tma_load_2d(WS + p * 8192, (p & 1) ? m1 : m0, (p & 1) ? col1 : col0, (Chunks<ISV>::SC0 + (p >> 1)) * 64, B_W);
          }
          if (i == WO_AT) {
            mbar_expect_tx(B_WO, ntile * 4096);
#pragma unroll 1
            for (int t = 0; t < 5; t++) tma_load_2d(WO + t * 16384, &P.wo, tile0 * 16 + t * 64, h * 128, B_WO);
            if (!ISV) {
              tma_load_2d(WO + 81920, &P.wo16, tile0 * 16 + 320, h * 128, B_WO);
              tma_load_2d(WO + 86016, &P.wo16, tile0 * 16 + 336, h * 128, B_WO);
            }
          }
        }
      }
    }
    PROF2(1);
    if (WG == 0 && w == 1) {
      uint4 v;
#pragma unroll 1
      for (int tries = 0; tries < POLL_TRIES; tries++) {
        asm volatile("ld.acquire.gpu.global.v4.u32 {%0,%1,%2,%3}, [%4];" : "=r"(v.x), "=r"(v.y), "=r"(v.z), "=r"(v.w)
                     : "l"(&g_mask[4 * min(lane, 23)]) : "memory");
        if (__all_sync(0xffffffffu, v.x & v.y & v.z & v.w & 0x100)) break;
        __nanosleep(100);
      }
      if (elect_one()) {
        asm volatile("fence.proxy.async.global;" ::: "memory");
        load_xn(P, 0, self);
      }
      sts128(OB + lane * 16, v.x, v.y, v.z, v.w);
    }
    named_bar_sync(NB_C, 256);
#pragma unroll
    for (int i = 0; i < 3; i++) {
      const int t = min(tile0 + 8 * i + w + (WG ? 0 : 4), 63);
      sel |= ((lds32(OB + ((t >> 1) * 3 + (t & 1)) * 4) >> (h >> 3)) & 1) << (2 * i + 1);
    }
    const uint32_t own = lds32(OB + (3 * h + rank) * 4) >> w, m2 = lds32(OB + (3 * h + 2) * 4) >> w;
    sel |= (own & 1) << 7 | (m2 & 1) << 8 | (m2 & 16) << 5;
  }
  asm volatile("barrier.cluster.wait.aligned;" ::: "memory");
  PRO(14);
  mbar_wait(B_W, 0);
  PRO(15);
  PROF2(4);
  GTSYNC(0);
  PROF2(2);
  KT_END(8);
  if (WG == 0) f_wg0<ISV>(P, wr, h, rank, sel, tid); else f_wg1<ISV>(P, wr, h, rank, sel, tid);
}

__device__ __forceinline__ void f_tail(const FParams& P, const int h, const uint32_t rank) {
  using namespace fk;
  const uint32_t base = mapa(0, rank) + SM0;
  constexpr uint32_t STAGE = 49152, TX = 4 * STAGE, TG = TX + 16384, FULL = TG + 16384, EMPT = FULL + 32, RES = FULL + 64, NOG = FULL + 72;
  const int tid = threadIdx.x, lane = tid & 31, wv = __shfl_sync(0xffffffffu, tid >> 5, 0), wg = wv >> 2;
  const int kq = h & 3, nt = (h >> 2) & 3, mb = TAIL_MB0 + 3 * (h >> 4) + rank;
  __syncthreads();
  if (tid == 0) {
    for (int i = 0; i < 4; i++) { mbar_init(base + FULL + 8 * i, 1); mbar_init(base + EMPT + 8 * i, 24); }
    mbar_init(base + RES, 1);
    fence_barrier_init();
  }
  __syncwarp();
  asm volatile("barrier.cluster.arrive.relaxed.aligned;\nbarrier.cluster.wait.aligned;" ::: "memory");
  KT_START(7);
  auto load_b = [&](int kb) {
    const uint32_t sb = base + (kb & 3) * STAGE + 16384, full = base + FULL + 8 * (kb & 3);
    mbar_expect_tx(full, STAGE);
    tma_load_2d_mc(sb + rank * 8192, &P.tb, nt * 256 + ((rank + kq) & 3) * 64, (kq * 16 + kb) * 64, full, 7);
    if (kb % 3 == rank) tma_load_2d_mc(sb + 3 * 8192, &P.tb, nt * 256 + ((3 + kq) & 3) * 64, (kq * 16 + kb) * 64, full, 7);
  };
  auto load_a = [&](int kb) { tma_load_2d(base + (kb & 3) * STAGE, &P.ta, (kq * 16 + kb) * 64, mb * 128, base + FULL + 8 * (kb & 3)); };
  if (wv == 0) {
    if (elect_one()) {
#pragma unroll 1
      for (int kb = 0; kb < 4; kb++) load_b(kb);
      wait_count(&g_oflag[mb], 32);
      asm volatile("fence.proxy.async.global;" ::: "memory");
#pragma unroll 1
      for (int kb = 0; kb < 4; kb++) load_a(kb);
    }
  } else if (wv == 4) {
    if (elect_one()) {
      const bool nog = ld_strong4(&g_next) == 0;
      sts32(base + NOG, nog);
      if (nog) {
        g_tfix[blockIdx.x] = 1;
        mbar_arrive(base + RES);
      } else {
        wait_count(&g_cnt[3][mb], GATE_CNT);
        asm volatile("fence.proxy.async.global;" ::: "memory");
        mbar_expect_tx(base + RES, 32768);
        tma_load_2d(base + TX, &P.tx, nt * 256 + kq * 64, mb * 128, base + RES);
        tma_load_2d(base + TG, &P.tg, nt * 256 + kq * 64, mb * 128, base + RES);
      }
    }
  }
  __syncwarp();
  float acc[128];
#pragma unroll
  for (int i = 0; i < 128; i++) acc[i] = 0.f;
#pragma unroll 1
  for (int kb = 0; kb < 16; kb++) {
    const uint32_t st = kb & 3, sa = base + st * STAGE + wg * 8192, sb = base + st * STAGE + 16384;
    mbar_wait(base + FULL + 8 * st, (kb >> 2) & 1);
    wg_fence();
#pragma unroll
    for (int k = 0; k < 4; k++) {
      wgmma_ss_n256_tb(acc, make_desc(sa + k * 32, 16, 1024), make_desc(sb + k * 2048, 8192, 1024), 1);
      if (k == 0) {
        wg_commit();
        wg_wait<1>();
        if (kb > 0 && kb <= 12 && lane < 3) mbar_arrive_cluster(base + EMPT + 8 * ((kb - 1) & 3), lane);
        wg_fence();
      }
    }
    wg_commit();
    if (kb >= 2 && kb < 14 && wv == ((kb & 1) << 2)) {
      if (elect_one()) {
        mbar_wait(base + EMPT + 8 * ((kb - 2) & 3), ((kb - 2) >> 2) & 1);
        load_b(kb + 2);
        load_a(kb + 2);
      }
      __syncwarp();
    }
  }
  wg_wait<0>();
#pragma unroll
  for (int j = 1; j < 4; j++) {
    uint4* dst = &g_tpart[((h & ~3) + ((j + kq) & 3)) * 3 + rank][j - 1][0][tid];
#pragma unroll
    for (int i = 0; i < 4; i++) {
      const float* a = &acc[32 * j + 8 * i];
      dst[i * 256] = make_uint4(pack_bf16(a[0], a[1]), pack_bf16(a[2], a[3]), pack_bf16(a[4], a[5]), pack_bf16(a[6], a[7]));
    }
  }
  __syncthreads();
  if (tid == 0) asm volatile("st.release.gpu.global.u32 [%0], 1;" ::"l"(&g_tflag[blockIdx.x]) : "memory");
  if (wv == 1) {
#pragma unroll 1
    for (int tries = 0; tries < POLL_TRIES; tries++) {
      uint32_t v;
      asm volatile("ld.acquire.gpu.global.u32 %0, [%1];" : "=r"(v) : "l"(&g_tflag[((h & ~3) + (lane & 3)) * 3 + rank]) : "memory");
      if (__all_sync(0xffffffffu, v)) break;
    }
  }
  mbar_wait(base + RES, 0);
  __syncthreads();
  const bool nog = lds32(base + NOG);
  uint4 pt[3][4];
#pragma unroll
  for (int j = 0; j < 3; j++)
#pragma unroll
    for (int i = 0; i < 4; i++) pt[j][i] = __ldcg(&g_tpart[blockIdx.x][j][i][tid]);
  const uint32_t xa = base + TX + (wv * 16 + ((lane >> 3) & 1) * 8 + (lane & 7)) * 128 + (((lane >> 4) ^ (lane & 7)) << 4);
#pragma unroll
  for (int i = 0; i < 4; i++) {
    uint32_t x[4], g[4], o[4];
    ldsm4(x, xa ^ (i << 5));
    ldsm4(g, (xa ^ (i << 5)) + 16384);
#pragma unroll
    for (int k = 0; k < 4; k++) {
      const uint32_t p0 = (&pt[0][i].x)[k], p1 = (&pt[1][i].x)[k], p2 = (&pt[2][i].x)[k];
      const uint32_t sv = pack_bf16((acc[8 * i + 2 * k] + bf_lo(p0)) + (bf_lo(p1) + bf_lo(p2)),
                                    (acc[8 * i + 2 * k + 1] + bf_hi(p0)) + (bf_hi(p1) + bf_hi(p2)));
      o[k] = nog ? sv : add_bf16x2(x[k], mul_bf16x2(sv, g[k]));
    }
    stsm4(xa ^ (i << 5), o[0], o[1], o[2], o[3]);
  }
  fence_proxy_async_smem();
  __syncthreads();
  if (tid == 0) {
    tma_store_2d(&P.tout, base + TX, nt * 256 + kq * 64, mb * 128);
    tma_store_commit();
    tma_store_wait_read();
  }
  KT_END(7);
}

__global__ void __launch_bounds__(256, 1) f_kernel(const __grid_constant__ FParams P) {
  using namespace fk;
  extern __shared__ __align__(1024) uint8_t smem_f[];
  uint32_t rank;
  asm("mov.u32 %0, %%cluster_ctarank;" : "=r"(rank));
  const int h = blockIdx.x / 3;
  if (smem_u32(smem_f) != mapa(0, rank) + SM0) return;
  PROF2(0);
  KT_START(1);
  KT_START(0);
  {
    const bool isv = rank == 2;
    const uint32_t self = mapa(0, rank);
    SMAP;
    const int tid = threadIdx.x, lane = tid & 31, wv = __shfl_sync(0xffffffffu, tid >> 5, 0);
    PRO(0);
    const int row0 = blockIdx.x * 8 + wv;
    const bool third = row0 + 1536 < cfg::S;
    uint32_t cur[1][16], raw[2][16];
    load_row16(cur[0], P.x + (size_t)row0 * cfg::D, lane);
    load_row16(raw[0], P.x + (size_t)(row0 + 768) * cfg::D, lane);
    load_row16(raw[1], P.x + (size_t)(row0 + (third ? 1536 : 0)) * cfg::D, lane);
    const CUtensorMap* m0 = isv ? &P.wv : &P.wq;
    const CUtensorMap* m1 = isv ? &P.wv : &P.wk;
    const int col0 = h * 128 + (isv ? 0 : 64 * rank), col1 = h * 128 + (isv ? 64 : 64 * rank);
    const int sc0 = isv ? Chunks<true>::SC0 : Chunks<false>::SC0;
    if (wv == 1) {
      const uint32_t off = (blockIdx.x * 32 + lane) * 688;
      if (off < cfg::D * cfg::D * 2) l2_prefetch(reinterpret_cast<const char*>(P.w1) + off, min(688u, cfg::D * cfg::D * 2 - off));
    }
    if (wv == 0) {
      if (elect_one()) {
        for (int i = 0; i < 2; i++) mbar_init(B_XN + 8 * i, 1);
        for (int i = 0; i < 4; i++) mbar_init(B_H2 + 8 * i, 1);
        mbar_init(B_SM, isv ? 1 : 6);
        mbar_init(B_VM, isv ? 8 : 1);
        mbar_init(B_VX, 1);
        mbar_init(B_ST, 1);
        mbar_init(B_PF, 2);
        for (int i = 0; i < 6; i++) mbar_init(B_PB + 8 * i, 1);
        mbar_init(B_W, 2);
        mbar_init(B_WO, 1);
        fence_barrier_init();
        mbar_expect_tx(B_SM, isv ? 2 * SP_SRC : SP_SRC);
        if (isv) mbar_expect_tx(B_ST, 7168);
        else { mbar_expect_tx(B_VM, 2048); mbar_expect_tx(B_VX, 8192); }
      }
    }
    const int j = 2 * h + rank;
    if (lane == 0) {
      const uint2 b = probe_pair(P.xch + (isv ? H1_BYTES + wv * 8192 + h * 128 : j * 32768 + (wv & 3) * 8192 + (wv >> 2) * 128),
                                 isv ? EMPTY : 0, PROBE + 64, P.nprobe);
      sts64(PROBE + wv * 8, b.x, b.y);
    }
    PROF2(3);
    PRO(1);
    __syncwarp();
    if (wv == 0) {
      asm volatile("{\n.reg .pred p;\nsetp.eq.u32 p, %0, %1;\n@p st.shared.u32 [%2], %0;\n}" ::"r"(raw[1][15]), "r"(cur[0][0] ^ raw[0][15]), "r"(PROBE + 64) : "memory");
      if (elect_one()) {
#pragma unroll 1
        for (int n = 0; n < 2 * PRE_G; n++) {
          const int i = n >> 1, g = n & 1, row = (g ? 10 + i : (i < sc0 ? i : 4 + i)) * 64;
          if (!g) mbar_expect_tx(B_PB + 8 * i, 32768);
          tma_load_2d(SM0 + n * 16384, m0, col0, row, B_PB + 8 * i);
          tma_load_2d(SM0 + n * 16384 + 8192, m1, col1, row, B_PB + 8 * i);
        }
      }
    }
    __syncthreads();
    PRO(2);
    asm volatile("barrier.cluster.arrive.relaxed.aligned;" ::: "memory");
    PRO(3);
    uint32_t pb[2], pc[2];
    lds64(pb, PROBE + (lane & 7) * 8);
    lds64(pc, PROBE + ((lane & 7) ^ 4) * 8);
    const uint32_t mask = __ballot_sync(0xffffffffu, isv ? pb[1] < pb[0] : min(pb[1], pc[1]) < min(pb[0], pc[0])) & (isv ? 255 : 15);
    if (!isv) {
#pragma unroll
      for (int i = 0; i < 4; i++) st_pub128(P.xch + j * 32768 + i * 8192 + ((mask >> i) & 1) * 4096 + tid * 16, 0);
      if (wv < 4) st_pub64(P.xch + H1_BYTES + (wv >> 1) * 32768 + (j >> 4) * 8192 + (wv & 1) * 4096 + (j & 15) * 256 + lane * 8, EMPTY, EMPTY);
    }
    if (blockIdx.x == 2) {
      if (tid < 96) (&g_cnt[0][0])[tid] = 0;
      else if (tid < 112) g_oflag[tid - 96] = 0;
      else if (tid == 112) g_next = 0;
      else if (tid >= 128 && tid < 224) { g_tflag[tid - 128] = 0; g_tfix[tid - 128] = 0; }
    }
#pragma unroll 1
    for (int it = 0; it < (third ? 6 : 4); it++) {
      ln_regs<1>(cur);
      store_row16(cur[0], ((it & 1) ? P.xn2 : P.xn_ptr) + (size_t)(row0 + (it >> 1) * 768) * cfg::D, lane);
      if (it == 0) PRO(4);
      if (it & 1) {
#pragma unroll
        for (int i = 0; i < 16; i++) { cur[0][i] = raw[0][i]; raw[0][i] = raw[1][i]; }
      }
    }
    PRO(5);
    __syncthreads();
    PRO(6);
    if (tid == 64) {
      __threadfence();
      PRO(7);
      pdl_launch_dependents();
      st_pub32(&g_mask[blockIdx.x], 0x100 | mask);
    }
    KT_END(0);
    __syncwarp();
  }
  const int wg = __shfl_sync(0xffffffffu, threadIdx.x >> 7, 0);
  if (rank == 2) { if (wg == 0) f_main<true, 0>(P, h, 2); else f_main<true, 1>(P, h, 2); }
  else { if (wg == 0) f_main<false, 0>(P, h, rank); else f_main<false, 1>(P, h, rank); }
  PROF2(5);
  GTSYNC(1);
  KT_END(1);
  __syncwarp();
  f_tail(P, h, rank);
}

#define GCL 1
namespace gk {
enum { T_B1 = 0, T_B2 = 1, T_B3 = 2, T_B4 = 3, T_O = 4, T_LN = 5, T_END = 7 };
constexpr int NST = 3, STAGE = 49152, MAXITEMS = 512, NEW = 3;
constexpr uint32_t OUTB = NST * STAGE, BARS = OUTB + 65536;
constexpr uint32_t B_FULL = BARS, B_EMPTY = BARS + 32, B_ITEM = BARS + 64, B_FILL = BARS + 128, B_FREE = BARS + 160, ITEMS = BARS + 192;
constexpr int SMEM = BARS + 256;
static_assert(GATE_CNT == 4 * NEW && T_B4 == 3, "gate counter");
}
struct GParams {
  CUtensorMap a[5], b[5];
  bf16* c[5];
  const bf16* r[5];
  bf16* x1n;
  int nitems, lnpos;
  uint16_t items[gk::MAXITEMS];
};
#define ILOG(i)

__device__ __forceinline__ void tma_load_3d_mc(uint32_t dst, const CUtensorMap* map, int x, int y, int z, uint32_t bar) {
  asm volatile("cp.async.bulk.tensor.3d.shared::cluster.global.mbarrier::complete_tx::bytes.multicast::cluster "
               "[%0], [%1, {%3, %4, %5}], [%2], %6;"
               ::"r"(dst), "l"(map), "r"(bar), "r"(x), "r"(y), "r"(z), "h"((uint16_t)3) : "memory");
}
__device__ __forceinline__ float tanh_approx(float x) { float y; asm("tanh.approx.f32 %0, %1;" : "=f"(y) : "f"(x)); return y; }
__global__ void __launch_bounds__(384, 1) g_kernel(const __grid_constant__ GParams P) {
  using namespace gk;
  extern __shared__ __align__(1024) uint8_t smem_g[];
  const uint32_t base = smem_u32(smem_g);
  const int tid = threadIdx.x, warp = __shfl_sync(0xffffffffu, tid >> 5, 0), lane = tid & 31;
  const int rank = blockIdx.x % GCL;
  KT_START(2);
  if (tid == 0) {
    for (int s = 0; s < NST; s++) { mbar_init(base + B_FULL + 8 * s, 1); mbar_init(base + B_EMPTY + 8 * s, 8 * GCL); }
    for (int s = 0; s < 8; s++) mbar_init(base + B_ITEM + 8 * s, 1);
    for (int s = 0; s < 2; s++) { mbar_init(base + B_FILL + 8 * s, 4); mbar_init(base + B_FREE + 8 * s, NEW); }
    fence_barrier_init();
  }
  __syncthreads();
  if (GCL > 1) cluster_sync();
  auto release = [&](uint32_t st) {
    if (GCL > 1) { if (lane < GCL) mbar_arrive_cluster(base + B_EMPTY + 8 * st, lane); }
    else if (lane == 0) mbar_arrive(base + B_EMPTY + 8 * st);
  };
  auto get_item = [&](int q) {
    mbar_wait(base + B_ITEM + 8 * (q & 7), (q >> 3) & 1);
    return lds32(base + ITEMS + 4 * (q & 7));
  };

  if (warp >= 8) {
   if (warp == 8) {
    if (lane == 0) {
      uint32_t st = 0, ph = 1;
#pragma unroll 1
      for (int q = 0;; q++) {
        if (GCL > 1) mbar_expect_tx(base + B_ITEM + 8 * (q & 7), 4);
        if (rank == 0) {
          const unsigned idx = atomicAdd(&g_next, 1), ln = idx - P.lnpos;
          const uint32_t v = (idx < (unsigned)P.nitems ? P.items[idx] : T_END) | (ln < 64 / GCL ? (ln + 1) << 16 : 0);
          if (GCL > 1) {
#pragma unroll
            for (int r = 0; r < GCL; r++) st_async32(mapa(base + ITEMS + 4 * (q & 7), r), v, mapa(base + B_ITEM + 8 * (q & 7), r));
          } else {
            sts32(base + ITEMS + 4 * (q & 7), v);
            mbar_arrive(base + B_ITEM + 8 * (q & 7));
          }
        }
        const uint32_t item = get_item(q);
        const int type = item & 7, mb = ((item >> 3) & 15) + rank, nt = (item >> 7) & 15;
        ILOG(1);
        if (type == T_END) break;
        if (type == T_B2) {
          wait_count(&g_cnt[T_B1][max(mb - 1, 0)], 4 * NEW); wait_count(&g_cnt[T_B1][mb], 4 * NEW); wait_count(&g_cnt[T_B1][min(mb + 1, 15)], 4 * NEW);
        } else if (type == T_B3) wait_count(&g_cnt[T_LN][mb], 32);
        else if (type == T_B4) wait_count(&g_cnt[T_B3][mb], 14 * NEW);
        else if (type == T_O) wait_count(&g_oflag[mb], 32);
        asm volatile("fence.proxy.async.global;" ::: "memory");
        ILOG(2);
        const CUtensorMap *ma = &P.a[type], *mbm = &P.b[type];
        const int nkb = type == T_B4 ? cfg::F / 64 : type == T_O ? cfg::HD / 64 : cfg::D / 64;
#pragma unroll 1
        for (int kb = 0; kb < nkb; kb++) {
          mbar_wait(base + B_EMPTY + 8 * st, ph);
          const uint32_t sa = base + st * STAGE, full = base + B_FULL + 8 * st;
          mbar_expect_tx(full, STAGE);
          int arow = mb * 128;
          if (type == T_B2) { const int qd = kb >> 2; arow += (qd == 0) ? -1 : (qd == 1) ? 1 : (qd == 2) ? -2 : 2; }
          if (GCL > 1) tma_load_3d_mc(sa + 16384 + rank * 16384, mbm, 0, kb * 64, nt * 4 + rank * 2, full);
          else tma_load_3d(sa + 16384, mbm, 0, kb * 64, nt * 4, full);
          tma_load_2d(sa, ma, kb * 64, arow, full);
          if (++st == NST) { st = 0; ph ^= 1; }
        }
      }
    }
   } else {
    const int ew = warp - 9;
#pragma unroll 1
    for (int q = 0;; q++) {
      const uint32_t item = get_item(q);
      const int type = item & 7, mb = ((item >> 3) & 15) + rank, nt = (item >> 7) & 15;
      if (type == T_END) break;
      if (type == T_O) wait_count(&g_cnt[T_B4][mb], 4 * NEW);
      const int ldc = type == T_B3 ? cfg::F : cfg::D;
      bf16* cp = P.c[type] + (size_t)mb * 128 * ldc + nt * 256 + lane * 8;
      const size_t roff = (size_t)mb * 128 * cfg::D + nt * 256 + lane * 8;
      const bf16 *rp = P.r[type] + roff, *gp = P.c[T_B4] + roff;
      const bool res = type == T_B2 || type >= T_B4, act = type != T_B2 && type != T_O;
      const float c1 = type == T_B4 ? 0.f : 0.035677408136300125f, c0 = type == T_B4 ? 0.5f : 0.7978845608028654f;
      uint32_t yn[4][4];
      uint4 rn[4], gn[4];
      auto fetch_res = [&](int grp) {
#pragma unroll
        for (int i = 0; i < 4; i++) {
          if (res) rn[i] = __ldcg(reinterpret_cast<const uint4*>(rp + (grp * 4 + i) * cfg::D));
          if (type == T_O) gn[i] = __ldcg(reinterpret_cast<const uint4*>(gp + (grp * 4 + i) * cfg::D));
        }
      };
      auto fetch_y = [&](int grp) {
#pragma unroll
        for (int i = 0; i < 4; i++) lds128(yn[i], base + OUTB + (grp * 4 + i) * 512 + ((lane ^ ((grp * 4 + i) & 7)) << 4));
      };
      if (type == T_B4) wait_count(&g_cnt[T_B2][mb], 4 * NEW);
      fetch_res(ew);
      mbar_wait(base + B_FILL, q & 1);
      fetch_y(ew);
#pragma unroll 1
      for (int grp = ew; grp < 32; grp += NEW) {
        uint32_t y[4][4];
#pragma unroll
        for (int i = 0; i < 4; i++) {
#pragma unroll
          for (int k = 0; k < 4; k++) y[i][k] = yn[i][k];
          if (type == T_O) {
            y[i][0] = mul_bf16x2(y[i][0], gn[i].x); y[i][1] = mul_bf16x2(y[i][1], gn[i].y);
            y[i][2] = mul_bf16x2(y[i][2], gn[i].z); y[i][3] = mul_bf16x2(y[i][3], gn[i].w);
          }
          if (res) {
            y[i][0] = add_bf16x2(y[i][0], rn[i].x); y[i][1] = add_bf16x2(y[i][1], rn[i].y);
            y[i][2] = add_bf16x2(y[i][2], rn[i].z); y[i][3] = add_bf16x2(y[i][3], rn[i].w);
          }
        }
        const int nx = grp + NEW;
        if (nx < 32) {
          fetch_res(nx);
          if (nx >= 16 && grp < 16) {
            __syncwarp();
            if (lane == 0) mbar_arrive(base + B_FREE);
            mbar_wait(base + B_FILL + 8, q & 1);
          }
          fetch_y(nx);
        }
        if (act) {
#pragma unroll
          for (int i = 0; i < 4; i++)
#pragma unroll
            for (int k = 0; k < 4; k++) {
              const float v0 = bf_lo(y[i][k]), v1 = bf_hi(y[i][k]);
              const float t0 = tanh_approx(v0 * fmaf(v0 * c1, v0, c0)), t1 = tanh_approx(v1 * fmaf(v1 * c1, v1, c0));
              const float h0 = 0.5f * v0, h1 = 0.5f * v1;
              y[i][k] = pack_bf16(fmaf(h0, t0, h0), fmaf(h1, t1, h1));
            }
        }
#pragma unroll
        for (int i = 0; i < 4; i++)
          *reinterpret_cast<uint4*>(cp + (size_t)(grp * 4 + i) * ldc) = make_uint4(y[i][0], y[i][1], y[i][2], y[i][3]);
      }
      __syncwarp();
      if (lane == 0) mbar_arrive(base + B_FREE + 8);
      if (type != T_O) {
        __threadfence();
        __syncwarp();
        if (lane == 0) atomicAdd(&g_cnt[type][mb], 1);
      }
      if (tid == 288) ILOG(7);
    }
   }
   __syncwarp();
   pdl_wait();
#pragma unroll 1
   for (int c = blockIdx.x; c < 96; c += gridDim.x) {
     if (__ldcg(&g_tfix[c]) == 0) continue;
     const int hh = c / 3, mb = TAIL_MB0 + 3 * (hh >> 4) + c % 3;
     wait_count(&g_cnt[T_B4][mb], GATE_CNT);
#pragma unroll 1
     for (int i = tid - 256; i < 1024; i += 128) {
       const size_t off = (size_t)(mb * 128 + (i >> 3)) * cfg::D + (hh & 15) * 64 + (i & 7) * 8;
       const uint4 sv = __ldcg(reinterpret_cast<const uint4*>(P.c[T_O] + off)), gv = __ldcg(reinterpret_cast<const uint4*>(P.c[T_B4] + off)),
                   xv = __ldcg(reinterpret_cast<const uint4*>(P.r[T_O] + off));
       *reinterpret_cast<uint4*>(P.c[T_O] + off) = make_uint4(add_bf16x2(xv.x, mul_bf16x2(sv.x, gv.x)), add_bf16x2(xv.y, mul_bf16x2(sv.y, gv.y)),
                                                              add_bf16x2(xv.z, mul_bf16x2(sv.z, gv.z)), add_bf16x2(xv.w, mul_bf16x2(sv.w, gv.w)));
     }
   }
   if (GCL > 1) cluster_sync();
  } else {
    const int wg = warp >> 2;
    const uint32_t outa = base + OUTB + (warp * 16 + ((lane >> 3) & 1) * 8 + (lane & 7)) * 512 + (((lane >> 4) ^ (lane & 7)) << 4);
    uint32_t st = 0, ph = 0;
    float acc[128];
#pragma unroll 1
    for (int q = 0;; q++) {
      const uint32_t item = get_item(q);
      const int type = item & 7;
      if (type == T_END) break;
      if (item >> 16) {
        const int ln = (item >> 16) - 1, lb = (ln >> 2) * GCL + rank;
        const size_t row = (size_t)(lb * 128 + (ln & 3) * 32 + warp * 4) * cfg::D;
        wait_count(&g_cnt[T_B2][lb], 4 * NEW);
        uint32_t raw[4][16];
#pragma unroll
        for (int r = 0; r < 4; r++) load_row16(raw[r], P.c[T_B2] + row + r * cfg::D, lane);
        ln_regs<4>(raw);
#pragma unroll
        for (int r = 0; r < 4; r++) store_row16(raw[r], P.x1n + row + r * cfg::D, lane);
        __threadfence();
        __syncwarp();
        if (lane == 0) atomicAdd(&g_cnt[T_LN][lb], 1);
        if (tid == 0) ILOG(6);
#pragma unroll
        for (int i = 0; i < 128; i++) acc[i] = 0.f;
      }
      const int nkb = type == T_B4 ? cfg::F / 64 : type == T_O ? cfg::HD / 64 : cfg::D / 64;
      uint32_t prev = 0;
#pragma unroll 1
      for (int kb = 0; kb < nkb; kb++) {
        if (kb == 0) mbar_wait(base + B_FULL + 8 * st, ph); else mbar_spin(base + B_FULL + 8 * st, ph);
        if (kb == 0 && tid == 0) ILOG(3);
        const uint32_t sa = base + st * STAGE + wg * 8192, sb = base + st * STAGE + 16384;
        wg_fence();
#pragma unroll
        for (int k = 0; k < 4; k++) {
          wgmma_ss_n256_tb(acc, make_desc(sa + k * 32, 16, 1024), make_desc(sb + k * 2048, 8192, 1024), (kb | k) != 0);
          if (k == 0) {
            wg_commit();
            wg_wait<1>();
            if (kb > 0) release(prev);
            wg_fence();
          }
        }
        wg_commit();
        prev = st;
        if (++st == NST) { st = 0; ph ^= 1; }
      }
      if (q > 0) mbar_wait(base + B_FREE + 8 * wg, (q - 1) & 1);
      wg_wait<0>();
      if (tid == 0) ILOG(4);
      release(prev);
#pragma unroll
      for (int j = 0; j < 16; j++)
        stsm4((outa ^ ((j & 3) << 5)) + (j >> 2) * 128, pack_bf16(acc[8 * j], acc[8 * j + 1]), pack_bf16(acc[8 * j + 2], acc[8 * j + 3]),
              pack_bf16(acc[8 * j + 4], acc[8 * j + 5]), pack_bf16(acc[8 * j + 6], acc[8 * j + 7]));
      __syncwarp();
      if (lane == 0) mbar_arrive(base + B_FILL + 8 * wg);
      if (tid == 0) ILOG(5);
    }
    KT_END(2);
    if (GCL > 1) cluster_sync();
  }
}

__device__ bf16 g_xn[cfg::S * cfg::D];
__device__ bf16 g_xn2[cfg::S * cfg::D];
__device__ bf16 g_h[cfg::S * cfg::D];
__device__ bf16 g_x1[cfg::S * cfg::D];
__device__ bf16 g_x1n[cfg::S * cfg::D];
__device__ bf16 g_u[cfg::S * cfg::F];
__device__ bf16 g_g[cfg::S * cfg::D];
__device__ bf16 g_o[cfg::S * cfg::HD];

typedef CUresult (*PFN_encodeTiled)(CUtensorMap*, CUtensorMapDataType, cuuint32_t, void*, const cuuint64_t*,
                                    const cuuint64_t*, const cuuint32_t*, const cuuint32_t*, CUtensorMapInterleave,
                                    CUtensorMapSwizzle, CUtensorMapL2promotion, CUtensorMapFloatOOBfill);

static PFN_encodeTiled get_encoder() {
  static PFN_encodeTiled fn = nullptr;
  if (!fn) {
    void* p = nullptr;
    cudaDriverEntryPointQueryResult st;
    cudaGetDriverEntryPoint("cuTensorMapEncodeTiled", &p, cudaEnableDefault, &st);
    fn = (PFN_encodeTiled)p;
  }
  return fn;
}
static CUtensorMap make_map(const void* ptr, int rows, int cols, int box_rows, int box_cols, int swizzle_bytes) {
  CUtensorMap m;
  cuuint64_t dims[2] = {(cuuint64_t)cols, (cuuint64_t)rows};
  cuuint64_t strides[1] = {(cuuint64_t)cols * 2};
  cuuint32_t box[2] = {(cuuint32_t)box_cols, (cuuint32_t)box_rows};
  cuuint32_t estr[2] = {1, 1};
  CUtensorMapSwizzle sw = swizzle_bytes == 128 ? CU_TENSOR_MAP_SWIZZLE_128B
                        : swizzle_bytes == 64 ? CU_TENSOR_MAP_SWIZZLE_64B
                        : swizzle_bytes == 32 ? CU_TENSOR_MAP_SWIZZLE_32B : CU_TENSOR_MAP_SWIZZLE_NONE;
  get_encoder()(&m, CU_TENSOR_MAP_DATA_TYPE_BFLOAT16, 2, const_cast<void*>(ptr), dims, strides, box, estr,
                CU_TENSOR_MAP_INTERLEAVE_NONE, sw, CU_TENSOR_MAP_L2_PROMOTION_L2_128B, CU_TENSOR_MAP_FLOAT_OOB_FILL_NONE);
  return m;
}
static CUtensorMap make_map3(const void* ptr, int rows, int cols, int box_rows, int nblk) {
  CUtensorMap m;
  cuuint64_t dims[3] = {64, (cuuint64_t)rows, (cuuint64_t)(cols / 64)};
  cuuint64_t strides[2] = {(cuuint64_t)cols * 2, 128};
  cuuint32_t box[3] = {64, (cuuint32_t)box_rows, (cuuint32_t)nblk};
  cuuint32_t estr[3] = {1, 1, 1};
  get_encoder()(&m, CU_TENSOR_MAP_DATA_TYPE_BFLOAT16, 3, const_cast<void*>(ptr), dims, strides, box, estr,
                CU_TENSOR_MAP_INTERLEAVE_NONE, CU_TENSOR_MAP_SWIZZLE_128B, CU_TENSOR_MAP_L2_PROMOTION_L2_128B,
                CU_TENSOR_MAP_FLOAT_OOB_FILL_NONE);
  return m;
}
template <class T> static T* sym(T& s) { void* p = nullptr; cudaGetSymbolAddress(&p, s); return (T*)p; }
#define SYM(name) ((bf16*)[] { void* p = nullptr; cudaGetSymbolAddress(&p, name); return p; }())

#define G_CTAS 36
#define LN_POS 64
static int build_items(uint16_t* it) {
  using namespace gk;
  int n = 0;
  auto add = [&](int type, int nrows, int ncols) {
    for (int mb = 0; mb < nrows; mb += GCL) for (int nt = 0; nt < ncols; nt++) it[n++] = (uint16_t)(type | mb << 3 | nt << 7);
  };
  add(T_B1, 16, 4); add(T_B2, 16, 4); add(T_B3, 16, 14); add(T_B4, 16, 4); add(T_O, TAIL_MB0, 4);
  return n;
}

extern "C" void kernel_launch(void* const* d_in, const int* in_sizes, int n_in, void* d_out, int out_size) {
  using namespace cfg;
  const bf16* x = (const bf16*)d_in[0];
  const bf16* mem0 = (const bf16*)d_in[1];
  const bf16* Wq = (const bf16*)d_in[2];
  const bf16* Wk = (const bf16*)d_in[3];
  const bf16* Wv = (const bf16*)d_in[4];
  const bf16* Wo = (const bf16*)d_in[5];
  const bf16* w1 = (const bf16*)d_in[8];
  const bf16* w2 = (const bf16*)d_in[9];
  const bf16* w3 = (const bf16*)d_in[10];
  const bf16* w4 = (const bf16*)d_in[11];
  bf16* out = (bf16*)d_out;
  cudaStream_t st = cudaStreamPerThread;

  bf16 *xn = SYM(g_xn), *xn2 = SYM(g_xn2), *hb = SYM(g_h), *x1 = SYM(g_x1), *x1n = SYM(g_x1n), *u = SYM(g_u),
       *g = SYM(g_g), *o = SYM(g_o);

  {
    cudaFuncSetAttribute(f_kernel, cudaFuncAttributeMaxDynamicSharedMemorySize, fk::SMEM);
    FParams P;
    P.wq = make_map(Wq, D, HD, 64, 64, 128); P.wk = make_map(Wk, D, HD, 64, 64, 128); P.wv = make_map(Wv, D, HD, 64, 64, 128);
    P.wo = make_map(Wo, HD, D, 128, 64, 128); P.wo16 = make_map(Wo, HD, D, 128, 16, 32); P.xn = make_map3(xn, S, D, 32, 4); P.xn12 = make_map3(xn, S, D, 32, 12); P.o = make_map3(o, S, HD, 32, 2);
    P.ta = make_map(o, S, HD, 128, 64, 128); P.tb = make_map(Wo, HD, D, 64, 64, 128); P.tx = make_map(x, S, D, 128, 64, 128);
    P.tg = make_map(g, S, D, 128, 64, 128); P.tout = make_map(out, S, D, 128, 64, 128);
    P.mem0 = mem0;
    P.nprobe = PROBE_N;
    P.x = x; P.w1 = w1; P.xn_ptr = xn; P.xn2 = xn2;
    P.xch = (char*)(((uintptr_t)SYM(g_xch) + 8191) & ~(uintptr_t)8191);
    cudaLaunchConfig_t cfg = {};
    cfg.gridDim = dim3(96); cfg.blockDim = dim3(256); cfg.dynamicSmemBytes = fk::SMEM; cfg.stream = st;
    cudaLaunchAttribute at[2];
    at[0].id = cudaLaunchAttributeClusterDimension;
    at[0].val.clusterDim.x = 3; at[0].val.clusterDim.y = 1; at[0].val.clusterDim.z = 1;
    cfg.attrs = at; cfg.numAttrs = 1;
    cudaLaunchKernelEx(&cfg, f_kernel, P);
  }
  {
    cudaFuncSetAttribute(g_kernel, cudaFuncAttributeMaxDynamicSharedMemorySize, gk::SMEM);
    GParams G;
    const bf16* as[5] = {xn2, hb, x1n, u, o};
    const bf16* bs[5] = {w1, w2, w3, w4, Wo};
    bf16* cs[5] = {hb, x1, u, g, out};
    const bf16* rs[5] = {xn, xn, xn, x1, x};
    const int ks[5] = {D, D, D, F, HD}, ns[5] = {D, D, F, D, D};
    for (int i = 0; i < 5; i++) {
      G.a[i] = make_map(as[i], S, ks[i], 128, 64, 128);
      G.b[i] = make_map3(bs[i], ks[i], ns[i], 64, 4 / GCL);
      G.c[i] = cs[i];
      G.r[i] = rs[i];
    }
    G.x1n = x1n;
    G.nitems = build_items(G.items);
    G.lnpos = LN_POS * 2 / GCL;
    cudaLaunchConfig_t cfg = {};
    cfg.gridDim = dim3(G_CTAS); cfg.blockDim = dim3(384); cfg.dynamicSmemBytes = gk::SMEM; cfg.stream = st;
    cudaLaunchAttribute at[2];
    at[0].id = cudaLaunchAttributeClusterDimension;
    at[0].val.clusterDim.x = GCL; at[0].val.clusterDim.y = 1; at[0].val.clusterDim.z = 1;
    at[1].id = cudaLaunchAttributeProgrammaticStreamSerialization;
    at[1].val.programmaticStreamSerializationAllowed = 1;
    cfg.attrs = at;
    cfg.numAttrs = 2;
    cudaLaunchKernelEx(&cfg, g_kernel, G);
  }
}
```

```cpp
#include <cuda_runtime.h>
#include <cuda_bf16.h>
#include <cuda.h>
#include <stdint.h>

typedef __nv_bfloat16 bf16;

namespace cfg {
constexpr int S = 2048;
constexpr int D = 1024;
constexpr int H = 32;
constexpr int DH = 128;
constexpr int HD = H * DH;
constexpr int M = 8;
constexpr int SEG = 32;
constexpr int NSEG = S / SEG;
constexpr int F = 3584;
}

__device__ __forceinline__ uint32_t smem_u32(const void* p) { return (uint32_t)__cvta_generic_to_shared(p); }

__device__ __forceinline__ void mbar_init(uint32_t bar, uint32_t count) {
  asm volatile("mbarrier.init.shared::cta.b64 [%0], %1;" ::"r"(bar), "r"(count) : "memory");
}
__device__ __forceinline__ void mbar_expect_tx(uint32_t bar, uint32_t bytes) {
  asm volatile("mbarrier.arrive.expect_tx.shared::cta.b64 _, [%0], %1;" ::"r"(bar), "r"(bytes) : "memory");
}
__device__ __forceinline__ void mbar_arrive(uint32_t bar) {
  asm volatile("mbarrier.arrive.shared::cta.b64 _, [%0];" ::"r"(bar) : "memory");
}
__device__ __forceinline__ bool mbar_try(uint32_t bar, uint32_t parity) {
  uint32_t done;
  asm volatile("{\n.reg .pred p;\nmbarrier.try_wait.parity.shared::cta.b64 p, [%1], %2, 20000;\nselp.u32 %0, 1, 0, p;\n}"
               : "=r"(done) : "r"(bar), "r"(parity) : "memory");
  return done != 0;
}
__device__ __forceinline__ bool mbar_try_nohint(uint32_t bar, uint32_t parity) {
  uint32_t done;
  asm volatile("{\n.reg .pred p;\nmbarrier.try_wait.parity.shared::cta.b64 p, [%1], %2;\nselp.u32 %0, 1, 0, p;\n}"
               : "=r"(done) : "r"(bar), "r"(parity) : "memory");
  return done != 0;
}
constexpr int MBAR_TRIES = 4096;
constexpr int POLL_TRIES = 1 << 16;
__device__ __forceinline__ void mbar_wait(uint32_t bar, uint32_t parity) {
#pragma unroll 1
  for (int n = 0; n < MBAR_TRIES; n++)
    if (mbar_try(bar, parity)) break;
}
__device__ __forceinline__ void mbar_wait_fast(uint32_t bar, uint32_t parity) {
#pragma unroll 1
  for (int n = 0; n < (POLL_TRIES << 4); n++)
    if (mbar_try_nohint(bar, parity)) break;
}
__device__ __forceinline__ void fence_barrier_init() { asm volatile("fence.mbarrier_init.release.cluster;" ::: "memory"); }
__device__ __forceinline__ void fence_proxy_async_smem() { asm volatile("fence.proxy.async.shared::cta;" ::: "memory"); }

__device__ __forceinline__ void tma_load_2d(uint32_t dst, const CUtensorMap* map, int x, int y, uint32_t bar) {
  asm volatile("cp.async.bulk.tensor.2d.shared::cluster.global.mbarrier::complete_tx::bytes [%0], [%1, {%3, %4}], [%2];"
               ::"r"(dst), "l"(map), "r"(bar), "r"(x), "r"(y) : "memory");
}
__device__ __forceinline__ void tma_load_3d(uint32_t dst, const CUtensorMap* map, int x, int y, int z, uint32_t bar) {
  asm volatile("cp.async.bulk.tensor.3d.shared::cluster.global.mbarrier::complete_tx::bytes [%0], [%1, {%3, %4, %5}], [%2];"
               ::"r"(dst), "l"(map), "r"(bar), "r"(x), "r"(y), "r"(z) : "memory");
}
__device__ __forceinline__ void tma_store_2d(const CUtensorMap* map, uint32_t src, int x, int y) {
  asm volatile("cp.async.bulk.tensor.2d.global.shared::cta.bulk_group [%0, {%2, %3}], [%1];"
               ::"l"(map), "r"(src), "r"(x), "r"(y) : "memory");
}
__device__ __forceinline__ void tma_store_commit() { asm volatile("cp.async.bulk.commit_group;" ::: "memory"); }
__device__ __forceinline__ void tma_store_wait_all() { asm volatile("cp.async.bulk.wait_group 0;" ::: "memory"); }
__device__ __forceinline__ void tma_store_wait_read() { asm volatile("cp.async.bulk.wait_group.read 0;" ::: "memory"); }
__device__ __forceinline__ void prefetch_tmap(const CUtensorMap* map) {
  asm volatile("prefetch.tensormap [%0];" ::"l"(map) : "memory");
}

__device__ __forceinline__ void wg_fence() { asm volatile("wgmma.fence.sync.aligned;" ::: "memory"); }
__device__ __forceinline__ void wg_commit() { asm volatile("wgmma.commit_group.sync.aligned;" ::: "memory"); }
template <int N> __device__ __forceinline__ void wg_wait() { asm volatile("wgmma.wait_group.sync.aligned %0;" ::"n"(N) : "memory"); }

#define named_bar_sync(id, n) asm volatile("bar.sync %0, %1;" ::"n"(id), "n"(n) : "memory")
#define named_bar_arrive(id, n) asm volatile("bar.arrive %0, %1;" ::"n"(id), "n"(n) : "memory")

__device__ __forceinline__ uint64_t make_desc(uint32_t addr, uint32_t lbo, uint32_t sbo) {
  return (uint64_t)((addr & 0x3FFFF) >> 4) | ((uint64_t)(lbo >> 4) << 16) | ((uint64_t)(sbo >> 4) << 32) | (1ull << 62);
}

__device__ __forceinline__ uint64_t make_desc0(uint32_t addr, uint32_t lbo, uint32_t sbo) {
  return (uint64_t)((addr & 0x3FFFF) >> 4) | ((uint64_t)(lbo >> 4) << 16) | ((uint64_t)(sbo >> 4) << 32);
}

__device__ __forceinline__ uint32_t pack_bf16(float lo, float hi) {
  uint32_t r;
  asm("cvt.rn.bf16x2.f32 %0, %1, %2;" : "=r"(r) : "f"(hi), "f"(lo));
  return r;
}
__device__ __forceinline__ float bf_lo(uint32_t v) { return __uint_as_float(v << 16); }
__device__ __forceinline__ float bf_hi(uint32_t v) { return __uint_as_float(v & 0xFFFF0000u); }
__device__ __forceinline__ float rbf(float v) { return __bfloat162float(__float2bfloat16_rn(v)); }

__device__ __forceinline__ void pdl_launch_dependents() { asm volatile("griddepcontrol.launch_dependents;" ::: "memory"); }
__device__ __forceinline__ void pdl_wait() { asm volatile("griddepcontrol.wait;" ::: "memory"); }

__device__ __forceinline__ float ex2_approx(float x) { float y; asm("ex2.approx.ftz.f32 %0, %1;" : "=f"(y) : "f"(x)); return y; }
__device__ __forceinline__ float rcp_approx(float x) { float y; asm("rcp.approx.ftz.f32 %0, %1;" : "=f"(y) : "f"(x)); return y; }

__device__ __forceinline__ void mul_sigmoid4(float (&v)[4], const float (&t)[4]) {
#pragma unroll
  for (int i = 0; i < 4; i += 2) {
    const float a = 1.0f + ex2_approx(fminf(t[i], 60.0f)), b = 1.0f + ex2_approx(fminf(t[i + 1], 60.0f));
    const float r = rcp_approx(a * b);
    v[i] *= b * r;
    v[i + 1] *= a * r;
  }
}
__device__ __forceinline__ void gelu4(float (&v)[4]) {
  float t[4];
#pragma unroll
  for (int i = 0; i < 4; i++) t[i] = v[i] * fmaf(v[i] * v[i], -0.10294324f, -2.30220819f);
  mul_sigmoid4(v, t);
}
__device__ __forceinline__ void silu4(float (&v)[4]) {
  float t[4];
#pragma unroll
  for (int i = 0; i < 4; i++) t[i] = v[i] * -1.4426950408889634f;
  mul_sigmoid4(v, t);
}

#define KT_START(id)
#define KT_END(id)

__device__ __forceinline__ void wgmma_ss_n256_tb(float (&d)[128], uint64_t da, uint64_t db, int scale_d) {
  asm volatile("{\n.reg .pred p;\nsetp.ne.b32 p, %130, 0;\n"
    "wgmma.mma_async.sync.aligned.m64n256k16.f32.bf16.bf16 "
    "{%0, %1, %2, %3, %4, %5, %6, %7, %8, %9, %10, %11, %12, %13, %14, %15, "
    "%16, %17, %18, %19, %20, %21, %22, %23, %24, %25, %26, %27, %28, %29, %30, %31, "
    "%32, %33, %34, %35, %36, %37, %38, %39, %40, %41, %42, %43, %44, %45, %46, %47, "
    "%48, %49, %50, %51, %52, %53, %54, %55, %56, %57, %58, %59, %60, %61, %62, %63, "
    "%64, %65, %66, %67, %68, %69, %70, %71, %72, %73, %74, %75, %76, %77, %78, %79, "
    "%80, %81, %82, %83, %84, %85, %86, %87, %88, %89, %90, %91, %92, %93, %94, %95, "
    "%96, %97, %98, %99, %100, %101, %102, %103, %104, %105, %106, %107, %108, %109, %110, %111, "
    "%112, %113, %114, %115, %116, %117, %118, %119, %120, %121, %122, %123, %124, %125, %126, %127}, "
    "%128, %129, p, 1, 1, 0, 1;\n}\n"
    : "+f"(d[0]), "+f"(d[1]), "+f"(d[2]), "+f"(d[3]), "+f"(d[4]), "+f"(d[5]), "+f"(d[6]), "+f"(d[7]),
      "+f"(d[8]), "+f"(d[9]), "+f"(d[10]), "+f"(d[11]), "+f"(d[12]), "+f"(d[13]), "+f"(d[14]), "+f"(d[15]),
      "+f"(d[16]), "+f"(d[17]), "+f"(d[18]), "+f"(d[19]), "+f"(d[20]), "+f"(d[21]), "+f"(d[22]), "+f"(d[23]),
      "+f"(d[24]), "+f"(d[25]), "+f"(d[26]), "+f"(d[27]), "+f"(d[28]), "+f"(d[29]), "+f"(d[30]), "+f"(d[31]),
      "+f"(d[32]), "+f"(d[33]), "+f"(d[34]), "+f"(d[35]), "+f"(d[36]), "+f"(d[37]), "+f"(d[38]), "+f"(d[39]),
      "+f"(d[40]), "+f"(d[41]), "+f"(d[42]), "+f"(d[43]), "+f"(d[44]), "+f"(d[45]), "+f"(d[46]), "+f"(d[47]),
      "+f"(d[48]), "+f"(d[49]), "+f"(d[50]), "+f"(d[51]), "+f"(d[52]), "+f"(d[53]), "+f"(d[54]), "+f"(d[55]),
      "+f"(d[56]), "+f"(d[57]), "+f"(d[58]), "+f"(d[59]), "+f"(d[60]), "+f"(d[61]), "+f"(d[62]), "+f"(d[63]),
      "+f"(d[64]), "+f"(d[65]), "+f"(d[66]), "+f"(d[67]), "+f"(d[68]), "+f"(d[69]), "+f"(d[70]), "+f"(d[71]),
      "+f"(d[72]), "+f"(d[73]), "+f"(d[74]), "+f"(d[75]), "+f"(d[76]), "+f"(d[77]), "+f"(d[78]), "+f"(d[79]),
      "+f"(d[80]), "+f"(d[81]), "+f"(d[82]), "+f"(d[83]), "+f"(d[84]), "+f"(d[85]), "+f"(d[86]), "+f"(d[87]),
      "+f"(d[88]), "+f"(d[89]), "+f"(d[90]), "+f"(d[91]), "+f"(d[92]), "+f"(d[93]), "+f"(d[94]), "+f"(d[95]),
      "+f"(d[96]), "+f"(d[97]), "+f"(d[98]), "+f"(d[99]), "+f"(d[100]), "+f"(d[101]), "+f"(d[102]), "+f"(d[103]),
      "+f"(d[104]), "+f"(d[105]), "+f"(d[106]), "+f"(d[107]), "+f"(d[108]), "+f"(d[109]), "+f"(d[110]), "+f"(d[111]),
      "+f"(d[112]), "+f"(d[113]), "+f"(d[114]), "+f"(d[115]), "+f"(d[116]), "+f"(d[117]), "+f"(d[118]), "+f"(d[119]),
      "+f"(d[120]), "+f"(d[121]), "+f"(d[122]), "+f"(d[123]), "+f"(d[124]), "+f"(d[125]), "+f"(d[126]), "+f"(d[127])
    : "l"(da), "l"(db), "r"(scale_d));
}
__device__ __forceinline__ void wgmma_rs_n32(float (&d)[16], const uint32_t* a, uint64_t db, int scale_d) {
  asm volatile("{\n.reg .pred p;\nsetp.ne.b32 p, %21, 0;\n"
    "wgmma.mma_async.sync.aligned.m64n32k16.f32.bf16.bf16 "
    "{%0, %1, %2, %3, %4, %5, %6, %7, %8, %9, %10, %11, %12, %13, %14, %15}, "
    "{%16, %17, %18, %19}, %20, p, 1, 1, 0;\n}\n"
    : "+f"(d[0]), "+f"(d[1]), "+f"(d[2]), "+f"(d[3]), "+f"(d[4]), "+f"(d[5]), "+f"(d[6]), "+f"(d[7]),
      "+f"(d[8]), "+f"(d[9]), "+f"(d[10]), "+f"(d[11]), "+f"(d[12]), "+f"(d[13]), "+f"(d[14]), "+f"(d[15])
    : "r"(a[0]), "r"(a[1]), "r"(a[2]), "r"(a[3]), "l"(db), "r"(scale_d));
}
__device__ __forceinline__ void wgmma_ss_n32_ta(float (&d)[16], uint64_t da, uint64_t db, int scale_d) {
  asm volatile("{\n.reg .pred p;\nsetp.ne.b32 p, %18, 0;\n"
    "wgmma.mma_async.sync.aligned.m64n32k16.f32.bf16.bf16 "
    "{%0, %1, %2, %3, %4, %5, %6, %7, %8, %9, %10, %11, %12, %13, %14, %15}, "
    "%16, %17, p, 1, 1, 1, 0;\n}\n"
    : "+f"(d[0]), "+f"(d[1]), "+f"(d[2]), "+f"(d[3]), "+f"(d[4]), "+f"(d[5]), "+f"(d[6]), "+f"(d[7]),
      "+f"(d[8]), "+f"(d[9]), "+f"(d[10]), "+f"(d[11]), "+f"(d[12]), "+f"(d[13]), "+f"(d[14]), "+f"(d[15])
    : "l"(da), "l"(db), "r"(scale_d));
}
__device__ __forceinline__ void wgmma_ss_n8_ta(float (&d)[4], uint64_t da, uint64_t db, int scale_d) {
  asm volatile("{\n.reg .pred p;\nsetp.ne.b32 p, %6, 0;\n"
    "wgmma.mma_async.sync.aligned.m64n8k16.f32.bf16.bf16 {%0, %1, %2, %3}, %4, %5, p, 1, 1, 1, 0;\n}\n"
    : "+f"(d[0]), "+f"(d[1]), "+f"(d[2]), "+f"(d[3]) : "l"(da), "l"(db), "r"(scale_d));
}
__device__ __forceinline__ void wgmma_ss_n48_tt(float (&d)[24], uint64_t da, uint64_t db, int scale_d) {
  asm volatile("{\n.reg .pred p;\nsetp.ne.b32 p, %26, 0;\n"
    "wgmma.mma_async.sync.aligned.m64n48k16.f32.bf16.bf16 "
    "{%0, %1, %2, %3, %4, %5, %6, %7, %8, %9, %10, %11, %12, %13, %14, %15, %16, %17, %18, %19, %20, %21, %22, %23}, "
    "%24, %25, p, 1, 1, 1, 1;\n}\n"
    : "+f"(d[0]), "+f"(d[1]), "+f"(d[2]), "+f"(d[3]), "+f"(d[4]), "+f"(d[5]), "+f"(d[6]), "+f"(d[7]), "+f"(d[8]), "+f"(d[9]), "+f"(d[10]), "+f"(d[11]), "+f"(d[12]), "+f"(d[13]), "+f"(d[14]), "+f"(d[15]), "+f"(d[16]), "+f"(d[17]), "+f"(d[18]), "+f"(d[19]), "+f"(d[20]), "+f"(d[21]), "+f"(d[22]), "+f"(d[23])
    : "l"(da), "l"(db), "r"(scale_d));
}
__device__ __forceinline__ void wgmma_ss_n32(float (&d)[16], uint64_t da, uint64_t db, int scale_d) {
  asm volatile("{\n.reg .pred p;\nsetp.ne.b32 p, %18, 0;\n"
    "wgmma.mma_async.sync.aligned.m64n32k16.f32.bf16.bf16 "
    "{%0, %1, %2, %3, %4, %5, %6, %7, %8, %9, %10, %11, %12, %13, %14, %15}, "
    "%16, %17, p, 1, 1, 0, 0;\n}\n"
    : "+f"(d[0]), "+f"(d[1]), "+f"(d[2]), "+f"(d[3]), "+f"(d[4]), "+f"(d[5]), "+f"(d[6]), "+f"(d[7]),
      "+f"(d[8]), "+f"(d[9]), "+f"(d[10]), "+f"(d[11]), "+f"(d[12]), "+f"(d[13]), "+f"(d[14]), "+f"(d[15])
    : "l"(da), "l"(db), "r"(scale_d));
}

__device__ __forceinline__ void tma_load_2d_mc(uint32_t dst, const CUtensorMap* map, int x, int y, uint32_t bar, uint16_t mask) {
  asm volatile("cp.async.bulk.tensor.2d.shared::cluster.global.mbarrier::complete_tx::bytes.multicast::cluster "
               "[%0], [%1, {%3, %4}], [%2], %5;"
               ::"r"(dst), "l"(map), "r"(bar), "r"(x), "r"(y), "h"(mask) : "memory");
}
__device__ __forceinline__ void mbar_arrive_cluster(uint32_t bar, uint32_t cta) {
  asm volatile("{\n.reg .b32 r;\nmapa.shared::cluster.u32 r, %0, %1;\nmbarrier.arrive.shared::cluster.b64 _, [r];\n}"
               ::"r"(bar), "r"(cta) : "memory");
}
__device__ __forceinline__ void cluster_sync() {
  asm volatile("barrier.cluster.arrive.release.aligned;\nbarrier.cluster.wait.acquire.aligned;" ::: "memory");
}
__device__ __forceinline__ void wait_count(const unsigned* p, unsigned need) {
#pragma unroll 1
  for (int tries = 0; tries < (1 << 16); tries++) {
    unsigned v;
    asm volatile("ld.acquire.gpu.global.u32 %0, [%1];" : "=r"(v) : "l"(p) : "memory");
    if (v >= need) break;
    __nanosleep(200);
  }
}
__device__ __forceinline__ uint32_t sub_bf16x2(uint32_t a, uint32_t b) {
  uint32_t d;
  asm("sub.rn.bf16x2 %0, %1, %2;" : "=r"(d) : "r"(a), "r"(b));
  return d;
}
__device__ __forceinline__ uint32_t add_bf16x2(uint32_t a, uint32_t b) {
  uint32_t d;
  asm("add.rn.bf16x2 %0, %1, %2;" : "=r"(d) : "r"(a), "r"(b));
  return d;
}
__device__ __forceinline__ uint32_t mul_bf16x2(uint32_t a, uint32_t b) {
  uint32_t d;
  asm("mul.rn.bf16x2 %0, %1, %2;" : "=r"(d) : "r"(a), "r"(b));
  return d;
}

template <int NR>
__device__ __forceinline__ void ln_regs(uint32_t (&raw)[NR][16]) {
  float m[NR], q[NR];
#pragma unroll
  for (int r = 0; r < NR; r++) {
    float s0 = 0.f, s1 = 0.f;
#pragma unroll
    for (int i = 0; i < 16; i++) { s0 += bf_lo(raw[r][i]); s1 += bf_hi(raw[r][i]); }
    m[r] = s0 + s1;
  }
#pragma unroll
  for (int o = 16; o > 0; o >>= 1)
#pragma unroll
    for (int r = 0; r < NR; r++) m[r] += __shfl_xor_sync(0xffffffffu, m[r], o);
#pragma unroll
  for (int r = 0; r < NR; r++) {
    m[r] *= 1.0f / 1024.0f;
    float s0 = 0.f, s1 = 0.f;
#pragma unroll
    for (int i = 0; i < 16; i++) {
      const float d0 = bf_lo(raw[r][i]) - m[r], d1 = bf_hi(raw[r][i]) - m[r];
      s0 = fmaf(d0, d0, s0); s1 = fmaf(d1, d1, s1);
    }
    q[r] = s0 + s1;
  }
#pragma unroll
  for (int o = 16; o > 0; o >>= 1)
#pragma unroll
    for (int r = 0; r < NR; r++) q[r] += __shfl_xor_sync(0xffffffffu, q[r], o);
#pragma unroll
  for (int r = 0; r < NR; r++) {
    const uint32_t mb = pack_bf16(m[r], m[r]);
    float sq;
    asm("sqrt.approx.f32 %0, %1;" : "=f"(sq) : "f"(rbf(rbf(q[r] * (1.0f / 1024.0f)) + 1e-5f)));
    const float inv = rcp_approx(rbf(sq));
#pragma unroll
    for (int i = 0; i < 16; i++) {
      const uint32_t d = sub_bf16x2(raw[r][i], mb);
      raw[r][i] = pack_bf16(bf_lo(d) * inv, bf_hi(d) * inv);
    }
  }
}
__device__ __forceinline__ void load_row16(uint32_t (&raw)[16], const bf16* src, int lane) {
#pragma unroll
  for (int j = 0; j < 4; j++) {
    const uint4 u = __ldcg(reinterpret_cast<const uint4*>(src + j * 256 + lane * 8));
    raw[4 * j] = u.x; raw[4 * j + 1] = u.y; raw[4 * j + 2] = u.z; raw[4 * j + 3] = u.w;
  }
}
__device__ __forceinline__ void store_row16(const uint32_t (&raw)[16], bf16* dst, int lane) {
#pragma unroll
  for (int j = 0; j < 4; j++)
    *reinterpret_cast<uint4*>(dst + j * 256 + lane * 8) = make_uint4(raw[4 * j], raw[4 * j + 1], raw[4 * j + 2], raw[4 * j + 3]);
}

namespace fk {
constexpr uint32_t SM0 = 1024;
constexpr uint32_t WO = SM0, WS = WO + 90112, XN = WS + 65536, VX = XN + 49152, QK = VX + 8192, PT = QK + 8192,
                   SP = PT + 4096, VM = SP + 2560, OB = VM + 2048, BAR = OB + 2048;
constexpr uint32_t MEMB = XN + 16384, RED = XN + 32768, VX2 = WO + 81920;
constexpr int SMEM = 232448;
static_assert(BAR + 512 == SM0 + SMEM, "shared memory layout");
constexpr uint32_t B_XN = BAR, B_H2 = BAR + 64, B_H1 = BAR + 120, ONES = BAR + 384, B_PF = BAR + 16, B_WO = BAR + 24, B_SM = BAR + 32, B_VM = BAR + 40, B_VX = BAR + 48, B_ST = BAR + 56, B_PB = BAR + 64, B_W = BAR + 112,
                   MASKS = BAR + 128, PROBE = BAR + 256;
constexpr int NB_M0 = 1, NB_M1 = 2, NB_C = 3, NB_O = 4, NB_ST = 5, NB_DU = 6, NB_CF = 7, NB_W1 = 8, NB_XE = 9, NB_HD = 10, NB_MX = 11, NB_O0 = 12;
#define D_H1 550
#define D_H2 1800
#define D_ST 100
#define SMQ 0x1E
#define SMV 0x1E
#define PRE_G 5
#define WO_AT 4
#define NS0 4
#define NS0V 4
#define NTA0 2
#define NTA1 1
#define PF0A 3
#define PF0 10
#define PF1A 0
#define PF1V 10
#define PF1 11
#define REFILL_EARLY 1
#define GATE_MX 0
#define VM_BULK 0
#define CF_AT 0
#define H2_AT 1
#define NPRE0 1
#define PROBE_N 4
#define SPACK 0
constexpr uint32_t SPW = SPACK ? 4 : 8, SP_SRC = 160 * SPW;
constexpr int H1_BYTES = 64 * 32768, H2_BYTES = 8 * 8192;
}

#define PROF(wg, i)
#define PROF2(i)
#define RETRY(i)
#define GTSYNC(i)
#define PRO(i)
#define TL(i)

__device__ uint4 g_xch[(fk::H1_BYTES + fk::H2_BYTES + 8192) / 16];
__device__ __align__(16) unsigned g_mask[128];
__device__ unsigned g_cnt[6][16];
__device__ unsigned g_next;
constexpr int TAIL_MB0 = 10, GATE_CNT = 12;
__device__ unsigned g_tflag[96], g_tfix[96];
__device__ uint4 g_tpart[96][3][4][256];
__device__ unsigned g_oflag[16];

#define LD_POLL "ld.global.L1::no_allocate"
__device__ __forceinline__ uint4 ld_poll16(const void* p) {
  uint4 v;
  asm volatile(LD_POLL ".v4.u32 {%0,%1,%2,%3}, [%4];" : "=r"(v.x), "=r"(v.y), "=r"(v.z), "=r"(v.w) : "l"(p) : "memory");
  return v;
}
__device__ __forceinline__ uint2 ld_poll8(const void* p) {
  uint2 v;
  asm volatile(LD_POLL ".v2.u32 {%0,%1}, [%2];" : "=r"(v.x), "=r"(v.y) : "l"(p) : "memory");
  return v;
}
__device__ __forceinline__ uint4 ld_strong16(const void* p) {
  uint4 v;
  asm volatile("ld.relaxed.gpu.global.v4.u32 {%0,%1,%2,%3}, [%4];" : "=r"(v.x), "=r"(v.y), "=r"(v.z), "=r"(v.w) : "l"(p) : "memory");
  return v;
}
__device__ __forceinline__ uint2 ld_strong8(const void* p) {
  uint2 v;
  asm volatile("ld.relaxed.gpu.global.v2.u32 {%0,%1}, [%2];" : "=r"(v.x), "=r"(v.y) : "l"(p) : "memory");
  return v;
}
__device__ __forceinline__ void st_pub32(void* p, uint32_t v) { asm volatile("st.relaxed.gpu.global.u32 [%0], %1;" ::"l"(p), "r"(v) : "memory"); }
__device__ __forceinline__ void st_pub16(void* p, uint32_t v) {
  asm volatile("st.relaxed.gpu.global.u16 [%0], %1;" ::"l"(p), "h"((uint16_t)v) : "memory");
}
__device__ __forceinline__ uint32_t ld_strong4(const void* p) {
  uint32_t v;
  asm volatile("ld.relaxed.gpu.global.u32 %0, [%1];" : "=r"(v) : "l"(p) : "memory");
  return v;
}
__device__ __forceinline__ void st_pub64(void* p, uint32_t a, uint32_t b) {
  asm volatile("st.relaxed.gpu.global.v2.u32 [%0], {%1,%2};" ::"l"(p), "r"(a), "r"(b) : "memory");
}
__device__ __forceinline__ void st_pub128(void* p, uint32_t a) {
  asm volatile("st.relaxed.gpu.global.v4.u32 [%0], {%1,%1,%1,%1};" ::"l"(p), "r"(a) : "memory");
}
constexpr uint32_t EMPTY = 0xFFFFFFFFu;
__device__ __forceinline__ uint32_t umax4(const uint4& v) { return max(max(v.x, v.y), max(v.z, v.w)); }
__device__ __forceinline__ void sts128(uint32_t a, uint32_t x, uint32_t y, uint32_t z, uint32_t w) {
  asm volatile("st.shared.v4.u32 [%0], {%1,%2,%3,%4};" ::"r"(a), "r"(x), "r"(y), "r"(z), "r"(w) : "memory");
}
__device__ __forceinline__ void sts64(uint32_t a, uint32_t x, uint32_t y) {
  asm volatile("st.shared.v2.u32 [%0], {%1,%2};" ::"r"(a), "r"(x), "r"(y) : "memory");
}
__device__ __forceinline__ void sts32(uint32_t a, uint32_t x) { asm volatile("st.shared.u32 [%0], %1;" ::"r"(a), "r"(x) : "memory"); }
__device__ __forceinline__ void sts128f(uint32_t a, float x, float y, float z, float w) {
  asm volatile("st.shared.v4.f32 [%0], {%1,%2,%3,%4};" ::"r"(a), "f"(x), "f"(y), "f"(z), "f"(w) : "memory");
}
__device__ __forceinline__ void sts64f(uint32_t a, float x, float y) {
  asm volatile("st.shared.v2.f32 [%0], {%1,%2};" ::"r"(a), "f"(x), "f"(y) : "memory");
}
__device__ __forceinline__ float4 lds128f(uint32_t a) {
  float4 v;
  asm volatile("ld.shared.v4.f32 {%0,%1,%2,%3}, [%4];" : "=f"(v.x), "=f"(v.y), "=f"(v.z), "=f"(v.w) : "r"(a) : "memory");
  return v;
}
__device__ __forceinline__ float2 lds64f(uint32_t a) {
  float2 v;
  asm volatile("ld.shared.v2.f32 {%0,%1}, [%2];" : "=f"(v.x), "=f"(v.y) : "r"(a) : "memory");
  return v;
}
__device__ __forceinline__ float2 lds64f_if(uint32_t a, bool on, float other) {
  float2 v = make_float2(other, other);
  asm volatile("{\n.reg .pred p;\nsetp.ne.u32 p, %3, 0;\n@p ld.shared.v2.f32 {%0,%1}, [%2];\n}" : "+f"(v.x), "+f"(v.y) : "r"(a), "r"((uint32_t)on) : "memory");
  return v;
}
__device__ __forceinline__ void lds128(uint32_t* r, uint32_t a) {
  asm volatile("ld.shared.v4.u32 {%0,%1,%2,%3}, [%4];" : "=r"(r[0]), "=r"(r[1]), "=r"(r[2]), "=r"(r[3]) : "r"(a) : "memory");
}
__device__ __forceinline__ void lds64(uint32_t* r, uint32_t a) {
  asm volatile("ld.shared.v2.u32 {%0,%1}, [%2];" : "=r"(r[0]), "=r"(r[1]) : "r"(a) : "memory");
}
__device__ __forceinline__ uint32_t lds32(uint32_t a) {
  uint32_t v;
  asm volatile("ld.shared.u32 %0, [%1];" : "=r"(v) : "r"(a) : "memory");
  return v;
}
__device__ __forceinline__ void ldsm4(uint32_t* r, uint32_t a) {
  asm volatile("ldmatrix.sync.aligned.m8n8.x4.shared.b16 {%0,%1,%2,%3}, [%4];"
               : "=r"(r[0]), "=r"(r[1]), "=r"(r[2]), "=r"(r[3]) : "r"(a) : "memory");
}
__device__ __forceinline__ void ldsm4t(uint32_t* r, uint32_t a) {
  asm volatile("ldmatrix.sync.aligned.m8n8.x4.trans.shared.b16 {%0,%1,%2,%3}, [%4];"
               : "=r"(r[0]), "=r"(r[1]), "=r"(r[2]), "=r"(r[3]) : "r"(a) : "memory");
}
__device__ __forceinline__ void stsm4(uint32_t a, uint32_t r0, uint32_t r1, uint32_t r2, uint32_t r3) {
  asm volatile("stmatrix.sync.aligned.m8n8.x4.shared.b16 [%0], {%1,%2,%3,%4};"
               ::"r"(a), "r"(r0), "r"(r1), "r"(r2), "r"(r3) : "memory");
}
__device__ __forceinline__ void stsm4t(uint32_t a, uint32_t r0, uint32_t r1, uint32_t r2, uint32_t r3) {
  asm volatile("stmatrix.sync.aligned.m8n8.x4.trans.shared.b16 [%0], {%1,%2,%3,%4};"
               ::"r"(a), "r"(r0), "r"(r1), "r"(r2), "r"(r3) : "memory");
}
__device__ __forceinline__ void mma16816(float* d, const uint32_t* a, uint32_t b0, uint32_t b1) {
  asm volatile("mma.sync.aligned.m16n8k16.row.col.f32.bf16.bf16.f32 {%0,%1,%2,%3}, {%4,%5,%6,%7}, {%8,%9}, {%0,%1,%2,%3};"
               : "+f"(d[0]), "+f"(d[1]), "+f"(d[2]), "+f"(d[3])
               : "r"(a[0]), "r"(a[1]), "r"(a[2]), "r"(a[3]), "r"(b0), "r"(b1));
}
__device__ __forceinline__ void mma16816z(float* d, const uint32_t* a, uint32_t b0, uint32_t b1) {
  asm volatile("mma.sync.aligned.m16n8k16.row.col.f32.bf16.bf16.f32 {%0,%1,%2,%3}, {%4,%5,%6,%7}, {%8,%9}, {%10,%10,%10,%10};"
               : "=f"(d[0]), "=f"(d[1]), "=f"(d[2]), "=f"(d[3])
               : "r"(a[0]), "r"(a[1]), "r"(a[2]), "r"(a[3]), "r"(b0), "r"(b1), "f"(0.f));
}
__device__ __forceinline__ void mma1688(float* d, uint32_t a0, uint32_t a1, uint32_t b0) {
  asm volatile("mma.sync.aligned.m16n8k8.row.col.f32.bf16.bf16.f32 {%0,%1,%2,%3}, {%4,%5}, {%6}, {%0,%1,%2,%3};"
               : "+f"(d[0]), "+f"(d[1]), "+f"(d[2]), "+f"(d[3]) : "r"(a0), "r"(a1), "r"(b0));
}
__device__ __forceinline__ uint32_t movtrans(uint32_t a) {
  uint32_t d;
  asm volatile("movmatrix.sync.aligned.m8n8.trans.b16 %0, %1;" : "=r"(d) : "r"(a));
  return d;
}
__device__ __forceinline__ uint32_t mapa(uint32_t a, uint32_t rank) {
  uint32_t d;
  asm("mapa.shared::cluster.u32 %0, %1, %2;" : "=r"(d) : "r"(a), "r"(rank));
  return d;
}
__device__ __forceinline__ void st_async64(uint32_t a, uint32_t x, uint32_t y, uint32_t bar) {
  asm volatile("st.async.weak.shared::cluster.mbarrier::complete_tx::bytes.v2.b32 [%0], {%1,%2}, [%3];"
               ::"r"(a), "r"(x), "r"(y), "r"(bar) : "memory");
}
__device__ __forceinline__ void st_async64f(uint32_t a, float x, float y, uint32_t bar) {
  st_async64(a, __float_as_uint(x), __float_as_uint(y), bar);
}
__device__ __forceinline__ void bulk_s2s(uint32_t dst, uint32_t src, uint32_t bytes, uint32_t bar) {
  asm volatile("cp.async.bulk.shared::cluster.shared::cta.mbarrier::complete_tx::bytes [%0], [%1], %2, [%3];"
               ::"r"(dst), "r"(src), "r"(bytes), "r"(bar) : "memory");
}
__device__ __forceinline__ void tma_store_3d(const CUtensorMap* map, uint32_t src, int x, int y, int z) {
  asm volatile("cp.async.bulk.tensor.3d.global.shared::cta.bulk_group [%0, {%2, %3, %4}], [%1];"
               ::"l"(map), "r"(src), "r"(x), "r"(y), "r"(z) : "memory");
}
__device__ __forceinline__ void mbar_spin(uint32_t bar, uint32_t parity) {
  asm volatile("{\n.reg .pred p;\n.reg .b32 n;\nmov.u32 n, 0x100000;\nMW_L:\n"
               "mbarrier.try_wait.parity.shared::cta.b64 p, [%0], %1;\n@p bra.uni MW_D;\n"
               "add.s32 n, n, -1;\nsetp.ne.u32 p, n, 0;\n@p bra.uni MW_L;\nMW_D:\n}" ::"r"(bar), "r"(parity) : "memory");
}
__device__ __forceinline__ bool mbar_test(uint32_t bar, uint32_t parity) {
  uint32_t done;
  asm volatile("{\n.reg .pred p;\nmbarrier.test_wait.parity.shared::cta.b64 p, [%1], %2;\nselp.u32 %0, 1, 0, p;\n}"
               : "=r"(done) : "r"(bar), "r"(parity) : "memory");
  return done != 0;
}
__device__ __forceinline__ void mbar_arrive_remote(uint32_t bar) {
  asm volatile("mbarrier.arrive.shared::cluster.b64 _, [%0];" ::"r"(bar) : "memory");
}
__device__ __forceinline__ bool elect_one() {
  uint32_t r;
  asm volatile("{\n.reg .pred p;\nelect.sync _|p, 0xffffffff;\nselp.u32 %0, 1, 0, p;\n}" : "=r"(r));
  return r != 0;
}
__device__ __forceinline__ void st_async32(uint32_t a, uint32_t x, uint32_t bar) {
  asm volatile("st.async.weak.shared::cluster.mbarrier::complete_tx::bytes.b32 [%0], %1, [%2];" ::"r"(a), "r"(x), "r"(bar) : "memory");
}
#define named_bar_and(id, n, in, out) \
  asm volatile("{\n.reg .pred p, q;\nsetp.ne.u32 p, %1, 0;\nbar.red.and.pred q, %2, %3, p;\nselp.u32 %0, 1, 0, q;\n}" \
               : "=r"(out) : "r"(in), "n"(id), "n"(n) : "memory")
__device__ __forceinline__ void bulk_g2s(uint32_t dst, const void* src, uint32_t bytes, uint32_t bar) {
  asm volatile("cp.async.bulk.shared::cluster.global.mbarrier::complete_tx::bytes [%0], [%1], %2, [%3];"
               ::"r"(dst), "l"(src), "r"(bytes), "r"(bar) : "memory");
}
__device__ __forceinline__ void l2_prefetch(const void* p, uint32_t bytes) {
  asm volatile("cp.async.bulk.prefetch.L2.global [%0], %1;" ::"l"(p), "r"(bytes) : "memory");
}

__device__ __forceinline__ uint32_t clk32() { uint32_t c; asm volatile("mov.u32 %0, %%clock;" : "=r"(c)::"memory"); return c; }
__device__ __forceinline__ void spin_until(uint32_t t) { while ((int32_t)(clk32() - t) < 0) {} }
#define PIN(x) asm volatile("" : "+r"(x))
#define OPQ                                                                                     \
  int tid_o = tid;                                                                              \
  asm volatile("" : "+r"(tid_o));                                                               \
  const int lane = tid_o & 31, w = (tid_o >> 5) & 3, t7 = tid_o & 127, lg = lane >> 2,          \
            lq = lane & 3, mi = lane >> 3, mr = lane & 7;                                       \
  (void)w; (void)t7; (void)lg; (void)lq; (void)mi; (void)mr; (void)lane

#define SMAP                                                                                                          \
  const uint32_t SM0 = self + fk::SM0, WO = self + fk::WO, WS = self + fk::WS, XN = self + fk::XN, VX = self + fk::VX, \
                 QK = self + fk::QK, PT = self + fk::PT, SP = self + fk::SP, VM = self + fk::VM, OB = self + fk::OB,   \
                 RED = self + fk::RED, VX2 = self + fk::VX2, MEMB = self + fk::MEMB, B_XN = self + fk::B_XN, B_SM = self + fk::B_SM,       \
                 B_VM = self + fk::B_VM, B_VX = self + fk::B_VX, B_ST = self + fk::B_ST, B_PB = self + fk::B_PB,       \
                 B_W = self + fk::B_W, B_H2 = self + fk::B_H2, B_H1 = self + fk::B_H1, B_PF = self + fk::B_PF, B_WO = self + fk::B_WO, MASKS = self + fk::MASKS, PROBE = self + fk::PROBE;                             \
  (void)SM0; (void)WO; (void)WS; (void)XN; (void)VX; (void)QK; (void)PT; (void)SP; (void)VM; (void)OB; (void)RED; (void)VX2; \
  (void)MEMB; (void)B_XN; (void)B_SM; (void)B_VM; (void)B_VX; (void)B_ST; (void)B_PB; (void)B_W; (void)MASKS; (void)PROBE; (void)B_H2; (void)B_H1; (void)B_PF; (void)B_WO

struct FParams {
  CUtensorMap wq, wk, wv, wo, wo16, xn, xn12, o;
  CUtensorMap ta, tb, tx, tg, tout;
  const bf16 *mem0, *x, *w1;
  bf16 *xn_ptr, *xn2;
  int nprobe;
  char* xch;
};

__device__ __forceinline__ uint2 probe_pair(char* p, uint32_t val, uint32_t dummy, int n) {
  uint2 best = make_uint2(0x7FFFFFFF, 0x7FFFFFFF);
  st_pub128(p, val); st_pub128(p + 16, val); st_pub128(p + 4096, val); st_pub128(p + 4112, val);
#pragma unroll 1
  for (int r = 0; r < n; r++) {
    uint32_t v;
    const uint32_t c0 = clk32();
    asm volatile("atom.relaxed.gpu.global.exch.b32 %0, [%1], %2;" : "=r"(v) : "l"(p + (r & 1) * 4096), "r"(val) : "memory");
    asm volatile("{\n.reg .pred p;\nsetp.eq.u32 p, %0, 0x12345678;\n@p st.shared.u32 [%1], %0;\n}" ::"r"(v), "r"(dummy) : "memory");
    const uint32_t d = clk32() - c0;
    if (r & 1) best.y = min(best.y, d); else best.x = min(best.x, d);
  }
  return best;
}

typedef uint32_t WRegs[6][2][4][4];

constexpr uint32_t nth_chunks(uint32_t mask) {
  uint32_t t = 0;
  for (int c = 0, n = 0; c < 10; c++) if ((mask >> c) & 1) t |= c << (4 * n++);
  return t;
}
constexpr uint64_t chunk_pos(uint32_t mask) {
  uint64_t t = 0;
  for (int c = 0, a = 0, b = 0; c < 10; c++) t |= (uint64_t)(((mask >> c) & 1) ? a++ : b++) << (4 * c);
  return t;
}
template <bool ISV> struct Chunks {
  static constexpr uint32_t MASK = ISV ? SMV : SMQ, SMT = nth_chunks(MASK), RFT = nth_chunks(~MASK & 1023);
  static_assert(!(MASK & 1), "the first chunk initialises the accumulators");
  static __device__ __forceinline__ constexpr int rf(int wg, int i) { return wg ? 10 + i : (RFT >> (4 * i)) & 15; }
  static __device__ __forceinline__ constexpr int sm(int i) { return (SMT >> (4 * i)) & 15; }
  static constexpr uint64_t IDX = chunk_pos(MASK);
  static __device__ __forceinline__ constexpr int idx(int c) { return (IDX >> (4 * c)) & 15; }
};

template <bool ISV, int WG> struct ProjCfg {
  static constexpr int N0 = ISV ? NS0V : NS0, NS = WG ? 8 - N0 : N0, P0 = WG ? N0 : 0, NTA = WG ? NTA1 : NTA0;
};
__device__ __forceinline__ void load_pair(uint32_t (&t)[4][4], uint32_t wsa, int pp) {
#pragma unroll
  for (int f = 0; f < 4; f++) ldsm4t(t[f], wsa + ((pp >> 1) * 2 + (f & 1)) * 8192 + ((pp & 1) * 2 + (f >> 1)) * 2048);
}
template <bool ISV, int WG>
__device__ __forceinline__ void proj_mem(const WRegs& wr, uint32_t (&ta)[ProjCfg<ISV, WG>::NTA][4][4], uint32_t wsa, uint32_t mba,
                                         float (&a0)[4], float (&a1)[4]) {
  constexpr int NS = ProjCfg<ISV, WG>::NS, P0 = ProjCfg<ISV, WG>::P0, NTA = ProjCfg<ISV, WG>::NTA, NP = 12 + NS;
  float acc[4][4];
  auto spos = [](int j) { return j < NTA ? j : j + (j - NTA + 1) * 12 / (NS - NTA > 0 ? NS - NTA : 1); };
  auto which = [&](int p) { int r = -1; for (int j = 0; j < NS; j++) if (spos(j) == p) r = j; return r; };
  auto nsm_before = [&](int p) { int n = 0; for (int j = 0; j < NS; j++) if (spos(j) < p) n++; return n; };
#pragma unroll
  for (int p = 0; p < NP; p++) {
    const int j = which(p), r = j >= 0 ? 0 : p - nsm_before(p);
    uint32_t bp[4], tl[4][4];
    ldsm4(bp, mba + (j >= 0 ? Chunks<ISV>::sm((P0 + (j >= 0 ? j : 0)) >> 1) * 1024 + ((P0 + j) & 1) * 512 : Chunks<ISV>::rf(WG, r >> 1) * 1024 + (r & 1) * 512));
    if (j >= NTA) load_pair(tl, wsa, P0 + j);
#pragma unroll
    for (int u = 0; u < 2; u++)
#pragma unroll
      for (int T = 0; T < 2; T++) {
        const uint32_t* a = j >= NTA ? tl[u * 2 + T] : j >= 0 ? ta[j >= 0 ? j % NTA : 0][u * 2 + T] : wr[r >> 1][T][(r & 1) * 2 + u];
        if (p == 0) mma16816z(acc[u * 2 + T], a, bp[2 * u], bp[2 * u + 1]);
        else mma16816(acc[u * 2 + T], a, bp[2 * u], bp[2 * u + 1]);
      }
  }
#pragma unroll
  for (int i = 0; i < 4; i++) { a0[i] = acc[0][i] + acc[2][i]; a1[i] = acc[1][i] + acc[3][i]; }
}
template <bool ISV, int WG, int J0, int J1>
__device__ __forceinline__ void proj_mem_prefetch(uint32_t (&ta)[ProjCfg<ISV, WG>::NTA][4][4], uint32_t wsa) {
#pragma unroll
  for (int j = J0; j < J1; j++) load_pair(ta[j], wsa, ProjCfg<ISV, WG>::P0 + j);
}

template <bool ISV, int WG>
__device__ __forceinline__ void proj_finish(const float (&a0)[4], const float (&a1)[4], uint32_t peer0, uint32_t peer1, uint32_t self, int tid, int warp,
                                            uint32_t (&vmo)[4]) {
  using namespace fk;
  SMAP;
  OPQ;
  if (!ISV) {
    stsm4(PT + mr * 16 + ((mi >> 1) ? WG * 1024 + w * 256 + (mi & 1) * 128 : 2048 + w * 512 + (mi & 1) * 256 + WG * 128),
          pack_bf16(a0[0], a0[1]), pack_bf16(a0[2], a0[3]), pack_bf16(a1[0], a1[1]), pack_bf16(a1[2], a1[3]));
    named_bar_sync(NB_C, 256);
  } else {
    if (WG == 0) sts128f(RED + t7 * 16, a1[0], a1[1], a1[2], a1[3]);
    else sts128f(RED + 2048 + t7 * 16, a0[0], a0[1], a0[2], a0[3]);
    if (WG == 1) { lds64(vmo, VM + t7 * 8); lds64(vmo + 2, VM + 1024 + t7 * 8); }
    named_bar_sync(NB_C, 256);
    const float4 p = lds128f(RED + (1 - WG) * 2048 + t7 * 16);
    const float* k = WG == 0 ? a0 : a1;
    const uint32_t v0 = pack_bf16(k[0] + p.x, k[1] + p.y), v1 = pack_bf16(k[2] + p.z, k[3] + p.w);
    const uint32_t off = VM + WG * 1024 + t7 * 8;
    if (VM_BULK) {
      sts64(off, v0, v1);
      fence_proxy_async_smem();
      __syncwarp();
      const uint32_t a = VM + WG * 1024 + warp * 256;
      if (elect_one()) {
        bulk_s2s(peer0 + a, a, 256, peer0 + B_VM);
        bulk_s2s(peer1 + a, a, 256, peer1 + B_VM);
        mbar_arrive(B_VM);
      }
    } else {
      st_async64(peer0 + off, v0, v1, peer0 + B_VM);
      st_async64(peer1 + off, v0, v1, peer1 + B_VM);
      sts64(off, v0, v1);
      __syncwarp();
      if (lane == 0) mbar_arrive(B_VM);
    }
  }
}

__device__ __forceinline__ void send_scores(float s0, float s1, uint32_t off, uint32_t peer0, uint32_t peer1, uint32_t bar, int lane) {
  if (SPACK) {
    const uint32_t v = pack_bf16(s0, s1);
    st_async32(peer0 + off, v, peer0 + bar);
    st_async32(peer1 + off, v, peer1 + bar);
    sts32(off, v);
  } else {
    st_async64f(peer0 + off, s0, s1, peer0 + bar);
    st_async64f(peer1 + off, s0, s1, peer1 + bar);
    sts64f(off, s0, s1);
  }
  __syncwarp();
  if (lane == 0) mbar_arrive(bar);
}

template <int NT, bool NARROW>
__device__ __forceinline__ uint32_t wo_addr(int f, uint32_t woa, uint32_t wob) {
  return (NARROW && f % NT == 2) ? wob + (f / NT) * 512 : woa + (f % NT) * 32768 + (f / NT) * 2048;
}
template <int NT, bool NARROW, int PF>
__device__ __forceinline__ void wo_phase(uint32_t (&wf)[PF][4], uint32_t woa, uint32_t wob, uint32_t oba, char* h1p, uint32_t sel, uint32_t tag) {
  float c[NT][4];
  uint32_t of[2][4];
  ldsm4t(of[0], oba);
#pragma unroll
  for (int k = 0; k < 8; k++) {
    if ((k & 1) == 0 && k + 2 < 8) ldsm4t(of[((k >> 1) + 1) & 1], oba + ((k >> 1) + 1) * 512);
#pragma unroll
    for (int i = 0; i < NT; i++) {
      const int f = k * NT + i;
      const uint32_t b0 = of[(k >> 1) & 1][2 * (k & 1)], b1 = of[(k >> 1) & 1][2 * (k & 1) + 1];
      if (k == 0) mma16816z(c[i], wf[f % PF], b0, b1); else mma16816(c[i], wf[f % PF], b0, b1);
      if (f + PF < 8 * NT) ldsm4t(wf[f % PF], wo_addr<NT, NARROW>(f + PF, woa, wob));
    }
  }
#pragma unroll
  for (int i = 0; i < NT; i++)
  {
    char* p = h1p + i * (8 * 32768) + ((sel >> (2 * i)) & 3) * 2048;
    const uint32_t tm = (sel >> 10) & 1;
    st_pub32(p, (pack_bf16(c[i][0], c[i][1]) & ~tm) | (tag & tm));
    st_pub32(p + 1024, (pack_bf16(c[i][2], c[i][3]) & ~tm) | (tag & tm));
  }
}
template <int NT, bool NARROW, int F0, int F1, int PF>
__device__ __forceinline__ void wo_prefetch(uint32_t (&wf)[PF][4], uint32_t woa, uint32_t wob) {
#pragma unroll
  for (int f = F0; f < F1; f++) ldsm4t(wf[f], wo_addr<NT, NARROW>(f, woa, wob));
}

template <bool ISV, int T, bool ADD>
__device__ __forceinline__ void tok_store(const float (&x)[16], uint32_t base, int tid) {
  OPQ;
  const uint32_t a = ISV ? base + w * 2048 + (mi & 1) * 1024 + T * 512 + (mi >> 1) * 128 + mr * 16
                         : base + T * 4096 + (mi >> 1) * 1024 + w * 256 + (mi & 1) * 128 + mr * 16;
  constexpr uint32_t STR = ISV ? 256 : 2048;
  uint32_t p[2][4];
  if (ADD) {
#pragma unroll
    for (int i = 0; i < 2; i++) ldsm4(p[i], a + i * STR);
  }
#pragma unroll
  for (int i = 0; i < 2; i++) {
#pragma unroll
    for (int k = 0; k < 4; k++)
      p[i][k] = ADD ? pack_bf16(x[8 * i + 2 * k] + bf_lo(p[i][k]), x[8 * i + 2 * k + 1] + bf_hi(p[i][k]))
                    : pack_bf16(x[8 * i + 2 * k], x[8 * i + 2 * k + 1]);
    stsm4(a + i * STR, p[i][0], p[i][1], p[i][2], p[i][3]);
  }
}

__device__ __forceinline__ void load_xn(const FParams& P, int seg, uint32_t self) {
  SMAP;
  mbar_expect_tx(B_XN, 49152);
  tma_load_3d(XN, &P.xn12, 0, seg * 32, 0, B_XN);
}

__device__ __forceinline__ uint64_t xn_desc(int slot, int u) { return make_desc(fk::XN + slot * 4096 + u * 32, 16, 1024); }

template <bool ISV>
__device__ __forceinline__ void f_wg0(const FParams& P, const WRegs& wr, const int h, const int rank, const uint32_t hw, int tid) {
  using namespace fk;
  const uint32_t self = mapa(0, (hw >> (2 * rank)) & 3), peer0 = mapa(0, (hw >> (ISV ? 0 : 2 * (rank ^ 1))) & 3) - self,
                 peer1 = mapa(0, (hw >> (ISV ? 2 : 4)) & 3) - self;
  SMAP;
  const int tile0 = rank * 22;
  const int warp = __shfl_sync(0xffffffffu, threadIdx.x >> 5, 0);
  const bool three = !ISV && warp < 2;
  uint32_t h2ph = 1;
  tid ^= 0x5500;
#pragma unroll 1
  for (int s = -1;;) {
    uint32_t ta[ProjCfg<ISV, 0>::NTA][4][4], wsa, mba;
    auto h2_src = [&]() { return P.xch + H1_BYTES + ((s & 1) * 4 + warp) * 8192 + ((tid >> (16 + (s & 1))) & 1) * 4096; };
    {
      const uint32_t ph = (s + 1) & 1;
      float x0[16], x1[16];
      mbar_spin(B_XN, ph);
      const uint32_t t_pub = clk32();
      PROF(0, 8);
      wg_fence();
#pragma unroll
      for (int c = 0; c < 10; c++) {
        if (c == 9) named_bar_arrive(NB_ST, 256);
#pragma unroll
        for (int u = 0; u < 4; u++) {
          const int ci = Chunks<ISV>::idx(c);
          if ((Chunks<ISV>::MASK >> c) & 1) {
            wgmma_ss_n32_ta(x0, make_desc(fk::WS + ci * 16384 + u * 2048, 8192, 1024), xn_desc(c, u), 1);
            wgmma_ss_n32_ta(x1, make_desc(fk::WS + ci * 16384 + 8192 + u * 2048, 8192, 1024), xn_desc(c, u), 1);
          } else {
            wgmma_rs_n32(x0, wr[ci][0][u], xn_desc(c, u), (c | u) != 0);
            wgmma_rs_n32(x1, wr[ci][1][u], xn_desc(c, u), (c | u) != 0);
          }
          if (c == 4 && u == 1) { wg_commit(); wg_wait<1>(); named_bar_arrive(NB_XE, 160); wg_fence(); }
        }
        if (c == 3) wg_commit();
      }
      wg_commit();
      wg_wait<0>();
      PROF(0, 10);
      const uint32_t tb = ISV ? (ph ? VX2 : VX) : QK;
      auto h2_issue = [&]() {
        if (s >= 0) {
          spin_until(t_pub + D_H2);
          PROF(0, 13);
          if (elect_one()) { mbar_expect_tx(B_H2 + 8 * warp, 4096); bulk_g2s(MEMB + warp * 4096, h2_src(), 4096, B_H2 + 8 * warp); }
        }
      };
      if (ISV || H2_AT == 0) h2_issue();
      named_bar_sync(NB_CF, ISV ? 160 : 256);
      tok_store<ISV, 0, false>(x0, tb, tid);
      if (!ISV && H2_AT == 1) h2_issue();
      tok_store<ISV, 1, false>(x1, tb, tid);
      if (!ISV && H2_AT == 2) h2_issue();
      named_bar_arrive(NB_DU, 256);
    }
    {
      OPQ;
      wsa = WS + ((mi >> 1) * 8 + mr) * 128 + (((2 * w + (mi & 1)) ^ mr) << 4);
      mba = MEMB + lane * 16;
      PIN(wsa); PIN(mba);
      if (s >= 0) {
        const char* src = h2_src();
        const uint32_t chk = MEMB + w * 4096 + lane * 32 + lg * 4, bar = B_H2 + 8 * warp;
        PROF(0, 11);
        proj_mem_prefetch<ISV, 0, 0, NPRE0>(ta, wsa);
#pragma unroll 1
        for (int tries = 0; tries < POLL_TRIES; tries++) {
          mbar_spin(bar, h2ph);
          h2ph ^= 1;
          const uint32_t mx = max(max(lds32(chk), lds32(chk + 1024)), max(lds32(chk + 2048), lds32(chk + 3072)));
          if (__all_sync(0xffffffffu, mx != EMPTY)) break;
          RETRY(1);
          if (elect_one()) { mbar_expect_tx(bar, 4096); bulk_g2s(MEMB + warp * 4096, src, 4096, bar); }
        }
      } else {
        const bf16* m0 = P.mem0 + mr * cfg::D + w * 256 + mi * 8;
#pragma unroll
        for (int i = 0; i < 8; i++) {
          const uint4 v = *reinterpret_cast<const uint4*>(m0 + i * 32);
          sts128(mba + w * 4096 + i * 512, v.x, v.y, v.z, v.w);
        }
        proj_mem_prefetch<ISV, 0, 0, NPRE0>(ta, wsa);
        mbar_wait(B_WO, 0);
      }
      PROF(0, 12);
      named_bar_arrive(NB_M1, 256);
      proj_mem_prefetch<ISV, 0, NPRE0, NTA0>(ta, wsa);
      named_bar_sync(NB_M0, 128);
    }
    s++;
    tid ^= 0x5500;
    {
      PROF(0, 1);
      float a0[4], a1[4];
      proj_mem<ISV, 0>(wr, ta, wsa, mba, a0, a1);
      PROF(0, 2);
      uint32_t unused[4];
      proj_finish<ISV, 0>(a0, a1, peer0, peer1, self, tid, warp, unused);
      PROF(0, 3);
      if (s + 1 == cfg::NSEG) break;
      uint32_t wf[PF0][4], woa, wob;
      {
        OPQ;
        if (!ISV) {
          uint32_t qf[4][4], kf[2][4];
          const uint32_t qa = PT + 2048 + lane * 16, ka = QK + 4096 + w * 1024 + lane * 16;
          ldsm4t(qf[0], qa); ldsm4t(kf[0], ka); ldsm4t(qf[1], qa + 512);
          ldsm4t(qf[2], qa + 1024); ldsm4t(kf[1], ka + 512); ldsm4t(qf[3], qa + 1536);
          float c0[4], c1[4];
          mma16816z(c0, qf[0], kf[0][0], kf[0][1]);
          mma16816z(c1, qf[1], kf[0][2], kf[0][3]);
          mma16816(c0, qf[2], kf[1][0], kf[1][1]);
          mma16816(c1, qf[3], kf[1][2], kf[1][3]);
          const float s0 = (c0[0] + c0[2]) + (c1[0] + c1[2]), s1 = (c0[1] + c0[3]) + (c1[1] + c1[3]);
          send_scores(s0, s1, SP + rank * SP_SRC + t7 * SPW, peer0, peer1, B_SM, lane);
        }
        PROF(0, 4);
        woa = WO + 16384 + ((mi >> 1) * 8 + mr) * 128 + (((2 * w + (mi & 1)) ^ mr) << 4);
        wob = WO + 81920 + w * 4096 + ((mi >> 1) * 8 + mr) * 32 + (((mi & 1) ^ (mr >> 2)) << 4);
        uint32_t vf[2][2][4], vm[2][2];
        if (!ISV) mbar_spin(B_VX, s & 1);
        PROF(0, 14);
#pragma unroll
        for (int T = 0; T < 2; T++)
#pragma unroll
          for (int kk = 0; kk < 2; kk++) ldsm4(vf[T][kk], ((ISV && (s & 1)) ? VX2 : VX) + w * 2048 + (mi & 1) * 1024 + (mi >> 1) * 128 + mr * 16 + T * 512 + kk * 256);
        if (three) wo_prefetch<3, true, 0, PF0A>(wf, woa, wob); else wo_prefetch<2, false, 0, PF0A>(wf, woa, wob);
        uint32_t spa = SP + lane * SPW, vma = VM + t7 * 8, oa = OB + (mi >> 1) * 1024 + w * 256 + (mi & 1) * 128 + mr * 16;
        PIN(spa); PIN(vma); PIN(oa);
        mbar_spin(B_SM, s & 1);
        PROF(0, 5);
        float sc[10];
#pragma unroll
        for (int j = 0; j < 5; j++) {
          if (SPACK) {
            const uint32_t x = lds32(spa + j * 128), y = lds32(spa + SP_SRC + j * 128);
            sc[2 * j] = bf_lo(x) + bf_lo(y); sc[2 * j + 1] = bf_hi(x) + bf_hi(y);
          } else {
            const float2 x = lds64f(spa + j * 256), y = lds64f(spa + SP_SRC + j * 256);
            sc[2 * j] = x.x + y.x; sc[2 * j + 1] = x.y + y.y;
          }
        }
        float m = fmaxf(fmaxf(fmaxf(sc[0], sc[1]), fmaxf(sc[2], sc[3])), fmaxf(fmaxf(sc[4], sc[5]), fmaxf(sc[6], sc[7])));
        m = fmaxf(m, fmaxf(sc[8], sc[9]));
        const bool vm_ok = mbar_test(B_VM, s & 1);
        m = fmaxf(m, __shfl_xor_sync(0xffffffffu, m, 1));
        m = fmaxf(m, __shfl_xor_sync(0xffffffffu, m, 2));
        PROF(0, 15);
        if (!vm_ok) mbar_spin(B_VM, s & 1);
        PROF(0, 0);
        lds64(vm[0], vma); lds64(vm[1], vma + 1024);
        if (ISV && GATE_MX) named_bar_arrive(NB_MX, 256);
        const float cs = 0.08838834764831845f * 1.4426950408889634f;
        const float mc = -m * cs;
        uint32_t pb[5];
#pragma unroll
        for (int j = 0; j < 5; j++) pb[j] = pack_bf16(ex2_approx(fmaf(sc[2 * j], cs, mc)), ex2_approx(fmaf(sc[2 * j + 1], cs, mc)));
        PROF(0, 6);
        float o0[4], o1[4], rs[4];
        const uint32_t ones[4] = {0x3F803F80u, 0x3F803F80u, 0x3F803F80u, 0x3F803F80u};
        mma16816z(rs, ones, pb[0], pb[1]);
        mma16816z(o0, vf[0][0], pb[0], pb[1]);
        mma16816z(o1, vf[1][0], pb[0], pb[1]);
        mma16816(rs, ones, pb[2], pb[3]);
        mma16816(o0, vf[0][1], pb[2], pb[3]);
        mma16816(o1, vf[1][1], pb[2], pb[3]);
        mma1688(rs, ones[0], ones[0], pb[4]);
        mma1688(o0, vm[0][0], vm[0][1], pb[4]);
        mma1688(o1, vm[1][0], vm[1][1], pb[4]);
        const float i0 = rcp_approx(rs[0]), i1 = rcp_approx(rs[1]);
        stsm4(oa, pack_bf16(o0[0] * i0, o0[1] * i1), pack_bf16(o0[2] * i0, o0[3] * i1),
              pack_bf16(o1[0] * i0, o1[1] * i1), pack_bf16(o1[2] * i0, o1[3] * i1));
      }
      {
        OPQ;
        named_bar_arrive(NB_O, 256);
        if (three) wo_prefetch<3, true, PF0A, PF0>(wf, woa, wob); else wo_prefetch<2, false, PF0A, PF0>(wf, woa, wob);
        char* h1p = P.xch + (tile0 + 4 + w) * 32768 + (h >> 3) * 8192 + (h & 7) * 128 + (((2 * lq + (lg & 1)) ^ (h & 7)) << 4) + (lg >> 1) * 4;
        uint32_t oba = OB + lane * 16;
        PIN(oba);
        PROF(0, 7);
        named_bar_sync(NB_O0, 128);
        const uint32_t tag = ((s >> 1) & 1) ^ 1;
        if (three) wo_phase<3, true>(wf, woa, wob, oba, h1p, tid >> 8, tag); else wo_phase<2, false>(wf, woa, wob, oba, h1p, tid >> 8, tag);
        PROF(0, 9);
        named_bar_sync(NB_HD, 256);
      }
    }
  }
}

template <bool ISV>
__device__ __forceinline__ void f_wg1(const FParams& P, const WRegs& wr, const int h, const int rank, const uint32_t hw, int tid) {
  using namespace fk;
  const uint32_t self = mapa(0, (hw >> (2 * rank)) & 3), peer0 = mapa(0, (hw >> (ISV ? 0 : 2 * (rank ^ 1))) & 3) - self,
                 peer1 = mapa(0, (hw >> (ISV ? 2 : 4)) & 3) - self;
  SMAP;
  const int tile0 = rank * 22;
  const int warp = __shfl_sync(0xffffffffu, (threadIdx.x >> 5) & 3, 0);
  uint32_t h1ph = 0;
  auto o_done = [&](int mb) {
    tma_store_wait_all();
    asm volatile("fence.proxy.async.global;" ::: "memory");
    asm volatile("red.relaxed.gpu.global.add.u32 [%0], 1;" ::"l"(&g_oflag[mb]) : "memory");
  };
  uint32_t vmo[4] = {0, 0, 0, 0};
  if (ISV) {
    OPQ;
    sts32(PT + (t7 >> 2) * 128 + ((5 ^ lg) << 4) + lq * 4, 0);
    sts32(PT + (t7 >> 2) * 128 + ((6 ^ lg) << 4) + lq * 4, 0);
  }
  tid ^= 0x5500;
#pragma unroll 1
  for (int s = -1;;) {
    uint32_t ta[ProjCfg<ISV, 1>::NTA][4][4], wsa, mba;
    if (s + 1 < cfg::NSEG) mbar_spin(B_XN, (s + 1) & 1);
    const uint32_t t_pub = clk32();
    auto refill = [&]() {
      if (warp == 3) {
        named_bar_sync(NB_XE, 160);
        if (elect_one()) {
          mbar_expect_tx(B_XN + 8, 16384);
          tma_load_3d(XN, &P.xn, 0, (s + 1) * 32, 12, B_XN + 8);
        }
      }
    };
    if (ISV) {
      if (s >= 1) {
        OPQ;
        if (warp == 0 && (s & 3) == 1 && s > 1) { if (elect_one()) o_done((s - 2) >> 2); }
        const uint32_t vb = (s & 1) ? VX : VX2;
        float x0[16], x1[16];
        wg_fence();
        wgmma_rs_n32(x0, vmo, make_desc(fk::PT + 64, 16, 1024), 0);
        wgmma_rs_n32(x1, vmo, make_desc(fk::PT + 96, 16, 1024), 0);
#pragma unroll
        for (int kk = 0; kk < 2; kk++) {
          wgmma_ss_n32(x0, make_desc0(vb + kk * 256, 128, 1024), make_desc(fk::PT + kk * 32, 16, 1024), 1);
          wgmma_ss_n32(x1, make_desc0(vb + 512 + kk * 256, 128, 1024), make_desc(fk::PT + kk * 32, 16, 1024), 1);
        }
        wg_commit();
        wg_wait<0>();
        named_bar_sync(NB_W1, 128);
        PROF(1, 4);
        const uint32_t stg = vb + (8 * (mi >> 1) + mr) * 128 + (((2 * w + (mi & 1)) ^ mr) << 4);
#pragma unroll
        for (int T = 0; T < 2; T++) {
          const float* x = T ? x1 : x0;
#pragma unroll
          for (int jj = 0; jj < 4; jj += 2)
            stsm4t(stg + T * 4096 + jj * 1024, pack_bf16(x[4 * jj], x[4 * jj + 1]), pack_bf16(x[4 * jj + 2], x[4 * jj + 3]),
                   pack_bf16(x[4 * jj + 4], x[4 * jj + 5]), pack_bf16(x[4 * jj + 6], x[4 * jj + 7]));
        }
        fence_proxy_async_smem();
        named_bar_sync(NB_W1, 128);
        PROF(1, 10);
        if (warp == 0) {
          if (elect_one()) {
            tma_store_3d(&P.o, vb, 0, (s - 1) * 32, 2 * h);
            tma_store_commit();
          }
          __syncwarp();
        }
        if (s == cfg::NSEG) break;
      }
      if (s + 1 < cfg::NSEG) refill();
      PROF(1, 11);
    } else if (s < 0) {
      named_bar_arrive(NB_CF, 256);
      refill();
    } else {
      float x[24];
      wg_fence();
#pragma unroll
      for (int k = 0; k < 4; k++) wgmma_ss_n48_tt(x, make_desc0(fk::QK + k * 256, 128, 1024), make_desc0(fk::QK + 4096 + k * 256, 128, 1024), k != 0);
      wg_commit();
      wg_wait<0>();
      PROF(1, 6);
      auto send_tok = [&]() {
        if (warp < 2) {
          OPQ;
          const uint32_t d0 = peer1 + QK + rank * 3584 + lane * 8 + w * 1280, d1 = d0 + 512 + w * 512, bar = peer1 + B_ST;
          mbar_spin(B_ST, s & 1);
          const float NEG = -500000000.0f / 0.08838834764831845f;
          const bool m0 = 2 * lq > lg, m1 = 2 * lq + 1 > lg;
          st_async64f(d0, x[16] + x[20], x[17] + x[21], bar);
          st_async64f(d1, x[18] + x[22], x[19] + x[23], bar);
          st_async64f(d1 + 256, x[2], x[3], bar);
          if (warp == 0) {
            st_async64f(d0 + 256, m0 ? NEG : x[0], m1 ? NEG : x[1], bar);
            st_async64f(d1 + 512, m0 ? NEG : x[6], m1 ? NEG : x[7], bar);
          } else {
            st_async64f(d0 + 256, x[0], x[1], bar);
            st_async64f(d1 + 512, x[6], x[7], bar);
            st_async64f(d0 + 512, x[4], x[5], bar);
            st_async64f(d0 + 768, m0 ? NEG : x[8], m1 ? NEG : x[9], bar);
            st_async64f(d1 + 768, x[10], x[11], bar);
            st_async64f(d1 + 1024, m0 ? NEG : x[14], m1 ? NEG : x[15], bar);
          }
        }
        PROF(1, 4);
      };
      const bool fin = s + 1 == cfg::NSEG;
      if (!fin) named_bar_arrive(NB_CF, 256);
      OPQ;
      const int j = 2 * h + rank;
      const char* src = P.xch + j * 32768 + warp * 8192 + __shfl_sync(0xffffffffu, (tid >> 14) & 3, 0) * 2048;
      char* dst = P.xch + H1_BYTES + (j >> 4) * 8192 + (lq >> 1) * 4096 + (j & 15) * 256 + (lq & 1) * 128 + (2 * w + (lg & 1)) * 16 + (lg >> 1) * 4;
      const uint32_t chk = VX + mi * 2048 + mr * 128 + (w ^ (mr >> 1)) * 32 + ((lane & 1) + 2 * mi) * 4;
      const uint32_t tmask = (s >> 1) & 1;
      if (!fin) {
        spin_until(t_pub + D_H1);
        if (elect_one()) { mbar_expect_tx(B_H1, 2048); bulk_g2s(VX + warp * 2048, src, 2048, B_H1); }
      }
      __syncwarp();
      send_tok();
      if (fin) { mbar_spin(B_VM, s & 1); break; }
      if (REFILL_EARLY) refill();
#pragma unroll 1
      for (int tries = 0; tries < POLL_TRIES; tries++) {
        float d0[4], d1[4];
        mbar_spin(B_H1, h1ph);
        h1ph ^= 1;
        PROF(1, 10);
        const uint32_t t0 = lds32(chk), t1 = lds32(chk + 1024);
        wg_fence();
        const uint64_t ones = (uint64_t)(fk::ONES >> 4);
        wgmma_ss_n8_ta(d0, make_desc(fk::VX, 8192, 2048), ones, 0);
        wgmma_ss_n8_ta(d1, make_desc(fk::VX + 1024, 8192, 2048), ones, 0);
        wgmma_ss_n8_ta(d0, make_desc(fk::VX + 4096, 8192, 2048), ones, 1);
        wgmma_ss_n8_ta(d1, make_desc(fk::VX + 5120, 8192, 2048), ones, 1);
        wg_commit();
        uint32_t tt;
        asm volatile("lop3.b32 %0, %1, %2, %3, 0x42;" : "=r"(tt) : "r"(t0), "r"(t1), "r"(tmask) : "memory");
        uint32_t ok = __all_sync(0xffffffffu, tt & 1);
        wg_wait<0>();
        if (ok) {
          st_pub32(dst + (s & 1) * 32768, (lq & 1) ? pack_bf16(d1[0], d1[2]) : pack_bf16(d0[0], d0[2]));
          st_pub32(dst + ((s & 1) ^ 1) * 32768, EMPTY);
        }
        named_bar_and(NB_W1, 128, ok, ok);
        if (ok) break;
        RETRY(0);
        if (elect_one()) { mbar_expect_tx(B_H1, 2048); bulk_g2s(VX + warp * 2048, src, 2048, B_H1); }
      }
      if ((tid & 255) == 192) mbar_arrive_remote(peer1 + B_PF);
      __syncwarp();
      if (!REFILL_EARLY) refill();
      PROF(1, 11);
    }
    if (!ISV || s + 1 < cfg::NSEG) {
      const uint32_t ph = (s + 1) & 1;
      float x0[16], x1[16];
      named_bar_sync(NB_ST, 256);
      PROF(1, 12);
      wg_fence();
#pragma unroll
      for (int c = 0; c < 6; c++) {
        if (c == 2) { mbar_spin(B_XN + 8, ph); wg_fence(); }
        if (ISV && c == CF_AT) {
          if (warp == 0) {
            if (elect_one()) tma_store_wait_read();
            __syncwarp();
            named_bar_arrive(NB_CF, 160);
          }
          wg_fence();
        }
#pragma unroll
        for (int u = 0; u < 4; u++) {
          wgmma_rs_n32(x0, wr[c][0][u], xn_desc(c < 2 ? 10 + c : c - 2, u), (c | u) != 0);
          wgmma_rs_n32(x1, wr[c][1][u], xn_desc(c < 2 ? 10 + c : c - 2, u), (c | u) != 0);
        }
      }
      wg_commit();
      OPQ;
      named_bar_sync(NB_DU, 256);
      if (ISV && s >= 0) mbar_spin(B_PF, s & 1);
      wg_wait<0>();
      PROF(1, 13);
      const uint32_t tb = ISV ? (ph ? VX2 : VX) : QK;
      tok_store<ISV, 1, true>(x1, tb, tid);
      tok_store<ISV, 0, true>(x0, tb, tid);
      if (ISV && s + 2 < cfg::NSEG) {
        fence_proxy_async_smem();
        __syncwarp();
        if (elect_one()) {
          bulk_s2s(peer0 + VX + warp * 2048, tb + warp * 2048, 2048, peer0 + B_VX);
          bulk_s2s(peer1 + VX + warp * 2048, tb + warp * 2048, 2048, peer1 + B_VX);
        }
      }
      wsa = WS + ((mi >> 1) * 8 + mr) * 128 + (((2 * w + (mi & 1)) ^ mr) << 4);
      mba = MEMB + lane * 16;
      PIN(wsa); PIN(mba);
      proj_mem_prefetch<ISV, 1, 0, NTA1>(ta, wsa);
      PROF(1, 14);
      if (s < 0) mbar_wait(B_WO, 0);
      named_bar_sync(NB_M1, 256);
      s++;
      PROF(1, 1);
      float a0[4], a1[4];
      proj_mem<ISV, 1>(wr, ta, wsa, mba, a0, a1);
      PROF(1, 2);
      proj_finish<ISV, 1>(a0, a1, peer0, peer1, self, tid, warp, vmo);
      PROF(1, 3);
    } else {
      OPQ;
      mbar_spin(B_VM, s & 1);
      lds64(vmo, VM + t7 * 8); lds64(vmo + 2, VM + 1024 + t7 * 8);
      s++;
    }
    tid ^= 0x5500;
    const bool last = s + 1 >= cfg::NSEG;
    constexpr int PFW = ISV ? PF1V : PF1;
    uint32_t wf[PFW][4], woa;
    if (ISV) {
      OPQ;
      woa = WO + ((mi >> 1) * 8 + mr) * 128 + (((2 * w + (mi & 1)) ^ mr) << 4);
      if (s >= 1) {
        const uint32_t sa = QK + ((w * (w + 3)) >> 1) * 256 + lane * 8;
        mbar_spin(B_ST, (s - 1) & 1);
        float sc[10];
        {
          const float NEG = -1000000000.0f / 0.08838834764831845f;
          float2 x[5], y[5];
#pragma unroll
          for (int b = 0; b < 5; b++) {
            x[b] = b < 2 ? lds64f(sa + b * 256) : lds64f_if(sa + b * 256, b <= w + 1, NEG);
            y[b] = b < 2 ? lds64f(sa + 3584 + b * 256) : lds64f_if(sa + 3584 + b * 256, b <= w + 1, 0.f);
          }
          wo_prefetch<3, false, 0, PF1A>(wf, woa, 0);
#pragma unroll
          for (int b = 0; b < 5; b++) { sc[2 * b] = x[b].x + y[b].x; sc[2 * b + 1] = x[b].y + y[b].y; }
        }
        float m = fmaxf(fmaxf(fmaxf(sc[0], sc[1]), fmaxf(sc[2], sc[3])), fmaxf(fmaxf(sc[4], sc[5]), fmaxf(sc[6], sc[7])));
        m = fmaxf(m, fmaxf(sc[8], sc[9]));
        m = fmaxf(m, __shfl_xor_sync(0xffffffffu, m, 1));
        m = fmaxf(m, __shfl_xor_sync(0xffffffffu, m, 2));
        const float cs = 0.08838834764831845f * 1.4426950408889634f;
#pragma unroll
        for (int i = 0; i < 10; i++) sc[i] = ex2_approx((sc[i] - m) * cs);
        float sum = ((sc[0] + sc[1]) + (sc[2] + sc[3])) + ((sc[4] + sc[5]) + (sc[6] + sc[7])) + (sc[8] + sc[9]);
        sum += __shfl_xor_sync(0xffffffffu, sum, 1);
        sum += __shfl_xor_sync(0xffffffffu, sum, 2);
        const float inv = rcp_approx(sum);
        const uint32_t pa = PT + (w * 8 + mr) * 128, pm = pack_bf16(sc[0] * inv, sc[1] * inv);
        stsm4(pa + ((mi ^ mr) << 4), pack_bf16(sc[2] * inv, sc[3] * inv), pack_bf16(sc[4] * inv, sc[5] * inv),
              pack_bf16(sc[6] * inv, sc[7] * inv), pack_bf16(sc[8] * inv, sc[9] * inv));
        asm volatile("stmatrix.sync.aligned.m8n8.x2.shared.b16 [%0], {%1,%1};" ::"r"(pa + ((((mi & 1) ? 7 : 4) ^ mr) << 4)), "r"(pm) : "memory");
      } else {
        wo_prefetch<3, false, 0, PF1A>(wf, woa, 0);
      }
      if (warp == 3 && !last) {
        mbar_spin(B_VM, s & 1);
        if (elect_one()) load_xn(P, s + 1, self);
      }
      PROF(1, 5);
    } else {
      if (warp == 0) {
        OPQ;
        uint32_t kf[4][4], qf[4][4];
        float c0[4], c1[4], d0[4], d1[4];
        const uint32_t ka = PT + (mi >> 1) * 1024 + (mi & 1) * 128 + mr * 16;
#pragma unroll
        for (int k = 0; k < 4; k++) { ldsm4t(qf[k], PT + 2048 + k * 512 + lane * 16); ldsm4t(kf[k], ka + k * 256); }
        mma16816z(c0, qf[0], kf[0][0], kf[0][1]); mma16816z(c1, qf[0], kf[0][2], kf[0][3]);
        mma16816z(d0, qf[1], kf[1][0], kf[1][1]); mma16816z(d1, qf[1], kf[1][2], kf[1][3]);
        mma16816(c0, qf[2], kf[2][0], kf[2][1]); mma16816(c1, qf[2], kf[2][2], kf[2][3]);
        mma16816(d0, qf[3], kf[3][0], kf[3][1]); mma16816(d1, qf[3], kf[3][2], kf[3][3]);
        const float s0 = ((c0[0] + c0[2]) + (c1[0] + c1[2])) + ((d0[0] + d0[2]) + (d1[0] + d1[2]));
        const float s1 = ((c0[1] + c0[3]) + (c1[1] + c1[3])) + ((d0[1] + d0[3]) + (d1[1] + d1[3]));
        if (!last) send_scores(s0, s1, SP + rank * SP_SRC + (128 + lane) * SPW, peer0, peer1, B_SM, lane);
        PROF(1, 5);
      } else {
        const uint32_t t_c = clk32() + lds32(B_XN) * 0;
        if (warp == 3 && !last) { if (elect_one()) load_xn(P, s + 1, self); }
        spin_until(t_c + D_ST);
      }
      OPQ;
      woa = WO + ((mi >> 1) * 8 + mr) * 128 + (((2 * w + (mi & 1)) ^ mr) << 4);
    }
    if (!last) {
      OPQ;
      uint32_t oba = OB + lane * 16;
      if (ISV && GATE_MX) named_bar_sync(NB_MX, 256);
      wo_prefetch<3, false, ISV ? PF1A : 0, PFW>(wf, woa, 0);
      char* h1p = P.xch + (tile0 + w) * 32768 + (h >> 3) * 8192 + (h & 7) * 128 + (((2 * lq + (lg & 1)) ^ (h & 7)) << 4) + (lg >> 1) * 4;
      fence_proxy_async_smem();
      PROF(1, 7);
      named_bar_sync(NB_O, 256);
      PROF(1, 8);
      wo_phase<3, false>(wf, woa, 0, oba, h1p, tid >> 8, ((s >> 1) & 1) ^ 1);
      PROF(1, 9);
      named_bar_sync(NB_HD, 256);
      if ((tid & 255) == 160) {
        if (s == 1) st_pub32(&g_mask[3 * h + rank], 0);
        if (s + 2 < cfg::NSEG) { mbar_expect_tx(B_SM, ISV ? 2 * SP_SRC : SP_SRC); if (!ISV) mbar_expect_tx(B_VX, 8192); }
        if (!ISV) mbar_expect_tx(B_VM, 2048);
      }
    } else {
      fence_proxy_async_smem();
      named_bar_sync(NB_W1, 128);
    }
    if (ISV && s < cfg::NSEG) {
      if ((tid & 255) == 161 && s >= 1) mbar_expect_tx(B_ST, 7168);
      if ((tid & 254) == 192) mbar_arrive_remote(((tid & 1) ? peer1 : peer0) + B_ST);
    }
    __syncwarp();
  }
  if (ISV && warp == 0) { if (elect_one()) o_done(15); }
}

template <bool ISV, int WG>
__device__ __forceinline__ void f_main(const FParams& P, const int h, const int rank, const uint32_t hw) {
  using namespace fk;
  const uint32_t self = mapa(0, (hw >> (2 * rank)) & 3);
  SMAP;
  const int tid = __shfl_sync(0xffffffffu, threadIdx.x, threadIdx.x & 31);
  const int tile0 = rank * 22, ntile = ISV ? 20 : 22;
  const CUtensorMap* m0 = ISV ? &P.wv : &P.wq;
  const CUtensorMap* m1 = ISV ? &P.wv : &P.wk;
  const int col0 = h * 128 + (ISV ? 0 : 64 * rank), col1 = h * 128 + (ISV ? 64 : 64 * rank);
  WRegs wr;
  uint32_t sel = 0;
  {
    OPQ;
    const uint32_t a = SM0 + WG * 16384 + ((mi >> 1) * 8 + mr) * 128 + (((2 * w + (mi & 1)) ^ mr) << 4);
#pragma unroll
    for (int i = 0; i < 6; i++) {
      mbar_wait(B_PB + 8 * i, 0);
      PRO(8 + i);
#pragma unroll
      for (int T = 0; T < 2; T++)
#pragma unroll
        for (int u = 0; u < 4; u++) ldsm4t(wr[i][T][u], a + i * 32768 + T * 8192 + u * 2048);
      named_bar_sync(NB_C, 256);
      if (WG == 1 && w == (i & 3)) {
        if (elect_one()) {
          if (i <= 2 && i + PRE_G < 6) {
#pragma unroll 1
            for (int n = 2 * (i + PRE_G); n < (i == 2 ? 12 : 2 * (i + PRE_G) + 2); n++) {
              const int ii = n >> 1, row = Chunks<ISV>::rf(n & 1, ii) * 64;
              if (!(n & 1)) mbar_expect_tx(B_PB + 8 * ii, 32768);
              tma_load_2d(SM0 + n * 16384, m0, col0, row, B_PB + 8 * ii);
              tma_load_2d(SM0 + n * 16384 + 8192, m1, col1, row, B_PB + 8 * ii);
            }
          }
          if (i == 3 || i == 4) {
            const int p0 = i == 3 ? 0 : 5, p1 = i == 3 ? 5 : 8;
            mbar_expect_tx(B_W, (p1 - p0) * 8192);
#pragma unroll 1
            for (int p = p0; p < p1; p++) tma_load_2d(WS + p * 8192, (p & 1) ? m1 : m0, (p & 1) ? col1 : col0, Chunks<ISV>::sm(p >> 1) * 64, B_W);
          }
          if (i == WO_AT) {
            mbar_expect_tx(B_WO, ntile * 4096);
#pragma unroll 1
            for (int t = 0; t < 5; t++) tma_load_2d(WO + t * 16384, &P.wo, tile0 * 16 + t * 64, h * 128, B_WO);
            if (!ISV) {
              tma_load_2d(WO + 81920, &P.wo16, tile0 * 16 + 320, h * 128, B_WO);
              tma_load_2d(WO + 86016, &P.wo16, tile0 * 16 + 336, h * 128, B_WO);
            }
          }
        }
      }
    }
    PROF2(1);
    if (WG == 0 && w == 1) {
      uint4 v;
#pragma unroll 1
      for (int tries = 0; tries < POLL_TRIES; tries++) {
        asm volatile("ld.acquire.gpu.global.v4.u32 {%0,%1,%2,%3}, [%4];" : "=r"(v.x), "=r"(v.y), "=r"(v.z), "=r"(v.w)
                     : "l"(&g_mask[4 * min(lane, 23)]) : "memory");
        if (__all_sync(0xffffffffu, v.x & v.y & v.z & v.w & 0x100)) break;
        __nanosleep(100);
      }
      if (elect_one()) {
        asm volatile("fence.proxy.async.global;" ::: "memory");
        load_xn(P, 0, self);
      }
      sts128(OB + lane * 16, v.x, v.y, v.z, v.w);
    }
    named_bar_sync(NB_C, 256);
#pragma unroll
    for (int i = 0; i < 3; i++) {
      const int t = min(tile0 + 8 * i + w + (WG ? 0 : 4), 63);
      sel |= ((lds32(OB + ((t >> 1) * 3 + (t & 1)) * 4) >> (h >> 3)) & 1) << (2 * i + 1);
    }
    const uint32_t own = lds32(OB + (3 * h + rank) * 4) >> w, m2 = lds32(OB + (3 * h + 2) * 4) >> w;
    sel |= (own & 1) << 7 | (m2 & 1) << 8 | (m2 & 16) << 5;
    sel |= (((((lg ^ h) & 1) << 2) | (lg >> 1)) == (h & 1) + 2 * (h >> 3)) << 10;
  }
  asm volatile("barrier.cluster.wait.aligned;" ::: "memory");
  PRO(14);
  mbar_wait(B_W, 0);
  PRO(15);
  PROF2(4);
  GTSYNC(0);
  PROF2(2);
  KT_END(8);
  if (WG == 0) f_wg0<ISV>(P, wr, h, rank, hw, tid | sel << 8); else f_wg1<ISV>(P, wr, h, rank, hw, tid | sel << 8);
}

__device__ __forceinline__ void f_tail(const FParams& P, const int h, const uint32_t rank) {
  using namespace fk;
  const uint32_t base = mapa(0, rank) + SM0;
  constexpr uint32_t STAGE = 49152, TX = 4 * STAGE, TG = TX + 16384, FULL = TG + 16384, EMPT = FULL + 32, RES = FULL + 64, NOG = FULL + 72;
  const int tid = threadIdx.x, lane = tid & 31, wv = __shfl_sync(0xffffffffu, tid >> 5, 0), wg = wv >> 2;
  const int kq = h & 3, nt = (h >> 2) & 3, mb = TAIL_MB0 + 3 * (h >> 4) + rank;
  TL(0);
  __syncthreads();
  if (tid == 0) {
    for (int i = 0; i < 4; i++) { mbar_init(base + FULL + 8 * i, 1); mbar_init(base + EMPT + 8 * i, 24); }
    mbar_init(base + RES, 1);
    fence_barrier_init();
  }
  __syncwarp();
  asm volatile("barrier.cluster.arrive.relaxed.aligned;\nbarrier.cluster.wait.aligned;" ::: "memory");
  KT_START(7);
  TL(1);
  auto load_b = [&](int kb) {
    const uint32_t sb = base + (kb & 3) * STAGE + 16384, full = base + FULL + 8 * (kb & 3);
    mbar_expect_tx(full, STAGE);
    tma_load_2d_mc(sb + rank * 8192, &P.tb, nt * 256 + ((rank + kq) & 3) * 64, (kq * 16 + kb) * 64, full, 7);
    if (kb % 3 == rank) tma_load_2d_mc(sb + 3 * 8192, &P.tb, nt * 256 + ((3 + kq) & 3) * 64, (kq * 16 + kb) * 64, full, 7);
  };
  auto load_a = [&](int kb) { tma_load_2d(base + (kb & 3) * STAGE, &P.ta, (kq * 16 + kb) * 64, mb * 128, base + FULL + 8 * (kb & 3)); };
  if (wv == 0) {
    if (elect_one()) {
#pragma unroll 1
      for (int kb = 0; kb < 4; kb++) load_b(kb);
      wait_count(&g_oflag[mb], 32);
      asm volatile("fence.proxy.async.global;" ::: "memory");
#pragma unroll 1
      for (int kb = 0; kb < 4; kb++) load_a(kb);
    }
  } else if (wv == 4) {
    if (elect_one()) {
      const bool nog = ld_strong4(&g_next) == 0;
      sts32(base + NOG, nog);
      if (nog) {
        g_tfix[blockIdx.x] = 1;
        mbar_arrive(base + RES);
      } else {
        wait_count(&g_cnt[3][mb], GATE_CNT);
        asm volatile("fence.proxy.async.global;" ::: "memory");
        mbar_expect_tx(base + RES, 32768);
        tma_load_2d(base + TX, &P.tx, nt * 256 + kq * 64, mb * 128, base + RES);
        tma_load_2d(base + TG, &P.tg, nt * 256 + kq * 64, mb * 128, base + RES);
      }
    }
  }
  __syncwarp();
  float acc[128];
#pragma unroll
  for (int i = 0; i < 128; i++) acc[i] = 0.f;
#pragma unroll 1
  for (int kb = 0; kb < 16; kb++) {
    const uint32_t st = kb & 3, sa = base + st * STAGE + wg * 8192, sb = base + st * STAGE + 16384;
    mbar_wait(base + FULL + 8 * st, (kb >> 2) & 1);
    if (kb == 0) TL(2);
    if (kb == 4) TL(3);
    if (kb == 10) TL(4);
    wg_fence();
#pragma unroll
    for (int k = 0; k < 4; k++) {
      wgmma_ss_n256_tb(acc, make_desc(sa + k * 32, 16, 1024), make_desc(sb + k * 2048, 8192, 1024), 1);
      if (k == 0) {
        wg_commit();
        wg_wait<1>();
        if (kb > 0 && kb <= 12 && lane < 3) mbar_arrive_cluster(base + EMPT + 8 * ((kb - 1) & 3), lane);
        wg_fence();
      }
    }
    wg_commit();
    if (kb >= 2 && kb < 14 && wv == ((kb & 1) << 2)) {
      if (elect_one()) {
        mbar_wait(base + EMPT + 8 * ((kb - 2) & 3), ((kb - 2) >> 2) & 1);
        load_b(kb + 2);
        load_a(kb + 2);
      }
      __syncwarp();
    }
  }
  wg_wait<0>();
  TL(5);
#pragma unroll
  for (int j = 1; j < 4; j++) {
    uint4* dst = &g_tpart[((h & ~3) + ((j + kq) & 3)) * 3 + rank][j - 1][0][tid];
#pragma unroll
    for (int i = 0; i < 4; i++) {
      const float* a = &acc[32 * j + 8 * i];
      dst[i * 256] = make_uint4(pack_bf16(a[0], a[1]), pack_bf16(a[2], a[3]), pack_bf16(a[4], a[5]), pack_bf16(a[6], a[7]));
    }
  }
  TL(6);
  __syncthreads();
  if (tid == 0) asm volatile("st.release.gpu.global.u32 [%0], 1;" ::"l"(&g_tflag[blockIdx.x]) : "memory");
  if (wv == 1) {
#pragma unroll 1
    for (int tries = 0; tries < POLL_TRIES; tries++) {
      uint32_t v;
      asm volatile("ld.acquire.gpu.global.u32 %0, [%1];" : "=r"(v) : "l"(&g_tflag[((h & ~3) + (lane & 3)) * 3 + rank]) : "memory");
      if (__all_sync(0xffffffffu, v)) break;
    }
  }
  mbar_wait(base + RES, 0);
  __syncthreads();
  const bool nog = lds32(base + NOG);
  TL(7);
  uint4 pt[3][4];
#pragma unroll
  for (int j = 0; j < 3; j++)
#pragma unroll
    for (int i = 0; i < 4; i++) pt[j][i] = __ldcg(&g_tpart[blockIdx.x][j][i][tid]);
  const uint32_t xa = base + TX + (wv * 16 + ((lane >> 3) & 1) * 8 + (lane & 7)) * 128 + (((lane >> 4) ^ (lane & 7)) << 4);
#pragma unroll
  for (int i = 0; i < 4; i++) {
    uint32_t x[4], g[4], o[4];
    ldsm4(x, xa ^ (i << 5));
    ldsm4(g, (xa ^ (i << 5)) + 16384);
#pragma unroll
    for (int k = 0; k < 4; k++) {
      const uint32_t p0 = (&pt[0][i].x)[k], p1 = (&pt[1][i].x)[k], p2 = (&pt[2][i].x)[k];
      const uint32_t sv = pack_bf16((acc[8 * i + 2 * k] + bf_lo(p0)) + (bf_lo(p1) + bf_lo(p2)),
                                    (acc[8 * i + 2 * k + 1] + bf_hi(p0)) + (bf_hi(p1) + bf_hi(p2)));
      o[k] = nog ? sv : add_bf16x2(x[k], mul_bf16x2(sv, g[k]));
    }
    stsm4(xa ^ (i << 5), o[0], o[1], o[2], o[3]);
  }
  TL(8);
  fence_proxy_async_smem();
  __syncthreads();
  TL(9);
  if (tid == 0) {
    tma_store_2d(&P.tout, base + TX, nt * 256 + kq * 64, mb * 128);
    tma_store_commit();
    tma_store_wait_read();
  }
  KT_END(7);
}

__global__ void __launch_bounds__(256, 1) f_kernel(const __grid_constant__ FParams P) {
  using namespace fk;
  extern __shared__ __align__(1024) uint8_t smem_f[];
  uint32_t crank, rank, hw;
  asm("mov.u32 %0, %%cluster_ctarank;" : "=r"(crank));
  const int h = blockIdx.x / 3;
  if (smem_u32(smem_f) != mapa(0, crank) + SM0) return;
  PROF2(0);
  KT_START(1);
  KT_START(0);
  {
    const uint32_t self = mapa(0, crank);
    SMAP;
    const int tid = threadIdx.x, lane = tid & 31, wv = __shfl_sync(0xffffffffu, tid >> 5, 0);
    PRO(0);
    const int row0 = blockIdx.x * 8 + wv;
    const bool third = row0 + 1536 < cfg::S;
    uint32_t cur[1][16], raw[2][16];
    load_row16(cur[0], P.x + (size_t)row0 * cfg::D, lane);
    load_row16(raw[0], P.x + (size_t)(row0 + 768) * cfg::D, lane);
    load_row16(raw[1], P.x + (size_t)(row0 + (third ? 1536 : 0)) * cfg::D, lane);
    {
      uint32_t tpc;
      asm("mov.u32 %0, %%smid;" : "=r"(tpc));
      if (tid == 0) sts32(PROBE + 96, tpc >> 1);
      asm volatile("barrier.cluster.arrive.release.aligned;\nbarrier.cluster.wait.acquire.aligned;" ::: "memory");
      asm volatile("ld.shared::cluster.u32 %0, [%1];" : "=r"(tpc) : "r"(mapa(PROBE + 96, lane % 3)) : "memory");
      const uint32_t t0 = __shfl_sync(0xffffffffu, tpc, 0), t1 = __shfl_sync(0xffffffffu, tpc, 1), t2 = __shfl_sync(0xffffffffu, tpc, 2);
      hw = t1 == t2 ? 0x09 : t0 == t2 ? 0x18 : 0x24;
      rank = (hw & 3) == crank ? 0 : ((hw >> 2) & 3) == crank ? 1 : 2;
    }
    const bool isv = rank == 2;
    const CUtensorMap* m0 = isv ? &P.wv : &P.wq;
    const CUtensorMap* m1 = isv ? &P.wv : &P.wk;
    const int col0 = h * 128 + (isv ? 0 : 64 * rank), col1 = h * 128 + (isv ? 64 : 64 * rank);
    if (wv == 1) {
      const uint32_t off = (blockIdx.x * 32 + lane) * 688;
      if (off < cfg::D * cfg::D * 2) l2_prefetch(reinterpret_cast<const char*>(P.w1) + off, min(688u, cfg::D * cfg::D * 2 - off));
    }
    if (wv == 0) {
      if (elect_one()) {
        for (int i = 0; i < 2; i++) mbar_init(B_XN + 8 * i, 1);
        mbar_init(B_H1, 4);
        mbar_init(B_SM, isv ? 1 : 6);
        mbar_init(B_VM, isv ? 8 : 1);
        mbar_init(B_VX, 1);
        mbar_init(B_ST, 1);
        mbar_init(B_PF, 2);
        for (int i = 0; i < 6; i++) mbar_init(B_PB + 8 * i, 1);
        mbar_init(B_W, 2);
        mbar_init(B_WO, 1);
        fence_barrier_init();
        mbar_expect_tx(B_SM, isv ? 2 * SP_SRC : SP_SRC);
        if (isv) mbar_expect_tx(B_ST, 7168);
        else { mbar_expect_tx(B_VM, 2048); mbar_expect_tx(B_VX, 8192); }
      }
    }
    const int j = 2 * h + rank;
    if (lane == 0) {
      const uint2 b = probe_pair(P.xch + (isv ? H1_BYTES + wv * 8192 + h * 128 : j * 32768 + (wv & 3) * 8192 + (wv >> 2) * 128),
                                 isv ? EMPTY : 0, PROBE + 64, P.nprobe);
      sts64(PROBE + wv * 8, b.x, b.y);
    }
    PROF2(3);
    PRO(1);
    __syncwarp();
    if (wv == 0) {
      asm volatile("{\n.reg .pred p;\nsetp.eq.u32 p, %0, %1;\n@p st.shared.u32 [%2], %0;\n}" ::"r"(raw[1][15]), "r"(cur[0][0] ^ raw[0][15]), "r"(PROBE + 64) : "memory");
      if (elect_one()) {
#pragma unroll 1
        for (int n = 0; n < 2 * PRE_G; n++) {
          const int i = n >> 1, g = n & 1, row = (isv ? Chunks<true>::rf(g, i) : Chunks<false>::rf(g, i)) * 64;
          if (!g) mbar_expect_tx(B_PB + 8 * i, 32768);
          tma_load_2d(SM0 + n * 16384, m0, col0, row, B_PB + 8 * i);
          tma_load_2d(SM0 + n * 16384 + 8192, m1, col1, row, B_PB + 8 * i);
        }
      }
    }
    __syncthreads();
    PRO(2);
    asm volatile("barrier.cluster.arrive.relaxed.aligned;" ::: "memory");
    PRO(3);
    if (wv == 2) { sts32(self + ONES + lane * 4, 0x3F803F80u); fence_proxy_async_smem(); }
    uint32_t pb[2], pc[2];
    lds64(pb, PROBE + (lane & 7) * 8);
    lds64(pc, PROBE + ((lane & 7) ^ 4) * 8);
    const uint32_t mask = __ballot_sync(0xffffffffu, isv ? pb[1] < pb[0] : min(pb[1], pc[1]) < min(pb[0], pc[0])) & (isv ? 255 : 15);
    if (!isv) {
#pragma unroll
      for (int i = 0; i < 4; i++) st_pub128(P.xch + j * 32768 + i * 8192 + ((mask >> i) & 1) * 4096 + tid * 16, 0);
      if (wv < 4) st_pub64(P.xch + H1_BYTES + (wv >> 1) * 32768 + (j >> 4) * 8192 + (wv & 1) * 4096 + (j & 15) * 256 + lane * 8, EMPTY, EMPTY);
    }
    if (blockIdx.x == 2) {
      if (tid < 96) (&g_cnt[0][0])[tid] = 0;
      else if (tid < 112) g_oflag[tid - 96] = 0;
      else if (tid == 112) g_next = 0;
      else if (tid >= 128 && tid < 224) { g_tflag[tid - 128] = 0; g_tfix[tid - 128] = 0; }
    }
#pragma unroll 1
    for (int it = 0; it < (third ? 6 : 4); it++) {
      ln_regs<1>(cur);
      store_row16(cur[0], ((it & 1) ? P.xn2 : P.xn_ptr) + (size_t)(row0 + (it >> 1) * 768) * cfg::D, lane);
      if (it == 0) PRO(4);
      if (it & 1) {
#pragma unroll
        for (int i = 0; i < 16; i++) { cur[0][i] = raw[0][i]; raw[0][i] = raw[1][i]; }
      }
    }
    PRO(5);
    __syncthreads();
    PRO(6);
    if (tid == 64) {
      __threadfence();
      PRO(7);
      pdl_launch_dependents();
      st_pub32(&g_mask[3 * h + rank], 0x100 | mask);
    }
    KT_END(0);
    __syncwarp();
  }
  const int wg = __shfl_sync(0xffffffffu, threadIdx.x >> 7, 0);
  if (rank == 2) { if (wg == 0) f_main<true, 0>(P, h, 2, hw); else f_main<true, 1>(P, h, 2, hw); }
  else { if (wg == 0) f_main<false, 0>(P, h, rank, hw); else f_main<false, 1>(P, h, rank, hw); }
  PROF2(5);
  GTSYNC(1);
  KT_END(1);
  __syncwarp();
  f_tail(P, h, crank);
}

#define GCL 1
namespace gk {
enum { T_B1 = 0, T_B2 = 1, T_B3 = 2, T_B4 = 3, T_O = 4, T_LN = 5, T_END = 7 };
constexpr int NST = 3, STAGE = 49152, MAXITEMS = 512, NEW = 3;
constexpr uint32_t OUTB = NST * STAGE, BARS = OUTB + 65536;
constexpr uint32_t B_FULL = BARS, B_EMPTY = BARS + 32, B_ITEM = BARS + 64, B_FILL = BARS + 128, B_FREE = BARS + 160, ITEMS = BARS + 192;
constexpr int SMEM = BARS + 256;
static_assert(GATE_CNT == 4 * NEW && T_B4 == 3, "gate counter");
}
struct GParams {
  CUtensorMap a[5], b[5];
  bf16* c[5];
  const bf16* r[5];
  bf16* x1n;
  int nitems, lnpos;
  uint16_t items[gk::MAXITEMS];
};
#define ILOG(i)

__device__ __forceinline__ void tma_load_3d_mc(uint32_t dst, const CUtensorMap* map, int x, int y, int z, uint32_t bar) {
  asm volatile("cp.async.bulk.tensor.3d.shared::cluster.global.mbarrier::complete_tx::bytes.multicast::cluster "
               "[%0], [%1, {%3, %4, %5}], [%2], %6;"
               ::"r"(dst), "l"(map), "r"(bar), "r"(x), "r"(y), "r"(z), "h"((uint16_t)3) : "memory");
}
__device__ __forceinline__ float tanh_approx(float x) { float y; asm("tanh.approx.f32 %0, %1;" : "=f"(y) : "f"(x)); return y; }
__global__ void __launch_bounds__(384, 1) g_kernel(const __grid_constant__ GParams P) {
  using namespace gk;
  extern __shared__ __align__(1024) uint8_t smem_g[];
  const uint32_t base = smem_u32(smem_g);
  const int tid = threadIdx.x, warp = __shfl_sync(0xffffffffu, tid >> 5, 0), lane = tid & 31;
  const int rank = blockIdx.x % GCL;
  KT_START(2);
  if (tid == 0) {
    for (int s = 0; s < NST; s++) { mbar_init(base + B_FULL + 8 * s, 1); mbar_init(base + B_EMPTY + 8 * s, 8 * GCL); }
    for (int s = 0; s < 8; s++) mbar_init(base + B_ITEM + 8 * s, 1);
    for (int s = 0; s < 2; s++) { mbar_init(base + B_FILL + 8 * s, 4); mbar_init(base + B_FREE + 8 * s, NEW); }
    fence_barrier_init();
  }
  __syncthreads();
  if (GCL > 1) cluster_sync();
  auto release = [&](uint32_t st) {
    if (GCL > 1) { if (lane < GCL) mbar_arrive_cluster(base + B_EMPTY + 8 * st, lane); }
    else if (lane == 0) mbar_arrive(base + B_EMPTY + 8 * st);
  };
  auto get_item = [&](int q) {
    mbar_wait(base + B_ITEM + 8 * (q & 7), (q >> 3) & 1);
    return lds32(base + ITEMS + 4 * (q & 7));
  };

  if (warp >= 8) {
   if (warp == 8) {
    if (lane == 0) {
      uint32_t st = 0, ph = 1;
#pragma unroll 1
      for (int q = 0;; q++) {
        if (GCL > 1) mbar_expect_tx(base + B_ITEM + 8 * (q & 7), 4);
        if (rank == 0) {
          const unsigned idx = atomicAdd(&g_next, 1), ln = idx - P.lnpos;
          const uint32_t v = (idx < (unsigned)P.nitems ? P.items[idx] : T_END) | (ln < 64 / GCL ? (ln + 1) << 16 : 0);
          if (GCL > 1) {
#pragma unroll
            for (int r = 0; r < GCL; r++) st_async32(mapa(base + ITEMS + 4 * (q & 7), r), v, mapa(base + B_ITEM + 8 * (q & 7), r));
          } else {
            sts32(base + ITEMS + 4 * (q & 7), v);
            mbar_arrive(base + B_ITEM + 8 * (q & 7));
          }
        }
        const uint32_t item = get_item(q);
        const int type = item & 7, mb = ((item >> 3) & 15) + rank, nt = (item >> 7) & 15;
        ILOG(1);
        if (q == 0) { __threadfence(); sts32(base + ITEMS + 32, ld_strong4(&g_oflag[14]) >= 32); }
        if (type == T_END) break;
        if (type == T_B2) {
          wait_count(&g_cnt[T_B1][max(mb - 1, 0)], 4 * NEW); wait_count(&g_cnt[T_B1][mb], 4 * NEW); wait_count(&g_cnt[T_B1][min(mb + 1, 15)], 4 * NEW);
        } else if (type == T_B3) wait_count(&g_cnt[T_LN][mb], 32);
        else if (type == T_B4) wait_count(&g_cnt[T_B3][mb], 14 * NEW);
        else if (type == T_O) wait_count(&g_oflag[mb], 32);
        asm volatile("fence.proxy.async.global;" ::: "memory");
        ILOG(2);
        const CUtensorMap *ma = &P.a[type], *mbm = &P.b[type];
        const int nkb = type == T_B4 ? cfg::F / 64 : type == T_O ? cfg::HD / 64 : cfg::D / 64;
#pragma unroll 1
        for (int kb = 0; kb < nkb; kb++) {
          mbar_wait(base + B_EMPTY + 8 * st, ph);
          const uint32_t sa = base + st * STAGE, full = base + B_FULL + 8 * st;
          mbar_expect_tx(full, STAGE);
          int arow = mb * 128;
          if (type == T_B2) { const int qd = kb >> 2; arow += (qd == 0) ? -1 : (qd == 1) ? 1 : (qd == 2) ? -2 : 2; }
          if (GCL > 1) tma_load_3d_mc(sa + 16384 + rank * 16384, mbm, 0, kb * 64, nt * 4 + rank * 2, full);
          else tma_load_3d(sa + 16384, mbm, 0, kb * 64, nt * 4, full);
          tma_load_2d(sa, ma, kb * 64, arow, full);
          if (++st == NST) { st = 0; ph ^= 1; }
        }
      }
    }
   } else {
    const int ew = warp - 9;
#pragma unroll 1
    for (int q = 0;; q++) {
      const uint32_t item = get_item(q);
      const int type = item & 7, mb = ((item >> 3) & 15) + rank, nt = (item >> 7) & 15;
      if (type == T_END) break;
      if (type == T_O) wait_count(&g_cnt[T_B4][mb], 4 * NEW);
      const int ldc = type == T_B3 ? cfg::F : cfg::D;
      bf16* cp = P.c[type] + (size_t)mb * 128 * ldc + nt * 256 + lane * 8;
      const size_t roff = (size_t)mb * 128 * cfg::D + nt * 256 + lane * 8;
      const bf16 *rp = P.r[type] + roff, *gp = P.c[T_B4] + roff;
      const bool res = type == T_B2 || type >= T_B4, act = type != T_B2 && type != T_O;
      const float c1 = type == T_B4 ? 0.f : 0.035677408136300125f, c0 = type == T_B4 ? 0.5f : 0.7978845608028654f;
      uint32_t yn[4][4];
      uint4 rn[4], gn[4];
      auto fetch_res = [&](int grp) {
#pragma unroll
        for (int i = 0; i < 4; i++) {
          if (res) rn[i] = __ldcg(reinterpret_cast<const uint4*>(rp + (grp * 4 + i) * cfg::D));
          if (type == T_O) gn[i] = __ldcg(reinterpret_cast<const uint4*>(gp + (grp * 4 + i) * cfg::D));
        }
      };
      auto fetch_y = [&](int grp) {
#pragma unroll
        for (int i = 0; i < 4; i++) lds128(yn[i], base + OUTB + (grp * 4 + i) * 512 + ((lane ^ ((grp * 4 + i) & 7)) << 4));
      };
      if (type == T_B4) wait_count(&g_cnt[T_B2][mb], 4 * NEW);
      fetch_res(ew);
      mbar_wait(base + B_FILL, q & 1);
      fetch_y(ew);
#pragma unroll 1
      for (int grp = ew; grp < 32; grp += NEW) {
        uint32_t y[4][4];
#pragma unroll
        for (int i = 0; i < 4; i++) {
#pragma unroll
          for (int k = 0; k < 4; k++) y[i][k] = yn[i][k];
          if (type == T_O) {
            y[i][0] = mul_bf16x2(y[i][0], gn[i].x); y[i][1] = mul_bf16x2(y[i][1], gn[i].y);
            y[i][2] = mul_bf16x2(y[i][2], gn[i].z); y[i][3] = mul_bf16x2(y[i][3], gn[i].w);
          }
          if (res) {
            y[i][0] = add_bf16x2(y[i][0], rn[i].x); y[i][1] = add_bf16x2(y[i][1], rn[i].y);
            y[i][2] = add_bf16x2(y[i][2], rn[i].z); y[i][3] = add_bf16x2(y[i][3], rn[i].w);
          }
        }
        const int nx = grp + NEW;
        if (nx < 32) {
          fetch_res(nx);
          if (nx >= 16 && grp < 16) {
            __syncwarp();
            if (lane == 0) mbar_arrive(base + B_FREE);
            mbar_wait(base + B_FILL + 8, q & 1);
          }
          fetch_y(nx);
        }
        if (act) {
#pragma unroll
          for (int i = 0; i < 4; i++)
#pragma unroll
            for (int k = 0; k < 4; k++) {
              const float v0 = bf_lo(y[i][k]), v1 = bf_hi(y[i][k]);
              const float t0 = tanh_approx(v0 * fmaf(v0 * c1, v0, c0)), t1 = tanh_approx(v1 * fmaf(v1 * c1, v1, c0));
              const float h0 = 0.5f * v0, h1 = 0.5f * v1;
              y[i][k] = pack_bf16(fmaf(h0, t0, h0), fmaf(h1, t1, h1));
            }
        }
#pragma unroll
        for (int i = 0; i < 4; i++)
          *reinterpret_cast<uint4*>(cp + (size_t)(grp * 4 + i) * ldc) = make_uint4(y[i][0], y[i][1], y[i][2], y[i][3]);
      }
      __syncwarp();
      if (lane == 0) mbar_arrive(base + B_FREE + 8);
      if (type != T_O) {
        __threadfence();
        __syncwarp();
        if (lane == 0) atomicAdd(&g_cnt[type][mb], 1);
      }
      if (tid == 288) ILOG(7);
    }
   }
   __syncwarp();
   named_bar_sync(1, 128);
   const bool late = lds32(base + ITEMS + 32);
   if (late) pdl_wait();
#pragma unroll 1
   for (int c = blockIdx.x; late && c < 96; c += gridDim.x) {
     if (__ldcg(&g_tfix[c]) == 0) continue;
     const int hh = c / 3, mb = TAIL_MB0 + 3 * (hh >> 4) + c % 3;
     wait_count(&g_cnt[T_B4][mb], GATE_CNT);
#pragma unroll 1
     for (int i = tid - 256; i < 1024; i += 128) {
       const size_t off = (size_t)(mb * 128 + (i >> 3)) * cfg::D + (hh & 15) * 64 + (i & 7) * 8;
       const uint4 sv = __ldcg(reinterpret_cast<const uint4*>(P.c[T_O] + off)), gv = __ldcg(reinterpret_cast<const uint4*>(P.c[T_B4] + off)),
                   xv = __ldcg(reinterpret_cast<const uint4*>(P.r[T_O] + off));
       *reinterpret_cast<uint4*>(P.c[T_O] + off) = make_uint4(add_bf16x2(xv.x, mul_bf16x2(sv.x, gv.x)), add_bf16x2(xv.y, mul_bf16x2(sv.y, gv.y)),
                                                              add_bf16x2(xv.z, mul_bf16x2(sv.z, gv.z)), add_bf16x2(xv.w, mul_bf16x2(sv.w, gv.w)));
     }
   }
   if (GCL > 1) cluster_sync();
  } else {
    const int wg = warp >> 2;
    const uint32_t outa = base + OUTB + (warp * 16 + ((lane >> 3) & 1) * 8 + (lane & 7)) * 512 + (((lane >> 4) ^ (lane & 7)) << 4);
    uint32_t st = 0, ph = 0;
    float acc[128];
#pragma unroll 1
    for (int q = 0;; q++) {
      const uint32_t item = get_item(q);
      const int type = item & 7;
      if (type == T_END) break;
      if (item >> 16) {
        const int ln = (item >> 16) - 1, lb = (ln >> 2) * GCL + rank;
        const size_t row = (size_t)(lb * 128 + (ln & 3) * 32 + warp * 4) * cfg::D;
        wait_count(&g_cnt[T_B2][lb], 4 * NEW);
        uint32_t raw[4][16];
#pragma unroll
        for (int r = 0; r < 4; r++) load_row16(raw[r], P.c[T_B2] + row + r * cfg::D, lane);
        ln_regs<4>(raw);
#pragma unroll
        for (int r = 0; r < 4; r++) store_row16(raw[r], P.x1n + row + r * cfg::D, lane);
        __threadfence();
        __syncwarp();
        if (lane == 0) atomicAdd(&g_cnt[T_LN][lb], 1);
        if (tid == 0) ILOG(6);
#pragma unroll
        for (int i = 0; i < 128; i++) acc[i] = 0.f;
      }
      const int nkb = type == T_B4 ? cfg::F / 64 : type == T_O ? cfg::HD / 64 : cfg::D / 64;
      uint32_t prev = 0;
#pragma unroll 1
      for (int kb = 0; kb < nkb; kb++) {
        if (kb == 0) mbar_wait(base + B_FULL + 8 * st, ph); else mbar_spin(base + B_FULL + 8 * st, ph);
        if (kb == 0 && tid == 0) ILOG(3);
        const uint32_t sa = base + st * STAGE + wg * 8192, sb = base + st * STAGE + 16384;
        wg_fence();
#pragma unroll
        for (int k = 0; k < 4; k++) {
          wgmma_ss_n256_tb(acc, make_desc(sa + k * 32, 16, 1024), make_desc(sb + k * 2048, 8192, 1024), (kb | k) != 0);
          if (k == 0) {
            wg_commit();
            wg_wait<1>();
            if (kb > 0) release(prev);
            wg_fence();
          }
        }
        wg_commit();
        prev = st;
        if (++st == NST) { st = 0; ph ^= 1; }
      }
      if (q > 0) mbar_wait(base + B_FREE + 8 * wg, (q - 1) & 1);
      wg_wait<0>();
      if (tid == 0) ILOG(4);
      release(prev);
#pragma unroll
      for (int j = 0; j < 16; j++)
        stsm4((outa ^ ((j & 3) << 5)) + (j >> 2) * 128, pack_bf16(acc[8 * j], acc[8 * j + 1]), pack_bf16(acc[8 * j + 2], acc[8 * j + 3]),
              pack_bf16(acc[8 * j + 4], acc[8 * j + 5]), pack_bf16(acc[8 * j + 6], acc[8 * j + 7]));
      __syncwarp();
      if (lane == 0) mbar_arrive(base + B_FILL + 8 * wg);
      if (tid == 0) ILOG(5);
    }
    KT_END(2);
    if (GCL > 1) cluster_sync();
  }
}

__device__ bf16 g_xn[cfg::S * cfg::D];
__device__ bf16 g_xn2[cfg::S * cfg::D];
__device__ bf16 g_h[cfg::S * cfg::D];
__device__ bf16 g_x1[cfg::S * cfg::D];
__device__ bf16 g_x1n[cfg::S * cfg::D];
__device__ bf16 g_u[cfg::S * cfg::F];
__device__ bf16 g_g[cfg::S * cfg::D];
__device__ bf16 g_o[cfg::S * cfg::HD];

typedef CUresult (*PFN_encodeTiled)(CUtensorMap*, CUtensorMapDataType, cuuint32_t, void*, const cuuint64_t*,
                                    const cuuint64_t*, const cuuint32_t*, const cuuint32_t*, CUtensorMapInterleave,
                                    CUtensorMapSwizzle, CUtensorMapL2promotion, CUtensorMapFloatOOBfill);

static PFN_encodeTiled get_encoder() {
  static PFN_encodeTiled fn = nullptr;
  if (!fn) {
    void* p = nullptr;
    cudaDriverEntryPointQueryResult st;
    cudaGetDriverEntryPoint("cuTensorMapEncodeTiled", &p, cudaEnableDefault, &st);
    fn = (PFN_encodeTiled)p;
  }
  return fn;
}
static CUtensorMap make_map(const void* ptr, int rows, int cols, int box_rows, int box_cols, int swizzle_bytes) {
  CUtensorMap m;
  cuuint64_t dims[2] = {(cuuint64_t)cols, (cuuint64_t)rows};
  cuuint64_t strides[1] = {(cuuint64_t)cols * 2};
  cuuint32_t box[2] = {(cuuint32_t)box_cols, (cuuint32_t)box_rows};
  cuuint32_t estr[2] = {1, 1};
  CUtensorMapSwizzle sw = swizzle_bytes == 128 ? CU_TENSOR_MAP_SWIZZLE_128B
                        : swizzle_bytes == 64 ? CU_TENSOR_MAP_SWIZZLE_64B
                        : swizzle_bytes == 32 ? CU_TENSOR_MAP_SWIZZLE_32B : CU_TENSOR_MAP_SWIZZLE_NONE;
  get_encoder()(&m, CU_TENSOR_MAP_DATA_TYPE_BFLOAT16, 2, const_cast<void*>(ptr), dims, strides, box, estr,
                CU_TENSOR_MAP_INTERLEAVE_NONE, sw, CU_TENSOR_MAP_L2_PROMOTION_L2_128B, CU_TENSOR_MAP_FLOAT_OOB_FILL_NONE);
  return m;
}
static CUtensorMap make_map3(const void* ptr, int rows, int cols, int box_rows, int nblk) {
  CUtensorMap m;
  cuuint64_t dims[3] = {64, (cuuint64_t)rows, (cuuint64_t)(cols / 64)};
  cuuint64_t strides[2] = {(cuuint64_t)cols * 2, 128};
  cuuint32_t box[3] = {64, (cuuint32_t)box_rows, (cuuint32_t)nblk};
  cuuint32_t estr[3] = {1, 1, 1};
  get_encoder()(&m, CU_TENSOR_MAP_DATA_TYPE_BFLOAT16, 3, const_cast<void*>(ptr), dims, strides, box, estr,
                CU_TENSOR_MAP_INTERLEAVE_NONE, CU_TENSOR_MAP_SWIZZLE_128B, CU_TENSOR_MAP_L2_PROMOTION_L2_128B,
                CU_TENSOR_MAP_FLOAT_OOB_FILL_NONE);
  return m;
}
template <class T> static T* sym(T& s) { void* p = nullptr; cudaGetSymbolAddress(&p, s); return (T*)p; }
#define SYM(name) ((bf16*)[] { void* p = nullptr; cudaGetSymbolAddress(&p, name); return p; }())

#define G_CTAS 36
#define LN_POS 64
static int build_items(uint16_t* it) {
  using namespace gk;
  int n = 0;
  auto add = [&](int type, int nrows, int ncols) {
    for (int mb = 0; mb < nrows; mb += GCL) for (int nt = 0; nt < ncols; nt++) it[n++] = (uint16_t)(type | mb << 3 | nt << 7);
  };
  add(T_B1, 16, 4); add(T_B2, 16, 4); add(T_B3, 16, 14); add(T_B4, 16, 4); add(T_O, TAIL_MB0, 4);
  return n;
}

extern "C" void kernel_launch(void* const* d_in, const int* in_sizes, int n_in, void* d_out, int out_size) {
  using namespace cfg;
  const bf16* x = (const bf16*)d_in[0];
  const bf16* mem0 = (const bf16*)d_in[1];
  const bf16* Wq = (const bf16*)d_in[2];
  const bf16* Wk = (const bf16*)d_in[3];
  const bf16* Wv = (const bf16*)d_in[4];
  const bf16* Wo = (const bf16*)d_in[5];
  const bf16* w1 = (const bf16*)d_in[8];
  const bf16* w2 = (const bf16*)d_in[9];
  const bf16* w3 = (const bf16*)d_in[10];
  const bf16* w4 = (const bf16*)d_in[11];
  bf16* out = (bf16*)d_out;
  cudaStream_t st = cudaStreamPerThread;

  bf16 *xn = SYM(g_xn), *xn2 = SYM(g_xn2), *hb = SYM(g_h), *x1 = SYM(g_x1), *x1n = SYM(g_x1n), *u = SYM(g_u),
       *g = SYM(g_g), *o = SYM(g_o);

  {
    cudaFuncSetAttribute(f_kernel, cudaFuncAttributeMaxDynamicSharedMemorySize, fk::SMEM);
    FParams P;
    P.wq = make_map(Wq, D, HD, 64, 64, 128); P.wk = make_map(Wk, D, HD, 64, 64, 128); P.wv = make_map(Wv, D, HD, 64, 64, 128);
    P.wo = make_map(Wo, HD, D, 128, 64, 128); P.wo16 = make_map(Wo, HD, D, 128, 16, 32); P.xn = make_map3(xn, S, D, 32, 4); P.xn12 = make_map3(xn, S, D, 32, 12); P.o = make_map3(o, S, HD, 32, 2);
    P.ta = make_map(o, S, HD, 128, 64, 128); P.tb = make_map(Wo, HD, D, 64, 64, 128); P.tx = make_map(x, S, D, 128, 64, 128);
    P.tg = make_map(g, S, D, 128, 64, 128); P.tout = make_map(out, S, D, 128, 64, 128);
    P.mem0 = mem0;
    P.nprobe = PROBE_N;
    P.x = x; P.w1 = w1; P.xn_ptr = xn; P.xn2 = xn2;
    P.xch = (char*)(((uintptr_t)SYM(g_xch) + 8191) & ~(uintptr_t)8191);
    cudaLaunchConfig_t cfg = {};
    cfg.gridDim = dim3(96); cfg.blockDim = dim3(256); cfg.dynamicSmemBytes = fk::SMEM; cfg.stream = st;
    cudaLaunchAttribute at[2];
    at[0].id = cudaLaunchAttributeClusterDimension;
    at[0].val.clusterDim.x = 3; at[0].val.clusterDim.y = 1; at[0].val.clusterDim.z = 1;
    cfg.attrs = at; cfg.numAttrs = 1;
    cudaLaunchKernelEx(&cfg, f_kernel, P);
  }
  {
    cudaFuncSetAttribute(g_kernel, cudaFuncAttributeMaxDynamicSharedMemorySize, gk::SMEM);
    GParams G;
    const bf16* as[5] = {xn2, hb, x1n, u, o};
    const bf16* bs[5] = {w1, w2, w3, w4, Wo};
    bf16* cs[5] = {hb, x1, u, g, out};
    const bf16* rs[5] = {xn, xn, xn, x1, x};
    const int ks[5] = {D, D, D, F, HD}, ns[5] = {D, D, F, D, D};
    for (int i = 0; i < 5; i++) {
      G.a[i] = make_map(as[i], S, ks[i], 128, 64, 128);
      G.b[i] = make_map3(bs[i], ks[i], ns[i], 64, 4 / GCL);
      G.c[i] = cs[i];
      G.r[i] = rs[i];
    }
    G.x1n = x1n;
    G.nitems = build_items(G.items);
    G.lnpos = LN_POS * 2 / GCL;
    cudaLaunchConfig_t cfg = {};
    cfg.gridDim = dim3(G_CTAS); cfg.blockDim = dim3(384); cfg.dynamicSmemBytes = gk::SMEM; cfg.stream = st;
    cudaLaunchAttribute at[2];
    at[0].id = cudaLaunchAttributeClusterDimension;
    at[0].val.clusterDim.x = GCL; at[0].val.clusterDim.y = 1; at[0].val.clusterDim.z = 1;
    at[1].id = cudaLaunchAttributeProgrammaticStreamSerialization;
    at[1].val.programmaticStreamSerializationAllowed = 1;
    cfg.attrs = at;
    cfg.numAttrs = 2;
    cudaLaunchKernelEx(&cfg, g_kernel, G);
  }
}
```

```cpp
#include <cuda_runtime.h>
#include <cuda_bf16.h>
#include <cuda.h>
#include <stdint.h>

typedef __nv_bfloat16 bf16;

namespace cfg {
constexpr int S = 2048;
constexpr int D = 1024;
constexpr int H = 32;
constexpr int DH = 128;
constexpr int HD = H * DH;
constexpr int M = 8;
constexpr int SEG = 32;
constexpr int NSEG = S / SEG;
constexpr int F = 3584;
}

__device__ __forceinline__ uint32_t smem_u32(const void* p) { return (uint32_t)__cvta_generic_to_shared(p); }

__device__ __forceinline__ void mbar_init(uint32_t bar, uint32_t count) {
  asm volatile("mbarrier.init.shared::cta.b64 [%0], %1;" ::"r"(bar), "r"(count) : "memory");
}
__device__ __forceinline__ void mbar_expect_tx(uint32_t bar, uint32_t bytes) {
  asm volatile("mbarrier.arrive.expect_tx.shared::cta.b64 _, [%0], %1;" ::"r"(bar), "r"(bytes) : "memory");
}
__device__ __forceinline__ void mbar_arrive(uint32_t bar) {
  asm volatile("mbarrier.arrive.shared::cta.b64 _, [%0];" ::"r"(bar) : "memory");
}
__device__ __forceinline__ bool mbar_try(uint32_t bar, uint32_t parity) {
  uint32_t done;
  asm volatile("{\n.reg .pred p;\nmbarrier.try_wait.parity.shared::cta.b64 p, [%1], %2, 20000;\nselp.u32 %0, 1, 0, p;\n}"
               : "=r"(done) : "r"(bar), "r"(parity) : "memory");
  return done != 0;
}
__device__ __forceinline__ bool mbar_try_nohint(uint32_t bar, uint32_t parity) {
  uint32_t done;
  asm volatile("{\n.reg .pred p;\nmbarrier.try_wait.parity.shared::cta.b64 p, [%1], %2;\nselp.u32 %0, 1, 0, p;\n}"
               : "=r"(done) : "r"(bar), "r"(parity) : "memory");
  return done != 0;
}
constexpr int MBAR_TRIES = 4096;
constexpr int POLL_TRIES = 1 << 16;
__device__ __forceinline__ void mbar_wait(uint32_t bar, uint32_t parity) {
#pragma unroll 1
  for (int n = 0; n < MBAR_TRIES; n++)
    if (mbar_try(bar, parity)) break;
}
__device__ __forceinline__ void mbar_wait_fast(uint32_t bar, uint32_t parity) {
#pragma unroll 1
  for (int n = 0; n < (POLL_TRIES << 4); n++)
    if (mbar_try_nohint(bar, parity)) break;
}
__device__ __forceinline__ void fence_barrier_init() { asm volatile("fence.mbarrier_init.release.cluster;" ::: "memory"); }
__device__ __forceinline__ void fence_proxy_async_smem() { asm volatile("fence.proxy.async.shared::cta;" ::: "memory"); }

__device__ __forceinline__ void tma_load_2d(uint32_t dst, const CUtensorMap* map, int x, int y, uint32_t bar) {
  asm volatile("cp.async.bulk.tensor.2d.shared::cluster.global.mbarrier::complete_tx::bytes [%0], [%1, {%3, %4}], [%2];"
               ::"r"(dst), "l"(map), "r"(bar), "r"(x), "r"(y) : "memory");
}
__device__ __forceinline__ void tma_load_3d(uint32_t dst, const CUtensorMap* map, int x, int y, int z, uint32_t bar) {
  asm volatile("cp.async.bulk.tensor.3d.shared::cluster.global.mbarrier::complete_tx::bytes [%0], [%1, {%3, %4, %5}], [%2];"
               ::"r"(dst), "l"(map), "r"(bar), "r"(x), "r"(y), "r"(z) : "memory");
}
__device__ __forceinline__ void tma_store_2d(const CUtensorMap* map, uint32_t src, int x, int y) {
  asm volatile("cp.async.bulk.tensor.2d.global.shared::cta.bulk_group [%0, {%2, %3}], [%1];"
               ::"l"(map), "r"(src), "r"(x), "r"(y) : "memory");
}
__device__ __forceinline__ void tma_store_commit() { asm volatile("cp.async.bulk.commit_group;" ::: "memory"); }
__device__ __forceinline__ void tma_store_wait_all() { asm volatile("cp.async.bulk.wait_group 0;" ::: "memory"); }
__device__ __forceinline__ void tma_store_wait_read() { asm volatile("cp.async.bulk.wait_group.read 0;" ::: "memory"); }
__device__ __forceinline__ void prefetch_tmap(const CUtensorMap* map) {
  asm volatile("prefetch.tensormap [%0];" ::"l"(map) : "memory");
}

__device__ __forceinline__ void wg_fence() { asm volatile("wgmma.fence.sync.aligned;" ::: "memory"); }
__device__ __forceinline__ void wg_commit() { asm volatile("wgmma.commit_group.sync.aligned;" ::: "memory"); }
template <int N> __device__ __forceinline__ void wg_wait() { asm volatile("wgmma.wait_group.sync.aligned %0;" ::"n"(N) : "memory"); }

#define named_bar_sync(id, n) asm volatile("bar.sync %0, %1;" ::"n"(id), "n"(n) : "memory")
#define named_bar_arrive(id, n) asm volatile("bar.arrive %0, %1;" ::"n"(id), "n"(n) : "memory")

__device__ __forceinline__ uint64_t make_desc(uint32_t addr, uint32_t lbo, uint32_t sbo) {
  return (uint64_t)((addr & 0x3FFFF) >> 4) | ((uint64_t)(lbo >> 4) << 16) | ((uint64_t)(sbo >> 4) << 32) | (1ull << 62);
}

__device__ __forceinline__ uint64_t make_desc0(uint32_t addr, uint32_t lbo, uint32_t sbo) {
  return (uint64_t)((addr & 0x3FFFF) >> 4) | ((uint64_t)(lbo >> 4) << 16) | ((uint64_t)(sbo >> 4) << 32);
}

__device__ __forceinline__ uint32_t pack_bf16(float lo, float hi) {
  uint32_t r;
  asm("cvt.rn.bf16x2.f32 %0, %1, %2;" : "=r"(r) : "f"(hi), "f"(lo));
  return r;
}
__device__ __forceinline__ float bf_lo(uint32_t v) { return __uint_as_float(v << 16); }
__device__ __forceinline__ float bf_hi(uint32_t v) { return __uint_as_float(v & 0xFFFF0000u); }
__device__ __forceinline__ float rbf(float v) { return __bfloat162float(__float2bfloat16_rn(v)); }

__device__ __forceinline__ void pdl_launch_dependents() { asm volatile("griddepcontrol.launch_dependents;" ::: "memory"); }
__device__ __forceinline__ void pdl_wait() { asm volatile("griddepcontrol.wait;" ::: "memory"); }

__device__ __forceinline__ float ex2_approx(float x) { float y; asm("ex2.approx.ftz.f32 %0, %1;" : "=f"(y) : "f"(x)); return y; }
__device__ __forceinline__ float rcp_approx(float x) { float y; asm("rcp.approx.ftz.f32 %0, %1;" : "=f"(y) : "f"(x)); return y; }

__device__ __forceinline__ void mul_sigmoid4(float (&v)[4], const float (&t)[4]) {
#pragma unroll
  for (int i = 0; i < 4; i += 2) {
    const float a = 1.0f + ex2_approx(fminf(t[i], 60.0f)), b = 1.0f + ex2_approx(fminf(t[i + 1], 60.0f));
    const float r = rcp_approx(a * b);
    v[i] *= b * r;
    v[i + 1] *= a * r;
  }
}
__device__ __forceinline__ void gelu4(float (&v)[4]) {
  float t[4];
#pragma unroll
  for (int i = 0; i < 4; i++) t[i] = v[i] * fmaf(v[i] * v[i], -0.10294324f, -2.30220819f);
  mul_sigmoid4(v, t);
}
__device__ __forceinline__ void silu4(float (&v)[4]) {
  float t[4];
#pragma unroll
  for (int i = 0; i < 4; i++) t[i] = v[i] * -1.4426950408889634f;
  mul_sigmoid4(v, t);
}

#define KT_START(id)
#define KT_END(id)

__device__ __forceinline__ void wgmma_ss_n256_tb(float (&d)[128], uint64_t da, uint64_t db, int scale_d) {
  asm volatile("{\n.reg .pred p;\nsetp.ne.b32 p, %130, 0;\n"
    "wgmma.mma_async.sync.aligned.m64n256k16.f32.bf16.bf16 "
    "{%0, %1, %2, %3, %4, %5, %6, %7, %8, %9, %10, %11, %12, %13, %14, %15, "
    "%16, %17, %18, %19, %20, %21, %22, %23, %24, %25, %26, %27, %28, %29, %30, %31, "
    "%32, %33, %34, %35, %36, %37, %38, %39, %40, %41, %42, %43, %44, %45, %46, %47, "
    "%48, %49, %50, %51, %52, %53, %54, %55, %56, %57, %58, %59, %60, %61, %62, %63, "
    "%64, %65, %66, %67, %68, %69, %70, %71, %72, %73, %74, %75, %76, %77, %78, %79, "
    "%80, %81, %82, %83, %84, %85, %86, %87, %88, %89, %90, %91, %92, %93, %94, %95, "
    "%96, %97, %98, %99, %100, %101, %102, %103, %104, %105, %106, %107, %108, %109, %110, %111, "
    "%112, %113, %114, %115, %116, %117, %118, %119, %120, %121, %122, %123, %124, %125, %126, %127}, "
    "%128, %129, p, 1, 1, 0, 1;\n}\n"
    : "+f"(d[0]), "+f"(d[1]), "+f"(d[2]), "+f"(d[3]), "+f"(d[4]), "+f"(d[5]), "+f"(d[6]), "+f"(d[7]),
      "+f"(d[8]), "+f"(d[9]), "+f"(d[10]), "+f"(d[11]), "+f"(d[12]), "+f"(d[13]), "+f"(d[14]), "+f"(d[15]),
      "+f"(d[16]), "+f"(d[17]), "+f"(d[18]), "+f"(d[19]), "+f"(d[20]), "+f"(d[21]), "+f"(d[22]), "+f"(d[23]),
      "+f"(d[24]), "+f"(d[25]), "+f"(d[26]), "+f"(d[27]), "+f"(d[28]), "+f"(d[29]), "+f"(d[30]), "+f"(d[31]),
      "+f"(d[32]), "+f"(d[33]), "+f"(d[34]), "+f"(d[35]), "+f"(d[36]), "+f"(d[37]), "+f"(d[38]), "+f"(d[39]),
      "+f"(d[40]), "+f"(d[41]), "+f"(d[42]), "+f"(d[43]), "+f"(d[44]), "+f"(d[45]), "+f"(d[46]), "+f"(d[47]),
      "+f"(d[48]), "+f"(d[49]), "+f"(d[50]), "+f"(d[51]), "+f"(d[52]), "+f"(d[53]), "+f"(d[54]), "+f"(d[55]),
      "+f"(d[56]), "+f"(d[57]), "+f"(d[58]), "+f"(d[59]), "+f"(d[60]), "+f"(d[61]), "+f"(d[62]), "+f"(d[63]),
      "+f"(d[64]), "+f"(d[65]), "+f"(d[66]), "+f"(d[67]), "+f"(d[68]), "+f"(d[69]), "+f"(d[70]), "+f"(d[71]),
      "+f"(d[72]), "+f"(d[73]), "+f"(d[74]), "+f"(d[75]), "+f"(d[76]), "+f"(d[77]), "+f"(d[78]), "+f"(d[79]),
      "+f"(d[80]), "+f"(d[81]), "+f"(d[82]), "+f"(d[83]), "+f"(d[84]), "+f"(d[85]), "+f"(d[86]), "+f"(d[87]),
      "+f"(d[88]), "+f"(d[89]), "+f"(d[90]), "+f"(d[91]), "+f"(d[92]), "+f"(d[93]), "+f"(d[94]), "+f"(d[95]),
      "+f"(d[96]), "+f"(d[97]), "+f"(d[98]), "+f"(d[99]), "+f"(d[100]), "+f"(d[101]), "+f"(d[102]), "+f"(d[103]),
      "+f"(d[104]), "+f"(d[105]), "+f"(d[106]), "+f"(d[107]), "+f"(d[108]), "+f"(d[109]), "+f"(d[110]), "+f"(d[111]),
      "+f"(d[112]), "+f"(d[113]), "+f"(d[114]), "+f"(d[115]), "+f"(d[116]), "+f"(d[117]), "+f"(d[118]), "+f"(d[119]),
      "+f"(d[120]), "+f"(d[121]), "+f"(d[122]), "+f"(d[123]), "+f"(d[124]), "+f"(d[125]), "+f"(d[126]), "+f"(d[127])
    : "l"(da), "l"(db), "r"(scale_d));
}
__device__ __forceinline__ void wgmma_rs_n32(float (&d)[16], const uint32_t* a, uint64_t db, int scale_d) {
  asm volatile("{\n.reg .pred p;\nsetp.ne.b32 p, %21, 0;\n"
    "wgmma.mma_async.sync.aligned.m64n32k16.f32.bf16.bf16 "
    "{%0, %1, %2, %3, %4, %5, %6, %7, %8, %9, %10, %11, %12, %13, %14, %15}, "
    "{%16, %17, %18, %19}, %20, p, 1, 1, 0;\n}\n"
    : "+f"(d[0]), "+f"(d[1]), "+f"(d[2]), "+f"(d[3]), "+f"(d[4]), "+f"(d[5]), "+f"(d[6]), "+f"(d[7]),
      "+f"(d[8]), "+f"(d[9]), "+f"(d[10]), "+f"(d[11]), "+f"(d[12]), "+f"(d[13]), "+f"(d[14]), "+f"(d[15])
    : "r"(a[0]), "r"(a[1]), "r"(a[2]), "r"(a[3]), "l"(db), "r"(scale_d));
}
__device__ __forceinline__ void wgmma_ss_n32_ta(float (&d)[16], uint64_t da, uint64_t db, int scale_d) {
  asm volatile("{\n.reg .pred p;\nsetp.ne.b32 p, %18, 0;\n"
    "wgmma.mma_async.sync.aligned.m64n32k16.f32.bf16.bf16 "
    "{%0, %1, %2, %3, %4, %5, %6, %7, %8, %9, %10, %11, %12, %13, %14, %15}, "
    "%16, %17, p, 1, 1, 1, 0;\n}\n"
    : "+f"(d[0]), "+f"(d[1]), "+f"(d[2]), "+f"(d[3]), "+f"(d[4]), "+f"(d[5]), "+f"(d[6]), "+f"(d[7]),
      "+f"(d[8]), "+f"(d[9]), "+f"(d[10]), "+f"(d[11]), "+f"(d[12]), "+f"(d[13]), "+f"(d[14]), "+f"(d[15])
    : "l"(da), "l"(db), "r"(scale_d));
}
__device__ __forceinline__ void wgmma_ss_n8_ta(float (&d)[4], uint64_t da, uint64_t db, int scale_d) {
  asm volatile("{\n.reg .pred p;\nsetp.ne.b32 p, %6, 0;\n"
    "wgmma.mma_async.sync.aligned.m64n8k16.f32.bf16.bf16 {%0, %1, %2, %3}, %4, %5, p, 1, 1, 1, 0;\n}\n"
    : "+f"(d[0]), "+f"(d[1]), "+f"(d[2]), "+f"(d[3]) : "l"(da), "l"(db), "r"(scale_d));
}
__device__ __forceinline__ void wgmma_ss_n48_tt(float (&d)[24], uint64_t da, uint64_t db, int scale_d) {
  asm volatile("{\n.reg .pred p;\nsetp.ne.b32 p, %26, 0;\n"
    "wgmma.mma_async.sync.aligned.m64n48k16.f32.bf16.bf16 "
    "{%0, %1, %2, %3, %4, %5, %6, %7, %8, %9, %10, %11, %12, %13, %14, %15, %16, %17, %18, %19, %20, %21, %22, %23}, "
    "%24, %25, p, 1, 1, 1, 1;\n}\n"
    : "+f"(d[0]), "+f"(d[1]), "+f"(d[2]), "+f"(d[3]), "+f"(d[4]), "+f"(d[5]), "+f"(d[6]), "+f"(d[7]), "+f"(d[8]), "+f"(d[9]), "+f"(d[10]), "+f"(d[11]), "+f"(d[12]), "+f"(d[13]), "+f"(d[14]), "+f"(d[15]), "+f"(d[16]), "+f"(d[17]), "+f"(d[18]), "+f"(d[19]), "+f"(d[20]), "+f"(d[21]), "+f"(d[22]), "+f"(d[23])
    : "l"(da), "l"(db), "r"(scale_d));
}
__device__ __forceinline__ void wgmma_ss_n32(float (&d)[16], uint64_t da, uint64_t db, int scale_d) {
  asm volatile("{\n.reg .pred p;\nsetp.ne.b32 p, %18, 0;\n"
    "wgmma.mma_async.sync.aligned.m64n32k16.f32.bf16.bf16 "
    "{%0, %1, %2, %3, %4, %5, %6, %7, %8, %9, %10, %11, %12, %13, %14, %15}, "
    "%16, %17, p, 1, 1, 0, 0;\n}\n"
    : "+f"(d[0]), "+f"(d[1]), "+f"(d[2]), "+f"(d[3]), "+f"(d[4]), "+f"(d[5]), "+f"(d[6]), "+f"(d[7]),
      "+f"(d[8]), "+f"(d[9]), "+f"(d[10]), "+f"(d[11]), "+f"(d[12]), "+f"(d[13]), "+f"(d[14]), "+f"(d[15])
    : "l"(da), "l"(db), "r"(scale_d));
}

__device__ __forceinline__ void tma_load_2d_mc(uint32_t dst, const CUtensorMap* map, int x, int y, uint32_t bar, uint16_t mask) {
  asm volatile("cp.async.bulk.tensor.2d.shared::cluster.global.mbarrier::complete_tx::bytes.multicast::cluster "
               "[%0], [%1, {%3, %4}], [%2], %5;"
               ::"r"(dst), "l"(map), "r"(bar), "r"(x), "r"(y), "h"(mask) : "memory");
}
__device__ __forceinline__ void mbar_arrive_cluster(uint32_t bar, uint32_t cta) {
  asm volatile("{\n.reg .b32 r;\nmapa.shared::cluster.u32 r, %0, %1;\nmbarrier.arrive.shared::cluster.b64 _, [r];\n}"
               ::"r"(bar), "r"(cta) : "memory");
}
__device__ __forceinline__ void cluster_sync() {
  asm volatile("barrier.cluster.arrive.release.aligned;\nbarrier.cluster.wait.acquire.aligned;" ::: "memory");
}
__device__ __forceinline__ void wait_count(const unsigned* p, unsigned need) {
#pragma unroll 1
  for (int tries = 0; tries < (1 << 16); tries++) {
    unsigned v;
    asm volatile("ld.acquire.gpu.global.u32 %0, [%1];" : "=r"(v) : "l"(p) : "memory");
    if (v >= need) break;
    __nanosleep(200);
  }
}
__device__ __forceinline__ uint32_t sub_bf16x2(uint32_t a, uint32_t b) {
  uint32_t d;
  asm("sub.rn.bf16x2 %0, %1, %2;" : "=r"(d) : "r"(a), "r"(b));
  return d;
}
__device__ __forceinline__ uint32_t add_bf16x2(uint32_t a, uint32_t b) {
  uint32_t d;
  asm("add.rn.bf16x2 %0, %1, %2;" : "=r"(d) : "r"(a), "r"(b));
  return d;
}
__device__ __forceinline__ uint32_t mul_bf16x2(uint32_t a, uint32_t b) {
  uint32_t d;
  asm("mul.rn.bf16x2 %0, %1, %2;" : "=r"(d) : "r"(a), "r"(b));
  return d;
}

template <int NR>
__device__ __forceinline__ void ln_regs(uint32_t (&raw)[NR][16]) {
  float m[NR], q[NR];
#pragma unroll
  for (int r = 0; r < NR; r++) {
    float s0 = 0.f, s1 = 0.f;
#pragma unroll
    for (int i = 0; i < 16; i++) { s0 += bf_lo(raw[r][i]); s1 += bf_hi(raw[r][i]); }
    m[r] = s0 + s1;
  }
#pragma unroll
  for (int o = 16; o > 0; o >>= 1)
#pragma unroll
    for (int r = 0; r < NR; r++) m[r] += __shfl_xor_sync(0xffffffffu, m[r], o);
#pragma unroll
  for (int r = 0; r < NR; r++) {
    m[r] *= 1.0f / 1024.0f;
    float s0 = 0.f, s1 = 0.f;
#pragma unroll
    for (int i = 0; i < 16; i++) {
      const float d0 = bf_lo(raw[r][i]) - m[r], d1 = bf_hi(raw[r][i]) - m[r];
      s0 = fmaf(d0, d0, s0); s1 = fmaf(d1, d1, s1);
    }
    q[r] = s0 + s1;
  }
#pragma unroll
  for (int o = 16; o > 0; o >>= 1)
#pragma unroll
    for (int r = 0; r < NR; r++) q[r] += __shfl_xor_sync(0xffffffffu, q[r], o);
#pragma unroll
  for (int r = 0; r < NR; r++) {
    const uint32_t mb = pack_bf16(m[r], m[r]);
    float sq;
    asm("sqrt.approx.f32 %0, %1;" : "=f"(sq) : "f"(rbf(rbf(q[r] * (1.0f / 1024.0f)) + 1e-5f)));
    const float inv = rcp_approx(rbf(sq));
#pragma unroll
    for (int i = 0; i < 16; i++) {
      const uint32_t d = sub_bf16x2(raw[r][i], mb);
      raw[r][i] = pack_bf16(bf_lo(d) * inv, bf_hi(d) * inv);
    }
  }
}
__device__ __forceinline__ void load_row16(uint32_t (&raw)[16], const bf16* src, int lane) {
#pragma unroll
  for (int j = 0; j < 4; j++) {
    const uint4 u = __ldcg(reinterpret_cast<const uint4*>(src + j * 256 + lane * 8));
    raw[4 * j] = u.x; raw[4 * j + 1] = u.y; raw[4 * j + 2] = u.z; raw[4 * j + 3] = u.w;
  }
}
__device__ __forceinline__ void store_row16(const uint32_t (&raw)[16], bf16* dst, int lane) {
#pragma unroll
  for (int j = 0; j < 4; j++)
    *reinterpret_cast<uint4*>(dst + j * 256 + lane * 8) = make_uint4(raw[4 * j], raw[4 * j + 1], raw[4 * j + 2], raw[4 * j + 3]);
}

namespace fk {
constexpr uint32_t SM0 = 1024;
constexpr uint32_t WO = SM0, WS = WO + 90112, XN = WS + 65536, VX = XN + 49152, QK = VX + 8192, PT = QK + 8192,
                   SP = PT + 4096, VM = SP + 2560, OB = VM + 2048, BAR = OB + 2048;
constexpr uint32_t MEMB = XN + 16384, RED = XN + 32768, VX2 = WO + 81920;
constexpr int SMEM = 232448;
static_assert(BAR + 512 == SM0 + SMEM, "shared memory layout");
constexpr uint32_t B_XN = BAR, B_H2 = BAR + 64, B_H1 = BAR + 120, ONES = BAR + 384, B_PF = BAR + 16, B_WO = BAR + 24, B_SM = BAR + 32, B_VM = BAR + 40, B_VX = BAR + 48, B_ST = BAR + 56, B_PB = BAR + 64, B_W = BAR + 112,
                   MASKS = BAR + 128, PROBE = BAR + 256;
constexpr int NB_M0 = 1, NB_M1 = 2, NB_C = 3, NB_O = 4, NB_ST = 5, NB_DU = 6, NB_CF = 7, NB_W1 = 8, NB_XE = 9, NB_HD = 10, NB_MX = 11, NB_O0 = 12;
#define D_H1 500
#define D_H2 1850
#define D_ST 100
#define SMQ 0x1E
#define SMV 0x1E
#define PRE_G 5
#define WO_AT 4
#define NS0 4
#define NS0V 4
#define NTA0 2
#define NTA1 1
#define PF0A 3
#define PF0 10
#define PF1A 0
#define PF1V 10
#define PF1 11
#define REFILL_EARLY 1
#define GATE_MX 0
#define GATE_Q 0
#define PF1Q 4
#define XN_EARLY 1
#define PACEQ 0x60
#define PACEV 0
#define PADD 1
#define VM_BULK 0
#define CF_AT 0
#define H2_AT 1
#define NPRE0 1
#define PROBE_N 4
#define SPACK 0
constexpr uint32_t SPW = SPACK ? 4 : 8, SP_SRC = 160 * SPW;
constexpr int H1_BYTES = 64 * 32768, H2_BYTES = 8 * 8192;
}

#define PROF(wg, i)
#define PROF2(i)
#define RETRY(i)
#define GTSYNC(i)
#define PRO(i)
#define TL(i)

__device__ uint4 g_xch[(fk::H1_BYTES + fk::H2_BYTES + 8192) / 16];
__device__ __align__(16) unsigned g_mask[128];
__device__ unsigned g_cnt[6][16];
__device__ unsigned g_next;
constexpr int TAIL_MB0 = 10, GATE_CNT = 12;
__device__ unsigned g_tflag[96], g_tfix[96];
__device__ uint4 g_tpart[96][3][4][256];
__device__ unsigned g_oflag[16];

#define LD_POLL "ld.global.L1::no_allocate"
__device__ __forceinline__ uint4 ld_poll16(const void* p) {
  uint4 v;
  asm volatile(LD_POLL ".v4.u32 {%0,%1,%2,%3}, [%4];" : "=r"(v.x), "=r"(v.y), "=r"(v.z), "=r"(v.w) : "l"(p) : "memory");
  return v;
}
__device__ __forceinline__ uint2 ld_poll8(const void* p) {
  uint2 v;
  asm volatile(LD_POLL ".v2.u32 {%0,%1}, [%2];" : "=r"(v.x), "=r"(v.y) : "l"(p) : "memory");
  return v;
}
__device__ __forceinline__ uint4 ld_strong16(const void* p) {
  uint4 v;
  asm volatile("ld.relaxed.gpu.global.v4.u32 {%0,%1,%2,%3}, [%4];" : "=r"(v.x), "=r"(v.y), "=r"(v.z), "=r"(v.w) : "l"(p) : "memory");
  return v;
}
__device__ __forceinline__ uint2 ld_strong8(const void* p) {
  uint2 v;
  asm volatile("ld.relaxed.gpu.global.v2.u32 {%0,%1}, [%2];" : "=r"(v.x), "=r"(v.y) : "l"(p) : "memory");
  return v;
}
__device__ __forceinline__ void st_pub32(void* p, uint32_t v) { asm volatile("st.relaxed.gpu.global.u32 [%0], %1;" ::"l"(p), "r"(v) : "memory"); }
__device__ __forceinline__ void st_pub16(void* p, uint32_t v) {
  asm volatile("st.relaxed.gpu.global.u16 [%0], %1;" ::"l"(p), "h"((uint16_t)v) : "memory");
}
__device__ __forceinline__ uint32_t ld_strong4(const void* p) {
  uint32_t v;
  asm volatile("ld.relaxed.gpu.global.u32 %0, [%1];" : "=r"(v) : "l"(p) : "memory");
  return v;
}
__device__ __forceinline__ void st_pub64(void* p, uint32_t a, uint32_t b) {
  asm volatile("st.relaxed.gpu.global.v2.u32 [%0], {%1,%2};" ::"l"(p), "r"(a), "r"(b) : "memory");
}
__device__ __forceinline__ void st_pub128(void* p, uint32_t a) {
  asm volatile("st.relaxed.gpu.global.v4.u32 [%0], {%1,%1,%1,%1};" ::"l"(p), "r"(a) : "memory");
}
constexpr uint32_t EMPTY = 0xFFFFFFFFu;
__device__ __forceinline__ uint32_t umax4(const uint4& v) { return max(max(v.x, v.y), max(v.z, v.w)); }
__device__ __forceinline__ void sts128(uint32_t a, uint32_t x, uint32_t y, uint32_t z, uint32_t w) {
  asm volatile("st.shared.v4.u32 [%0], {%1,%2,%3,%4};" ::"r"(a), "r"(x), "r"(y), "r"(z), "r"(w) : "memory");
}
__device__ __forceinline__ void sts64(uint32_t a, uint32_t x, uint32_t y) {
  asm volatile("st.shared.v2.u32 [%0], {%1,%2};" ::"r"(a), "r"(x), "r"(y) : "memory");
}
__device__ __forceinline__ void sts32(uint32_t a, uint32_t x) { asm volatile("st.shared.u32 [%0], %1;" ::"r"(a), "r"(x) : "memory"); }
__device__ __forceinline__ void sts128f(uint32_t a, float x, float y, float z, float w) {
  asm volatile("st.shared.v4.f32 [%0], {%1,%2,%3,%4};" ::"r"(a), "f"(x), "f"(y), "f"(z), "f"(w) : "memory");
}
__device__ __forceinline__ void sts64f(uint32_t a, float x, float y) {
  asm volatile("st.shared.v2.f32 [%0], {%1,%2};" ::"r"(a), "f"(x), "f"(y) : "memory");
}
__device__ __forceinline__ float4 lds128f(uint32_t a) {
  float4 v;
  asm volatile("ld.shared.v4.f32 {%0,%1,%2,%3}, [%4];" : "=f"(v.x), "=f"(v.y), "=f"(v.z), "=f"(v.w) : "r"(a) : "memory");
  return v;
}
__device__ __forceinline__ float2 lds64f(uint32_t a) {
  float2 v;
  asm volatile("ld.shared.v2.f32 {%0,%1}, [%2];" : "=f"(v.x), "=f"(v.y) : "r"(a) : "memory");
  return v;
}
__device__ __forceinline__ float2 lds64f_if(uint32_t a, bool on, float other) {
  float2 v = make_float2(other, other);
  asm volatile("{\n.reg .pred p;\nsetp.ne.u32 p, %3, 0;\n@p ld.shared.v2.f32 {%0,%1}, [%2];\n}" : "+f"(v.x), "+f"(v.y) : "r"(a), "r"((uint32_t)on) : "memory");
  return v;
}
__device__ __forceinline__ void lds128(uint32_t* r, uint32_t a) {
  asm volatile("ld.shared.v4.u32 {%0,%1,%2,%3}, [%4];" : "=r"(r[0]), "=r"(r[1]), "=r"(r[2]), "=r"(r[3]) : "r"(a) : "memory");
}
__device__ __forceinline__ void lds64(uint32_t* r, uint32_t a) {
  asm volatile("ld.shared.v2.u32 {%0,%1}, [%2];" : "=r"(r[0]), "=r"(r[1]) : "r"(a) : "memory");
}
__device__ __forceinline__ uint32_t lds32(uint32_t a) {
  uint32_t v;
  asm volatile("ld.shared.u32 %0, [%1];" : "=r"(v) : "r"(a) : "memory");
  return v;
}
__device__ __forceinline__ void ldsm4(uint32_t* r, uint32_t a) {
  asm volatile("ldmatrix.sync.aligned.m8n8.x4.shared.b16 {%0,%1,%2,%3}, [%4];"
               : "=r"(r[0]), "=r"(r[1]), "=r"(r[2]), "=r"(r[3]) : "r"(a) : "memory");
}
__device__ __forceinline__ void ldsm4t(uint32_t* r, uint32_t a) {
  asm volatile("ldmatrix.sync.aligned.m8n8.x4.trans.shared.b16 {%0,%1,%2,%3}, [%4];"
               : "=r"(r[0]), "=r"(r[1]), "=r"(r[2]), "=r"(r[3]) : "r"(a) : "memory");
}
__device__ __forceinline__ void stsm4(uint32_t a, uint32_t r0, uint32_t r1, uint32_t r2, uint32_t r3) {
  asm volatile("stmatrix.sync.aligned.m8n8.x4.shared.b16 [%0], {%1,%2,%3,%4};"
               ::"r"(a), "r"(r0), "r"(r1), "r"(r2), "r"(r3) : "memory");
}
__device__ __forceinline__ void stsm4t(uint32_t a, uint32_t r0, uint32_t r1, uint32_t r2, uint32_t r3) {
  asm volatile("stmatrix.sync.aligned.m8n8.x4.trans.shared.b16 [%0], {%1,%2,%3,%4};"
               ::"r"(a), "r"(r0), "r"(r1), "r"(r2), "r"(r3) : "memory");
}
__device__ __forceinline__ void mma16816(float* d, const uint32_t* a, uint32_t b0, uint32_t b1) {
  asm volatile("mma.sync.aligned.m16n8k16.row.col.f32.bf16.bf16.f32 {%0,%1,%2,%3}, {%4,%5,%6,%7}, {%8,%9}, {%0,%1,%2,%3};"
               : "+f"(d[0]), "+f"(d[1]), "+f"(d[2]), "+f"(d[3])
               : "r"(a[0]), "r"(a[1]), "r"(a[2]), "r"(a[3]), "r"(b0), "r"(b1));
}
__device__ __forceinline__ void mma16816z(float* d, const uint32_t* a, uint32_t b0, uint32_t b1) {
  asm volatile("mma.sync.aligned.m16n8k16.row.col.f32.bf16.bf16.f32 {%0,%1,%2,%3}, {%4,%5,%6,%7}, {%8,%9}, {%10,%10,%10,%10};"
               : "=f"(d[0]), "=f"(d[1]), "=f"(d[2]), "=f"(d[3])
               : "r"(a[0]), "r"(a[1]), "r"(a[2]), "r"(a[3]), "r"(b0), "r"(b1), "f"(0.f));
}
__device__ __forceinline__ void mma1688(float* d, uint32_t a0, uint32_t a1, uint32_t b0) {
  asm volatile("mma.sync.aligned.m16n8k8.row.col.f32.bf16.bf16.f32 {%0,%1,%2,%3}, {%4,%5}, {%6}, {%0,%1,%2,%3};"
               : "+f"(d[0]), "+f"(d[1]), "+f"(d[2]), "+f"(d[3]) : "r"(a0), "r"(a1), "r"(b0));
}
__device__ __forceinline__ uint32_t movtrans(uint32_t a) {
  uint32_t d;
  asm volatile("movmatrix.sync.aligned.m8n8.trans.b16 %0, %1;" : "=r"(d) : "r"(a));
  return d;
}
__device__ __forceinline__ uint32_t mapa(uint32_t a, uint32_t rank) {
  uint32_t d;
  asm("mapa.shared::cluster.u32 %0, %1, %2;" : "=r"(d) : "r"(a), "r"(rank));
  return d;
}
__device__ __forceinline__ void st_async64(uint32_t a, uint32_t x, uint32_t y, uint32_t bar) {
  asm volatile("st.async.weak.shared::cluster.mbarrier::complete_tx::bytes.v2.b32 [%0], {%1,%2}, [%3];"
               ::"r"(a), "r"(x), "r"(y), "r"(bar) : "memory");
}
__device__ __forceinline__ void st_async64f(uint32_t a, float x, float y, uint32_t bar) {
  st_async64(a, __float_as_uint(x), __float_as_uint(y), bar);
}
__device__ __forceinline__ void bulk_s2s(uint32_t dst, uint32_t src, uint32_t bytes, uint32_t bar) {
  asm volatile("cp.async.bulk.shared::cluster.shared::cta.mbarrier::complete_tx::bytes [%0], [%1], %2, [%3];"
               ::"r"(dst), "r"(src), "r"(bytes), "r"(bar) : "memory");
}
__device__ __forceinline__ void tma_store_3d(const CUtensorMap* map, uint32_t src, int x, int y, int z) {
  asm volatile("cp.async.bulk.tensor.3d.global.shared::cta.bulk_group [%0, {%2, %3, %4}], [%1];"
               ::"l"(map), "r"(src), "r"(x), "r"(y), "r"(z) : "memory");
}
__device__ __forceinline__ void mbar_spin(uint32_t bar, uint32_t parity) {
  asm volatile("{\n.reg .pred p;\n.reg .b32 n;\nmov.u32 n, 0x100000;\nMW_L:\n"
               "mbarrier.try_wait.parity.shared::cta.b64 p, [%0], %1;\n@p bra.uni MW_D;\n"
               "add.s32 n, n, -1;\nsetp.ne.u32 p, n, 0;\n@p bra.uni MW_L;\nMW_D:\n}" ::"r"(bar), "r"(parity) : "memory");
}
__device__ __forceinline__ bool mbar_test(uint32_t bar, uint32_t parity) {
  uint32_t done;
  asm volatile("{\n.reg .pred p;\nmbarrier.test_wait.parity.shared::cta.b64 p, [%1], %2;\nselp.u32 %0, 1, 0, p;\n}"
               : "=r"(done) : "r"(bar), "r"(parity) : "memory");
  return done != 0;
}
__device__ __forceinline__ void mbar_arrive_remote(uint32_t bar) {
  asm volatile("mbarrier.arrive.shared::cluster.b64 _, [%0];" ::"r"(bar) : "memory");
}
__device__ __forceinline__ bool elect_one() {
  uint32_t r;
  asm volatile("{\n.reg .pred p;\nelect.sync _|p, 0xffffffff;\nselp.u32 %0, 1, 0, p;\n}" : "=r"(r));
  return r != 0;
}
__device__ __forceinline__ void st_async32(uint32_t a, uint32_t x, uint32_t bar) {
  asm volatile("st.async.weak.shared::cluster.mbarrier::complete_tx::bytes.b32 [%0], %1, [%2];" ::"r"(a), "r"(x), "r"(bar) : "memory");
}
#define named_bar_and(id, n, in, out) \
  asm volatile("{\n.reg .pred p, q;\nsetp.ne.u32 p, %1, 0;\nbar.red.and.pred q, %2, %3, p;\nselp.u32 %0, 1, 0, q;\n}" \
               : "=r"(out) : "r"(in), "n"(id), "n"(n) : "memory")
__device__ __forceinline__ void bulk_g2s(uint32_t dst, const void* src, uint32_t bytes, uint32_t bar) {
  asm volatile("cp.async.bulk.shared::cluster.global.mbarrier::complete_tx::bytes [%0], [%1], %2, [%3];"
               ::"r"(dst), "l"(src), "r"(bytes), "r"(bar) : "memory");
}
__device__ __forceinline__ void l2_prefetch(const void* p, uint32_t bytes) {
  asm volatile("cp.async.bulk.prefetch.L2.global [%0], %1;" ::"l"(p), "r"(bytes) : "memory");
}

__device__ __forceinline__ uint32_t clk32() { uint32_t c; asm volatile("mov.u32 %0, %%clock;" : "=r"(c)::"memory"); return c; }
__device__ __forceinline__ void spin_until(uint32_t t) { while ((int32_t)(clk32() - t) < 0) {} }
#define PIN(x) asm volatile("" : "+r"(x))
#define OPQ                                                                                     \
  int tid_o = tid;                                                                              \
  asm volatile("" : "+r"(tid_o));                                                               \
  const int lane = tid_o & 31, w = (tid_o >> 5) & 3, t7 = tid_o & 127, lg = lane >> 2,          \
            lq = lane & 3, mi = lane >> 3, mr = lane & 7;                                       \
  (void)w; (void)t7; (void)lg; (void)lq; (void)mi; (void)mr; (void)lane

#define SMAP                                                                                                          \
  const uint32_t SM0 = self + fk::SM0, WO = self + fk::WO, WS = self + fk::WS, XN = self + fk::XN, VX = self + fk::VX, \
                 QK = self + fk::QK, PT = self + fk::PT, SP = self + fk::SP, VM = self + fk::VM, OB = self + fk::OB,   \
                 RED = self + fk::RED, VX2 = self + fk::VX2, MEMB = self + fk::MEMB, B_XN = self + fk::B_XN, B_SM = self + fk::B_SM,       \
                 B_VM = self + fk::B_VM, B_VX = self + fk::B_VX, B_ST = self + fk::B_ST, B_PB = self + fk::B_PB,       \
                 B_W = self + fk::B_W, B_H2 = self + fk::B_H2, B_H1 = self + fk::B_H1, B_PF = self + fk::B_PF, B_WO = self + fk::B_WO, MASKS = self + fk::MASKS, PROBE = self + fk::PROBE;                             \
  (void)SM0; (void)WO; (void)WS; (void)XN; (void)VX; (void)QK; (void)PT; (void)SP; (void)VM; (void)OB; (void)RED; (void)VX2; \
  (void)MEMB; (void)B_XN; (void)B_SM; (void)B_VM; (void)B_VX; (void)B_ST; (void)B_PB; (void)B_W; (void)MASKS; (void)PROBE; (void)B_H2; (void)B_H1; (void)B_PF; (void)B_WO

struct FParams {
  CUtensorMap wq, wk, wv, wo, wo16, xn, xn12, o;
  CUtensorMap ta, tb, tx, tg, tout;
  const bf16 *mem0, *x, *w1;
  bf16 *xn_ptr, *xn2;
  int nprobe;
  char* xch;
};

__device__ __forceinline__ uint2 probe_pair(char* p, uint32_t val, uint32_t dummy, int n) {
  uint2 best = make_uint2(0x7FFFFFFF, 0x7FFFFFFF);
  st_pub128(p, val); st_pub128(p + 16, val); st_pub128(p + 4096, val); st_pub128(p + 4112, val);
#pragma unroll 1
  for (int r = 0; r < n; r++) {
    uint32_t v;
    const uint32_t c0 = clk32();
    asm volatile("atom.relaxed.gpu.global.exch.b32 %0, [%1], %2;" : "=r"(v) : "l"(p + (r & 1) * 4096), "r"(val) : "memory");
    asm volatile("{\n.reg .pred p;\nsetp.eq.u32 p, %0, 0x12345678;\n@p st.shared.u32 [%1], %0;\n}" ::"r"(v), "r"(dummy) : "memory");
    const uint32_t d = clk32() - c0;
    if (r & 1) best.y = min(best.y, d); else best.x = min(best.x, d);
  }
  return best;
}

typedef uint32_t WRegs[6][2][4][4];

constexpr uint32_t nth_chunks(uint32_t mask) {
  uint32_t t = 0;
  for (int c = 0, n = 0; c < 10; c++) if ((mask >> c) & 1) t |= c << (4 * n++);
  return t;
}
constexpr uint64_t chunk_pos(uint32_t mask) {
  uint64_t t = 0;
  for (int c = 0, a = 0, b = 0; c < 10; c++) t |= (uint64_t)(((mask >> c) & 1) ? a++ : b++) << (4 * c);
  return t;
}
template <bool ISV> struct Chunks {
  static constexpr uint32_t MASK = ISV ? SMV : SMQ, SMT = nth_chunks(MASK), RFT = nth_chunks(~MASK & 1023);
  static_assert(!(MASK & 1), "the first chunk initialises the accumulators");
  static __device__ __forceinline__ constexpr int rf(int wg, int i) { return wg ? 10 + i : (RFT >> (4 * i)) & 15; }
  static __device__ __forceinline__ constexpr int sm(int i) { return (SMT >> (4 * i)) & 15; }
  static constexpr uint64_t IDX = chunk_pos(MASK);
  static __device__ __forceinline__ constexpr int idx(int c) { return (IDX >> (4 * c)) & 15; }
};

template <bool ISV, int WG> struct ProjCfg {
  static constexpr int N0 = ISV ? NS0V : NS0, NS = WG ? 8 - N0 : N0, P0 = WG ? N0 : 0, NTA = WG ? NTA1 : NTA0;
};
__device__ __forceinline__ void load_pair(uint32_t (&t)[4][4], uint32_t wsa, int pp) {
#pragma unroll
  for (int f = 0; f < 4; f++) ldsm4t(t[f], wsa + ((pp >> 1) * 2 + (f & 1)) * 8192 + ((pp & 1) * 2 + (f >> 1)) * 2048);
}
template <bool ISV, int WG>
__device__ __forceinline__ void proj_mem(const WRegs& wr, uint32_t (&ta)[ProjCfg<ISV, WG>::NTA][4][4], uint32_t wsa, uint32_t mba,
                                         float (&a0)[4], float (&a1)[4]) {
  constexpr int NS = ProjCfg<ISV, WG>::NS, P0 = ProjCfg<ISV, WG>::P0, NTA = ProjCfg<ISV, WG>::NTA, NP = 12 + NS;
  float acc[4][4];
  auto spos = [](int j) { return j < NTA ? j : j + (j - NTA + 1) * 12 / (NS - NTA > 0 ? NS - NTA : 1); };
  auto which = [&](int p) { int r = -1; for (int j = 0; j < NS; j++) if (spos(j) == p) r = j; return r; };
  auto nsm_before = [&](int p) { int n = 0; for (int j = 0; j < NS; j++) if (spos(j) < p) n++; return n; };
#pragma unroll
  for (int p = 0; p < NP; p++) {
    const int j = which(p), r = j >= 0 ? 0 : p - nsm_before(p);
    uint32_t bp[4], tl[4][4];
    ldsm4(bp, mba + (j >= 0 ? Chunks<ISV>::sm((P0 + (j >= 0 ? j : 0)) >> 1) * 1024 + ((P0 + j) & 1) * 512 : Chunks<ISV>::rf(WG, r >> 1) * 1024 + (r & 1) * 512));
    if (j >= NTA) load_pair(tl, wsa, P0 + j);
#pragma unroll
    for (int u = 0; u < 2; u++)
#pragma unroll
      for (int T = 0; T < 2; T++) {
        const uint32_t* a = j >= NTA ? tl[u * 2 + T] : j >= 0 ? ta[j >= 0 ? j % NTA : 0][u * 2 + T] : wr[r >> 1][T][(r & 1) * 2 + u];
        if (p == 0) mma16816z(acc[u * 2 + T], a, bp[2 * u], bp[2 * u + 1]);
        else mma16816(acc[u * 2 + T], a, bp[2 * u], bp[2 * u + 1]);
      }
  }
#pragma unroll
  for (int i = 0; i < 4; i++) { a0[i] = acc[0][i] + acc[2][i]; a1[i] = acc[1][i] + acc[3][i]; }
}
template <bool ISV, int WG, int J0, int J1>
__device__ __forceinline__ void proj_mem_prefetch(uint32_t (&ta)[ProjCfg<ISV, WG>::NTA][4][4], uint32_t wsa) {
#pragma unroll
  for (int j = J0; j < J1; j++) load_pair(ta[j], wsa, ProjCfg<ISV, WG>::P0 + j);
}

template <bool ISV, int WG>
__device__ __forceinline__ void proj_finish(const float (&a0)[4], const float (&a1)[4], uint32_t peer0, uint32_t peer1, uint32_t self, int tid, int warp,
                                            uint32_t (&vmo)[4]) {
  using namespace fk;
  SMAP;
  OPQ;
  if (!ISV) {
    stsm4(PT + mr * 16 + ((mi >> 1) ? WG * 1024 + w * 256 + (mi & 1) * 128 : 2048 + w * 512 + (mi & 1) * 256 + WG * 128),
          pack_bf16(a0[0], a0[1]), pack_bf16(a0[2], a0[3]), pack_bf16(a1[0], a1[1]), pack_bf16(a1[2], a1[3]));
    named_bar_sync(NB_C, 256);
  } else {
    if (WG == 0) sts128f(RED + t7 * 16, a1[0], a1[1], a1[2], a1[3]);
    else sts128f(RED + 2048 + t7 * 16, a0[0], a0[1], a0[2], a0[3]);
    if (WG == 1) { lds64(vmo, VM + t7 * 8); lds64(vmo + 2, VM + 1024 + t7 * 8); }
    named_bar_sync(NB_C, 256);
    const float4 p = lds128f(RED + (1 - WG) * 2048 + t7 * 16);
    const float* k = WG == 0 ? a0 : a1;
    const uint32_t v0 = pack_bf16(k[0] + p.x, k[1] + p.y), v1 = pack_bf16(k[2] + p.z, k[3] + p.w);
    const uint32_t off = VM + WG * 1024 + t7 * 8;
    if (VM_BULK) {
      sts64(off, v0, v1);
      fence_proxy_async_smem();
      __syncwarp();
      const uint32_t a = VM + WG * 1024 + warp * 256;
      if (elect_one()) {
        bulk_s2s(peer0 + a, a, 256, peer0 + B_VM);
        bulk_s2s(peer1 + a, a, 256, peer1 + B_VM);
        mbar_arrive(B_VM);
      }
    } else {
      st_async64(peer0 + off, v0, v1, peer0 + B_VM);
      st_async64(peer1 + off, v0, v1, peer1 + B_VM);
      sts64(off, v0, v1);
      __syncwarp();
      if (lane == 0) mbar_arrive(B_VM);
    }
  }
}

__device__ __forceinline__ void send_scores(float s0, float s1, uint32_t off, uint32_t peer0, uint32_t peer1, uint32_t bar, int lane) {
  if (SPACK) {
    const uint32_t v = pack_bf16(s0, s1);
    st_async32(peer0 + off, v, peer0 + bar);
    st_async32(peer1 + off, v, peer1 + bar);
    sts32(off, v);
  } else {
    st_async64f(peer0 + off, s0, s1, peer0 + bar);
    st_async64f(peer1 + off, s0, s1, peer1 + bar);
    sts64f(off, s0, s1);
  }
  __syncwarp();
  if (lane == 0) mbar_arrive(bar);
}

template <int NT, bool NARROW>
__device__ __forceinline__ uint32_t wo_addr(int f, uint32_t woa, uint32_t wob) {
  return (NARROW && f % NT == 2) ? wob + (f / NT) * 512 : woa + (f % NT) * 32768 + (f / NT) * 2048;
}
template <int NT, bool NARROW, int PF>
__device__ __forceinline__ void wo_phase(uint32_t (&wf)[PF][4], uint32_t woa, uint32_t wob, uint32_t oba, char* h1p, uint32_t sel, uint32_t tag) {
  float c[NT][4];
  uint32_t of[2][4];
  ldsm4t(of[0], oba);
#pragma unroll
  for (int k = 0; k < 8; k++) {
    if ((k & 1) == 0 && k + 2 < 8) ldsm4t(of[((k >> 1) + 1) & 1], oba + ((k >> 1) + 1) * 512);
#pragma unroll
    for (int i = 0; i < NT; i++) {
      const int f = k * NT + i;
      const uint32_t b0 = of[(k >> 1) & 1][2 * (k & 1)], b1 = of[(k >> 1) & 1][2 * (k & 1) + 1];
      if (k == 0) mma16816z(c[i], wf[f % PF], b0, b1); else mma16816(c[i], wf[f % PF], b0, b1);
      if (f + PF < 8 * NT) ldsm4t(wf[f % PF], wo_addr<NT, NARROW>(f + PF, woa, wob));
    }
  }
#pragma unroll
  for (int i = 0; i < NT; i++)
  {
    char* p = h1p + i * (8 * 32768) + ((sel >> (2 * i)) & 3) * 2048;
    const uint32_t tm = (sel >> 10) & 1;
    st_pub32(p, (pack_bf16(c[i][0], c[i][1]) & ~tm) | (tag & tm));
    st_pub32(p + 1024, (pack_bf16(c[i][2], c[i][3]) & ~tm) | (tag & tm));
  }
}
template <int NT, bool NARROW, int F0, int F1, int PF>
__device__ __forceinline__ void wo_prefetch(uint32_t (&wf)[PF][4], uint32_t woa, uint32_t wob) {
#pragma unroll
  for (int f = F0; f < F1; f++) ldsm4t(wf[f], wo_addr<NT, NARROW>(f, woa, wob));
}

template <bool ISV> __device__ __forceinline__ uint32_t tok_addr(uint32_t base, int tid) {
  OPQ;
  return ISV ? base + w * 2048 + (mi & 1) * 1024 + (mi >> 1) * 128 + mr * 16 : base + (mi >> 1) * 1024 + w * 256 + (mi & 1) * 128 + mr * 16;
}
template <bool ISV> __device__ __forceinline__ constexpr uint32_t tok_off(int T, int i) { return ISV ? T * 512 + i * 256 : T * 4096 + i * 2048; }
template <bool ISV, int T, bool ADD>
__device__ __forceinline__ void tok_store(const float (&x)[16], uint32_t a, const uint32_t (&p)[2][4]) {
#pragma unroll
  for (int i = 0; i < 2; i++) {
    uint32_t r[4];
#pragma unroll
    for (int k = 0; k < 4; k++)
      r[k] = !ADD ? pack_bf16(x[8 * i + 2 * k], x[8 * i + 2 * k + 1])
           : PADD ? add_bf16x2(pack_bf16(x[8 * i + 2 * k], x[8 * i + 2 * k + 1]), p[i][k])
                  : pack_bf16(x[8 * i + 2 * k] + bf_lo(p[i][k]), x[8 * i + 2 * k + 1] + bf_hi(p[i][k]));
    stsm4(a + tok_off<ISV>(T, i), r[0], r[1], r[2], r[3]);
  }
}

__device__ __forceinline__ void load_xn(const FParams& P, int seg, uint32_t self) {
  SMAP;
  mbar_expect_tx(B_XN, 49152);
  tma_load_3d(XN, &P.xn12, 0, seg * 32, 0, B_XN);
}

__device__ __forceinline__ uint64_t xn_desc(int slot, int u) { return make_desc(fk::XN + slot * 4096 + u * 32, 16, 1024); }

template <bool ISV>
__device__ __forceinline__ void f_wg0(const FParams& P, const WRegs& wr, const int h, const int rank, const uint32_t hw, int tid) {
  using namespace fk;
  const uint32_t self = mapa(0, (hw >> (2 * rank)) & 3), peer0 = mapa(0, (hw >> (ISV ? 0 : 2 * (rank ^ 1))) & 3) - self,
                 peer1 = mapa(0, (hw >> (ISV ? 2 : 4)) & 3) - self;
  SMAP;
  const int tile0 = rank * 22;
  const int warp = __shfl_sync(0xffffffffu, threadIdx.x >> 5, 0);
  const bool three = !ISV && warp < 2;
  uint32_t h2ph = 1;
  tid ^= 0x5500;
#pragma unroll 1
  for (int s = -1;;) {
    uint32_t ta[ProjCfg<ISV, 0>::NTA][4][4], wsa, mba;
    auto h2_src = [&]() { return P.xch + H1_BYTES + ((s & 1) * 4 + warp) * 8192 + ((tid >> (16 + (s & 1))) & 1) * 4096; };
    {
      const uint32_t ph = (s + 1) & 1;
      float x0[16], x1[16];
      uint32_t t_pub = 0;
      if (!XN_EARLY || s < 0) mbar_spin(B_XN, ph);
      wg_fence();
#pragma unroll
      for (int c = 0; c < 10; c++) {
        if (c == 9) named_bar_arrive(NB_ST, 256);
#pragma unroll
        for (int u = 0; u < 4; u++) {
          const int ci = Chunks<ISV>::idx(c);
          if ((Chunks<ISV>::MASK >> c) & 1) {
            wgmma_ss_n32_ta(x0, make_desc(fk::WS + ci * 16384 + u * 2048, 8192, 1024), xn_desc(c, u), 1);
            wgmma_ss_n32_ta(x1, make_desc(fk::WS + ci * 16384 + 8192 + u * 2048, 8192, 1024), xn_desc(c, u), 1);
          } else {
            wgmma_rs_n32(x0, wr[ci][0][u], xn_desc(c, u), (c | u) != 0);
            wgmma_rs_n32(x1, wr[ci][1][u], xn_desc(c, u), (c | u) != 0);
          }
          if (((ISV ? PACEV : PACEQ) >> c) & 1) { wg_commit(); wg_wait<2>(); wg_fence(); }
          if (c == 4 && u == 1) { wg_commit(); wg_wait<1>(); named_bar_arrive(NB_XE, 160); wg_fence(); }
        }
        if (c == 0) { t_pub = clk32() - 60; PROF(0, 8); }
        if (c == 3) wg_commit();
      }
      wg_commit();
      wg_wait<0>();
      PROF(0, 10);
      const uint32_t tb = ISV ? (ph ? VX2 : VX) : QK;
      auto h2_issue = [&]() {
        if (s >= 0) {
          spin_until(t_pub + D_H2);
          PROF(0, 13);
          if (elect_one()) { mbar_expect_tx(B_H2 + 8 * warp, 4096); bulk_g2s(MEMB + warp * 4096, h2_src(), 4096, B_H2 + 8 * warp); }
        }
      };
      if (ISV || H2_AT == 0) h2_issue();
      named_bar_sync(NB_CF, ISV ? 160 : 256);
      const uint32_t none[2][4] = {}, tka = tok_addr<ISV>(tb, tid);
      tok_store<ISV, 0, false>(x0, tka, none);
      if (!ISV && H2_AT == 1) h2_issue();
      tok_store<ISV, 1, false>(x1, tka, none);
      if (!ISV && H2_AT == 2) h2_issue();
      named_bar_arrive(NB_DU, 256);
    }
    {
      OPQ;
      wsa = WS + ((mi >> 1) * 8 + mr) * 128 + (((2 * w + (mi & 1)) ^ mr) << 4);
      mba = MEMB + lane * 16;
      PIN(wsa); PIN(mba);
      if (s >= 0) {
        const char* src = h2_src();
        const uint32_t chk = MEMB + w * 4096 + lane * 32 + lg * 4, bar = B_H2 + 8 * warp;
        PROF(0, 11);
        proj_mem_prefetch<ISV, 0, 0, NPRE0>(ta, wsa);
#pragma unroll 1
        for (int tries = 0; tries < POLL_TRIES; tries++) {
          mbar_spin(bar, h2ph);
          h2ph ^= 1;
          const uint32_t mx = max(max(lds32(chk), lds32(chk + 1024)), max(lds32(chk + 2048), lds32(chk + 3072)));
          if (__all_sync(0xffffffffu, mx != EMPTY)) break;
          RETRY(1);
          if (elect_one()) { mbar_expect_tx(bar, 4096); bulk_g2s(MEMB + warp * 4096, src, 4096, bar); }
        }
      } else {
        const bf16* m0 = P.mem0 + mr * cfg::D + w * 256 + mi * 8;
#pragma unroll
        for (int i = 0; i < 8; i++) {
          const uint4 v = *reinterpret_cast<const uint4*>(m0 + i * 32);
          sts128(mba + w * 4096 + i * 512, v.x, v.y, v.z, v.w);
        }
        proj_mem_prefetch<ISV, 0, 0, NPRE0>(ta, wsa);
        mbar_wait(B_WO, 0);
      }
      PROF(0, 12);
      named_bar_arrive(NB_M1, 256);
      proj_mem_prefetch<ISV, 0, NPRE0, NTA0>(ta, wsa);
      named_bar_sync(NB_M0, 128);
    }
    s++;
    tid ^= 0x5500;
    {
      PROF(0, 1);
      float a0[4], a1[4];
      proj_mem<ISV, 0>(wr, ta, wsa, mba, a0, a1);
      PROF(0, 2);
      uint32_t unused[4];
      proj_finish<ISV, 0>(a0, a1, peer0, peer1, self, tid, warp, unused);
      PROF(0, 3);
      if (s + 1 == cfg::NSEG) break;
      uint32_t wf[PF0][4], woa, wob;
      bool xn_ok;
      {
        OPQ;
        if (!ISV) {
          uint32_t qf[4][4], kf[2][4];
          const uint32_t qa = PT + 2048 + lane * 16, ka = QK + 4096 + w * 1024 + lane * 16;
          ldsm4t(qf[0], qa); ldsm4t(kf[0], ka); ldsm4t(qf[1], qa + 512);
          ldsm4t(qf[2], qa + 1024); ldsm4t(kf[1], ka + 512); ldsm4t(qf[3], qa + 1536);
          float c0[4], c1[4];
          mma16816z(c0, qf[0], kf[0][0], kf[0][1]);
          mma16816z(c1, qf[1], kf[0][2], kf[0][3]);
          mma16816(c0, qf[2], kf[1][0], kf[1][1]);
          mma16816(c1, qf[3], kf[1][2], kf[1][3]);
          const float s0 = (c0[0] + c0[2]) + (c1[0] + c1[2]), s1 = (c0[1] + c0[3]) + (c1[1] + c1[3]);
          send_scores(s0, s1, SP + rank * SP_SRC + t7 * SPW, peer0, peer1, B_SM, lane);
        }
        PROF(0, 4);
        woa = WO + 16384 + ((mi >> 1) * 8 + mr) * 128 + (((2 * w + (mi & 1)) ^ mr) << 4);
        wob = WO + 81920 + w * 4096 + ((mi >> 1) * 8 + mr) * 32 + (((mi & 1) ^ (mr >> 2)) << 4);
        uint32_t vf[2][2][4], vm[2][2];
        if (!ISV) mbar_spin(B_VX, s & 1);
        PROF(0, 14);
#pragma unroll
        for (int T = 0; T < 2; T++)
#pragma unroll
          for (int kk = 0; kk < 2; kk++) ldsm4(vf[T][kk], ((ISV && (s & 1)) ? VX2 : VX) + w * 2048 + (mi & 1) * 1024 + (mi >> 1) * 128 + mr * 16 + T * 512 + kk * 256);
        if (three) wo_prefetch<3, true, 0, PF0A>(wf, woa, wob); else wo_prefetch<2, false, 0, PF0A>(wf, woa, wob);
        uint32_t spa = SP + lane * SPW, vma = VM + t7 * 8, oa = OB + (mi >> 1) * 1024 + w * 256 + (mi & 1) * 128 + mr * 16;
        PIN(spa); PIN(vma); PIN(oa);
        mbar_spin(B_SM, s & 1);
        PROF(0, 5);
        float sc[10];
#pragma unroll
        for (int j = 0; j < 5; j++) {
          if (SPACK) {
            const uint32_t x = lds32(spa + j * 128), y = lds32(spa + SP_SRC + j * 128);
            sc[2 * j] = bf_lo(x) + bf_lo(y); sc[2 * j + 1] = bf_hi(x) + bf_hi(y);
          } else {
            const float2 x = lds64f(spa + j * 256), y = lds64f(spa + SP_SRC + j * 256);
            sc[2 * j] = x.x + y.x; sc[2 * j + 1] = x.y + y.y;
          }
        }
        float m = fmaxf(fmaxf(fmaxf(sc[0], sc[1]), fmaxf(sc[2], sc[3])), fmaxf(fmaxf(sc[4], sc[5]), fmaxf(sc[6], sc[7])));
        m = fmaxf(m, fmaxf(sc[8], sc[9]));
        const bool vm_ok = mbar_test(B_VM, s & 1);
        m = fmaxf(m, __shfl_xor_sync(0xffffffffu, m, 1));
        m = fmaxf(m, __shfl_xor_sync(0xffffffffu, m, 2));
        PROF(0, 15);
        if (!vm_ok) mbar_spin(B_VM, s & 1);
        PROF(0, 0);
        lds64(vm[0], vma); lds64(vm[1], vma + 1024);
        if (ISV ? GATE_MX : GATE_Q) named_bar_arrive(NB_MX, 256);
        const float cs = 0.08838834764831845f * 1.4426950408889634f;
        const float mc = -m * cs;
        uint32_t pb[5];
#pragma unroll
        for (int j = 0; j < 5; j++) pb[j] = pack_bf16(ex2_approx(fmaf(sc[2 * j], cs, mc)), ex2_approx(fmaf(sc[2 * j + 1], cs, mc)));
        PROF(0, 6);
        float o0[4], o1[4], rs[4];
        const uint32_t ones[4] = {0x3F803F80u, 0x3F803F80u, 0x3F803F80u, 0x3F803F80u};
        mma16816z(rs, ones, pb[0], pb[1]);
        mma16816z(o0, vf[0][0], pb[0], pb[1]);
        mma16816z(o1, vf[1][0], pb[0], pb[1]);
        mma16816(rs, ones, pb[2], pb[3]);
        mma16816(o0, vf[0][1], pb[2], pb[3]);
        mma16816(o1, vf[1][1], pb[2], pb[3]);
        mma1688(rs, ones[0], ones[0], pb[4]);
        mma1688(o0, vm[0][0], vm[0][1], pb[4]);
        mma1688(o1, vm[1][0], vm[1][1], pb[4]);
        const float i0 = rcp_approx(rs[0]), i1 = rcp_approx(rs[1]);
        stsm4(oa, pack_bf16(o0[0] * i0, o0[1] * i1), pack_bf16(o0[2] * i0, o0[3] * i1),
              pack_bf16(o1[0] * i0, o1[1] * i1), pack_bf16(o1[2] * i0, o1[3] * i1));
      }
      {
        OPQ;
        named_bar_arrive(NB_O, 256);
        if (three) wo_prefetch<3, true, PF0A, PF0>(wf, woa, wob); else wo_prefetch<2, false, PF0A, PF0>(wf, woa, wob);
        xn_ok = mbar_test(B_XN, (s + 1) & 1);
        char* h1p = P.xch + (tile0 + 4 + w) * 32768 + (h >> 3) * 8192 + (h & 7) * 128 + (((2 * lq + (lg & 1)) ^ (h & 7)) << 4) + (lg >> 1) * 4;
        uint32_t oba = OB + lane * 16;
        PIN(oba);
        PROF(0, 7);
        named_bar_sync(NB_O0, 128);
        const uint32_t tag = ((s >> 1) & 1) ^ 1;
        if (three) wo_phase<3, true>(wf, woa, wob, oba, h1p, tid >> 8, tag); else wo_phase<2, false>(wf, woa, wob, oba, h1p, tid >> 8, tag);
        PROF(0, 9);
        if (XN_EARLY && !xn_ok) mbar_spin(B_XN, (s + 1) & 1);
        named_bar_sync(NB_HD, 256);
      }
    }
  }
}

template <bool ISV>
__device__ __forceinline__ void f_wg1(const FParams& P, const WRegs& wr, const int h, const int rank, const uint32_t hw, int tid) {
  using namespace fk;
  const uint32_t self = mapa(0, (hw >> (2 * rank)) & 3), peer0 = mapa(0, (hw >> (ISV ? 0 : 2 * (rank ^ 1))) & 3) - self,
                 peer1 = mapa(0, (hw >> (ISV ? 2 : 4)) & 3) - self;
  SMAP;
  const int tile0 = rank * 22;
  const int warp = __shfl_sync(0xffffffffu, (threadIdx.x >> 5) & 3, 0);
  uint32_t h1ph = 0;
  auto o_done = [&](int mb) {
    tma_store_wait_all();
    asm volatile("fence.proxy.async.global;" ::: "memory");
    asm volatile("red.relaxed.gpu.global.add.u32 [%0], 1;" ::"l"(&g_oflag[mb]) : "memory");
  };
  uint32_t vmo[4] = {0, 0, 0, 0};
  if (ISV) {
    OPQ;
    sts32(PT + (t7 >> 2) * 128 + ((5 ^ lg) << 4) + lq * 4, 0);
    sts32(PT + (t7 >> 2) * 128 + ((6 ^ lg) << 4) + lq * 4, 0);
  }
  tid ^= 0x5500;
#pragma unroll 1
  for (int s = -1;;) {
    uint32_t ta[ProjCfg<ISV, 1>::NTA][4][4], wsa, mba;
    if (s + 1 < cfg::NSEG) mbar_spin(B_XN, (s + 1) & 1);
    const uint32_t t_pub = clk32();
    auto refill = [&]() {
      if (warp == 3) {
        named_bar_sync(NB_XE, 160);
        if (elect_one()) {
          mbar_expect_tx(B_XN + 8, 16384);
          tma_load_3d(XN, &P.xn, 0, (s + 1) * 32, 12, B_XN + 8);
        }
      }
    };
    auto arm = [&]() {
      if ((tid & 255) == 160) {
        if (s == 1) st_pub32(&g_mask[3 * h + rank], 0);
        if (s + 2 < cfg::NSEG) { mbar_expect_tx(B_SM, ISV ? 2 * SP_SRC : SP_SRC); if (!ISV) mbar_expect_tx(B_VX, 8192); }
        if (!ISV && s + 1 < cfg::NSEG) mbar_expect_tx(B_VM, 2048);
        if (ISV && s >= 1 && s < cfg::NSEG) mbar_expect_tx(B_ST, 7168);
      }
      if (ISV && s < cfg::NSEG && (tid & 254) == 192) mbar_arrive_remote(((tid & 1) ? peer1 : peer0) + B_ST);
      __syncwarp();
    };
    if (ISV) {
      if (s >= 0) arm();
      if (s >= 1) {
        OPQ;
        if (warp == 0 && (s & 3) == 1 && s > 1) { if (elect_one()) o_done((s - 2) >> 2); }
        const uint32_t vb = (s & 1) ? VX : VX2;
        float x0[16], x1[16];
        wg_fence();
        wgmma_rs_n32(x0, vmo, make_desc(fk::PT + 64, 16, 1024), 0);
        wgmma_rs_n32(x1, vmo, make_desc(fk::PT + 96, 16, 1024), 0);
#pragma unroll
        for (int kk = 0; kk < 2; kk++) {
          wgmma_ss_n32(x0, make_desc0(vb + kk * 256, 128, 1024), make_desc(fk::PT + kk * 32, 16, 1024), 1);
          wgmma_ss_n32(x1, make_desc0(vb + 512 + kk * 256, 128, 1024), make_desc(fk::PT + kk * 32, 16, 1024), 1);
        }
        wg_commit();
        wg_wait<0>();
        named_bar_sync(NB_W1, 128);
        PROF(1, 4);
        const uint32_t stg = vb + (8 * (mi >> 1) + mr) * 128 + (((2 * w + (mi & 1)) ^ mr) << 4);
#pragma unroll
        for (int T = 0; T < 2; T++) {
          const float* x = T ? x1 : x0;
#pragma unroll
          for (int jj = 0; jj < 4; jj += 2)
            stsm4t(stg + T * 4096 + jj * 1024, pack_bf16(x[4 * jj], x[4 * jj + 1]), pack_bf16(x[4 * jj + 2], x[4 * jj + 3]),
                   pack_bf16(x[4 * jj + 4], x[4 * jj + 5]), pack_bf16(x[4 * jj + 6], x[4 * jj + 7]));
        }
        fence_proxy_async_smem();
        named_bar_sync(NB_W1, 128);
        PROF(1, 10);
        if (warp == 0) {
          if (elect_one()) {
            tma_store_3d(&P.o, vb, 0, (s - 1) * 32, 2 * h);
            tma_store_commit();
          }
          __syncwarp();
        }
        if (s == cfg::NSEG) break;
      }
      if (s + 1 < cfg::NSEG) refill();
      PROF(1, 11);
    } else if (s < 0) {
      named_bar_arrive(NB_CF, 256);
      refill();
    } else {
      float x[24];
      wg_fence();
#pragma unroll
      for (int k = 0; k < 4; k++) wgmma_ss_n48_tt(x, make_desc0(fk::QK + k * 256, 128, 1024), make_desc0(fk::QK + 4096 + k * 256, 128, 1024), k != 0);
      wg_commit();
      arm();
      auto send_tok = [&]() {
        if (warp < 2) {
          OPQ;
          const uint32_t d0 = peer1 + QK + rank * 3584 + lane * 8 + w * 1280, d1 = d0 + 512 + w * 512, bar = peer1 + B_ST;
          mbar_spin(B_ST, s & 1);
          const float NEG = -500000000.0f / 0.08838834764831845f;
          const bool m0 = 2 * lq > lg, m1 = 2 * lq + 1 > lg;
          st_async64f(d0, x[16] + x[20], x[17] + x[21], bar);
          st_async64f(d1, x[18] + x[22], x[19] + x[23], bar);
          st_async64f(d1 + 256, x[2], x[3], bar);
          if (warp == 0) {
            st_async64f(d0 + 256, m0 ? NEG : x[0], m1 ? NEG : x[1], bar);
            st_async64f(d1 + 512, m0 ? NEG : x[6], m1 ? NEG : x[7], bar);
          } else {
            st_async64f(d0 + 256, x[0], x[1], bar);
            st_async64f(d1 + 512, x[6], x[7], bar);
            st_async64f(d0 + 512, x[4], x[5], bar);
            st_async64f(d0 + 768, m0 ? NEG : x[8], m1 ? NEG : x[9], bar);
            st_async64f(d1 + 768, x[10], x[11], bar);
            st_async64f(d1 + 1024, m0 ? NEG : x[14], m1 ? NEG : x[15], bar);
          }
        }
        PROF(1, 4);
      };
      const bool fin = s + 1 == cfg::NSEG;
      OPQ;
      const int j = 2 * h + rank;
      const char* src = P.xch + j * 32768 + warp * 8192 + __shfl_sync(0xffffffffu, (tid >> 14) & 3, 0) * 2048;
      char* dst = P.xch + H1_BYTES + (j >> 4) * 8192 + (lq >> 1) * 4096 + (j & 15) * 256 + (lq & 1) * 128 + (2 * w + (lg & 1)) * 16 + (lg >> 1) * 4;
      const uint32_t chk = VX + mi * 2048 + mr * 128 + (w ^ (mr >> 1)) * 32 + ((lane & 1) + 2 * mi) * 4;
      const uint32_t tmask = (s >> 1) & 1;
      if (!fin) {
        spin_until(t_pub + D_H1);
        if (elect_one()) { mbar_expect_tx(B_H1, 2048); bulk_g2s(VX + warp * 2048, src, 2048, B_H1); }
      }
      __syncwarp();
      wg_wait<0>();
      PROF(1, 6);
      send_tok();
      if (fin) { mbar_spin(B_VM, s & 1); break; }
      named_bar_arrive(NB_CF, 256);
      if (REFILL_EARLY) refill();
#pragma unroll 1
      for (int tries = 0; tries < POLL_TRIES; tries++) {
        float d0[4], d1[4], d2[4], d3[4];
        mbar_spin(B_H1, h1ph);
        h1ph ^= 1;
        PROF(1, 10);
        const uint32_t t0 = lds32(chk), t1 = lds32(chk + 1024);
        wg_fence();
        const uint64_t ones = (uint64_t)(fk::ONES >> 4);
        wgmma_ss_n8_ta(d0, make_desc(fk::VX, 8192, 2048), ones, 0);
        wgmma_ss_n8_ta(d1, make_desc(fk::VX + 1024, 8192, 2048), ones, 0);
        wgmma_ss_n8_ta(d2, make_desc(fk::VX + 4096, 8192, 2048), ones, 0);
        wgmma_ss_n8_ta(d3, make_desc(fk::VX + 5120, 8192, 2048), ones, 0);
        wg_commit();
        uint32_t tt;
        asm volatile("lop3.b32 %0, %1, %2, %3, 0x42;" : "=r"(tt) : "r"(t0), "r"(t1), "r"(tmask) : "memory");
        uint32_t ok = __all_sync(0xffffffffu, tt & 1);
        wg_wait<0>();
        if (ok) {
          st_pub32(dst + (s & 1) * 32768, (lq & 1) ? pack_bf16(d1[0] + d3[0], d1[2] + d3[2]) : pack_bf16(d0[0] + d2[0], d0[2] + d2[2]));
          PROF(1, 12);
          st_pub32(dst + ((s & 1) ^ 1) * 32768, EMPTY);
        }
        named_bar_and(NB_W1, 128, ok, ok);
        if (ok) break;
        RETRY(0);
        if (elect_one()) { mbar_expect_tx(B_H1, 2048); bulk_g2s(VX + warp * 2048, src, 2048, B_H1); }
      }
      if ((tid & 255) == 192) mbar_arrive_remote(peer1 + B_PF);
      __syncwarp();
      if (!REFILL_EARLY) refill();
      PROF(1, 11);
    }
    if (!ISV || s + 1 < cfg::NSEG) {
      const uint32_t ph = (s + 1) & 1;
      float x0[16], x1[16];
      named_bar_sync(NB_ST, 256);
      wg_fence();
#pragma unroll
      for (int c = 0; c < 6; c++) {
        if (c == 2) {
          mbar_spin(B_XN + 8, ph);
          if (ISV && s >= 0) mbar_spin(B_PF, s & 1);
          wg_fence();
        }
        if (ISV && c == CF_AT) {
          if (warp == 0) {
            if (elect_one()) tma_store_wait_read();
            __syncwarp();
            named_bar_arrive(NB_CF, 160);
          }
          wg_fence();
        }
#pragma unroll
        for (int u = 0; u < 4; u++) {
          wgmma_rs_n32(x0, wr[c][0][u], xn_desc(c < 2 ? 10 + c : c - 2, u), (c | u) != 0);
          wgmma_rs_n32(x1, wr[c][1][u], xn_desc(c < 2 ? 10 + c : c - 2, u), (c | u) != 0);
        }
      }
      wg_commit();
      OPQ;
      const uint32_t tb = ISV ? (ph ? VX2 : VX) : QK, tka = tok_addr<ISV>(tb, tid);
      uint32_t p0[2][4], p1[2][4];
      named_bar_sync(NB_DU, 256);
      ldsm4(p1[0], tka + tok_off<ISV>(1, 0)); ldsm4(p1[1], tka + tok_off<ISV>(1, 1));
      ldsm4(p0[0], tka + tok_off<ISV>(0, 0)); ldsm4(p0[1], tka + tok_off<ISV>(0, 1));
      wg_wait<0>();
      PROF(1, 13);
      tok_store<ISV, 1, true>(x1, tka, p1);
      tok_store<ISV, 0, true>(x0, tka, p0);
      if (ISV && s + 2 < cfg::NSEG) {
        fence_proxy_async_smem();
        __syncwarp();
        if (elect_one()) {
          bulk_s2s(peer0 + VX + warp * 2048, tb + warp * 2048, 2048, peer0 + B_VX);
          bulk_s2s(peer1 + VX + warp * 2048, tb + warp * 2048, 2048, peer1 + B_VX);
        }
      }
      wsa = WS + ((mi >> 1) * 8 + mr) * 128 + (((2 * w + (mi & 1)) ^ mr) << 4);
      mba = MEMB + lane * 16;
      PIN(wsa); PIN(mba);
      proj_mem_prefetch<ISV, 1, 0, NTA1>(ta, wsa);
      PROF(1, 14);
      if (s < 0) mbar_wait(B_WO, 0);
      named_bar_sync(NB_M1, 256);
      s++;
      PROF(1, 1);
      float a0[4], a1[4];
      proj_mem<ISV, 1>(wr, ta, wsa, mba, a0, a1);
      PROF(1, 2);
      proj_finish<ISV, 1>(a0, a1, peer0, peer1, self, tid, warp, vmo);
      PROF(1, 3);
    } else {
      OPQ;
      mbar_spin(B_VM, s & 1);
      lds64(vmo, VM + t7 * 8); lds64(vmo + 2, VM + 1024 + t7 * 8);
      s++;
    }
    tid ^= 0x5500;
    const bool last = s + 1 >= cfg::NSEG;
    constexpr int PFW = ISV ? PF1V : PF1;
    uint32_t wf[PFW][4], woa;
    if (ISV) {
      OPQ;
      woa = WO + ((mi >> 1) * 8 + mr) * 128 + (((2 * w + (mi & 1)) ^ mr) << 4);
      if (s >= 1) {
        const uint32_t sa = QK + ((w * (w + 3)) >> 1) * 256 + lane * 8;
        mbar_spin(B_ST, (s - 1) & 1);
        float sc[10];
        {
          const float NEG = -1000000000.0f / 0.08838834764831845f;
          float2 x[5], y[5];
#pragma unroll
          for (int b = 0; b < 5; b++) {
            x[b] = b < 2 ? lds64f(sa + b * 256) : lds64f_if(sa + b * 256, b <= w + 1, NEG);
            y[b] = b < 2 ? lds64f(sa + 3584 + b * 256) : lds64f_if(sa + 3584 + b * 256, b <= w + 1, 0.f);
          }
          wo_prefetch<3, false, 0, PF1A>(wf, woa, 0);
#pragma unroll
          for (int b = 0; b < 5; b++) { sc[2 * b] = x[b].x + y[b].x; sc[2 * b + 1] = x[b].y + y[b].y; }
        }
        float m = fmaxf(fmaxf(fmaxf(sc[0], sc[1]), fmaxf(sc[2], sc[3])), fmaxf(fmaxf(sc[4], sc[5]), fmaxf(sc[6], sc[7])));
        m = fmaxf(m, fmaxf(sc[8], sc[9]));
        m = fmaxf(m, __shfl_xor_sync(0xffffffffu, m, 1));
        m = fmaxf(m, __shfl_xor_sync(0xffffffffu, m, 2));
        const float cs = 0.08838834764831845f * 1.4426950408889634f;
#pragma unroll
        for (int i = 0; i < 10; i++) sc[i] = ex2_approx((sc[i] - m) * cs);
        float sum = ((sc[0] + sc[1]) + (sc[2] + sc[3])) + ((sc[4] + sc[5]) + (sc[6] + sc[7])) + (sc[8] + sc[9]);
        sum += __shfl_xor_sync(0xffffffffu, sum, 1);
        sum += __shfl_xor_sync(0xffffffffu, sum, 2);
        const float inv = rcp_approx(sum);
        const uint32_t pa = PT + (w * 8 + mr) * 128, pm = pack_bf16(sc[0] * inv, sc[1] * inv);
        stsm4(pa + ((mi ^ mr) << 4), pack_bf16(sc[2] * inv, sc[3] * inv), pack_bf16(sc[4] * inv, sc[5] * inv),
              pack_bf16(sc[6] * inv, sc[7] * inv), pack_bf16(sc[8] * inv, sc[9] * inv));
        asm volatile("stmatrix.sync.aligned.m8n8.x2.shared.b16 [%0], {%1,%1};" ::"r"(pa + ((((mi & 1) ? 7 : 4) ^ mr) << 4)), "r"(pm) : "memory");
      } else {
        wo_prefetch<3, false, 0, PF1A>(wf, woa, 0);
      }
      if (warp == 3 && !last) {
        mbar_spin(B_VM, s & 1);
        if (elect_one()) load_xn(P, s + 1, self);
      }
      PROF(1, 5);
    } else {
      if (warp == 0) {
        OPQ;
        uint32_t kf[4][4], qf[4][4];
        float c0[4], c1[4], d0[4], d1[4];
        const uint32_t ka = PT + (mi >> 1) * 1024 + (mi & 1) * 128 + mr * 16;
#pragma unroll
        for (int k = 0; k < 4; k++) { ldsm4t(qf[k], PT + 2048 + k * 512 + lane * 16); ldsm4t(kf[k], ka + k * 256); }
        mma16816z(c0, qf[0], kf[0][0], kf[0][1]); mma16816z(c1, qf[0], kf[0][2], kf[0][3]);
        mma16816z(d0, qf[1], kf[1][0], kf[1][1]); mma16816z(d1, qf[1], kf[1][2], kf[1][3]);
        mma16816(c0, qf[2], kf[2][0], kf[2][1]); mma16816(c1, qf[2], kf[2][2], kf[2][3]);
        mma16816(d0, qf[3], kf[3][0], kf[3][1]); mma16816(d1, qf[3], kf[3][2], kf[3][3]);
        const float s0 = ((c0[0] + c0[2]) + (c1[0] + c1[2])) + ((d0[0] + d0[2]) + (d1[0] + d1[2]));
        const float s1 = ((c0[1] + c0[3]) + (c1[1] + c1[3])) + ((d0[1] + d0[3]) + (d1[1] + d1[3]));
        if (!last) send_scores(s0, s1, SP + rank * SP_SRC + (128 + lane) * SPW, peer0, peer1, B_SM, lane);
        PROF(1, 5);
      } else {
        const uint32_t t_c = clk32() + lds32(B_XN) * 0;
        if (warp == 3 && !last) { if (elect_one()) load_xn(P, s + 1, self); }
        spin_until(t_c + D_ST);
      }
      OPQ;
      woa = WO + ((mi >> 1) * 8 + mr) * 128 + (((2 * w + (mi & 1)) ^ mr) << 4);
    }
    if (!last) {
      OPQ;
      uint32_t oba = OB + lane * 16;
      if (!ISV) wo_prefetch<3, false, 0, PF1Q>(wf, woa, 0);
      if (ISV ? GATE_MX : GATE_Q) named_bar_sync(NB_MX, 256);
      wo_prefetch<3, false, ISV ? PF1A : PF1Q, PFW>(wf, woa, 0);
      char* h1p = P.xch + (tile0 + w) * 32768 + (h >> 3) * 8192 + (h & 7) * 128 + (((2 * lq + (lg & 1)) ^ (h & 7)) << 4) + (lg >> 1) * 4;
      fence_proxy_async_smem();
      PROF(1, 7);
      named_bar_sync(NB_O, 256);
      PROF(1, 8);
      wo_phase<3, false>(wf, woa, 0, oba, h1p, tid >> 8, ((s >> 1) & 1) ^ 1);
      PROF(1, 9);
      named_bar_sync(NB_HD, 256);
    } else {
      fence_proxy_async_smem();
      named_bar_sync(NB_W1, 128);
    }
  }
  if (ISV && warp == 0) { if (elect_one()) o_done(15); }
}

template <bool ISV, int WG>
__device__ __forceinline__ void f_main(const FParams& P, const int h, const int rank, const uint32_t hw) {
  using namespace fk;
  const uint32_t self = mapa(0, (hw >> (2 * rank)) & 3);
  SMAP;
  const int tid = __shfl_sync(0xffffffffu, threadIdx.x, threadIdx.x & 31);
  const int tile0 = rank * 22, ntile = ISV ? 20 : 22;
  const CUtensorMap* m0 = ISV ? &P.wv : &P.wq;
  const CUtensorMap* m1 = ISV ? &P.wv : &P.wk;
  const int col0 = h * 128 + (ISV ? 0 : 64 * rank), col1 = h * 128 + (ISV ? 64 : 64 * rank);
  WRegs wr;
  uint32_t sel = 0;
  {
    OPQ;
    const uint32_t a = SM0 + WG * 16384 + ((mi >> 1) * 8 + mr) * 128 + (((2 * w + (mi & 1)) ^ mr) << 4);
#pragma unroll
    for (int i = 0; i < 6; i++) {
      mbar_wait(B_PB + 8 * i, 0);
      PRO(8 + i);
#pragma unroll
      for (int T = 0; T < 2; T++)
#pragma unroll
        for (int u = 0; u < 4; u++) ldsm4t(wr[i][T][u], a + i * 32768 + T * 8192 + u * 2048);
      named_bar_sync(NB_C, 256);
      if (WG == 1 && w == (i & 3)) {
        if (elect_one()) {
          if (i <= 2 && i + PRE_G < 6) {
#pragma unroll 1
            for (int n = 2 * (i + PRE_G); n < (i == 2 ? 12 : 2 * (i + PRE_G) + 2); n++) {
              const int ii = n >> 1, row = Chunks<ISV>::rf(n & 1, ii) * 64;
              if (!(n & 1)) mbar_expect_tx(B_PB + 8 * ii, 32768);
              tma_load_2d(SM0 + n * 16384, m0, col0, row, B_PB + 8 * ii);
              tma_load_2d(SM0 + n * 16384 + 8192, m1, col1, row, B_PB + 8 * ii);
            }
          }
          if (i == 3 || i == 4) {
            const int p0 = i == 3 ? 0 : 5, p1 = i == 3 ? 5 : 8;
            mbar_expect_tx(B_W, (p1 - p0) * 8192);
#pragma unroll 1
            for (int p = p0; p < p1; p++) tma_load_2d(WS + p * 8192, (p & 1) ? m1 : m0, (p & 1) ? col1 : col0, Chunks<ISV>::sm(p >> 1) * 64, B_W);
          }
          if (i == WO_AT) {
            mbar_expect_tx(B_WO, ntile * 4096);
#pragma unroll 1
            for (int t = 0; t < 5; t++) tma_load_2d(WO + t * 16384, &P.wo, tile0 * 16 + t * 64, h * 128, B_WO);
            if (!ISV) {
              tma_load_2d(WO + 81920, &P.wo16, tile0 * 16 + 320, h * 128, B_WO);
              tma_load_2d(WO + 86016, &P.wo16, tile0 * 16 + 336, h * 128, B_WO);
            }
          }
        }
      }
    }
    PROF2(1);
    if (WG == 0 && w == 1) {
      uint4 v;
#pragma unroll 1
      for (int tries = 0; tries < POLL_TRIES; tries++) {
        asm volatile("ld.acquire.gpu.global.v4.u32 {%0,%1,%2,%3}, [%4];" : "=r"(v.x), "=r"(v.y), "=r"(v.z), "=r"(v.w)
                     : "l"(&g_mask[4 * min(lane, 23)]) : "memory");
        if (__all_sync(0xffffffffu, v.x & v.y & v.z & v.w & 0x100)) break;
        __nanosleep(100);
      }
      if (elect_one()) {
        asm volatile("fence.proxy.async.global;" ::: "memory");
        load_xn(P, 0, self);
      }
      sts128(OB + lane * 16, v.x, v.y, v.z, v.w);
    }
    named_bar_sync(NB_C, 256);
#pragma unroll
    for (int i = 0; i < 3; i++) {
      const int t = min(tile0 + 8 * i + w + (WG ? 0 : 4), 63);
      sel |= ((lds32(OB + ((t >> 1) * 3 + (t & 1)) * 4) >> (h >> 3)) & 1) << (2 * i + 1);
    }
    const uint32_t own = lds32(OB + (3 * h + rank) * 4) >> w, m2 = lds32(OB + (3 * h + 2) * 4) >> w;
    sel |= (own & 1) << 7 | (m2 & 1) << 8 | (m2 & 16) << 5;
    sel |= (((((lg ^ h) & 1) << 2) | (lg >> 1)) == (h & 1) + 2 * (h >> 3)) << 10;
  }
  asm volatile("barrier.cluster.wait.aligned;" ::: "memory");
  PRO(14);
  mbar_wait(B_W, 0);
  PRO(15);
  PROF2(4);
  GTSYNC(0);
  PROF2(2);
  KT_END(8);
  if (WG == 0) f_wg0<ISV>(P, wr, h, rank, hw, tid | sel << 8); else f_wg1<ISV>(P, wr, h, rank, hw, tid | sel << 8);
}

__device__ __forceinline__ void f_tail(const FParams& P, const int h, const uint32_t rank) {
  using namespace fk;
  const uint32_t base = mapa(0, rank) + SM0;
  constexpr uint32_t STAGE = 49152, TX = 4 * STAGE, TG = TX + 16384, FULL = TG + 16384, EMPT = FULL + 32, RES = FULL + 64, NOG = FULL + 72;
  const int tid = threadIdx.x, lane = tid & 31, wv = __shfl_sync(0xffffffffu, tid >> 5, 0), wg = wv >> 2;
  const int kq = h & 3, nt = (h >> 2) & 3, mb = TAIL_MB0 + 3 * (h >> 4) + rank;
  TL(0);
  __syncthreads();
  if (tid == 0) {
    for (int i = 0; i < 4; i++) { mbar_init(base + FULL + 8 * i, 1); mbar_init(base + EMPT + 8 * i, 24); }
    mbar_init(base + RES, 1);
    fence_barrier_init();
  }
  __syncwarp();
  asm volatile("barrier.cluster.arrive.relaxed.aligned;\nbarrier.cluster.wait.aligned;" ::: "memory");
  KT_START(7);
  TL(1);
  auto load_b = [&](int kb) {
    const uint32_t sb = base + (kb & 3) * STAGE + 16384, full = base + FULL + 8 * (kb & 3);
    mbar_expect_tx(full, STAGE);
    tma_load_2d_mc(sb + rank * 8192, &P.tb, nt * 256 + ((rank + kq) & 3) * 64, (kq * 16 + kb) * 64, full, 7);
    if (kb % 3 == rank) tma_load_2d_mc(sb + 3 * 8192, &P.tb, nt * 256 + ((3 + kq) & 3) * 64, (kq * 16 + kb) * 64, full, 7);
  };
  auto load_a = [&](int kb) { tma_load_2d(base + (kb & 3) * STAGE, &P.ta, (kq * 16 + kb) * 64, mb * 128, base + FULL + 8 * (kb & 3)); };
  if (wv == 0) {
    if (elect_one()) {
#pragma unroll 1
      for (int kb = 0; kb < 4; kb++) load_b(kb);
      wait_count(&g_oflag[mb], 32);
      asm volatile("fence.proxy.async.global;" ::: "memory");
#pragma unroll 1
      for (int kb = 0; kb < 4; kb++) load_a(kb);
    }
  } else if (wv == 4) {
    if (elect_one()) {
      const bool nog = ld_strong4(&g_next) == 0;
      sts32(base + NOG, nog);
      if (nog) {
        g_tfix[blockIdx.x] = 1;
        mbar_arrive(base + RES);
      } else {
        wait_count(&g_cnt[3][mb], GATE_CNT);
        asm volatile("fence.proxy.async.global;" ::: "memory");
        mbar_expect_tx(base + RES, 32768);
        tma_load_2d(base + TX, &P.tx, nt * 256 + kq * 64, mb * 128, base + RES);
        tma_load_2d(base + TG, &P.tg, nt * 256 + kq * 64, mb * 128, base + RES);
      }
    }
  }
  __syncwarp();
  float acc[128];
#pragma unroll
  for (int i = 0; i < 128; i++) acc[i] = 0.f;
#pragma unroll 1
  for (int kb = 0; kb < 16; kb++) {
    const uint32_t st = kb & 3, sa = base + st * STAGE + wg * 8192, sb = base + st * STAGE + 16384;
    mbar_wait(base + FULL + 8 * st, (kb >> 2) & 1);
    if (kb == 0) TL(2);
    if (kb == 4) TL(3);
    if (kb == 10) TL(4);
    wg_fence();
#pragma unroll
    for (int k = 0; k < 4; k++) {
      wgmma_ss_n256_tb(acc, make_desc(sa + k * 32, 16, 1024), make_desc(sb + k * 2048, 8192, 1024), 1);
      if (k == 0) {
        wg_commit();
        wg_wait<1>();
        if (kb > 0 && kb <= 12 && lane < 3) mbar_arrive_cluster(base + EMPT + 8 * ((kb - 1) & 3), lane);
        wg_fence();
      }
    }
    wg_commit();
    if (kb >= 2 && kb < 14 && wv == ((kb & 1) << 2)) {
      if (elect_one()) {
        mbar_wait(base + EMPT + 8 * ((kb - 2) & 3), ((kb - 2) >> 2) & 1);
        load_b(kb + 2);
        load_a(kb + 2);
      }
      __syncwarp();
    }
  }
  wg_wait<0>();
  TL(5);
#pragma unroll
  for (int j = 1; j < 4; j++) {
    uint4* dst = &g_tpart[((h & ~3) + ((j + kq) & 3)) * 3 + rank][j - 1][0][tid];
#pragma unroll
    for (int i = 0; i < 4; i++) {
      const float* a = &acc[32 * j + 8 * i];
      dst[i * 256] = make_uint4(pack_bf16(a[0], a[1]), pack_bf16(a[2], a[3]), pack_bf16(a[4], a[5]), pack_bf16(a[6], a[7]));
    }
  }
  TL(6);
  __syncthreads();
  if (tid == 0) asm volatile("st.release.gpu.global.u32 [%0], 1;" ::"l"(&g_tflag[blockIdx.x]) : "memory");
  if (wv == 1) {
#pragma unroll 1
    for (int tries = 0; tries < POLL_TRIES; tries++) {
      uint32_t v;
      asm volatile("ld.acquire.gpu.global.u32 %0, [%1];" : "=r"(v) : "l"(&g_tflag[((h & ~3) + (lane & 3)) * 3 + rank]) : "memory");
      if (__all_sync(0xffffffffu, v)) break;
    }
  }
  mbar_wait(base + RES, 0);
  __syncthreads();
  const bool nog = lds32(base + NOG);
  TL(7);
  uint4 pt[3][4];
#pragma unroll
  for (int j = 0; j < 3; j++)
#pragma unroll
    for (int i = 0; i < 4; i++) pt[j][i] = __ldcg(&g_tpart[blockIdx.x][j][i][tid]);
  const uint32_t xa = base + TX + (wv * 16 + ((lane >> 3) & 1) * 8 + (lane & 7)) * 128 + (((lane >> 4) ^ (lane & 7)) << 4);
#pragma unroll
  for (int i = 0; i < 4; i++) {
    uint32_t x[4], g[4], o[4];
    ldsm4(x, xa ^ (i << 5));
    ldsm4(g, (xa ^ (i << 5)) + 16384);
#pragma unroll
    for (int k = 0; k < 4; k++) {
      const uint32_t p0 = (&pt[0][i].x)[k], p1 = (&pt[1][i].x)[k], p2 = (&pt[2][i].x)[k];
      const uint32_t sv = pack_bf16((acc[8 * i + 2 * k] + bf_lo(p0)) + (bf_lo(p1) + bf_lo(p2)),
                                    (acc[8 * i + 2 * k + 1] + bf_hi(p0)) + (bf_hi(p1) + bf_hi(p2)));
      o[k] = nog ? sv : add_bf16x2(x[k], mul_bf16x2(sv, g[k]));
    }
    stsm4(xa ^ (i << 5), o[0], o[1], o[2], o[3]);
  }
  TL(8);
  fence_proxy_async_smem();
  __syncthreads();
  TL(9);
  if (tid == 0) {
    tma_store_2d(&P.tout, base + TX, nt * 256 + kq * 64, mb * 128);
    tma_store_commit();
    tma_store_wait_read();
  }
  KT_END(7);
}

__global__ void __launch_bounds__(256, 1) f_kernel(const __grid_constant__ FParams P) {
  using namespace fk;
  extern __shared__ __align__(1024) uint8_t smem_f[];
  uint32_t crank, rank, hw;
  asm("mov.u32 %0, %%cluster_ctarank;" : "=r"(crank));
  const int h = blockIdx.x / 3;
  if (smem_u32(smem_f) != mapa(0, crank) + SM0) return;
  PROF2(0);
  KT_START(1);
  KT_START(0);
  {
    const uint32_t self = mapa(0, crank);
    SMAP;
    const int tid = threadIdx.x, lane = tid & 31, wv = __shfl_sync(0xffffffffu, tid >> 5, 0);
    PRO(0);
    const int row0 = blockIdx.x * 8 + wv;
    const bool third = row0 + 1536 < cfg::S;
    uint32_t cur[1][16], raw[2][16];
    load_row16(cur[0], P.x + (size_t)row0 * cfg::D, lane);
    load_row16(raw[0], P.x + (size_t)(row0 + 768) * cfg::D, lane);
    load_row16(raw[1], P.x + (size_t)(row0 + (third ? 1536 : 0)) * cfg::D, lane);
    {
      uint32_t tpc;
      asm("mov.u32 %0, %%smid;" : "=r"(tpc));
      if (tid == 0) sts32(PROBE + 96, tpc >> 1);
      asm volatile("barrier.cluster.arrive.release.aligned;\nbarrier.cluster.wait.acquire.aligned;" ::: "memory");
      asm volatile("ld.shared::cluster.u32 %0, [%1];" : "=r"(tpc) : "r"(mapa(PROBE + 96, lane % 3)) : "memory");
      const uint32_t t0 = __shfl_sync(0xffffffffu, tpc, 0), t1 = __shfl_sync(0xffffffffu, tpc, 1), t2 = __shfl_sync(0xffffffffu, tpc, 2);
      hw = t1 == t2 ? 0x09 : t0 == t2 ? 0x18 : 0x24;
      rank = (hw & 3) == crank ? 0 : ((hw >> 2) & 3) == crank ? 1 : 2;
    }
    const bool isv = rank == 2;
    const CUtensorMap* m0 = isv ? &P.wv : &P.wq;
    const CUtensorMap* m1 = isv ? &P.wv : &P.wk;
    const int col0 = h * 128 + (isv ? 0 : 64 * rank), col1 = h * 128 + (isv ? 64 : 64 * rank);
    if (wv == 0) {
      if (elect_one()) {
        for (int i = 0; i < 2; i++) mbar_init(B_XN + 8 * i, 1);
        mbar_init(B_H1, 4);
        mbar_init(B_SM, isv ? 1 : 6);
        mbar_init(B_VM, isv ? 8 : 1);
        mbar_init(B_VX, 1);
        mbar_init(B_ST, 1);
        mbar_init(B_PF, 2);
        for (int i = 0; i < 6; i++) mbar_init(B_PB + 8 * i, 1);
        mbar_init(B_W, 2);
        mbar_init(B_WO, 1);
        fence_barrier_init();
        mbar_expect_tx(B_SM, isv ? 2 * SP_SRC : SP_SRC);
        if (isv) mbar_expect_tx(B_ST, 7168);
        else { mbar_expect_tx(B_VM, 2048); mbar_expect_tx(B_VX, 8192); }
      }
    }
    const int j = 2 * h + rank;
    if (lane == 0) {
      const uint2 b = probe_pair(P.xch + (isv ? H1_BYTES + wv * 8192 + h * 128 : j * 32768 + (wv & 3) * 8192 + (wv >> 2) * 128),
                                 isv ? EMPTY : 0, PROBE + 64, P.nprobe);
      sts64(PROBE + wv * 8, b.x, b.y);
    }
    PROF2(3);
    PRO(1);
    __syncwarp();
    if (wv == 1) {
      const uint32_t off = (blockIdx.x * 32 + lane) * 688;
      if (off < cfg::D * cfg::D * 2) l2_prefetch(reinterpret_cast<const char*>(P.w1) + off, min(688u, cfg::D * cfg::D * 2 - off));
    }
    if (wv == 0) {
      asm volatile("{\n.reg .pred p;\nsetp.eq.u32 p, %0, %1;\n@p st.shared.u32 [%2], %0;\n}" ::"r"(raw[1][15]), "r"(cur[0][0] ^ raw[0][15]), "r"(PROBE + 64) : "memory");
      if (elect_one()) {
#pragma unroll 1
        for (int n = 0; n < 2 * PRE_G; n++) {
          const int i = n >> 1, g = n & 1, row = (isv ? Chunks<true>::rf(g, i) : Chunks<false>::rf(g, i)) * 64;
          if (!g) mbar_expect_tx(B_PB + 8 * i, 32768);
          tma_load_2d(SM0 + n * 16384, m0, col0, row, B_PB + 8 * i);
          tma_load_2d(SM0 + n * 16384 + 8192, m1, col1, row, B_PB + 8 * i);
        }
      }
    }
    __syncthreads();
    PRO(2);
    asm volatile("barrier.cluster.arrive.relaxed.aligned;" ::: "memory");
    PRO(3);
    if (wv == 2) { sts32(self + ONES + lane * 4, 0x3F803F80u); fence_proxy_async_smem(); }
    uint32_t pb[2], pc[2];
    lds64(pb, PROBE + (lane & 7) * 8);
    lds64(pc, PROBE + ((lane & 7) ^ 4) * 8);
    const uint32_t mask = __ballot_sync(0xffffffffu, isv ? pb[1] < pb[0] : min(pb[1], pc[1]) < min(pb[0], pc[0])) & (isv ? 255 : 15);
    if (!isv) {
#pragma unroll
      for (int i = 0; i < 4; i++) st_pub128(P.xch + j * 32768 + i * 8192 + ((mask >> i) & 1) * 4096 + tid * 16, 0);
      if (wv < 4) st_pub64(P.xch + H1_BYTES + (wv >> 1) * 32768 + (j >> 4) * 8192 + (wv & 1) * 4096 + (j & 15) * 256 + lane * 8, EMPTY, EMPTY);
    }
    if (blockIdx.x == 2) {
      if (tid < 96) (&g_cnt[0][0])[tid] = 0;
      else if (tid < 112) g_oflag[tid - 96] = 0;
      else if (tid == 112) g_next = 0;
      else if (tid >= 128 && tid < 224) { g_tflag[tid - 128] = 0; g_tfix[tid - 128] = 0; }
    }
#pragma unroll 1
    for (int it = 0; it < (third ? 6 : 4); it++) {
      ln_regs<1>(cur);
      store_row16(cur[0], ((it & 1) ? P.xn2 : P.xn_ptr) + (size_t)(row0 + (it >> 1) * 768) * cfg::D, lane);
      if (it == 0) PRO(4);
      if (it & 1) {
#pragma unroll
        for (int i = 0; i < 16; i++) { cur[0][i] = raw[0][i]; raw[0][i] = raw[1][i]; }
      }
    }
    PRO(5);
    __syncthreads();
    PRO(6);
    if (tid == 64) {
      __threadfence();
      PRO(7);
      pdl_launch_dependents();
      st_pub32(&g_mask[3 * h + rank], 0x100 | mask);
    }
    KT_END(0);
    __syncwarp();
  }
  const int wg = __shfl_sync(0xffffffffu, threadIdx.x >> 7, 0);
  if (rank == 2) { if (wg == 0) f_main<true, 0>(P, h, 2, hw); else f_main<true, 1>(P, h, 2, hw); }
  else { if (wg == 0) f_main<false, 0>(P, h, rank, hw); else f_main<false, 1>(P, h, rank, hw); }
  PROF2(5);
  GTSYNC(1);
  KT_END(1);
  __syncwarp();
  f_tail(P, h, crank);
}

#define GCL 1
namespace gk {
enum { T_B1 = 0, T_B2 = 1, T_B3 = 2, T_B4 = 3, T_O = 4, T_LN = 5, T_END = 7 };
constexpr int NST = 3, STAGE = 49152, MAXITEMS = 512, NEW = 3;
constexpr uint32_t OUTB = NST * STAGE, BARS = OUTB + 65536;
constexpr uint32_t B_FULL = BARS, B_EMPTY = BARS + 32, B_ITEM = BARS + 64, B_FILL = BARS + 128, B_FREE = BARS + 160, ITEMS = BARS + 192;
constexpr int SMEM = BARS + 256;
static_assert(GATE_CNT == 4 * NEW && T_B4 == 3, "gate counter");
}
struct GParams {
  CUtensorMap a[5], b[5];
  bf16* c[5];
  const bf16* r[5];
  bf16* x1n;
  int nitems, lnpos;
  uint16_t items[gk::MAXITEMS];
};
#define ILOG(i)

__device__ __forceinline__ void tma_load_3d_mc(uint32_t dst, const CUtensorMap* map, int x, int y, int z, uint32_t bar) {
  asm volatile("cp.async.bulk.tensor.3d.shared::cluster.global.mbarrier::complete_tx::bytes.multicast::cluster "
               "[%0], [%1, {%3, %4, %5}], [%2], %6;"
               ::"r"(dst), "l"(map), "r"(bar), "r"(x), "r"(y), "r"(z), "h"((uint16_t)3) : "memory");
}
__device__ __forceinline__ float tanh_approx(float x) { float y; asm("tanh.approx.f32 %0, %1;" : "=f"(y) : "f"(x)); return y; }
__global__ void __launch_bounds__(384, 1) g_kernel(const __grid_constant__ GParams P) {
  using namespace gk;
  extern __shared__ __align__(1024) uint8_t smem_g[];
  const uint32_t base = smem_u32(smem_g);
  const int tid = threadIdx.x, warp = __shfl_sync(0xffffffffu, tid >> 5, 0), lane = tid & 31;
  const int rank = blockIdx.x % GCL;
  KT_START(2);
  if (tid == 0) {
    for (int s = 0; s < NST; s++) { mbar_init(base + B_FULL + 8 * s, 1); mbar_init(base + B_EMPTY + 8 * s, 8 * GCL); }
    for (int s = 0; s < 8; s++) mbar_init(base + B_ITEM + 8 * s, 1);
    for (int s = 0; s < 2; s++) { mbar_init(base + B_FILL + 8 * s, 4); mbar_init(base + B_FREE + 8 * s, NEW); }
    fence_barrier_init();
  }
  __syncthreads();
  if (GCL > 1) cluster_sync();
  auto release = [&](uint32_t st) {
    if (GCL > 1) { if (lane < GCL) mbar_arrive_cluster(base + B_EMPTY + 8 * st, lane); }
    else if (lane == 0) mbar_arrive(base + B_EMPTY + 8 * st);
  };
  auto get_item = [&](int q) {
    mbar_wait(base + B_ITEM + 8 * (q & 7), (q >> 3) & 1);
    return lds32(base + ITEMS + 4 * (q & 7));
  };

  if (warp >= 8) {
   if (warp == 8) {
    if (lane == 0) {
      uint32_t st = 0, ph = 1;
#pragma unroll 1
      for (int q = 0;; q++) {
        if (GCL > 1) mbar_expect_tx(base + B_ITEM + 8 * (q & 7), 4);
        if (rank == 0) {
          const unsigned idx = atomicAdd(&g_next, 1), ln = idx - P.lnpos;
          const uint32_t v = (idx < (unsigned)P.nitems ? P.items[idx] : T_END) | (ln < 64 / GCL ? (ln + 1) << 16 : 0);
          if (GCL > 1) {
#pragma unroll
            for (int r = 0; r < GCL; r++) st_async32(mapa(base + ITEMS + 4 * (q & 7), r), v, mapa(base + B_ITEM + 8 * (q & 7), r));
          } else {
            sts32(base + ITEMS + 4 * (q & 7), v);
            mbar_arrive(base + B_ITEM + 8 * (q & 7));
          }
        }
        const uint32_t item = get_item(q);
        const int type = item & 7, mb = ((item >> 3) & 15) + rank, nt = (item >> 7) & 15;
        ILOG(1);
        if (q == 0) { __threadfence(); sts32(base + ITEMS + 32, ld_strong4(&g_oflag[14]) >= 32); }
        if (type == T_END) break;
        if (type == T_B2) {
          wait_count(&g_cnt[T_B1][max(mb - 1, 0)], 4 * NEW); wait_count(&g_cnt[T_B1][mb], 4 * NEW); wait_count(&g_cnt[T_B1][min(mb + 1, 15)], 4 * NEW);
        } else if (type == T_B3) wait_count(&g_cnt[T_LN][mb], 32);
        else if (type == T_B4) wait_count(&g_cnt[T_B3][mb], 14 * NEW);
        else if (type == T_O) wait_count(&g_oflag[mb], 32);
        asm volatile("fence.proxy.async.global;" ::: "memory");
        ILOG(2);
        const CUtensorMap *ma = &P.a[type], *mbm = &P.b[type];
        const int nkb = type == T_B4 ? cfg::F / 64 : type == T_O ? cfg::HD / 64 : cfg::D / 64;
#pragma unroll 1
        for (int kb = 0; kb < nkb; kb++) {
          mbar_wait(base + B_EMPTY + 8 * st, ph);
          const uint32_t sa = base + st * STAGE, full = base + B_FULL + 8 * st;
          mbar_expect_tx(full, STAGE);
          int arow = mb * 128;
          if (type == T_B2) { const int qd = kb >> 2; arow += (qd == 0) ? -1 : (qd == 1) ? 1 : (qd == 2) ? -2 : 2; }
          if (GCL > 1) tma_load_3d_mc(sa + 16384 + rank * 16384, mbm, 0, kb * 64, nt * 4 + rank * 2, full);
          else tma_load_3d(sa + 16384, mbm, 0, kb * 64, nt * 4, full);
          tma_load_2d(sa, ma, kb * 64, arow, full);
          if (++st == NST) { st = 0; ph ^= 1; }
        }
      }
    }
   } else {
    const int ew = warp - 9;
#pragma unroll 1
    for (int q = 0;; q++) {
      const uint32_t item = get_item(q);
      const int type = item & 7, mb = ((item >> 3) & 15) + rank, nt = (item >> 7) & 15;
      if (type == T_END) break;
      if (type == T_O) wait_count(&g_cnt[T_B4][mb], 4 * NEW);
      const int ldc = type == T_B3 ? cfg::F : cfg::D;
      bf16* cp = P.c[type] + (size_t)mb * 128 * ldc + nt * 256 + lane * 8;
      const size_t roff = (size_t)mb * 128 * cfg::D + nt * 256 + lane * 8;
      const bf16 *rp = P.r[type] + roff, *gp = P.c[T_B4] + roff;
      const bool res = type == T_B2 || type >= T_B4, act = type != T_B2 && type != T_O;
      const float c1 = type == T_B4 ? 0.f : 0.035677408136300125f, c0 = type == T_B4 ? 0.5f : 0.7978845608028654f;
      uint32_t yn[4][4];
      uint4 rn[4], gn[4];
      auto fetch_res = [&](int grp) {
#pragma unroll
        for (int i = 0; i < 4; i++) {
          if (res) rn[i] = __ldcg(reinterpret_cast<const uint4*>(rp + (grp * 4 + i) * cfg::D));
          if (type == T_O) gn[i] = __ldcg(reinterpret_cast<const uint4*>(gp + (grp * 4 + i) * cfg::D));
        }
      };
      auto fetch_y = [&](int grp) {
#pragma unroll
        for (int i = 0; i < 4; i++) lds128(yn[i], base + OUTB + (grp * 4 + i) * 512 + ((lane ^ ((grp * 4 + i) & 7)) << 4));
      };
      if (type == T_B4) wait_count(&g_cnt[T_B2][mb], 4 * NEW);
      fetch_res(ew);
      mbar_wait(base + B_FILL, q & 1);
      fetch_y(ew);
#pragma unroll 1
      for (int grp = ew; grp < 32; grp += NEW) {
        uint32_t y[4][4];
#pragma unroll
        for (int i = 0; i < 4; i++) {
#pragma unroll
          for (int k = 0; k < 4; k++) y[i][k] = yn[i][k];
          if (type == T_O) {
            y[i][0] = mul_bf16x2(y[i][0], gn[i].x); y[i][1] = mul_bf16x2(y[i][1], gn[i].y);
            y[i][2] = mul_bf16x2(y[i][2], gn[i].z); y[i][3] = mul_bf16x2(y[i][3], gn[i].w);
          }
          if (res) {
            y[i][0] = add_bf16x2(y[i][0], rn[i].x); y[i][1] = add_bf16x2(y[i][1], rn[i].y);
            y[i][2] = add_bf16x2(y[i][2], rn[i].z); y[i][3] = add_bf16x2(y[i][3], rn[i].w);
          }
        }
        const int nx = grp + NEW;
        if (nx < 32) {
          fetch_res(nx);
          if (nx >= 16 && grp < 16) {
            __syncwarp();
            if (lane == 0) mbar_arrive(base + B_FREE);
            mbar_wait(base + B_FILL + 8, q & 1);
          }
          fetch_y(nx);
        }
        if (act) {
#pragma unroll
          for (int i = 0; i < 4; i++)
#pragma unroll
            for (int k = 0; k < 4; k++) {
              const float v0 = bf_lo(y[i][k]), v1 = bf_hi(y[i][k]);
              const float t0 = tanh_approx(v0 * fmaf(v0 * c1, v0, c0)), t1 = tanh_approx(v1 * fmaf(v1 * c1, v1, c0));
              const float h0 = 0.5f * v0, h1 = 0.5f * v1;
              y[i][k] = pack_bf16(fmaf(h0, t0, h0), fmaf(h1, t1, h1));
            }
        }
#pragma unroll
        for (int i = 0; i < 4; i++)
          *reinterpret_cast<uint4*>(cp + (size_t)(grp * 4 + i) * ldc) = make_uint4(y[i][0], y[i][1], y[i][2], y[i][3]);
      }
      __syncwarp();
      if (lane == 0) mbar_arrive(base + B_FREE + 8);
      if (type != T_O) {
        __threadfence();
        __syncwarp();
        if (lane == 0) atomicAdd(&g_cnt[type][mb], 1);
      }
      if (tid == 288) ILOG(7);
    }
   }
   __syncwarp();
   named_bar_sync(1, 128);
   const bool late = lds32(base + ITEMS + 32);
   if (late) pdl_wait();
#pragma unroll 1
   for (int c = blockIdx.x; late && c < 96; c += gridDim.x) {
     if (__ldcg(&g_tfix[c]) == 0) continue;
     const int hh = c / 3, mb = TAIL_MB0 + 3 * (hh >> 4) + c % 3;
     wait_count(&g_cnt[T_B4][mb], GATE_CNT);
#pragma unroll 1
     for (int i = tid - 256; i < 1024; i += 128) {
       const size_t off = (size_t)(mb * 128 + (i >> 3)) * cfg::D + (hh & 15) * 64 + (i & 7) * 8;
       const uint4 sv = __ldcg(reinterpret_cast<const uint4*>(P.c[T_O] + off)), gv = __ldcg(reinterpret_cast<const uint4*>(P.c[T_B4] + off)),
                   xv = __ldcg(reinterpret_cast<const uint4*>(P.r[T_O] + off));
       *reinterpret_cast<uint4*>(P.c[T_O] + off) = make_uint4(add_bf16x2(xv.x, mul_bf16x2(sv.x, gv.x)), add_bf16x2(xv.y, mul_bf16x2(sv.y, gv.y)),
                                                              add_bf16x2(xv.z, mul_bf16x2(sv.z, gv.z)), add_bf16x2(xv.w, mul_bf16x2(sv.w, gv.w)));
     }
   }
   if (GCL > 1) cluster_sync();
  } else {
    const int wg = warp >> 2;
    const uint32_t outa = base + OUTB + (warp * 16 + ((lane >> 3) & 1) * 8 + (lane & 7)) * 512 + (((lane >> 4) ^ (lane & 7)) << 4);
    uint32_t st = 0, ph = 0;
    float acc[128];
#pragma unroll 1
    for (int q = 0;; q++) {
      const uint32_t item = get_item(q);
      const int type = item & 7;
      if (type == T_END) break;
      if (item >> 16) {
        const int ln = (item >> 16) - 1, lb = (ln >> 2) * GCL + rank;
        const size_t row = (size_t)(lb * 128 + (ln & 3) * 32 + warp * 4) * cfg::D;
        wait_count(&g_cnt[T_B2][lb], 4 * NEW);
        uint32_t raw[4][16];
#pragma unroll
        for (int r = 0; r < 4; r++) load_row16(raw[r], P.c[T_B2] + row + r * cfg::D, lane);
        ln_regs<4>(raw);
#pragma unroll
        for (int r = 0; r < 4; r++) store_row16(raw[r], P.x1n + row + r * cfg::D, lane);
        __threadfence();
        __syncwarp();
        if (lane == 0) atomicAdd(&g_cnt[T_LN][lb], 1);
        if (tid == 0) ILOG(6);
#pragma unroll
        for (int i = 0; i < 128; i++) acc[i] = 0.f;
      }
      const int nkb = type == T_B4 ? cfg::F / 64 : type == T_O ? cfg::HD / 64 : cfg::D / 64;
      uint32_t prev = 0;
#pragma unroll 1
      for (int kb = 0; kb < nkb; kb++) {
        if (kb == 0) mbar_wait(base + B_FULL + 8 * st, ph); else mbar_spin(base + B_FULL + 8 * st, ph);
        if (kb == 0 && tid == 0) ILOG(3);
        const uint32_t sa = base + st * STAGE + wg * 8192, sb = base + st * STAGE + 16384;
        wg_fence();
#pragma unroll
        for (int k = 0; k < 4; k++) {
          wgmma_ss_n256_tb(acc, make_desc(sa + k * 32, 16, 1024), make_desc(sb + k * 2048, 8192, 1024), (kb | k) != 0);
          if (k == 0) {
            wg_commit();
            wg_wait<1>();
            if (kb > 0) release(prev);
            wg_fence();
          }
        }
        wg_commit();
        prev = st;
        if (++st == NST) { st = 0; ph ^= 1; }
      }
      if (q > 0) mbar_wait(base + B_FREE + 8 * wg, (q - 1) & 1);
      wg_wait<0>();
      if (tid == 0) ILOG(4);
      release(prev);
#pragma unroll
      for (int j = 0; j < 16; j++)
        stsm4((outa ^ ((j & 3) << 5)) + (j >> 2) * 128, pack_bf16(acc[8 * j], acc[8 * j + 1]), pack_bf16(acc[8 * j + 2], acc[8 * j + 3]),
              pack_bf16(acc[8 * j + 4], acc[8 * j + 5]), pack_bf16(acc[8 * j + 6], acc[8 * j + 7]));
      __syncwarp();
      if (lane == 0) mbar_arrive(base + B_FILL + 8 * wg);
      if (tid == 0) ILOG(5);
    }
    KT_END(2);
    if (GCL > 1) cluster_sync();
  }
}

__device__ bf16 g_xn[cfg::S * cfg::D];
__device__ bf16 g_xn2[cfg::S * cfg::D];
__device__ bf16 g_h[cfg::S * cfg::D];
__device__ bf16 g_x1[cfg::S * cfg::D];
__device__ bf16 g_x1n[cfg::S * cfg::D];
__device__ bf16 g_u[cfg::S * cfg::F];
__device__ bf16 g_g[cfg::S * cfg::D];
__device__ bf16 g_o[cfg::S * cfg::HD];

typedef CUresult (*PFN_encodeTiled)(CUtensorMap*, CUtensorMapDataType, cuuint32_t, void*, const cuuint64_t*,
                                    const cuuint64_t*, const cuuint32_t*, const cuuint32_t*, CUtensorMapInterleave,
                                    CUtensorMapSwizzle, CUtensorMapL2promotion, CUtensorMapFloatOOBfill);

static PFN_encodeTiled get_encoder() {
  static PFN_encodeTiled fn = nullptr;
  if (!fn) {
    void* p = nullptr;
    cudaDriverEntryPointQueryResult st;
    cudaGetDriverEntryPoint("cuTensorMapEncodeTiled", &p, cudaEnableDefault, &st);
    fn = (PFN_encodeTiled)p;
  }
  return fn;
}
static CUtensorMap make_map(const void* ptr, int rows, int cols, int box_rows, int box_cols, int swizzle_bytes) {
  CUtensorMap m;
  cuuint64_t dims[2] = {(cuuint64_t)cols, (cuuint64_t)rows};
  cuuint64_t strides[1] = {(cuuint64_t)cols * 2};
  cuuint32_t box[2] = {(cuuint32_t)box_cols, (cuuint32_t)box_rows};
  cuuint32_t estr[2] = {1, 1};
  CUtensorMapSwizzle sw = swizzle_bytes == 128 ? CU_TENSOR_MAP_SWIZZLE_128B
                        : swizzle_bytes == 64 ? CU_TENSOR_MAP_SWIZZLE_64B
                        : swizzle_bytes == 32 ? CU_TENSOR_MAP_SWIZZLE_32B : CU_TENSOR_MAP_SWIZZLE_NONE;
  get_encoder()(&m, CU_TENSOR_MAP_DATA_TYPE_BFLOAT16, 2, const_cast<void*>(ptr), dims, strides, box, estr,
                CU_TENSOR_MAP_INTERLEAVE_NONE, sw, CU_TENSOR_MAP_L2_PROMOTION_L2_128B, CU_TENSOR_MAP_FLOAT_OOB_FILL_NONE);
  return m;
}
static CUtensorMap make_map3(const void* ptr, int rows, int cols, int box_rows, int nblk) {
  CUtensorMap m;
  cuuint64_t dims[3] = {64, (cuuint64_t)rows, (cuuint64_t)(cols / 64)};
  cuuint64_t strides[2] = {(cuuint64_t)cols * 2, 128};
  cuuint32_t box[3] = {64, (cuuint32_t)box_rows, (cuuint32_t)nblk};
  cuuint32_t estr[3] = {1, 1, 1};
  get_encoder()(&m, CU_TENSOR_MAP_DATA_TYPE_BFLOAT16, 3, const_cast<void*>(ptr), dims, strides, box, estr,
                CU_TENSOR_MAP_INTERLEAVE_NONE, CU_TENSOR_MAP_SWIZZLE_128B, CU_TENSOR_MAP_L2_PROMOTION_L2_128B,
                CU_TENSOR_MAP_FLOAT_OOB_FILL_NONE);
  return m;
}
template <class T> static T* sym(T& s) { void* p = nullptr; cudaGetSymbolAddress(&p, s); return (T*)p; }
#define SYM(name) ((bf16*)[] { void* p = nullptr; cudaGetSymbolAddress(&p, name); return p; }())

#define G_CTAS 36
#define LN_POS 64
static int build_items(uint16_t* it) {
  using namespace gk;
  int n = 0;
  auto add = [&](int type, int nrows, int ncols) {
    for (int mb = 0; mb < nrows; mb += GCL) for (int nt = 0; nt < ncols; nt++) it[n++] = (uint16_t)(type | mb << 3 | nt << 7);
  };
  add(T_B1, 16, 4); add(T_B2, 16, 4); add(T_B3, 16, 14); add(T_B4, 16, 4); add(T_O, TAIL_MB0, 4);
  return n;
}

extern "C" void kernel_launch(void* const* d_in, const int* in_sizes, int n_in, void* d_out, int out_size) {
  using namespace cfg;
  const bf16* x = (const bf16*)d_in[0];
  const bf16* mem0 = (const bf16*)d_in[1];
  const bf16* Wq = (const bf16*)d_in[2];
  const bf16* Wk = (const bf16*)d_in[3];
  const bf16* Wv = (const bf16*)d_in[4];
  const bf16* Wo = (const bf16*)d_in[5];
  const bf16* w1 = (const bf16*)d_in[8];
  const bf16* w2 = (const bf16*)d_in[9];
  const bf16* w3 = (const bf16*)d_in[10];
  const bf16* w4 = (const bf16*)d_in[11];
  bf16* out = (bf16*)d_out;
  cudaStream_t st = cudaStreamPerThread;

  bf16 *xn = SYM(g_xn), *xn2 = SYM(g_xn2), *hb = SYM(g_h), *x1 = SYM(g_x1), *x1n = SYM(g_x1n), *u = SYM(g_u),
       *g = SYM(g_g), *o = SYM(g_o);

  {
    cudaFuncSetAttribute(f_kernel, cudaFuncAttributeMaxDynamicSharedMemorySize, fk::SMEM);
    FParams P;
    P.wq = make_map(Wq, D, HD, 64, 64, 128); P.wk = make_map(Wk, D, HD, 64, 64, 128); P.wv = make_map(Wv, D, HD, 64, 64, 128);
    P.wo = make_map(Wo, HD, D, 128, 64, 128); P.wo16 = make_map(Wo, HD, D, 128, 16, 32); P.xn = make_map3(xn, S, D, 32, 4); P.xn12 = make_map3(xn, S, D, 32, 12); P.o = make_map3(o, S, HD, 32, 2);
    P.ta = make_map(o, S, HD, 128, 64, 128); P.tb = make_map(Wo, HD, D, 64, 64, 128); P.tx = make_map(x, S, D, 128, 64, 128);
    P.tg = make_map(g, S, D, 128, 64, 128); P.tout = make_map(out, S, D, 128, 64, 128);
    P.mem0 = mem0;
    P.nprobe = PROBE_N;
    P.x = x; P.w1 = w1; P.xn_ptr = xn; P.xn2 = xn2;
    P.xch = (char*)(((uintptr_t)SYM(g_xch) + 8191) & ~(uintptr_t)8191);
    cudaLaunchConfig_t cfg = {};
    cfg.gridDim = dim3(96); cfg.blockDim = dim3(256); cfg.dynamicSmemBytes = fk::SMEM; cfg.stream = st;
    cudaLaunchAttribute at[2];
    at[0].id = cudaLaunchAttributeClusterDimension;
    at[0].val.clusterDim.x = 3; at[0].val.clusterDim.y = 1; at[0].val.clusterDim.z = 1;
    cfg.attrs = at; cfg.numAttrs = 1;
    cudaLaunchKernelEx(&cfg, f_kernel, P);
  }
  {
    cudaFuncSetAttribute(g_kernel, cudaFuncAttributeMaxDynamicSharedMemorySize, gk::SMEM);
    GParams G;
    const bf16* as[5] = {xn2, hb, x1n, u, o};
    const bf16* bs[5] = {w1, w2, w3, w4, Wo};
    bf16* cs[5] = {hb, x1, u, g, out};
    const bf16* rs[5] = {xn, xn, xn, x1, x};
    const int ks[5] = {D, D, D, F, HD}, ns[5] = {D, D, F, D, D};
    for (int i = 0; i < 5; i++) {
      G.a[i] = make_map(as[i], S, ks[i], 128, 64, 128);
      G.b[i] = make_map3(bs[i], ks[i], ns[i], 64, 4 / GCL);
      G.c[i] = cs[i];
      G.r[i] = rs[i];
    }
    G.x1n = x1n;
    G.nitems = build_items(G.items);
    G.lnpos = LN_POS * 2 / GCL;
    cudaLaunchConfig_t cfg = {};
    cfg.gridDim = dim3(G_CTAS); cfg.blockDim = dim3(384); cfg.dynamicSmemBytes = gk::SMEM; cfg.stream = st;
    cudaLaunchAttribute at[2];
    at[0].id = cudaLaunchAttributeClusterDimension;
    at[0].val.clusterDim.x = GCL; at[0].val.clusterDim.y = 1; at[0].val.clusterDim.z = 1;
    at[1].id = cudaLaunchAttributeProgrammaticStreamSerialization;
    at[1].val.programmaticStreamSerializationAllowed = 1;
    cfg.attrs = at;
    cfg.numAttrs = 2;
    cudaLaunchKernelEx(&cfg, g_kernel, G);
  }
}
```

```cpp
#include <cuda_runtime.h>
#include <cuda_bf16.h>
#include <cuda.h>
#include <stdint.h>

typedef __nv_bfloat16 bf16;

namespace cfg {
constexpr int S = 2048;
constexpr int D = 1024;
constexpr int H = 32;
constexpr int DH = 128;
constexpr int HD = H * DH;
constexpr int M = 8;
constexpr int SEG = 32;
constexpr int NSEG = S / SEG;
constexpr int F = 3584;
}

__device__ __forceinline__ uint32_t smem_u32(const void* p) { return (uint32_t)__cvta_generic_to_shared(p); }

__device__ __forceinline__ void mbar_init(uint32_t bar, uint32_t count) {
  asm volatile("mbarrier.init.shared::cta.b64 [%0], %1;" ::"r"(bar), "r"(count) : "memory");
}
__device__ __forceinline__ void mbar_expect_tx(uint32_t bar, uint32_t bytes) {
  asm volatile("mbarrier.arrive.expect_tx.shared::cta.b64 _, [%0], %1;" ::"r"(bar), "r"(bytes) : "memory");
}
__device__ __forceinline__ void mbar_arrive(uint32_t bar) {
  asm volatile("mbarrier.arrive.shared::cta.b64 _, [%0];" ::"r"(bar) : "memory");
}
__device__ __forceinline__ bool mbar_try(uint32_t bar, uint32_t parity) {
  uint32_t done;
  asm volatile("{\n.reg .pred p;\nmbarrier.try_wait.parity.shared::cta.b64 p, [%1], %2, 20000;\nselp.u32 %0, 1, 0, p;\n}"
               : "=r"(done) : "r"(bar), "r"(parity) : "memory");
  return done != 0;
}
__device__ __forceinline__ bool mbar_try_nohint(uint32_t bar, uint32_t parity) {
  uint32_t done;
  asm volatile("{\n.reg .pred p;\nmbarrier.try_wait.parity.shared::cta.b64 p, [%1], %2;\nselp.u32 %0, 1, 0, p;\n}"
               : "=r"(done) : "r"(bar), "r"(parity) : "memory");
  return done != 0;
}
constexpr int MBAR_TRIES = 4096;
constexpr int POLL_TRIES = 1 << 16;
__device__ __forceinline__ void mbar_wait(uint32_t bar, uint32_t parity) {
#pragma unroll 1
  for (int n = 0; n < MBAR_TRIES; n++)
    if (mbar_try(bar, parity)) break;
}
__device__ __forceinline__ void mbar_wait_fast(uint32_t bar, uint32_t parity) {
#pragma unroll 1
  for (int n = 0; n < (POLL_TRIES << 4); n++)
    if (mbar_try_nohint(bar, parity)) break;
}
__device__ __forceinline__ void fence_barrier_init() { asm volatile("fence.mbarrier_init.release.cluster;" ::: "memory"); }
__device__ __forceinline__ void fence_proxy_async_smem() { asm volatile("fence.proxy.async.shared::cta;" ::: "memory"); }

__device__ __forceinline__ void tma_load_2d(uint32_t dst, const CUtensorMap* map, int x, int y, uint32_t bar) {
  asm volatile("cp.async.bulk.tensor.2d.shared::cluster.global.mbarrier::complete_tx::bytes [%0], [%1, {%3, %4}], [%2];"
               ::"r"(dst), "l"(map), "r"(bar), "r"(x), "r"(y) : "memory");
}
__device__ __forceinline__ void tma_load_3d(uint32_t dst, const CUtensorMap* map, int x, int y, int z, uint32_t bar) {
  asm volatile("cp.async.bulk.tensor.3d.shared::cluster.global.mbarrier::complete_tx::bytes [%0], [%1, {%3, %4, %5}], [%2];"
               ::"r"(dst), "l"(map), "r"(bar), "r"(x), "r"(y), "r"(z) : "memory");
}
__device__ __forceinline__ void tma_store_2d(const CUtensorMap* map, uint32_t src, int x, int y) {
  asm volatile("cp.async.bulk.tensor.2d.global.shared::cta.bulk_group [%0, {%2, %3}], [%1];"
               ::"l"(map), "r"(src), "r"(x), "r"(y) : "memory");
}
__device__ __forceinline__ void tma_store_commit() { asm volatile("cp.async.bulk.commit_group;" ::: "memory"); }
__device__ __forceinline__ void tma_store_wait_all() { asm volatile("cp.async.bulk.wait_group 0;" ::: "memory"); }
__device__ __forceinline__ void tma_store_wait_read() { asm volatile("cp.async.bulk.wait_group.read 0;" ::: "memory"); }
__device__ __forceinline__ void prefetch_tmap(const CUtensorMap* map) {
  asm volatile("prefetch.tensormap [%0];" ::"l"(map) : "memory");
}

__device__ __forceinline__ void wg_fence() { asm volatile("wgmma.fence.sync.aligned;" ::: "memory"); }
__device__ __forceinline__ void wg_commit() { asm volatile("wgmma.commit_group.sync.aligned;" ::: "memory"); }
template <int N> __device__ __forceinline__ void wg_wait() { asm volatile("wgmma.wait_group.sync.aligned %0;" ::"n"(N) : "memory"); }

#define named_bar_sync(id, n) asm volatile("bar.sync %0, %1;" ::"n"(id), "n"(n) : "memory")
#define named_bar_arrive(id, n) asm volatile("bar.arrive %0, %1;" ::"n"(id), "n"(n) : "memory")

__device__ __forceinline__ uint64_t make_desc(uint32_t addr, uint32_t lbo, uint32_t sbo) {
  return (uint64_t)((addr & 0x3FFFF) >> 4) | ((uint64_t)(lbo >> 4) << 16) | ((uint64_t)(sbo >> 4) << 32) | (1ull << 62);
}

__device__ __forceinline__ uint64_t make_desc0(uint32_t addr, uint32_t lbo, uint32_t sbo) {
  return (uint64_t)((addr & 0x3FFFF) >> 4) | ((uint64_t)(lbo >> 4) << 16) | ((uint64_t)(sbo >> 4) << 32);
}

__device__ __forceinline__ uint32_t pack_bf16(float lo, float hi) {
  uint32_t r;
  asm("cvt.rn.bf16x2.f32 %0, %1, %2;" : "=r"(r) : "f"(hi), "f"(lo));
  return r;
}
__device__ __forceinline__ float bf_lo(uint32_t v) { return __uint_as_float(v << 16); }
__device__ __forceinline__ float bf_hi(uint32_t v) { return __uint_as_float(v & 0xFFFF0000u); }
__device__ __forceinline__ float rbf(float v) { return __bfloat162float(__float2bfloat16_rn(v)); }

__device__ __forceinline__ void pdl_launch_dependents() { asm volatile("griddepcontrol.launch_dependents;" ::: "memory"); }
__device__ __forceinline__ void pdl_wait() { asm volatile("griddepcontrol.wait;" ::: "memory"); }

__device__ __forceinline__ float ex2_approx(float x) { float y; asm("ex2.approx.ftz.f32 %0, %1;" : "=f"(y) : "f"(x)); return y; }
__device__ __forceinline__ float rcp_approx(float x) { float y; asm("rcp.approx.ftz.f32 %0, %1;" : "=f"(y) : "f"(x)); return y; }

__device__ __forceinline__ void mul_sigmoid4(float (&v)[4], const float (&t)[4]) {
#pragma unroll
  for (int i = 0; i < 4; i += 2) {
    const float a = 1.0f + ex2_approx(fminf(t[i], 60.0f)), b = 1.0f + ex2_approx(fminf(t[i + 1], 60.0f));
    const float r = rcp_approx(a * b);
    v[i] *= b * r;
    v[i + 1] *= a * r;
  }
}
__device__ __forceinline__ void gelu4(float (&v)[4]) {
  float t[4];
#pragma unroll
  for (int i = 0; i < 4; i++) t[i] = v[i] * fmaf(v[i] * v[i], -0.10294324f, -2.30220819f);
  mul_sigmoid4(v, t);
}
__device__ __forceinline__ void silu4(float (&v)[4]) {
  float t[4];
#pragma unroll
  for (int i = 0; i < 4; i++) t[i] = v[i] * -1.4426950408889634f;
  mul_sigmoid4(v, t);
}

#define KT_START(id)
#define KT_END(id)

__device__ __forceinline__ void wgmma_ss_n256_tb(float (&d)[128], uint64_t da, uint64_t db, int scale_d) {
  asm volatile("{\n.reg .pred p;\nsetp.ne.b32 p, %130, 0;\n"
    "wgmma.mma_async.sync.aligned.m64n256k16.f32.bf16.bf16 "
    "{%0, %1, %2, %3, %4, %5, %6, %7, %8, %9, %10, %11, %12, %13, %14, %15, "
    "%16, %17, %18, %19, %20, %21, %22, %23, %24, %25, %26, %27, %28, %29, %30, %31, "
    "%32, %33, %34, %35, %36, %37, %38, %39, %40, %41, %42, %43, %44, %45, %46, %47, "
    "%48, %49, %50, %51, %52, %53, %54, %55, %56, %57, %58, %59, %60, %61, %62, %63, "
    "%64, %65, %66, %67, %68, %69, %70, %71, %72, %73, %74, %75, %76, %77, %78, %79, "
    "%80, %81, %82, %83, %84, %85, %86, %87, %88, %89, %90, %91, %92, %93, %94, %95, "
    "%96, %97, %98, %99, %100, %101, %102, %103, %104, %105, %106, %107, %108, %109, %110, %111, "
    "%112, %113, %114, %115, %116, %117, %118, %119, %120, %121, %122, %123, %124, %125, %126, %127}, "
    "%128, %129, p, 1, 1, 0, 1;\n}\n"
    : "+f"(d[0]), "+f"(d[1]), "+f"(d[2]), "+f"(d[3]), "+f"(d[4]), "+f"(d[5]), "+f"(d[6]), "+f"(d[7]),
      "+f"(d[8]), "+f"(d[9]), "+f"(d[10]), "+f"(d[11]), "+f"(d[12]), "+f"(d[13]), "+f"(d[14]), "+f"(d[15]),
      "+f"(d[16]), "+f"(d[17]), "+f"(d[18]), "+f"(d[19]), "+f"(d[20]), "+f"(d[21]), "+f"(d[22]), "+f"(d[23]),
      "+f"(d[24]), "+f"(d[25]), "+f"(d[26]), "+f"(d[27]), "+f"(d[28]), "+f"(d[29]), "+f"(d[30]), "+f"(d[31]),
      "+f"(d[32]), "+f"(d[33]), "+f"(d[34]), "+f"(d[35]), "+f"(d[36]), "+f"(d[37]), "+f"(d[38]), "+f"(d[39]),
      "+f"(d[40]), "+f"(d[41]), "+f"(d[42]), "+f"(d[43]), "+f"(d[44]), "+f"(d[45]), "+f"(d[46]), "+f"(d[47]),
      "+f"(d[48]), "+f"(d[49]), "+f"(d[50]), "+f"(d[51]), "+f"(d[52]), "+f"(d[53]), "+f"(d[54]), "+f"(d[55]),
      "+f"(d[56]), "+f"(d[57]), "+f"(d[58]), "+f"(d[59]), "+f"(d[60]), "+f"(d[61]), "+f"(d[62]), "+f"(d[63]),
      "+f"(d[64]), "+f"(d[65]), "+f"(d[66]), "+f"(d[67]), "+f"(d[68]), "+f"(d[69]), "+f"(d[70]), "+f"(d[71]),
      "+f"(d[72]), "+f"(d[73]), "+f"(d[74]), "+f"(d[75]), "+f"(d[76]), "+f"(d[77]), "+f"(d[78]), "+f"(d[79]),
      "+f"(d[80]), "+f"(d[81]), "+f"(d[82]), "+f"(d[83]), "+f"(d[84]), "+f"(d[85]), "+f"(d[86]), "+f"(d[87]),
      "+f"(d[88]), "+f"(d[89]), "+f"(d[90]), "+f"(d[91]), "+f"(d[92]), "+f"(d[93]), "+f"(d[94]), "+f"(d[95]),
      "+f"(d[96]), "+f"(d[97]), "+f"(d[98]), "+f"(d[99]), "+f"(d[100]), "+f"(d[101]), "+f"(d[102]), "+f"(d[103]),
      "+f"(d[104]), "+f"(d[105]), "+f"(d[106]), "+f"(d[107]), "+f"(d[108]), "+f"(d[109]), "+f"(d[110]), "+f"(d[111]),
      "+f"(d[112]), "+f"(d[113]), "+f"(d[114]), "+f"(d[115]), "+f"(d[116]), "+f"(d[117]), "+f"(d[118]), "+f"(d[119]),
      "+f"(d[120]), "+f"(d[121]), "+f"(d[122]), "+f"(d[123]), "+f"(d[124]), "+f"(d[125]), "+f"(d[126]), "+f"(d[127])
    : "l"(da), "l"(db), "r"(scale_d));
}
__device__ __forceinline__ void wgmma_rs_n32(float (&d)[16], const uint32_t* a, uint64_t db, int scale_d) {
  asm volatile("{\n.reg .pred p;\nsetp.ne.b32 p, %21, 0;\n"
    "wgmma.mma_async.sync.aligned.m64n32k16.f32.bf16.bf16 "
    "{%0, %1, %2, %3, %4, %5, %6, %7, %8, %9, %10, %11, %12, %13, %14, %15}, "
    "{%16, %17, %18, %19}, %20, p, 1, 1, 0;\n}\n"
    : "+f"(d[0]), "+f"(d[1]), "+f"(d[2]), "+f"(d[3]), "+f"(d[4]), "+f"(d[5]), "+f"(d[6]), "+f"(d[7]),
      "+f"(d[8]), "+f"(d[9]), "+f"(d[10]), "+f"(d[11]), "+f"(d[12]), "+f"(d[13]), "+f"(d[14]), "+f"(d[15])
    : "r"(a[0]), "r"(a[1]), "r"(a[2]), "r"(a[3]), "l"(db), "r"(scale_d));
}
__device__ __forceinline__ void wgmma_ss_n32_ta(float (&d)[16], uint64_t da, uint64_t db, int scale_d) {
  asm volatile("{\n.reg .pred p;\nsetp.ne.b32 p, %18, 0;\n"
    "wgmma.mma_async.sync.aligned.m64n32k16.f32.bf16.bf16 "
    "{%0, %1, %2, %3, %4, %5, %6, %7, %8, %9, %10, %11, %12, %13, %14, %15}, "
    "%16, %17, p, 1, 1, 1, 0;\n}\n"
    : "+f"(d[0]), "+f"(d[1]), "+f"(d[2]), "+f"(d[3]), "+f"(d[4]), "+f"(d[5]), "+f"(d[6]), "+f"(d[7]),
      "+f"(d[8]), "+f"(d[9]), "+f"(d[10]), "+f"(d[11]), "+f"(d[12]), "+f"(d[13]), "+f"(d[14]), "+f"(d[15])
    : "l"(da), "l"(db), "r"(scale_d));
}
__device__ __forceinline__ void wgmma_ss_n8_ta(float (&d)[4], uint64_t da, uint64_t db, int scale_d) {
  asm volatile("{\n.reg .pred p;\nsetp.ne.b32 p, %6, 0;\n"
    "wgmma.mma_async.sync.aligned.m64n8k16.f32.bf16.bf16 {%0, %1, %2, %3}, %4, %5, p, 1, 1, 1, 0;\n}\n"
    : "+f"(d[0]), "+f"(d[1]), "+f"(d[2]), "+f"(d[3]) : "l"(da), "l"(db), "r"(scale_d));
}
__device__ __forceinline__ void wgmma_ss_n48_tt(float (&d)[24], uint64_t da, uint64_t db, int scale_d) {
  asm volatile("{\n.reg .pred p;\nsetp.ne.b32 p, %26, 0;\n"
    "wgmma.mma_async.sync.aligned.m64n48k16.f32.bf16.bf16 "
    "{%0, %1, %2, %3, %4, %5, %6, %7, %8, %9, %10, %11, %12, %13, %14, %15, %16, %17, %18, %19, %20, %21, %22, %23}, "
    "%24, %25, p, 1, 1, 1, 1;\n}\n"
    : "+f"(d[0]), "+f"(d[1]), "+f"(d[2]), "+f"(d[3]), "+f"(d[4]), "+f"(d[5]), "+f"(d[6]), "+f"(d[7]), "+f"(d[8]), "+f"(d[9]), "+f"(d[10]), "+f"(d[11]), "+f"(d[12]), "+f"(d[13]), "+f"(d[14]), "+f"(d[15]), "+f"(d[16]), "+f"(d[17]), "+f"(d[18]), "+f"(d[19]), "+f"(d[20]), "+f"(d[21]), "+f"(d[22]), "+f"(d[23])
    : "l"(da), "l"(db), "r"(scale_d));
}
__device__ __forceinline__ void wgmma_ss_n32(float (&d)[16], uint64_t da, uint64_t db, int scale_d) {
  asm volatile("{\n.reg .pred p;\nsetp.ne.b32 p, %18, 0;\n"
    "wgmma.mma_async.sync.aligned.m64n32k16.f32.bf16.bf16 "
    "{%0, %1, %2, %3, %4, %5, %6, %7, %8, %9, %10, %11, %12, %13, %14, %15}, "
    "%16, %17, p, 1, 1, 0, 0;\n}\n"
    : "+f"(d[0]), "+f"(d[1]), "+f"(d[2]), "+f"(d[3]), "+f"(d[4]), "+f"(d[5]), "+f"(d[6]), "+f"(d[7]),
      "+f"(d[8]), "+f"(d[9]), "+f"(d[10]), "+f"(d[11]), "+f"(d[12]), "+f"(d[13]), "+f"(d[14]), "+f"(d[15])
    : "l"(da), "l"(db), "r"(scale_d));
}

__device__ __forceinline__ void tma_load_2d_mc(uint32_t dst, const CUtensorMap* map, int x, int y, uint32_t bar, uint16_t mask) {
  asm volatile("cp.async.bulk.tensor.2d.shared::cluster.global.mbarrier::complete_tx::bytes.multicast::cluster "
               "[%0], [%1, {%3, %4}], [%2], %5;"
               ::"r"(dst), "l"(map), "r"(bar), "r"(x), "r"(y), "h"(mask) : "memory");
}
__device__ __forceinline__ void mbar_arrive_cluster(uint32_t bar, uint32_t cta) {
  asm volatile("{\n.reg .b32 r;\nmapa.shared::cluster.u32 r, %0, %1;\nmbarrier.arrive.shared::cluster.b64 _, [r];\n}"
               ::"r"(bar), "r"(cta) : "memory");
}
__device__ __forceinline__ void cluster_sync() {
  asm volatile("barrier.cluster.arrive.release.aligned;\nbarrier.cluster.wait.acquire.aligned;" ::: "memory");
}
__device__ __forceinline__ void wait_count(const unsigned* p, unsigned need) {
#pragma unroll 1
  for (int tries = 0; tries < (1 << 18); tries++) {
    unsigned v;
    asm volatile("ld.acquire.gpu.global.u32 %0, [%1];" : "=r"(v) : "l"(p) : "memory");
    if (v >= need) break;
    __nanosleep(64);
  }
}
__device__ __forceinline__ uint32_t sub_bf16x2(uint32_t a, uint32_t b) {
  uint32_t d;
  asm("sub.rn.bf16x2 %0, %1, %2;" : "=r"(d) : "r"(a), "r"(b));
  return d;
}
__device__ __forceinline__ uint32_t add_bf16x2(uint32_t a, uint32_t b) {
  uint32_t d;
  asm("add.rn.bf16x2 %0, %1, %2;" : "=r"(d) : "r"(a), "r"(b));
  return d;
}
__device__ __forceinline__ uint32_t mul_bf16x2(uint32_t a, uint32_t b) {
  uint32_t d;
  asm("mul.rn.bf16x2 %0, %1, %2;" : "=r"(d) : "r"(a), "r"(b));
  return d;
}

template <int NR>
__device__ __forceinline__ void ln_regs(uint32_t (&raw)[NR][16]) {
  float m[NR], q[NR];
#pragma unroll
  for (int r = 0; r < NR; r++) {
    float s0 = 0.f, s1 = 0.f;
#pragma unroll
    for (int i = 0; i < 16; i++) { s0 += bf_lo(raw[r][i]); s1 += bf_hi(raw[r][i]); }
    m[r] = s0 + s1;
  }
#pragma unroll
  for (int o = 16; o > 0; o >>= 1)
#pragma unroll
    for (int r = 0; r < NR; r++) m[r] += __shfl_xor_sync(0xffffffffu, m[r], o);
#pragma unroll
  for (int r = 0; r < NR; r++) {
    m[r] *= 1.0f / 1024.0f;
    float s0 = 0.f, s1 = 0.f;
#pragma unroll
    for (int i = 0; i < 16; i++) {
      const float d0 = bf_lo(raw[r][i]) - m[r], d1 = bf_hi(raw[r][i]) - m[r];
      s0 = fmaf(d0, d0, s0); s1 = fmaf(d1, d1, s1);
    }
    q[r] = s0 + s1;
  }
#pragma unroll
  for (int o = 16; o > 0; o >>= 1)
#pragma unroll
    for (int r = 0; r < NR; r++) q[r] += __shfl_xor_sync(0xffffffffu, q[r], o);
#pragma unroll
  for (int r = 0; r < NR; r++) {
    const uint32_t mb = pack_bf16(m[r], m[r]);
    float sq;
    asm("sqrt.approx.f32 %0, %1;" : "=f"(sq) : "f"(rbf(rbf(q[r] * (1.0f / 1024.0f)) + 1e-5f)));
    const float inv = rcp_approx(rbf(sq));
#pragma unroll
    for (int i = 0; i < 16; i++) {
      const uint32_t d = sub_bf16x2(raw[r][i], mb);
      raw[r][i] = pack_bf16(bf_lo(d) * inv, bf_hi(d) * inv);
    }
  }
}
__device__ __forceinline__ void load_row16(uint32_t (&raw)[16], const bf16* src, int lane) {
#pragma unroll
  for (int j = 0; j < 4; j++) {
    const uint4 u = __ldcg(reinterpret_cast<const uint4*>(src + j * 256 + lane * 8));
    raw[4 * j] = u.x; raw[4 * j + 1] = u.y; raw[4 * j + 2] = u.z; raw[4 * j + 3] = u.w;
  }
}
__device__ __forceinline__ void store_row16(const uint32_t (&raw)[16], bf16* dst, int lane) {
#pragma unroll
  for (int j = 0; j < 4; j++)
    *reinterpret_cast<uint4*>(dst + j * 256 + lane * 8) = make_uint4(raw[4 * j], raw[4 * j + 1], raw[4 * j + 2], raw[4 * j + 3]);
}

namespace fk {
constexpr uint32_t SM0 = 1024;
constexpr uint32_t WO = SM0, WS = WO + 90112, XN = WS + 65536, VX = XN + 49152, QK = VX + 8192, PT = QK + 8192,
                   SP = PT + 4096, VM = SP + 2560, OB = VM + 2048, BAR = OB + 2048;
constexpr uint32_t MEMB = XN + 16384, RED = XN + 32768, VX2 = WO + 81920;
constexpr int SMEM = 232448;
static_assert(BAR + 512 == SM0 + SMEM, "shared memory layout");
constexpr uint32_t B_XN = BAR, B_H2 = BAR + 64, B_H1 = BAR + 120, ONES = BAR + 384, B_PF = BAR + 16, B_WO = BAR + 24, B_SM = BAR + 32, B_VM = BAR + 40, B_VX = BAR + 48, B_ST = BAR + 56, B_PB = BAR + 64, B_W = BAR + 112,
                   MASKS = BAR + 128, PROBE = BAR + 256;
constexpr int NB_M0 = 1, NB_M1 = 2, NB_C = 3, NB_O = 4, NB_ST = 5, NB_DU = 6, NB_CF = 7, NB_W1 = 8, NB_XE = 9, NB_HD = 10, NB_MX = 11, NB_O0 = 12;
#define D_H1 500
#define D_H2 1850
#define D_ST 100
#define SMQ 0x1E
#define SMV 0x1E
#define PRE_G 5
#define WO_AT 4
#define NS0 4
#define NS0V 4
#define NTA0 2
#define NTA1 1
#define PF0A 3
#define PF0 10
#define PF1A 0
#define PF1V 10
#define PF1 11
#define REFILL_EARLY 1
#define GATE_MX 0
#define GATE_Q 0
#define PF1Q 4
#define XN_EARLY 1
#define PACEQ 0x60
#define PACEV 0
#define PADD 1
#define VM_BULK 0
#define CF_AT 0
#define H2_AT 1
#define NPRE0 1
#define PROBE_N 4
#define SPACK 0
constexpr uint32_t SPW = SPACK ? 4 : 8, SP_SRC = 160 * SPW;
constexpr int H1_BYTES = 64 * 32768, H2_BYTES = 8 * 8192;
}

#define PROF(wg, i)
#define PROF2(i)
#define RETRY(i)
#define GTSYNC(i)
#define PRO(i)
#define TL(i)
#define TL2(t, i)

__device__ uint4 g_xch[(fk::H1_BYTES + fk::H2_BYTES + 8192) / 16];
__device__ __align__(16) unsigned g_mask[128];
__device__ unsigned g_cnt[6][16];
__device__ unsigned g_next;
constexpr int TAIL_MB0 = 10, GATE_CNT = 12;
__device__ __align__(16) unsigned g_tfix[96], g_lnok[4];
__device__ uint4 g_tpart[96][3][4][256];
__device__ unsigned g_oflag[16];

#define LD_POLL "ld.global.L1::no_allocate"
__device__ __forceinline__ uint4 ld_poll16(const void* p) {
  uint4 v;
  asm volatile(LD_POLL ".v4.u32 {%0,%1,%2,%3}, [%4];" : "=r"(v.x), "=r"(v.y), "=r"(v.z), "=r"(v.w) : "l"(p) : "memory");
  return v;
}
__device__ __forceinline__ uint2 ld_poll8(const void* p) {
  uint2 v;
  asm volatile(LD_POLL ".v2.u32 {%0,%1}, [%2];" : "=r"(v.x), "=r"(v.y) : "l"(p) : "memory");
  return v;
}
__device__ __forceinline__ uint4 ld_strong16(const void* p) {
  uint4 v;
  asm volatile("ld.relaxed.gpu.global.v4.u32 {%0,%1,%2,%3}, [%4];" : "=r"(v.x), "=r"(v.y), "=r"(v.z), "=r"(v.w) : "l"(p) : "memory");
  return v;
}
__device__ __forceinline__ uint2 ld_strong8(const void* p) {
  uint2 v;
  asm volatile("ld.relaxed.gpu.global.v2.u32 {%0,%1}, [%2];" : "=r"(v.x), "=r"(v.y) : "l"(p) : "memory");
  return v;
}
__device__ __forceinline__ void st_pub32(void* p, uint32_t v) { asm volatile("st.relaxed.gpu.global.u32 [%0], %1;" ::"l"(p), "r"(v) : "memory"); }
__device__ __forceinline__ void st_pub16(void* p, uint32_t v) {
  asm volatile("st.relaxed.gpu.global.u16 [%0], %1;" ::"l"(p), "h"((uint16_t)v) : "memory");
}
__device__ __forceinline__ uint32_t ld_strong4(const void* p) {
  uint32_t v;
  asm volatile("ld.relaxed.gpu.global.u32 %0, [%1];" : "=r"(v) : "l"(p) : "memory");
  return v;
}
__device__ __forceinline__ void st_pub64(void* p, uint32_t a, uint32_t b) {
  asm volatile("st.relaxed.gpu.global.v2.u32 [%0], {%1,%2};" ::"l"(p), "r"(a), "r"(b) : "memory");
}
__device__ __forceinline__ void st_pub128(void* p, uint32_t a) {
  asm volatile("st.relaxed.gpu.global.v4.u32 [%0], {%1,%1,%1,%1};" ::"l"(p), "r"(a) : "memory");
}
constexpr uint32_t EMPTY = 0xFFFFFFFFu;
__device__ __forceinline__ uint32_t umax4(const uint4& v) { return max(max(v.x, v.y), max(v.z, v.w)); }
__device__ __forceinline__ void sts128(uint32_t a, uint32_t x, uint32_t y, uint32_t z, uint32_t w) {
  asm volatile("st.shared.v4.u32 [%0], {%1,%2,%3,%4};" ::"r"(a), "r"(x), "r"(y), "r"(z), "r"(w) : "memory");
}
__device__ __forceinline__ void sts64(uint32_t a, uint32_t x, uint32_t y) {
  asm volatile("st.shared.v2.u32 [%0], {%1,%2};" ::"r"(a), "r"(x), "r"(y) : "memory");
}
__device__ __forceinline__ void sts32(uint32_t a, uint32_t x) { asm volatile("st.shared.u32 [%0], %1;" ::"r"(a), "r"(x) : "memory"); }
__device__ __forceinline__ void sts128f(uint32_t a, float x, float y, float z, float w) {
  asm volatile("st.shared.v4.f32 [%0], {%1,%2,%3,%4};" ::"r"(a), "f"(x), "f"(y), "f"(z), "f"(w) : "memory");
}
__device__ __forceinline__ void sts64f(uint32_t a, float x, float y) {
  asm volatile("st.shared.v2.f32 [%0], {%1,%2};" ::"r"(a), "f"(x), "f"(y) : "memory");
}
__device__ __forceinline__ float4 lds128f(uint32_t a) {
  float4 v;
  asm volatile("ld.shared.v4.f32 {%0,%1,%2,%3}, [%4];" : "=f"(v.x), "=f"(v.y), "=f"(v.z), "=f"(v.w) : "r"(a) : "memory");
  return v;
}
__device__ __forceinline__ float2 lds64f(uint32_t a) {
  float2 v;
  asm volatile("ld.shared.v2.f32 {%0,%1}, [%2];" : "=f"(v.x), "=f"(v.y) : "r"(a) : "memory");
  return v;
}
__device__ __forceinline__ float2 lds64f_if(uint32_t a, bool on, float other) {
  float2 v = make_float2(other, other);
  asm volatile("{\n.reg .pred p;\nsetp.ne.u32 p, %3, 0;\n@p ld.shared.v2.f32 {%0,%1}, [%2];\n}" : "+f"(v.x), "+f"(v.y) : "r"(a), "r"((uint32_t)on) : "memory");
  return v;
}
__device__ __forceinline__ void lds128(uint32_t* r, uint32_t a) {
  asm volatile("ld.shared.v4.u32 {%0,%1,%2,%3}, [%4];" : "=r"(r[0]), "=r"(r[1]), "=r"(r[2]), "=r"(r[3]) : "r"(a) : "memory");
}
__device__ __forceinline__ void lds64(uint32_t* r, uint32_t a) {
  asm volatile("ld.shared.v2.u32 {%0,%1}, [%2];" : "=r"(r[0]), "=r"(r[1]) : "r"(a) : "memory");
}
__device__ __forceinline__ uint32_t lds32(uint32_t a) {
  uint32_t v;
  asm volatile("ld.shared.u32 %0, [%1];" : "=r"(v) : "r"(a) : "memory");
  return v;
}
__device__ __forceinline__ void ldsm4(uint32_t* r, uint32_t a) {
  asm volatile("ldmatrix.sync.aligned.m8n8.x4.shared.b16 {%0,%1,%2,%3}, [%4];"
               : "=r"(r[0]), "=r"(r[1]), "=r"(r[2]), "=r"(r[3]) : "r"(a) : "memory");
}
__device__ __forceinline__ void ldsm4t(uint32_t* r, uint32_t a) {
  asm volatile("ldmatrix.sync.aligned.m8n8.x4.trans.shared.b16 {%0,%1,%2,%3}, [%4];"
               : "=r"(r[0]), "=r"(r[1]), "=r"(r[2]), "=r"(r[3]) : "r"(a) : "memory");
}
__device__ __forceinline__ void stsm4(uint32_t a, uint32_t r0, uint32_t r1, uint32_t r2, uint32_t r3) {
  asm volatile("stmatrix.sync.aligned.m8n8.x4.shared.b16 [%0], {%1,%2,%3,%4};"
               ::"r"(a), "r"(r0), "r"(r1), "r"(r2), "r"(r3) : "memory");
}
__device__ __forceinline__ void stsm4t(uint32_t a, uint32_t r0, uint32_t r1, uint32_t r2, uint32_t r3) {
  asm volatile("stmatrix.sync.aligned.m8n8.x4.trans.shared.b16 [%0], {%1,%2,%3,%4};"
               ::"r"(a), "r"(r0), "r"(r1), "r"(r2), "r"(r3) : "memory");
}
__device__ __forceinline__ void mma16816(float* d, const uint32_t* a, uint32_t b0, uint32_t b1) {
  asm volatile("mma.sync.aligned.m16n8k16.row.col.f32.bf16.bf16.f32 {%0,%1,%2,%3}, {%4,%5,%6,%7}, {%8,%9}, {%0,%1,%2,%3};"
               : "+f"(d[0]), "+f"(d[1]), "+f"(d[2]), "+f"(d[3])
               : "r"(a[0]), "r"(a[1]), "r"(a[2]), "r"(a[3]), "r"(b0), "r"(b1));
}
__device__ __forceinline__ void mma16816z(float* d, const uint32_t* a, uint32_t b0, uint32_t b1) {
  asm volatile("mma.sync.aligned.m16n8k16.row.col.f32.bf16.bf16.f32 {%0,%1,%2,%3}, {%4,%5,%6,%7}, {%8,%9}, {%10,%10,%10,%10};"
               : "=f"(d[0]), "=f"(d[1]), "=f"(d[2]), "=f"(d[3])
               : "r"(a[0]), "r"(a[1]), "r"(a[2]), "r"(a[3]), "r"(b0), "r"(b1), "f"(0.f));
}
__device__ __forceinline__ void mma1688(float* d, uint32_t a0, uint32_t a1, uint32_t b0) {
  asm volatile("mma.sync.aligned.m16n8k8.row.col.f32.bf16.bf16.f32 {%0,%1,%2,%3}, {%4,%5}, {%6}, {%0,%1,%2,%3};"
               : "+f"(d[0]), "+f"(d[1]), "+f"(d[2]), "+f"(d[3]) : "r"(a0), "r"(a1), "r"(b0));
}
__device__ __forceinline__ uint32_t movtrans(uint32_t a) {
  uint32_t d;
  asm volatile("movmatrix.sync.aligned.m8n8.trans.b16 %0, %1;" : "=r"(d) : "r"(a));
  return d;
}
__device__ __forceinline__ uint32_t mapa(uint32_t a, uint32_t rank) {
  uint32_t d;
  asm("mapa.shared::cluster.u32 %0, %1, %2;" : "=r"(d) : "r"(a), "r"(rank));
  return d;
}
__device__ __forceinline__ void st_async64(uint32_t a, uint32_t x, uint32_t y, uint32_t bar) {
  asm volatile("st.async.weak.shared::cluster.mbarrier::complete_tx::bytes.v2.b32 [%0], {%1,%2}, [%3];"
               ::"r"(a), "r"(x), "r"(y), "r"(bar) : "memory");
}
__device__ __forceinline__ void st_async64f(uint32_t a, float x, float y, uint32_t bar) {
  st_async64(a, __float_as_uint(x), __float_as_uint(y), bar);
}
__device__ __forceinline__ void bulk_s2s(uint32_t dst, uint32_t src, uint32_t bytes, uint32_t bar) {
  asm volatile("cp.async.bulk.shared::cluster.shared::cta.mbarrier::complete_tx::bytes [%0], [%1], %2, [%3];"
               ::"r"(dst), "r"(src), "r"(bytes), "r"(bar) : "memory");
}
__device__ __forceinline__ void tma_store_3d(const CUtensorMap* map, uint32_t src, int x, int y, int z) {
  asm volatile("cp.async.bulk.tensor.3d.global.shared::cta.bulk_group [%0, {%2, %3, %4}], [%1];"
               ::"l"(map), "r"(src), "r"(x), "r"(y), "r"(z) : "memory");
}
__device__ __forceinline__ void mbar_spin(uint32_t bar, uint32_t parity) {
  asm volatile("{\n.reg .pred p;\n.reg .b32 n;\nmov.u32 n, 0x100000;\nMW_L:\n"
               "mbarrier.try_wait.parity.shared::cta.b64 p, [%0], %1;\n@p bra.uni MW_D;\n"
               "add.s32 n, n, -1;\nsetp.ne.u32 p, n, 0;\n@p bra.uni MW_L;\nMW_D:\n}" ::"r"(bar), "r"(parity) : "memory");
}
__device__ __forceinline__ bool mbar_test(uint32_t bar, uint32_t parity) {
  uint32_t done;
  asm volatile("{\n.reg .pred p;\nmbarrier.test_wait.parity.shared::cta.b64 p, [%1], %2;\nselp.u32 %0, 1, 0, p;\n}"
               : "=r"(done) : "r"(bar), "r"(parity) : "memory");
  return done != 0;
}
__device__ __forceinline__ void mbar_arrive_remote(uint32_t bar) {
  asm volatile("mbarrier.arrive.shared::cluster.b64 _, [%0];" ::"r"(bar) : "memory");
}
__device__ __forceinline__ bool elect_one() {
  uint32_t r;
  asm volatile("{\n.reg .pred p;\nelect.sync _|p, 0xffffffff;\nselp.u32 %0, 1, 0, p;\n}" : "=r"(r));
  return r != 0;
}
__device__ __forceinline__ void st_async32(uint32_t a, uint32_t x, uint32_t bar) {
  asm volatile("st.async.weak.shared::cluster.mbarrier::complete_tx::bytes.b32 [%0], %1, [%2];" ::"r"(a), "r"(x), "r"(bar) : "memory");
}
#define named_bar_and(id, n, in, out) \
  asm volatile("{\n.reg .pred p, q;\nsetp.ne.u32 p, %1, 0;\nbar.red.and.pred q, %2, %3, p;\nselp.u32 %0, 1, 0, q;\n}" \
               : "=r"(out) : "r"(in), "n"(id), "n"(n) : "memory")
__device__ __forceinline__ void bulk_g2s(uint32_t dst, const void* src, uint32_t bytes, uint32_t bar) {
  asm volatile("cp.async.bulk.shared::cluster.global.mbarrier::complete_tx::bytes [%0], [%1], %2, [%3];"
               ::"r"(dst), "l"(src), "r"(bytes), "r"(bar) : "memory");
}
__device__ __forceinline__ void l2_prefetch(const void* p, uint32_t bytes) {
  asm volatile("cp.async.bulk.prefetch.L2.global [%0], %1;" ::"l"(p), "r"(bytes) : "memory");
}

__device__ __forceinline__ uint32_t clk32() { uint32_t c; asm volatile("mov.u32 %0, %%clock;" : "=r"(c)::"memory"); return c; }
__device__ __forceinline__ void spin_until(uint32_t t) { while ((int32_t)(clk32() - t) < 0) {} }
#define PIN(x) asm volatile("" : "+r"(x))
#define OPQ                                                                                     \
  int tid_o = tid;                                                                              \
  asm volatile("" : "+r"(tid_o));                                                               \
  const int lane = tid_o & 31, w = (tid_o >> 5) & 3, t7 = tid_o & 127, lg = lane >> 2,          \
            lq = lane & 3, mi = lane >> 3, mr = lane & 7;                                       \
  (void)w; (void)t7; (void)lg; (void)lq; (void)mi; (void)mr; (void)lane

#define SMAP                                                                                                          \
  const uint32_t SM0 = self + fk::SM0, WO = self + fk::WO, WS = self + fk::WS, XN = self + fk::XN, VX = self + fk::VX, \
                 QK = self + fk::QK, PT = self + fk::PT, SP = self + fk::SP, VM = self + fk::VM, OB = self + fk::OB,   \
                 RED = self + fk::RED, VX2 = self + fk::VX2, MEMB = self + fk::MEMB, B_XN = self + fk::B_XN, B_SM = self + fk::B_SM,       \
                 B_VM = self + fk::B_VM, B_VX = self + fk::B_VX, B_ST = self + fk::B_ST, B_PB = self + fk::B_PB,       \
                 B_W = self + fk::B_W, B_H2 = self + fk::B_H2, B_H1 = self + fk::B_H1, B_PF = self + fk::B_PF, B_WO = self + fk::B_WO, MASKS = self + fk::MASKS, PROBE = self + fk::PROBE;                             \
  (void)SM0; (void)WO; (void)WS; (void)XN; (void)VX; (void)QK; (void)PT; (void)SP; (void)VM; (void)OB; (void)RED; (void)VX2; \
  (void)MEMB; (void)B_XN; (void)B_SM; (void)B_VM; (void)B_VX; (void)B_ST; (void)B_PB; (void)B_W; (void)MASKS; (void)PROBE; (void)B_H2; (void)B_H1; (void)B_PF; (void)B_WO

struct FParams {
  CUtensorMap wq, wk, wv, wo, wo16, xn, xn12, o;
  CUtensorMap ta, tb, tx, tg, tout;
  const bf16 *mem0, *x, *w1;
  bf16 *xn_ptr, *xn2;
  int nprobe;
  char* xch;
};

__device__ __forceinline__ uint2 probe_pair(char* p, uint32_t val, uint32_t dummy, int n) {
  uint2 best = make_uint2(0x7FFFFFFF, 0x7FFFFFFF);
  st_pub128(p, val); st_pub128(p + 16, val); st_pub128(p + 4096, val); st_pub128(p + 4112, val);
#pragma unroll 1
  for (int r = 0; r < n; r++) {
    uint32_t v;
    const uint32_t c0 = clk32();
    asm volatile("atom.relaxed.gpu.global.exch.b32 %0, [%1], %2;" : "=r"(v) : "l"(p + (r & 1) * 4096), "r"(val) : "memory");
    asm volatile("{\n.reg .pred p;\nsetp.eq.u32 p, %0, 0x12345678;\n@p st.shared.u32 [%1], %0;\n}" ::"r"(v), "r"(dummy) : "memory");
    const uint32_t d = clk32() - c0;
    if (r & 1) best.y = min(best.y, d); else best.x = min(best.x, d);
  }
  return best;
}

typedef uint32_t WRegs[6][2][4][4];

constexpr uint32_t nth_chunks(uint32_t mask) {
  uint32_t t = 0;
  for (int c = 0, n = 0; c < 10; c++) if ((mask >> c) & 1) t |= c << (4 * n++);
  return t;
}
constexpr uint64_t chunk_pos(uint32_t mask) {
  uint64_t t = 0;
  for (int c = 0, a = 0, b = 0; c < 10; c++) t |= (uint64_t)(((mask >> c) & 1) ? a++ : b++) << (4 * c);
  return t;
}
template <bool ISV> struct Chunks {
  static constexpr uint32_t MASK = ISV ? SMV : SMQ, SMT = nth_chunks(MASK), RFT = nth_chunks(~MASK & 1023);
  static_assert(!(MASK & 1), "the first chunk initialises the accumulators");
  static __device__ __forceinline__ constexpr int rf(int wg, int i) { return wg ? 10 + i : (RFT >> (4 * i)) & 15; }
  static __device__ __forceinline__ constexpr int sm(int i) { return (SMT >> (4 * i)) & 15; }
  static constexpr uint64_t IDX = chunk_pos(MASK);
  static __device__ __forceinline__ constexpr int idx(int c) { return (IDX >> (4 * c)) & 15; }
};

template <bool ISV, int WG> struct ProjCfg {
  static constexpr int N0 = ISV ? NS0V : NS0, NS = WG ? 8 - N0 : N0, P0 = WG ? N0 : 0, NTA = WG ? NTA1 : NTA0;
};
__device__ __forceinline__ void load_pair(uint32_t (&t)[4][4], uint32_t wsa, int pp) {
#pragma unroll
  for (int f = 0; f < 4; f++) ldsm4t(t[f], wsa + ((pp >> 1) * 2 + (f & 1)) * 8192 + ((pp & 1) * 2 + (f >> 1)) * 2048);
}
template <bool ISV, int WG>
__device__ __forceinline__ void proj_mem(const WRegs& wr, uint32_t (&ta)[ProjCfg<ISV, WG>::NTA][4][4], uint32_t wsa, uint32_t mba,
                                         float (&a0)[4], float (&a1)[4]) {
  constexpr int NS = ProjCfg<ISV, WG>::NS, P0 = ProjCfg<ISV, WG>::P0, NTA = ProjCfg<ISV, WG>::NTA, NP = 12 + NS;
  float acc[4][4];
  auto spos = [](int j) { return j < NTA ? j : j + (j - NTA + 1) * 12 / (NS - NTA > 0 ? NS - NTA : 1); };
  auto which = [&](int p) { int r = -1; for (int j = 0; j < NS; j++) if (spos(j) == p) r = j; return r; };
  auto nsm_before = [&](int p) { int n = 0; for (int j = 0; j < NS; j++) if (spos(j) < p) n++; return n; };
#pragma unroll
  for (int p = 0; p < NP; p++) {
    const int j = which(p), r = j >= 0 ? 0 : p - nsm_before(p);
    uint32_t bp[4], tl[4][4];
    ldsm4(bp, mba + (j >= 0 ? Chunks<ISV>::sm((P0 + (j >= 0 ? j : 0)) >> 1) * 1024 + ((P0 + j) & 1) * 512 : Chunks<ISV>::rf(WG, r >> 1) * 1024 + (r & 1) * 512));
    if (j >= NTA) load_pair(tl, wsa, P0 + j);
#pragma unroll
    for (int u = 0; u < 2; u++)
#pragma unroll
      for (int T = 0; T < 2; T++) {
        const uint32_t* a = j >= NTA ? tl[u * 2 + T] : j >= 0 ? ta[j >= 0 ? j % NTA : 0][u * 2 + T] : wr[r >> 1][T][(r & 1) * 2 + u];
        if (p == 0) mma16816z(acc[u * 2 + T], a, bp[2 * u], bp[2 * u + 1]);
        else mma16816(acc[u * 2 + T], a, bp[2 * u], bp[2 * u + 1]);
      }
  }
#pragma unroll
  for (int i = 0; i < 4; i++) { a0[i] = acc[0][i] + acc[2][i]; a1[i] = acc[1][i] + acc[3][i]; }
}
template <bool ISV, int WG, int J0, int J1>
__device__ __forceinline__ void proj_mem_prefetch(uint32_t (&ta)[ProjCfg<ISV, WG>::NTA][4][4], uint32_t wsa) {
#pragma unroll
  for (int j = J0; j < J1; j++) load_pair(ta[j], wsa, ProjCfg<ISV, WG>::P0 + j);
}

template <bool ISV, int WG>
__device__ __forceinline__ void proj_finish(const float (&a0)[4], const float (&a1)[4], uint32_t peer0, uint32_t peer1, uint32_t self, int tid, int warp,
                                            uint32_t (&vmo)[4]) {
  using namespace fk;
  SMAP;
  OPQ;
  if (!ISV) {
    stsm4(PT + mr * 16 + ((mi >> 1) ? WG * 1024 + w * 256 + (mi & 1) * 128 : 2048 + w * 512 + (mi & 1) * 256 + WG * 128),
          pack_bf16(a0[0], a0[1]), pack_bf16(a0[2], a0[3]), pack_bf16(a1[0], a1[1]), pack_bf16(a1[2], a1[3]));
    named_bar_sync(NB_C, 256);
  } else {
    if (WG == 0) sts128f(RED + t7 * 16, a1[0], a1[1], a1[2], a1[3]);
    else sts128f(RED + 2048 + t7 * 16, a0[0], a0[1], a0[2], a0[3]);
    if (WG == 1) { lds64(vmo, VM + t7 * 8); lds64(vmo + 2, VM + 1024 + t7 * 8); }
    named_bar_sync(NB_C, 256);
    const float4 p = lds128f(RED + (1 - WG) * 2048 + t7 * 16);
    const float* k = WG == 0 ? a0 : a1;
    const uint32_t v0 = pack_bf16(k[0] + p.x, k[1] + p.y), v1 = pack_bf16(k[2] + p.z, k[3] + p.w);
    const uint32_t off = VM + WG * 1024 + t7 * 8;
    if (VM_BULK) {
      sts64(off, v0, v1);
      fence_proxy_async_smem();
      __syncwarp();
      const uint32_t a = VM + WG * 1024 + warp * 256;
      if (elect_one()) {
        bulk_s2s(peer0 + a, a, 256, peer0 + B_VM);
        bulk_s2s(peer1 + a, a, 256, peer1 + B_VM);
        mbar_arrive(B_VM);
      }
    } else {
      st_async64(peer0 + off, v0, v1, peer0 + B_VM);
      st_async64(peer1 + off, v0, v1, peer1 + B_VM);
      sts64(off, v0, v1);
      __syncwarp();
      if (lane == 0) mbar_arrive(B_VM);
    }
  }
}

__device__ __forceinline__ void send_scores(float s0, float s1, uint32_t off, uint32_t peer0, uint32_t peer1, uint32_t bar, int lane) {
  if (SPACK) {
    const uint32_t v = pack_bf16(s0, s1);
    st_async32(peer0 + off, v, peer0 + bar);
    st_async32(peer1 + off, v, peer1 + bar);
    sts32(off, v);
  } else {
    st_async64f(peer0 + off, s0, s1, peer0 + bar);
    st_async64f(peer1 + off, s0, s1, peer1 + bar);
    sts64f(off, s0, s1);
  }
  __syncwarp();
  if (lane == 0) mbar_arrive(bar);
}

template <int NT, bool NARROW>
__device__ __forceinline__ uint32_t wo_addr(int f, uint32_t woa, uint32_t wob) {
  return (NARROW && f % NT == 2) ? wob + (f / NT) * 512 : woa + (f % NT) * 32768 + (f / NT) * 2048;
}
template <int NT, bool NARROW, int PF>
__device__ __forceinline__ void wo_phase(uint32_t (&wf)[PF][4], uint32_t woa, uint32_t wob, uint32_t oba, char* h1p, uint32_t sel, uint32_t tag) {
  float c[NT][4];
  uint32_t of[2][4];
  ldsm4t(of[0], oba);
#pragma unroll
  for (int k = 0; k < 8; k++) {
    if ((k & 1) == 0 && k + 2 < 8) ldsm4t(of[((k >> 1) + 1) & 1], oba + ((k >> 1) + 1) * 512);
#pragma unroll
    for (int i = 0; i < NT; i++) {
      const int f = k * NT + i;
      const uint32_t b0 = of[(k >> 1) & 1][2 * (k & 1)], b1 = of[(k >> 1) & 1][2 * (k & 1) + 1];
      if (k == 0) mma16816z(c[i], wf[f % PF], b0, b1); else mma16816(c[i], wf[f % PF], b0, b1);
      if (f + PF < 8 * NT) ldsm4t(wf[f % PF], wo_addr<NT, NARROW>(f + PF, woa, wob));
    }
  }
#pragma unroll
  for (int i = 0; i < NT; i++)
  {
    char* p = h1p + i * (8 * 32768) + ((sel >> (2 * i)) & 3) * 2048;
    const uint32_t tm = (sel >> 10) & 1;
    st_pub32(p, (pack_bf16(c[i][0], c[i][1]) & ~tm) | (tag & tm));
    st_pub32(p + 1024, (pack_bf16(c[i][2], c[i][3]) & ~tm) | (tag & tm));
  }
}
template <int NT, bool NARROW, int F0, int F1, int PF>
__device__ __forceinline__ void wo_prefetch(uint32_t (&wf)[PF][4], uint32_t woa, uint32_t wob) {
#pragma unroll
  for (int f = F0; f < F1; f++) ldsm4t(wf[f], wo_addr<NT, NARROW>(f, woa, wob));
}

template <bool ISV> __device__ __forceinline__ uint32_t tok_addr(uint32_t base, int tid) {
  OPQ;
  return ISV ? base + w * 2048 + (mi & 1) * 1024 + (mi >> 1) * 128 + mr * 16 : base + (mi >> 1) * 1024 + w * 256 + (mi & 1) * 128 + mr * 16;
}
template <bool ISV> __device__ __forceinline__ constexpr uint32_t tok_off(int T, int i) { return ISV ? T * 512 + i * 256 : T * 4096 + i * 2048; }
template <bool ISV, int T, bool ADD>
__device__ __forceinline__ void tok_store(const float (&x)[16], uint32_t a, const uint32_t (&p)[2][4]) {
#pragma unroll
  for (int i = 0; i < 2; i++) {
    uint32_t r[4];
#pragma unroll
    for (int k = 0; k < 4; k++)
      r[k] = !ADD ? pack_bf16(x[8 * i + 2 * k], x[8 * i + 2 * k + 1])
           : PADD ? add_bf16x2(pack_bf16(x[8 * i + 2 * k], x[8 * i + 2 * k + 1]), p[i][k])
                  : pack_bf16(x[8 * i + 2 * k] + bf_lo(p[i][k]), x[8 * i + 2 * k + 1] + bf_hi(p[i][k]));
    stsm4(a + tok_off<ISV>(T, i), r[0], r[1], r[2], r[3]);
  }
}

__device__ __forceinline__ void load_xn(const FParams& P, int seg, uint32_t self) {
  SMAP;
  mbar_expect_tx(B_XN, 49152);
  tma_load_3d(XN, &P.xn12, 0, seg * 32, 0, B_XN);
}

__device__ __forceinline__ uint64_t xn_desc(int slot, int u) { return make_desc(fk::XN + slot * 4096 + u * 32, 16, 1024); }

template <bool ISV>
__device__ __forceinline__ void f_wg0(const FParams& P, const WRegs& wr, const int h, const int rank, const uint32_t hw, int tid) {
  using namespace fk;
  const uint32_t self = mapa(0, (hw >> (2 * rank)) & 3), peer0 = mapa(0, (hw >> (ISV ? 0 : 2 * (rank ^ 1))) & 3) - self,
                 peer1 = mapa(0, (hw >> (ISV ? 2 : 4)) & 3) - self;
  SMAP;
  const int tile0 = rank * 22;
  const int warp = __shfl_sync(0xffffffffu, threadIdx.x >> 5, 0);
  const bool three = !ISV && warp < 2;
  uint32_t h2ph = 1;
  tid ^= 0x5500;
#pragma unroll 1
  for (int s = -1;;) {
    uint32_t ta[ProjCfg<ISV, 0>::NTA][4][4], wsa, mba;
    auto h2_src = [&]() { return P.xch + H1_BYTES + ((s & 1) * 4 + warp) * 8192 + ((tid >> (16 + (s & 1))) & 1) * 4096; };
    {
      const uint32_t ph = (s + 1) & 1;
      float x0[16], x1[16];
      uint32_t t_pub = 0;
      if (!XN_EARLY || s < 0) mbar_spin(B_XN, ph);
      wg_fence();
#pragma unroll
      for (int c = 0; c < 10; c++) {
        if (c == 9) named_bar_arrive(NB_ST, 256);
#pragma unroll
        for (int u = 0; u < 4; u++) {
          const int ci = Chunks<ISV>::idx(c);
          if ((Chunks<ISV>::MASK >> c) & 1) {
            wgmma_ss_n32_ta(x0, make_desc(fk::WS + ci * 16384 + u * 2048, 8192, 1024), xn_desc(c, u), 1);
            wgmma_ss_n32_ta(x1, make_desc(fk::WS + ci * 16384 + 8192 + u * 2048, 8192, 1024), xn_desc(c, u), 1);
          } else {
            wgmma_rs_n32(x0, wr[ci][0][u], xn_desc(c, u), (c | u) != 0);
            wgmma_rs_n32(x1, wr[ci][1][u], xn_desc(c, u), (c | u) != 0);
          }
          if (((ISV ? PACEV : PACEQ) >> c) & 1) { wg_commit(); wg_wait<2>(); wg_fence(); }
          if (c == 4 && u == 1) { wg_commit(); wg_wait<1>(); named_bar_arrive(NB_XE, 160); wg_fence(); }
        }
        if (c == 0) { t_pub = clk32() - 60; PROF(0, 8); }
        if (c == 3) wg_commit();
      }
      wg_commit();
      wg_wait<0>();
      PROF(0, 10);
      const uint32_t tb = ISV ? (ph ? VX2 : VX) : QK;
      auto h2_issue = [&]() {
        if (s >= 0) {
          spin_until(t_pub + D_H2);
          PROF(0, 13);
          if (elect_one()) { mbar_expect_tx(B_H2 + 8 * warp, 4096); bulk_g2s(MEMB + warp * 4096, h2_src(), 4096, B_H2 + 8 * warp); }
        }
      };
      if (ISV || H2_AT == 0) h2_issue();
      named_bar_sync(NB_CF, ISV ? 160 : 256);
      const uint32_t none[2][4] = {}, tka = tok_addr<ISV>(tb, tid);
      tok_store<ISV, 0, false>(x0, tka, none);
      if (!ISV && H2_AT == 1) h2_issue();
      tok_store<ISV, 1, false>(x1, tka, none);
      if (!ISV && H2_AT == 2) h2_issue();
      named_bar_arrive(NB_DU, 256);
    }
    {
      OPQ;
      wsa = WS + ((mi >> 1) * 8 + mr) * 128 + (((2 * w + (mi & 1)) ^ mr) << 4);
      mba = MEMB + lane * 16;
      PIN(wsa); PIN(mba);
      if (s >= 0) {
        const char* src = h2_src();
        const uint32_t chk = MEMB + w * 4096 + lane * 32 + lg * 4, bar = B_H2 + 8 * warp;
        PROF(0, 11);
        proj_mem_prefetch<ISV, 0, 0, NPRE0>(ta, wsa);
#pragma unroll 1
        for (int tries = 0; tries < POLL_TRIES; tries++) {
          mbar_spin(bar, h2ph);
          h2ph ^= 1;
          const uint32_t mx = max(max(lds32(chk), lds32(chk + 1024)), max(lds32(chk + 2048), lds32(chk + 3072)));
          if (__all_sync(0xffffffffu, mx != EMPTY)) break;
          RETRY(1);
          if (elect_one()) { mbar_expect_tx(bar, 4096); bulk_g2s(MEMB + warp * 4096, src, 4096, bar); }
        }
      } else {
        const bf16* m0 = P.mem0 + mr * cfg::D + w * 256 + mi * 8;
#pragma unroll
        for (int i = 0; i < 8; i++) {
          const uint4 v = *reinterpret_cast<const uint4*>(m0 + i * 32);
          sts128(mba + w * 4096 + i * 512, v.x, v.y, v.z, v.w);
        }
        proj_mem_prefetch<ISV, 0, 0, NPRE0>(ta, wsa);
        mbar_wait(B_WO, 0);
      }
      PROF(0, 12);
      named_bar_arrive(NB_M1, 256);
      proj_mem_prefetch<ISV, 0, NPRE0, NTA0>(ta, wsa);
      named_bar_sync(NB_M0, 128);
    }
    s++;
    tid ^= 0x5500;
    {
      PROF(0, 1);
      float a0[4], a1[4];
      proj_mem<ISV, 0>(wr, ta, wsa, mba, a0, a1);
      PROF(0, 2);
      uint32_t unused[4];
      proj_finish<ISV, 0>(a0, a1, peer0, peer1, self, tid, warp, unused);
      PROF(0, 3);
      if (s + 1 == cfg::NSEG) break;
      uint32_t wf[PF0][4], woa, wob;
      bool xn_ok;
      {
        OPQ;
        if (!ISV) {
          uint32_t qf[4][4], kf[2][4];
          const uint32_t qa = PT + 2048 + lane * 16, ka = QK + 4096 + w * 1024 + lane * 16;
          ldsm4t(qf[0], qa); ldsm4t(kf[0], ka); ldsm4t(qf[1], qa + 512);
          ldsm4t(qf[2], qa + 1024); ldsm4t(kf[1], ka + 512); ldsm4t(qf[3], qa + 1536);
          float c0[4], c1[4];
          mma16816z(c0, qf[0], kf[0][0], kf[0][1]);
          mma16816z(c1, qf[1], kf[0][2], kf[0][3]);
          mma16816(c0, qf[2], kf[1][0], kf[1][1]);
          mma16816(c1, qf[3], kf[1][2], kf[1][3]);
          const float s0 = (c0[0] + c0[2]) + (c1[0] + c1[2]), s1 = (c0[1] + c0[3]) + (c1[1] + c1[3]);
          send_scores(s0, s1, SP + rank * SP_SRC + t7 * SPW, peer0, peer1, B_SM, lane);
        }
        PROF(0, 4);
        woa = WO + 16384 + ((mi >> 1) * 8 + mr) * 128 + (((2 * w + (mi & 1)) ^ mr) << 4);
        wob = WO + 81920 + w * 4096 + ((mi >> 1) * 8 + mr) * 32 + (((mi & 1) ^ (mr >> 2)) << 4);
        uint32_t vf[2][2][4], vm[2][2];
        if (!ISV) mbar_spin(B_VX, s & 1);
        PROF(0, 14);
#pragma unroll
        for (int T = 0; T < 2; T++)
#pragma unroll
          for (int kk = 0; kk < 2; kk++) ldsm4(vf[T][kk], ((ISV && (s & 1)) ? VX2 : VX) + w * 2048 + (mi & 1) * 1024 + (mi >> 1) * 128 + mr * 16 + T * 512 + kk * 256);
        if (three) wo_prefetch<3, true, 0, PF0A>(wf, woa, wob); else wo_prefetch<2, false, 0, PF0A>(wf, woa, wob);
        uint32_t spa = SP + lane * SPW, vma = VM + t7 * 8, oa = OB + (mi >> 1) * 1024 + w * 256 + (mi & 1) * 128 + mr * 16;
        PIN(spa); PIN(vma); PIN(oa);
        mbar_spin(B_SM, s & 1);
        PROF(0, 5);
        float sc[10];
#pragma unroll
        for (int j = 0; j < 5; j++) {
          if (SPACK) {
            const uint32_t x = lds32(spa + j * 128), y = lds32(spa + SP_SRC + j * 128);
            sc[2 * j] = bf_lo(x) + bf_lo(y); sc[2 * j + 1] = bf_hi(x) + bf_hi(y);
          } else {
            const float2 x = lds64f(spa + j * 256), y = lds64f(spa + SP_SRC + j * 256);
            sc[2 * j] = x.x + y.x; sc[2 * j + 1] = x.y + y.y;
          }
        }
        float m = fmaxf(fmaxf(fmaxf(sc[0], sc[1]), fmaxf(sc[2], sc[3])), fmaxf(fmaxf(sc[4], sc[5]), fmaxf(sc[6], sc[7])));
        m = fmaxf(m, fmaxf(sc[8], sc[9]));
        const bool vm_ok = mbar_test(B_VM, s & 1);
        m = fmaxf(m, __shfl_xor_sync(0xffffffffu, m, 1));
        m = fmaxf(m, __shfl_xor_sync(0xffffffffu, m, 2));
        PROF(0, 15);
        if (!vm_ok) mbar_spin(B_VM, s & 1);
        PROF(0, 0);
        lds64(vm[0], vma); lds64(vm[1], vma + 1024);
        if (ISV ? GATE_MX : GATE_Q) named_bar_arrive(NB_MX, 256);
        const float cs = 0.08838834764831845f * 1.4426950408889634f;
        const float mc = -m * cs;
        uint32_t pb[5];
#pragma unroll
        for (int j = 0; j < 5; j++) pb[j] = pack_bf16(ex2_approx(fmaf(sc[2 * j], cs, mc)), ex2_approx(fmaf(sc[2 * j + 1], cs, mc)));
        PROF(0, 6);
        float o0[4], o1[4], rs[4];
        const uint32_t ones[4] = {0x3F803F80u, 0x3F803F80u, 0x3F803F80u, 0x3F803F80u};
        mma16816z(rs, ones, pb[0], pb[1]);
        mma16816z(o0, vf[0][0], pb[0], pb[1]);
        mma16816z(o1, vf[1][0], pb[0], pb[1]);
        mma16816(rs, ones, pb[2], pb[3]);
        mma16816(o0, vf[0][1], pb[2], pb[3]);
        mma16816(o1, vf[1][1], pb[2], pb[3]);
        mma1688(rs, ones[0], ones[0], pb[4]);
        mma1688(o0, vm[0][0], vm[0][1], pb[4]);
        mma1688(o1, vm[1][0], vm[1][1], pb[4]);
        const float i0 = rcp_approx(rs[0]), i1 = rcp_approx(rs[1]);
        stsm4(oa, pack_bf16(o0[0] * i0, o0[1] * i1), pack_bf16(o0[2] * i0, o0[3] * i1),
              pack_bf16(o1[0] * i0, o1[1] * i1), pack_bf16(o1[2] * i0, o1[3] * i1));
      }
      {
        OPQ;
        named_bar_arrive(NB_O, 256);
        if (three) wo_prefetch<3, true, PF0A, PF0>(wf, woa, wob); else wo_prefetch<2, false, PF0A, PF0>(wf, woa, wob);
        xn_ok = mbar_test(B_XN, (s + 1) & 1);
        char* h1p = P.xch + (tile0 + 4 + w) * 32768 + (h >> 3) * 8192 + (h & 7) * 128 + (((2 * lq + (lg & 1)) ^ (h & 7)) << 4) + (lg >> 1) * 4;
        uint32_t oba = OB + lane * 16;
        PIN(oba);
        PROF(0, 7);
        named_bar_sync(NB_O0, 128);
        const uint32_t tag = ((s >> 1) & 1) ^ 1;
        if (three) wo_phase<3, true>(wf, woa, wob, oba, h1p, tid >> 8, tag); else wo_phase<2, false>(wf, woa, wob, oba, h1p, tid >> 8, tag);
        PROF(0, 9);
        if (XN_EARLY && !xn_ok) mbar_spin(B_XN, (s + 1) & 1);
        named_bar_sync(NB_HD, 256);
      }
    }
  }
}

template <bool ISV>
__device__ __forceinline__ void f_wg1(const FParams& P, const WRegs& wr, const int h, const int rank, const uint32_t hw, int tid) {
  using namespace fk;
  const uint32_t self = mapa(0, (hw >> (2 * rank)) & 3), peer0 = mapa(0, (hw >> (ISV ? 0 : 2 * (rank ^ 1))) & 3) - self,
                 peer1 = mapa(0, (hw >> (ISV ? 2 : 4)) & 3) - self;
  SMAP;
  const int tile0 = rank * 22;
  const int warp = __shfl_sync(0xffffffffu, (threadIdx.x >> 5) & 3, 0);
  uint32_t h1ph = 0;
  auto o_done = [&](int mb) {
    tma_store_wait_all();
    asm volatile("fence.proxy.async.global;" ::: "memory");
    asm volatile("red.relaxed.gpu.global.add.u32 [%0], 1;" ::"l"(&g_oflag[mb]) : "memory");
  };
  uint32_t vmo[4] = {0, 0, 0, 0};
  if (ISV) {
    OPQ;
    sts32(PT + (t7 >> 2) * 128 + ((5 ^ lg) << 4) + lq * 4, 0);
    sts32(PT + (t7 >> 2) * 128 + ((6 ^ lg) << 4) + lq * 4, 0);
  }
  tid ^= 0x5500;
#pragma unroll 1
  for (int s = -1;;) {
    uint32_t ta[ProjCfg<ISV, 1>::NTA][4][4], wsa, mba;
    if (s + 1 < cfg::NSEG) mbar_spin(B_XN, (s + 1) & 1);
    const uint32_t t_pub = clk32();
    auto refill = [&]() {
      if (warp == 3) {
        named_bar_sync(NB_XE, 160);
        if (elect_one()) {
          mbar_expect_tx(B_XN + 8, 16384);
          tma_load_3d(XN, &P.xn, 0, (s + 1) * 32, 12, B_XN + 8);
        }
      }
    };
    auto arm = [&]() {
      if ((tid & 255) == 160) {
        if (s == 1) st_pub32(&g_mask[3 * h + rank], 0);
        if (s + 2 < cfg::NSEG) { mbar_expect_tx(B_SM, ISV ? 2 * SP_SRC : SP_SRC); if (!ISV) mbar_expect_tx(B_VX, 8192); }
        if (!ISV && s + 1 < cfg::NSEG) mbar_expect_tx(B_VM, 2048);
        if (ISV && s >= 1 && s < cfg::NSEG) mbar_expect_tx(B_ST, 7168);
      }
      if (ISV && s < cfg::NSEG && (tid & 254) == 192) mbar_arrive_remote(((tid & 1) ? peer1 : peer0) + B_ST);
      __syncwarp();
    };
    if (ISV) {
      if (s >= 0) arm();
      if (s >= 1) {
        OPQ;
        if (warp == 0 && (s & 3) == 1 && s > 1) { if (elect_one()) o_done((s - 2) >> 2); }
        const uint32_t vb = (s & 1) ? VX : VX2;
        float x0[16], x1[16];
        wg_fence();
        wgmma_rs_n32(x0, vmo, make_desc(fk::PT + 64, 16, 1024), 0);
        wgmma_rs_n32(x1, vmo, make_desc(fk::PT + 96, 16, 1024), 0);
#pragma unroll
        for (int kk = 0; kk < 2; kk++) {
          wgmma_ss_n32(x0, make_desc0(vb + kk * 256, 128, 1024), make_desc(fk::PT + kk * 32, 16, 1024), 1);
          wgmma_ss_n32(x1, make_desc0(vb + 512 + kk * 256, 128, 1024), make_desc(fk::PT + kk * 32, 16, 1024), 1);
        }
        wg_commit();
        wg_wait<0>();
        named_bar_sync(NB_W1, 128);
        PROF(1, 4);
        const uint32_t stg = vb + (8 * (mi >> 1) + mr) * 128 + (((2 * w + (mi & 1)) ^ mr) << 4);
#pragma unroll
        for (int T = 0; T < 2; T++) {
          const float* x = T ? x1 : x0;
#pragma unroll
          for (int jj = 0; jj < 4; jj += 2)
            stsm4t(stg + T * 4096 + jj * 1024, pack_bf16(x[4 * jj], x[4 * jj + 1]), pack_bf16(x[4 * jj + 2], x[4 * jj + 3]),
                   pack_bf16(x[4 * jj + 4], x[4 * jj + 5]), pack_bf16(x[4 * jj + 6], x[4 * jj + 7]));
        }
        fence_proxy_async_smem();
        named_bar_sync(NB_W1, 128);
        PROF(1, 10);
        if (warp == 0) {
          if (elect_one()) {
            tma_store_3d(&P.o, vb, 0, (s - 1) * 32, 2 * h);
            tma_store_commit();
          }
          __syncwarp();
        }
        if (s == cfg::NSEG) break;
      }
      if (s + 1 < cfg::NSEG) refill();
      PROF(1, 11);
    } else if (s < 0) {
      named_bar_arrive(NB_CF, 256);
      refill();
    } else {
      float x[24];
      wg_fence();
#pragma unroll
      for (int k = 0; k < 4; k++) wgmma_ss_n48_tt(x, make_desc0(fk::QK + k * 256, 128, 1024), make_desc0(fk::QK + 4096 + k * 256, 128, 1024), k != 0);
      wg_commit();
      arm();
      auto send_tok = [&]() {
        if (warp < 2) {
          OPQ;
          const uint32_t d0 = peer1 + QK + rank * 3584 + lane * 8 + w * 1280, d1 = d0 + 512 + w * 512, bar = peer1 + B_ST;
          mbar_spin(B_ST, s & 1);
          const float NEG = -500000000.0f / 0.08838834764831845f;
          const bool m0 = 2 * lq > lg, m1 = 2 * lq + 1 > lg;
          st_async64f(d0, x[16] + x[20], x[17] + x[21], bar);
          st_async64f(d1, x[18] + x[22], x[19] + x[23], bar);
          st_async64f(d1 + 256, x[2], x[3], bar);
          if (warp == 0) {
            st_async64f(d0 + 256, m0 ? NEG : x[0], m1 ? NEG : x[1], bar);
            st_async64f(d1 + 512, m0 ? NEG : x[6], m1 ? NEG : x[7], bar);
          } else {
            st_async64f(d0 + 256, x[0], x[1], bar);
            st_async64f(d1 + 512, x[6], x[7], bar);
            st_async64f(d0 + 512, x[4], x[5], bar);
            st_async64f(d0 + 768, m0 ? NEG : x[8], m1 ? NEG : x[9], bar);
            st_async64f(d1 + 768, x[10], x[11], bar);
            st_async64f(d1 + 1024, m0 ? NEG : x[14], m1 ? NEG : x[15], bar);
          }
        }
        PROF(1, 4);
      };
      const bool fin = s + 1 == cfg::NSEG;
      OPQ;
      const int j = 2 * h + rank;
      const char* src = P.xch + j * 32768 + warp * 8192 + __shfl_sync(0xffffffffu, (tid >> 14) & 3, 0) * 2048;
      char* dst = P.xch + H1_BYTES + (j >> 4) * 8192 + (lq >> 1) * 4096 + (j & 15) * 256 + (lq & 1) * 128 + (2 * w + (lg & 1)) * 16 + (lg >> 1) * 4;
      const uint32_t chk = VX + mi * 2048 + mr * 128 + (w ^ (mr >> 1)) * 32 + ((lane & 1) + 2 * mi) * 4;
      const uint32_t tmask = (s >> 1) & 1;
      if (!fin) {
        spin_until(t_pub + D_H1);
        if (elect_one()) { mbar_expect_tx(B_H1, 2048); bulk_g2s(VX + warp * 2048, src, 2048, B_H1); }
      }
      __syncwarp();
      wg_wait<0>();
      PROF(1, 6);
      send_tok();
      if (fin) { mbar_spin(B_VM, s & 1); break; }
      named_bar_arrive(NB_CF, 256);
      if (REFILL_EARLY) refill();
#pragma unroll 1
      for (int tries = 0; tries < POLL_TRIES; tries++) {
        float d0[4], d1[4], d2[4], d3[4];
        mbar_spin(B_H1, h1ph);
        h1ph ^= 1;
        PROF(1, 10);
        const uint32_t t0 = lds32(chk), t1 = lds32(chk + 1024);
        wg_fence();
        const uint64_t ones = (uint64_t)(fk::ONES >> 4);
        wgmma_ss_n8_ta(d0, make_desc(fk::VX, 8192, 2048), ones, 0);
        wgmma_ss_n8_ta(d1, make_desc(fk::VX + 1024, 8192, 2048), ones, 0);
        wgmma_ss_n8_ta(d2, make_desc(fk::VX + 4096, 8192, 2048), ones, 0);
        wgmma_ss_n8_ta(d3, make_desc(fk::VX + 5120, 8192, 2048), ones, 0);
        wg_commit();
        uint32_t tt;
        asm volatile("lop3.b32 %0, %1, %2, %3, 0x42;" : "=r"(tt) : "r"(t0), "r"(t1), "r"(tmask) : "memory");
        uint32_t ok = __all_sync(0xffffffffu, tt & 1);
        wg_wait<0>();
        if (ok) {
          st_pub32(dst + (s & 1) * 32768, (lq & 1) ? pack_bf16(d1[0] + d3[0], d1[2] + d3[2]) : pack_bf16(d0[0] + d2[0], d0[2] + d2[2]));
          PROF(1, 12);
          st_pub32(dst + ((s & 1) ^ 1) * 32768, EMPTY);
        }
        named_bar_and(NB_W1, 128, ok, ok);
        if (ok) break;
        RETRY(0);
        if (elect_one()) { mbar_expect_tx(B_H1, 2048); bulk_g2s(VX + warp * 2048, src, 2048, B_H1); }
      }
      if ((tid & 255) == 192) mbar_arrive_remote(peer1 + B_PF);
      __syncwarp();
      if (!REFILL_EARLY) refill();
      PROF(1, 11);
    }
    if (!ISV || s + 1 < cfg::NSEG) {
      const uint32_t ph = (s + 1) & 1;
      float x0[16], x1[16];
      named_bar_sync(NB_ST, 256);
      wg_fence();
#pragma unroll
      for (int c = 0; c < 6; c++) {
        if (c == 2) {
          mbar_spin(B_XN + 8, ph);
          if (ISV && s >= 0) mbar_spin(B_PF, s & 1);
          wg_fence();
        }
        if (ISV && c == CF_AT) {
          if (warp == 0) {
            if (elect_one()) tma_store_wait_read();
            __syncwarp();
            named_bar_arrive(NB_CF, 160);
          }
          wg_fence();
        }
#pragma unroll
        for (int u = 0; u < 4; u++) {
          wgmma_rs_n32(x0, wr[c][0][u], xn_desc(c < 2 ? 10 + c : c - 2, u), (c | u) != 0);
          wgmma_rs_n32(x1, wr[c][1][u], xn_desc(c < 2 ? 10 + c : c - 2, u), (c | u) != 0);
        }
      }
      wg_commit();
      OPQ;
      const uint32_t tb = ISV ? (ph ? VX2 : VX) : QK, tka = tok_addr<ISV>(tb, tid);
      uint32_t p0[2][4], p1[2][4];
      named_bar_sync(NB_DU, 256);
      ldsm4(p1[0], tka + tok_off<ISV>(1, 0)); ldsm4(p1[1], tka + tok_off<ISV>(1, 1));
      ldsm4(p0[0], tka + tok_off<ISV>(0, 0)); ldsm4(p0[1], tka + tok_off<ISV>(0, 1));
      wg_wait<0>();
      PROF(1, 13);
      tok_store<ISV, 1, true>(x1, tka, p1);
      tok_store<ISV, 0, true>(x0, tka, p0);
      if (ISV && s + 2 < cfg::NSEG) {
        fence_proxy_async_smem();
        __syncwarp();
        if (elect_one()) {
          bulk_s2s(peer0 + VX + warp * 2048, tb + warp * 2048, 2048, peer0 + B_VX);
          bulk_s2s(peer1 + VX + warp * 2048, tb + warp * 2048, 2048, peer1 + B_VX);
        }
      }
      wsa = WS + ((mi >> 1) * 8 + mr) * 128 + (((2 * w + (mi & 1)) ^ mr) << 4);
      mba = MEMB + lane * 16;
      PIN(wsa); PIN(mba);
      proj_mem_prefetch<ISV, 1, 0, NTA1>(ta, wsa);
      PROF(1, 14);
      if (s < 0) mbar_wait(B_WO, 0);
      named_bar_sync(NB_M1, 256);
      s++;
      PROF(1, 1);
      float a0[4], a1[4];
      proj_mem<ISV, 1>(wr, ta, wsa, mba, a0, a1);
      PROF(1, 2);
      proj_finish<ISV, 1>(a0, a1, peer0, peer1, self, tid, warp, vmo);
      PROF(1, 3);
    } else {
      OPQ;
      mbar_spin(B_VM, s & 1);
      lds64(vmo, VM + t7 * 8); lds64(vmo + 2, VM + 1024 + t7 * 8);
      s++;
    }
    tid ^= 0x5500;
    const bool last = s + 1 >= cfg::NSEG;
    constexpr int PFW = ISV ? PF1V : PF1;
    uint32_t wf[PFW][4], woa;
    if (ISV) {
      OPQ;
      woa = WO + ((mi >> 1) * 8 + mr) * 128 + (((2 * w + (mi & 1)) ^ mr) << 4);
      if (s >= 1) {
        const uint32_t sa = QK + ((w * (w + 3)) >> 1) * 256 + lane * 8;
        mbar_spin(B_ST, (s - 1) & 1);
        float sc[10];
        {
          const float NEG = -1000000000.0f / 0.08838834764831845f;
          float2 x[5], y[5];
#pragma unroll
          for (int b = 0; b < 5; b++) {
            x[b] = b < 2 ? lds64f(sa + b * 256) : lds64f_if(sa + b * 256, b <= w + 1, NEG);
            y[b] = b < 2 ? lds64f(sa + 3584 + b * 256) : lds64f_if(sa + 3584 + b * 256, b <= w + 1, 0.f);
          }
          wo_prefetch<3, false, 0, PF1A>(wf, woa, 0);
#pragma unroll
          for (int b = 0; b < 5; b++) { sc[2 * b] = x[b].x + y[b].x; sc[2 * b + 1] = x[b].y + y[b].y; }
        }
        float m = fmaxf(fmaxf(fmaxf(sc[0], sc[1]), fmaxf(sc[2], sc[3])), fmaxf(fmaxf(sc[4], sc[5]), fmaxf(sc[6], sc[7])));
        m = fmaxf(m, fmaxf(sc[8], sc[9]));
        m = fmaxf(m, __shfl_xor_sync(0xffffffffu, m, 1));
        m = fmaxf(m, __shfl_xor_sync(0xffffffffu, m, 2));
        const float cs = 0.08838834764831845f * 1.4426950408889634f;
#pragma unroll
        for (int i = 0; i < 10; i++) sc[i] = ex2_approx((sc[i] - m) * cs);
        float sum = ((sc[0] + sc[1]) + (sc[2] + sc[3])) + ((sc[4] + sc[5]) + (sc[6] + sc[7])) + (sc[8] + sc[9]);
        sum += __shfl_xor_sync(0xffffffffu, sum, 1);
        sum += __shfl_xor_sync(0xffffffffu, sum, 2);
        const float inv = rcp_approx(sum);
        const uint32_t pa = PT + (w * 8 + mr) * 128, pm = pack_bf16(sc[0] * inv, sc[1] * inv);
        stsm4(pa + ((mi ^ mr) << 4), pack_bf16(sc[2] * inv, sc[3] * inv), pack_bf16(sc[4] * inv, sc[5] * inv),
              pack_bf16(sc[6] * inv, sc[7] * inv), pack_bf16(sc[8] * inv, sc[9] * inv));
        asm volatile("stmatrix.sync.aligned.m8n8.x2.shared.b16 [%0], {%1,%1};" ::"r"(pa + ((((mi & 1) ? 7 : 4) ^ mr) << 4)), "r"(pm) : "memory");
      } else {
        wo_prefetch<3, false, 0, PF1A>(wf, woa, 0);
      }
      if (warp == 3 && !last) {
        mbar_spin(B_VM, s & 1);
        if (elect_one()) load_xn(P, s + 1, self);
      }
      PROF(1, 5);
    } else {
      if (warp == 0) {
        OPQ;
        uint32_t kf[4][4], qf[4][4];
        float c0[4], c1[4], d0[4], d1[4];
        const uint32_t ka = PT + (mi >> 1) * 1024 + (mi & 1) * 128 + mr * 16;
#pragma unroll
        for (int k = 0; k < 4; k++) { ldsm4t(qf[k], PT + 2048 + k * 512 + lane * 16); ldsm4t(kf[k], ka + k * 256); }
        mma16816z(c0, qf[0], kf[0][0], kf[0][1]); mma16816z(c1, qf[0], kf[0][2], kf[0][3]);
        mma16816z(d0, qf[1], kf[1][0], kf[1][1]); mma16816z(d1, qf[1], kf[1][2], kf[1][3]);
        mma16816(c0, qf[2], kf[2][0], kf[2][1]); mma16816(c1, qf[2], kf[2][2], kf[2][3]);
        mma16816(d0, qf[3], kf[3][0], kf[3][1]); mma16816(d1, qf[3], kf[3][2], kf[3][3]);
        const float s0 = ((c0[0] + c0[2]) + (c1[0] + c1[2])) + ((d0[0] + d0[2]) + (d1[0] + d1[2]));
        const float s1 = ((c0[1] + c0[3]) + (c1[1] + c1[3])) + ((d0[1] + d0[3]) + (d1[1] + d1[3]));
        if (!last) send_scores(s0, s1, SP + rank * SP_SRC + (128 + lane) * SPW, peer0, peer1, B_SM, lane);
        PROF(1, 5);
      } else {
        const uint32_t t_c = clk32() + lds32(B_XN) * 0;
        if (warp == 3 && !last) { if (elect_one()) load_xn(P, s + 1, self); }
        spin_until(t_c + D_ST);
      }
      OPQ;
      woa = WO + ((mi >> 1) * 8 + mr) * 128 + (((2 * w + (mi & 1)) ^ mr) << 4);
    }
    if (!last) {
      OPQ;
      uint32_t oba = OB + lane * 16;
      if (!ISV) wo_prefetch<3, false, 0, PF1Q>(wf, woa, 0);
      if (ISV ? GATE_MX : GATE_Q) named_bar_sync(NB_MX, 256);
      wo_prefetch<3, false, ISV ? PF1A : PF1Q, PFW>(wf, woa, 0);
      char* h1p = P.xch + (tile0 + w) * 32768 + (h >> 3) * 8192 + (h & 7) * 128 + (((2 * lq + (lg & 1)) ^ (h & 7)) << 4) + (lg >> 1) * 4;
      fence_proxy_async_smem();
      PROF(1, 7);
      named_bar_sync(NB_O, 256);
      PROF(1, 8);
      wo_phase<3, false>(wf, woa, 0, oba, h1p, tid >> 8, ((s >> 1) & 1) ^ 1);
      PROF(1, 9);
      named_bar_sync(NB_HD, 256);
    } else {
      fence_proxy_async_smem();
      named_bar_sync(NB_W1, 128);
    }
  }
  if (ISV && warp == 0) { if (elect_one()) o_done(15); }
}

template <bool ISV, int WG>
__device__ __forceinline__ void f_main(const FParams& P, const int h, const int rank, const uint32_t hw) {
  using namespace fk;
  const uint32_t self = mapa(0, (hw >> (2 * rank)) & 3);
  SMAP;
  const int tid = __shfl_sync(0xffffffffu, threadIdx.x, threadIdx.x & 31);
  const int tile0 = rank * 22, ntile = ISV ? 20 : 22;
  const CUtensorMap* m0 = ISV ? &P.wv : &P.wq;
  const CUtensorMap* m1 = ISV ? &P.wv : &P.wk;
  const int col0 = h * 128 + (ISV ? 0 : 64 * rank), col1 = h * 128 + (ISV ? 64 : 64 * rank);
  WRegs wr;
  uint32_t sel = 0;
  {
    OPQ;
    const uint32_t a = SM0 + WG * 16384 + ((mi >> 1) * 8 + mr) * 128 + (((2 * w + (mi & 1)) ^ mr) << 4);
#pragma unroll
    for (int i = 0; i < 6; i++) {
      mbar_wait(B_PB + 8 * i, 0);
      PRO(8 + i);
#pragma unroll
      for (int T = 0; T < 2; T++)
#pragma unroll
        for (int u = 0; u < 4; u++) ldsm4t(wr[i][T][u], a + i * 32768 + T * 8192 + u * 2048);
      named_bar_sync(NB_C, 256);
      if (WG == 1 && w == (i & 3)) {
        if (elect_one()) {
          if (i <= 2 && i + PRE_G < 6) {
#pragma unroll 1
            for (int n = 2 * (i + PRE_G); n < (i == 2 ? 12 : 2 * (i + PRE_G) + 2); n++) {
              const int ii = n >> 1, row = Chunks<ISV>::rf(n & 1, ii) * 64;
              if (!(n & 1)) mbar_expect_tx(B_PB + 8 * ii, 32768);
              tma_load_2d(SM0 + n * 16384, m0, col0, row, B_PB + 8 * ii);
              tma_load_2d(SM0 + n * 16384 + 8192, m1, col1, row, B_PB + 8 * ii);
            }
          }
          if (i == 3 || i == 4) {
            const int p0 = i == 3 ? 0 : 5, p1 = i == 3 ? 5 : 8;
            mbar_expect_tx(B_W, (p1 - p0) * 8192);
#pragma unroll 1
            for (int p = p0; p < p1; p++) tma_load_2d(WS + p * 8192, (p & 1) ? m1 : m0, (p & 1) ? col1 : col0, Chunks<ISV>::sm(p >> 1) * 64, B_W);
          }
          if (i == WO_AT) {
            mbar_expect_tx(B_WO, ntile * 4096);
#pragma unroll 1
            for (int t = 0; t < 5; t++) tma_load_2d(WO + t * 16384, &P.wo, tile0 * 16 + t * 64, h * 128, B_WO);
            if (!ISV) {
              tma_load_2d(WO + 81920, &P.wo16, tile0 * 16 + 320, h * 128, B_WO);
              tma_load_2d(WO + 86016, &P.wo16, tile0 * 16 + 336, h * 128, B_WO);
            }
          }
        }
      }
    }
    PROF2(1);
    if (WG == 0 && w == 1) {
      uint4 v;
#pragma unroll 1
      for (int tries = 0; tries < POLL_TRIES; tries++) {
        asm volatile("ld.acquire.gpu.global.v4.u32 {%0,%1,%2,%3}, [%4];" : "=r"(v.x), "=r"(v.y), "=r"(v.z), "=r"(v.w)
                     : "l"(&g_mask[4 * min(lane, 23)]) : "memory");
        if (__all_sync(0xffffffffu, v.x & v.y & v.z & v.w & 0x100)) break;
        __nanosleep(100);
      }
      if (elect_one()) {
        asm volatile("fence.proxy.async.global;" ::: "memory");
        load_xn(P, 0, self);
        if (blockIdx.x == 2) { __threadfence(); st_pub128(g_lnok, 0x100); }
      }
      sts128(OB + lane * 16, v.x, v.y, v.z, v.w);
    }
    named_bar_sync(NB_C, 256);
#pragma unroll
    for (int i = 0; i < 3; i++) {
      const int t = min(tile0 + 8 * i + w + (WG ? 0 : 4), 63);
      sel |= ((lds32(OB + ((t >> 1) * 3 + (t & 1)) * 4) >> (h >> 3)) & 1) << (2 * i + 1);
    }
    const uint32_t own = lds32(OB + (3 * h + rank) * 4) >> w, m2 = lds32(OB + (3 * h + 2) * 4) >> w;
    sel |= (own & 1) << 7 | (m2 & 1) << 8 | (m2 & 16) << 5;
    sel |= (((((lg ^ h) & 1) << 2) | (lg >> 1)) == (h & 1) + 2 * (h >> 3)) << 10;
  }
  asm volatile("barrier.cluster.wait.aligned;" ::: "memory");
  PRO(14);
  mbar_wait(B_W, 0);
  PRO(15);
  PROF2(4);
  GTSYNC(0);
  PROF2(2);
  KT_END(8);
  if (WG == 0) f_wg0<ISV>(P, wr, h, rank, hw, tid | sel << 8); else f_wg1<ISV>(P, wr, h, rank, hw, tid | sel << 8);
}

__device__ __forceinline__ void f_tail(const FParams& P, const int h, const uint32_t rank, const bool isv) {
  using namespace fk;
  const uint32_t self = mapa(0, rank), base = self + SM0;
  const uint32_t FULL = self + SP, EMPT = FULL + 32, RES = FULL + 64, NOG = FULL + 72;
  const int tid = threadIdx.x, lane = tid & 31, wv = __shfl_sync(0xffffffffu, tid >> 5, 0), wg = wv >> 2;
  const int kq = h & 3, nt = (h >> 2) & 3, mb = TAIL_MB0 + 3 * (h >> 4) + rank;
  auto a_off = [](uint32_t st) { return (0x98685800u >> (8 * st) & 255) * 1024; };
  auto b_off = [](uint32_t st) { return (0xA8783010u >> (8 * st) & 255) * 1024; };
  static_assert(VX2 - SM0 == 80 * 1024 && VX - SM0 == 200 * 1024, "stage layout");
  auto load_b = [&](int kb) {
    const uint32_t sb = base + b_off(kb & 3), full = FULL + 8 * (kb & 3);
    mbar_expect_tx(full, 49152);
    tma_load_2d_mc(sb + rank * 8192, &P.tb, nt * 256 + ((rank + kq) & 3) * 64, (kq * 16 + kb) * 64, full, 7);
    if (kb % 3 == rank) tma_load_2d_mc(sb + 3 * 8192, &P.tb, nt * 256 + ((3 + kq) & 3) * 64, (kq * 16 + kb) * 64, full, 7);
  };
  auto load_a = [&](int kb) { tma_load_2d(base + a_off(kb & 3), &P.ta, (kq * 16 + kb) * 64, mb * 128, FULL + 8 * (kb & 3)); };
  TL(0);
  TL2(128, 10); TL2(160, 11);
  if (wv == 0) {
    if (elect_one()) {
      prefetch_tmap(&P.tb); prefetch_tmap(&P.ta);
      if (isv) mbar_spin(self + B_VM, (cfg::NSEG - 1) & 1);
      for (int i = 0; i < 4; i++) { mbar_init(FULL + 8 * i, 1); mbar_init(EMPT + 8 * i, 24); }
      mbar_init(RES, 1);
      fence_barrier_init();
      mbar_arrive_cluster(self + B_W, rank == 0 ? 1 : 0);
      mbar_arrive_cluster(self + B_W, rank == 2 ? 1 : 2);
      mbar_spin(self + B_W, 1);
#pragma unroll 1
      for (int kb = 0; kb < 4; kb++) load_b(kb);
      TL2(0, 12);
      wait_count(&g_oflag[mb], 32);
      asm volatile("fence.proxy.async.global;" ::: "memory");
      TL2(0, 13);
#pragma unroll 1
      for (int kb = 0; kb < 4; kb++) load_a(kb);
      TL2(0, 14);
    }
  }
  if (wv == 1) {
    if (lane == 0) {
      prefetch_tmap(&P.tx); prefetch_tmap(&P.tg); prefetch_tmap(&P.tout);
      uint32_t gc;
      asm volatile("ld.acquire.gpu.global.u32 %0, [%1];" : "=r"(gc) : "l"(&g_cnt[3][mb]) : "memory");
      const bool ng = gc < GATE_CNT && ld_strong4(&g_next) == 0;
      sts32(NOG, ng ? 1 : gc < GATE_CNT ? 2 : 0);
      if (ng) g_tfix[blockIdx.x] = 1;
      asm volatile("cp.async.bulk.prefetch.tensor.2d.L2.global [%0, {%1, %2}];" ::"l"(&P.tx), "r"(nt * 256 + kq * 64), "r"(mb * 128) : "memory");
    }
  } else if (wv == 2 || wv == 3) {
#pragma unroll 2
    for (int i = tid - 64; i < 3072; i += 64) st_pub128(&g_tpart[blockIdx.x][0][0][0] + i, EMPTY);
  }
  float acc[128];
  __syncthreads();
  KT_START(7);
  const uint32_t gate = lds32(NOG);
  const bool nog = gate == 1;
  if (gate) TL(15); else TL(15);
#pragma unroll 1
  for (int kb = 0; kb < 16; kb++) {
    const uint32_t st = kb & 3, sa = base + a_off(st) + wg * 8192, sb = base + b_off(st);
    mbar_spin(FULL + 8 * st, (kb >> 2) & 1);
    if (kb == 0) TL(2);
    if (kb == 4) TL(3);
    if (kb == 10) TL(4);
    wg_fence();
#pragma unroll
    for (int k = 0; k < 4; k++) {
      wgmma_ss_n256_tb(acc, make_desc(sa + k * 32, 16, 1024), make_desc(sb + k * 2048, 8192, 1024), (kb | k) != 0);
      if (k == 0) {
        wg_commit();
        wg_wait<1>();
        if (kb > 0 && kb <= 13 && lane < 3) mbar_arrive_cluster(EMPT + 8 * ((kb - 1) & 3), lane);
        wg_fence();
      }
    }
    wg_commit();
    if (kb >= 2 && kb < 15 && wv == ((kb & 1) << 2)) {
      if (elect_one()) {
        mbar_spin(EMPT + 8 * ((kb - 2) & 3), ((kb - 2) >> 2) & 1);
        if (kb < 14) {
          load_b(kb + 2);
          load_a(kb + 2);
        } else if (nog) {
          mbar_arrive(RES);
        } else {
          if (gate) wait_count(&g_cnt[3][mb], GATE_CNT);
          asm volatile("fence.proxy.async.global;" ::: "memory");
          mbar_expect_tx(RES, 32768);
          tma_load_2d(base, &P.tx, nt * 256 + kq * 64, mb * 128, RES);
          tma_load_2d(base + 16384, &P.tg, nt * 256 + kq * 64, mb * 128, RES);
        }
      }
      __syncwarp();
    }
  }
  wg_wait<0>();
  TL(5);
#pragma unroll
  for (int j = 1; j < 4; j++) {
    uint4* dst = &g_tpart[((h & ~3) + ((j + kq) & 3)) * 3 + rank][j - 1][0][tid];
#pragma unroll
    for (int i = 0; i < 4; i++) {
      const float* a = &acc[32 * j + 8 * i];
      asm volatile("st.relaxed.gpu.global.v4.u32 [%0], {%1,%2,%3,%4};" ::"l"(dst + i * 256), "r"(pack_bf16(a[0], a[1])),
                   "r"(pack_bf16(a[2], a[3])), "r"(pack_bf16(a[4], a[5])), "r"(pack_bf16(a[6], a[7])) : "memory");
    }
  }
  TL(6);
#pragma unroll 1
  for (int j = 0, tries = 0; j < 3 && tries < POLL_TRIES; tries++) {
    uint4 pt[4];
#pragma unroll
    for (int i = 0; i < 4; i++) pt[i] = ld_strong16(&g_tpart[blockIdx.x][j][i][tid]);
    if (!__all_sync(0xffffffffu, max(max(umax4(pt[0]), umax4(pt[1])), max(umax4(pt[2]), umax4(pt[3]))) != EMPTY)) continue;
#pragma unroll
    for (int i = 0; i < 16; i++) { acc[2 * i] += bf_lo((&pt[0].x)[i]); acc[2 * i + 1] += bf_hi((&pt[0].x)[i]); }
    j++;
  }
  mbar_spin(RES, 0);
  TL(7);
  const uint32_t xa = base + (wv * 16 + ((lane >> 3) & 1) * 8 + (lane & 7)) * 128 + (((lane >> 4) ^ (lane & 7)) << 4);
#pragma unroll
  for (int i = 0; i < 4; i++) {
    uint32_t x[4], g[4], o[4];
    ldsm4(x, xa ^ (i << 5));
    ldsm4(g, (xa ^ (i << 5)) + 16384);
#pragma unroll
    for (int k = 0; k < 4; k++) {
      const uint32_t sv = pack_bf16(acc[8 * i + 2 * k], acc[8 * i + 2 * k + 1]);
      o[k] = nog ? sv : add_bf16x2(x[k], mul_bf16x2(sv, g[k]));
    }
    stsm4(xa ^ (i << 5), o[0], o[1], o[2], o[3]);
  }
  TL(8);
  fence_proxy_async_smem();
  __syncwarp();
  if (elect_one()) {
    tma_store_2d(&P.tout, base + wv * 2048, nt * 256 + kq * 64, mb * 128 + wv * 16);
    tma_store_commit();
    tma_store_wait_read();
  }
  TL(9);
  KT_END(7);
}

__global__ void __launch_bounds__(256, 1) f_kernel(const __grid_constant__ FParams P) {
  using namespace fk;
  extern __shared__ __align__(1024) uint8_t smem_f[];
  uint32_t crank, rank, hw;
  asm("mov.u32 %0, %%cluster_ctarank;" : "=r"(crank));
  const int h = blockIdx.x / 3;
  if (smem_u32(smem_f) != mapa(0, crank) + SM0) return;
  PROF2(0);
  KT_START(1);
  KT_START(0);
  {
    const uint32_t self = mapa(0, crank);
    SMAP;
    const int tid = threadIdx.x, lane = tid & 31, wv = __shfl_sync(0xffffffffu, tid >> 5, 0);
    PRO(0);
    if (wv == 0) {
      uint32_t sm;
      asm("mov.u32 %0, %%smid;" : "=r"(sm));
      sts32(PROBE + 96, sm >> 1);
      asm volatile("fence.release.sync_restrict::shared::cta.cluster;" ::: "memory");
    }
    asm volatile("barrier.cluster.arrive.relaxed.aligned;" ::: "memory");
    if (wv == 7) {
      if (blockIdx.x == 2) {
#pragma unroll
        for (int i = 0; i < 3; i++) { (&g_cnt[0][0])[32 * i + lane] = 0; g_tfix[32 * i + lane] = 0; }
        if (lane < 16) g_oflag[lane] = 0;
        if (lane == 0) { g_next = 0; g_lnok[0] = 0; }
        __threadfence();
        __syncwarp();
      }
      pdl_launch_dependents();
    }
    const int row0 = blockIdx.x * 8 + wv;
    const bool third = row0 + 1536 < cfg::S;
    uint32_t cur[1][16], raw[2][16];
    load_row16(cur[0], P.x + (size_t)row0 * cfg::D, lane);
    load_row16(raw[0], P.x + (size_t)(row0 + 768) * cfg::D, lane);
    load_row16(raw[1], P.x + (size_t)(row0 + (third ? 1536 : 0)) * cfg::D, lane);
    {
      uint32_t tpc;
      asm volatile("barrier.cluster.wait.aligned;" ::: "memory");
      asm volatile("ld.shared::cluster.u32 %0, [%1];" : "=r"(tpc) : "r"(mapa(PROBE + 96, lane % 3)) : "memory");
      const uint32_t t0 = __shfl_sync(0xffffffffu, tpc, 0), t1 = __shfl_sync(0xffffffffu, tpc, 1), t2 = __shfl_sync(0xffffffffu, tpc, 2);
      hw = t1 == t2 ? 0x09 : t0 == t2 ? 0x18 : 0x24;
      rank = (hw & 3) == crank ? 0 : ((hw >> 2) & 3) == crank ? 1 : 2;
    }
    const bool isv = rank == 2;
    const CUtensorMap* m0 = isv ? &P.wv : &P.wq;
    const CUtensorMap* m1 = isv ? &P.wv : &P.wk;
    const int col0 = h * 128 + (isv ? 0 : 64 * rank), col1 = h * 128 + (isv ? 64 : 64 * rank);
    if (wv == 0) {
      if (elect_one()) {
        for (int i = 0; i < 2; i++) mbar_init(B_XN + 8 * i, 1);
        mbar_init(B_H1, 4);
        mbar_init(B_SM, isv ? 1 : 6);
        mbar_init(B_VM, isv ? 8 : 1);
        mbar_init(B_VX, 1);
        mbar_init(B_ST, 1);
        mbar_init(B_PF, 2);
        for (int i = 0; i < 6; i++) mbar_init(B_PB + 8 * i, 1);
        mbar_init(B_W, 2);
        mbar_init(B_WO, 1);
        fence_barrier_init();
        mbar_expect_tx(B_SM, isv ? 2 * SP_SRC : SP_SRC);
        if (isv) mbar_expect_tx(B_ST, 7168);
        else { mbar_expect_tx(B_VM, 2048); mbar_expect_tx(B_VX, 8192); }
      }
    }
    const int j = 2 * h + rank;
    if (lane == 0) {
      const uint2 b = probe_pair(P.xch + (isv ? H1_BYTES + wv * 8192 + h * 128 : j * 32768 + (wv & 3) * 8192 + (wv >> 2) * 128),
                                 isv ? EMPTY : 0, PROBE + 64, P.nprobe);
      sts64(PROBE + wv * 8, b.x, b.y);
    }
    PROF2(3);
    PRO(1);
    __syncwarp();
    if (wv == 1) {
      const uint32_t off = (blockIdx.x * 32 + lane) * 688;
      if (off < cfg::D * cfg::D * 2) l2_prefetch(reinterpret_cast<const char*>(P.w1) + off, min(688u, cfg::D * cfg::D * 2 - off));
    }
    if (wv == 0) {
      asm volatile("{\n.reg .pred p;\nsetp.eq.u32 p, %0, %1;\n@p st.shared.u32 [%2], %0;\n}" ::"r"(raw[1][15]), "r"(cur[0][0] ^ raw[0][15]), "r"(PROBE + 64) : "memory");
      if (elect_one()) {
#pragma unroll 1
        for (int n = 0; n < 2 * PRE_G; n++) {
          const int i = n >> 1, g = n & 1, row = (isv ? Chunks<true>::rf(g, i) : Chunks<false>::rf(g, i)) * 64;
          if (!g) mbar_expect_tx(B_PB + 8 * i, 32768);
          tma_load_2d(SM0 + n * 16384, m0, col0, row, B_PB + 8 * i);
          tma_load_2d(SM0 + n * 16384 + 8192, m1, col1, row, B_PB + 8 * i);
        }
      }
    }
    __syncthreads();
    PRO(2);
    asm volatile("barrier.cluster.arrive.relaxed.aligned;" ::: "memory");
    PRO(3);
    if (wv == 2) { sts32(self + ONES + lane * 4, 0x3F803F80u); fence_proxy_async_smem(); }
    uint32_t pb[2], pc[2];
    lds64(pb, PROBE + (lane & 7) * 8);
    lds64(pc, PROBE + ((lane & 7) ^ 4) * 8);
    const uint32_t mask = __ballot_sync(0xffffffffu, isv ? pb[1] < pb[0] : min(pb[1], pc[1]) < min(pb[0], pc[0])) & (isv ? 255 : 15);
    if (!isv) {
#pragma unroll
      for (int i = 0; i < 4; i++) st_pub128(P.xch + j * 32768 + i * 8192 + ((mask >> i) & 1) * 4096 + tid * 16, 0);
      if (wv < 4) st_pub64(P.xch + H1_BYTES + (wv >> 1) * 32768 + (j >> 4) * 8192 + (wv & 1) * 4096 + (j & 15) * 256 + lane * 8, EMPTY, EMPTY);
    }
#pragma unroll 1
    for (int it = 0; it < (third ? 6 : 4); it++) {
      ln_regs<1>(cur);
      store_row16(cur[0], ((it & 1) ? P.xn2 : P.xn_ptr) + (size_t)(row0 + (it >> 1) * 768) * cfg::D, lane);
      if (it == 0) PRO(4);
      if (it & 1) {
#pragma unroll
        for (int i = 0; i < 16; i++) { cur[0][i] = raw[0][i]; raw[0][i] = raw[1][i]; }
      }
    }
    PRO(5);
    __syncthreads();
    PRO(6);
    if (tid == 64) {
      __threadfence();
      PRO(7);
      st_pub32(&g_mask[3 * h + rank], 0x100 | mask);
    }
    KT_END(0);
    __syncwarp();
  }
  const int wg = __shfl_sync(0xffffffffu, threadIdx.x >> 7, 0);
  if (rank == 2) { if (wg == 0) f_main<true, 0>(P, h, 2, hw); else f_main<true, 1>(P, h, 2, hw); }
  else { if (wg == 0) f_main<false, 0>(P, h, rank, hw); else f_main<false, 1>(P, h, rank, hw); }
  PROF2(5);
  KT_END(1);
  __syncwarp();
  f_tail(P, h, crank, rank == 2);
}

#define GCL 1
namespace gk {
enum { T_B1 = 0, T_B2 = 1, T_B3 = 2, T_B4 = 3, T_O = 4, T_LN = 5, T_END = 7 };
constexpr int NST = 3, STAGE = 49152, MAXITEMS = 512, NEW = 3;
constexpr uint32_t OUTB = NST * STAGE, BARS = OUTB + 65536;
constexpr uint32_t B_FULL = BARS, B_EMPTY = BARS + 32, B_ITEM = BARS + 64, B_FILL = BARS + 128, B_FREE = BARS + 160, B_LN = BARS + 176, ITEMS = BARS + 192;
constexpr int SMEM = BARS + 256;
static_assert(GATE_CNT == 4 * NEW && T_B4 == 3, "gate counter");
}
struct GParams {
  CUtensorMap a[5], b[5];
  bf16* c[5];
  const bf16* r[5];
  bf16* x1n;
  int nitems, lnpos;
  uint16_t items[gk::MAXITEMS];
};
#define ILOG(i)

__device__ __forceinline__ void tma_load_3d_mc(uint32_t dst, const CUtensorMap* map, int x, int y, int z, uint32_t bar) {
  asm volatile("cp.async.bulk.tensor.3d.shared::cluster.global.mbarrier::complete_tx::bytes.multicast::cluster "
               "[%0], [%1, {%3, %4, %5}], [%2], %6;"
               ::"r"(dst), "l"(map), "r"(bar), "r"(x), "r"(y), "r"(z), "h"((uint16_t)3) : "memory");
}
__device__ __forceinline__ float tanh_approx(float x) { float y; asm("tanh.approx.f32 %0, %1;" : "=f"(y) : "f"(x)); return y; }
__global__ void __launch_bounds__(384, 1) g_kernel(const __grid_constant__ GParams P) {
  using namespace gk;
  extern __shared__ __align__(1024) uint8_t smem_g[];
  const uint32_t base = smem_u32(smem_g);
  const int tid = threadIdx.x, warp = __shfl_sync(0xffffffffu, tid >> 5, 0), lane = tid & 31;
  const int rank = blockIdx.x % GCL;
  KT_START(2);
  if (tid == 0) {
    for (int s = 0; s < NST; s++) { mbar_init(base + B_FULL + 8 * s, 1); mbar_init(base + B_EMPTY + 8 * s, 8 * GCL); }
    for (int s = 0; s < 8; s++) mbar_init(base + B_ITEM + 8 * s, 1);
    for (int s = 0; s < 2; s++) { mbar_init(base + B_FILL + 8 * s, 4); mbar_init(base + B_FREE + 8 * s, NEW); }
    mbar_init(base + B_LN, 1);
    fence_barrier_init();
  }
  __syncthreads();
  if (GCL > 1) cluster_sync();
  auto release = [&](uint32_t st) {
    if (GCL > 1) { if (lane < GCL) mbar_arrive_cluster(base + B_EMPTY + 8 * st, lane); }
    else if (lane == 0) mbar_arrive(base + B_EMPTY + 8 * st);
  };
  auto get_item = [&](int q) {
    mbar_wait(base + B_ITEM + 8 * (q & 7), (q >> 3) & 1);
    return lds32(base + ITEMS + 4 * (q & 7));
  };

  if (warp == 8) {
    if (lane < 10) prefetch_tmap(&P.a[0] + lane);
    if (lane == 0) {
      uint32_t st = 0, ph = 1;
#pragma unroll 1
      for (int q = 0;; q++) {
        if (GCL > 1) mbar_expect_tx(base + B_ITEM + 8 * (q & 7), 4);
        if (rank == 0) {
          const unsigned idx = atomicAdd(&g_next, 1), ln = idx - P.lnpos;
          const uint32_t v = (idx < (unsigned)P.nitems ? P.items[idx] : T_END) | (ln < 64 / GCL ? (ln + 1) << 16 : 0);
          if (GCL > 1) {
#pragma unroll
            for (int r = 0; r < GCL; r++) st_async32(mapa(base + ITEMS + 4 * (q & 7), r), v, mapa(base + B_ITEM + 8 * (q & 7), r));
          } else {
            sts32(base + ITEMS + 4 * (q & 7), v);
            mbar_arrive(base + B_ITEM + 8 * (q & 7));
          }
        }
        const uint32_t item = get_item(q);
        const int type = item & 7, mb = ((item >> 3) & 15) + rank, nt = (item >> 7) & 15;
        ILOG(1);
        if (q == 0) { __threadfence(); sts32(base + ITEMS + 32, ld_strong4(&g_oflag[14]) >= 32); }
        if (type == T_END) break;
        if (type == T_B2) {
          wait_count(&g_cnt[T_B1][max(mb - 1, 0)], 4 * NEW); wait_count(&g_cnt[T_B1][mb], 4 * NEW); wait_count(&g_cnt[T_B1][min(mb + 1, 15)], 4 * NEW);
        } else if (type == T_B3) wait_count(&g_cnt[T_LN][mb], 32);
        else if (type == T_B4) wait_count(&g_cnt[T_B3][mb], 14 * NEW);
        else if (type == T_O) wait_count(&g_oflag[mb], 32);
        asm volatile("fence.proxy.async.global;" ::: "memory");
        ILOG(2);
        const CUtensorMap *ma = &P.a[type], *mbm = &P.b[type];
        const int nkb = type == T_B4 ? cfg::F / 64 : type == T_O ? cfg::HD / 64 : cfg::D / 64;
#pragma unroll 1
        for (int kb = 0; kb < nkb; kb++) {
          mbar_wait(base + B_EMPTY + 8 * st, ph);
          const uint32_t sa = base + st * STAGE, full = base + B_FULL + 8 * st;
          mbar_expect_tx(full, STAGE);
          int arow = mb * 128;
          if (type == T_B2) { const int qd = kb >> 2; arow += (qd == 0) ? -1 : (qd == 1) ? 1 : (qd == 2) ? -2 : 2; }
          if (GCL > 1) tma_load_3d_mc(sa + 16384 + rank * 16384, mbm, 0, kb * 64, nt * 4 + rank * 2, full);
          else tma_load_3d(sa + 16384, mbm, 0, kb * 64, nt * 4, full);
          if (q == 0 && kb == 0) { mbar_wait(base + B_LN, 0); asm volatile("fence.proxy.async.global;" ::: "memory"); }
          tma_load_2d(sa, ma, kb * 64, arow, full);
          if (++st == NST) { st = 0; ph ^= 1; }
        }
      }
    }
  } else {
    const int wg = warp >> 2, ew = warp > 8 ? warp - 9 : warp + NEW;
    const uint32_t outa = base + OUTB + (warp * 16 + ((lane >> 3) & 1) * 8 + (lane & 7)) * 512 + (((lane >> 4) ^ (lane & 7)) << 4);
    uint32_t st = 0, ph = 0;
    float acc[128];
    auto kill_acc = [&]() {
#pragma unroll
      for (int i = 0; i < 128; i++) acc[i] = 0.f;
    };
    if (warp == 9) {
#pragma unroll 1
      for (int tries = 0; tries < POLL_TRIES; tries++) {
        uint4 v;
        asm volatile("ld.acquire.gpu.global.v4.u32 {%0,%1,%2,%3}, [%4];" : "=r"(v.x), "=r"(v.y), "=r"(v.z), "=r"(v.w)
                     : "l"(lane < 24 ? &g_mask[4 * lane] : &g_lnok[0]) : "memory");
        const uint32_t ok = __ballot_sync(0xffffffffu, v.x & v.y & v.z & v.w & 0x100);
        if ((ok & 0xFFFFFF) == 0xFFFFFF || (ok >> 24)) break;
        __nanosleep(200);
      }
      if (lane == 0) mbar_arrive(base + B_LN);
    }
    uint32_t next = get_item(0);
#pragma unroll 1
    for (int q = 0;; q++) {
      const uint32_t item = next;
      const int type = item & 7, mb = ((item >> 3) & 15) + rank, nt = (item >> 7) & 15;
      if (type == T_END) break;
      if (warp < 8) {
      if (item >> 16) {
        const int ln = (item >> 16) - 1, lb = (ln >> 2) * GCL + rank;
        const size_t row = (size_t)(lb * 128 + (ln & 3) * 32 + warp * 4) * cfg::D;
        wait_count(&g_cnt[T_B2][lb], 4 * NEW);
        uint32_t cur[2][16], nxt[2][16];
#pragma unroll
        for (int r = 0; r < 2; r++) {
          load_row16(cur[r], P.c[T_B2] + row + r * cfg::D, lane);
          load_row16(nxt[r], P.c[T_B2] + row + (r + 2) * cfg::D, lane);
        }
#pragma unroll 1
        for (int r2 = 0; r2 < 4; r2 += 2) {
          ln_regs<2>(cur);
#pragma unroll
          for (int r = 0; r < 2; r++) {
            store_row16(cur[r], P.x1n + row + (r2 + r) * cfg::D, lane);
#pragma unroll
            for (int i = 0; i < 16; i++) cur[r][i] = nxt[r][i];
          }
        }
        __syncwarp();
        if (lane == 0) asm volatile("red.release.gpu.global.add.u32 [%0], 1;" ::"l"(&g_cnt[T_LN][lb]) : "memory");
        __syncwarp();
        if (tid == 0) ILOG(6);
        kill_acc();
      }
      const int nkb = type == T_B4 ? cfg::F / 64 : type == T_O ? cfg::HD / 64 : cfg::D / 64;
      uint32_t prev = 0;
      mbar_wait(base + B_FULL + 8 * st, ph);
#pragma unroll 1
      for (int kb = 0; kb < nkb; kb++) {
        mbar_spin(base + B_FULL + 8 * st, ph);
        if (kb == 0 && tid == 0) ILOG(3);
        const uint64_t da = make_desc(base + wg * 8192, 16, 1024) + st * (STAGE >> 4), db = make_desc(base + 16384, 8192, 1024) + st * (STAGE >> 4);
        wg_fence();
#pragma unroll
        for (int k = 0; k < 4; k++) {
          wgmma_ss_n256_tb(acc, da + k * 2, db + k * 128, (kb | k) != 0);
          if (k == 0) {
            wg_commit();
            wg_wait<1>();
            if (kb > 0) release(prev);
            wg_fence();
          }
        }
        wg_commit();
        prev = st;
        if (++st == NST) { st = 0; ph ^= 1; }
      }
      next = get_item(q + 1);
      if (q > 0) mbar_wait(base + B_FREE + 8 * wg, (q - 1) & 1);
      wg_wait<0>();
      if (tid == 0) ILOG(4);
      release(prev);
#pragma unroll
      for (int j = 0; j < 16; j++)
        stsm4((outa ^ ((j & 3) << 5)) + (j >> 2) * 128, pack_bf16(acc[8 * j], acc[8 * j + 1]), pack_bf16(acc[8 * j + 2], acc[8 * j + 3]),
              pack_bf16(acc[8 * j + 4], acc[8 * j + 5]), pack_bf16(acc[8 * j + 6], acc[8 * j + 7]));
      __syncwarp();
      if (lane == 0) mbar_arrive(base + B_FILL + 8 * wg);
      if (tid == 0) ILOG(5);
      if ((next & 7) != T_END) continue;
      }
      if (type == T_O) wait_count(&g_cnt[T_B4][mb], 4 * NEW);
      const int ldc = type == T_B3 ? cfg::F : cfg::D;
      bf16* cp = P.c[type] + (size_t)mb * 128 * ldc + nt * 256 + lane * 8;
      const size_t roff = (size_t)mb * 128 * cfg::D + nt * 256 + lane * 8;
      const bf16 *rp = P.r[type] + roff, *gp = P.c[T_B4] + roff;
      const bool res = type == T_B2 || type >= T_B4, act = type != T_B2 && type != T_O;
      const float c1 = type == T_B4 ? 0.f : 0.035677408136300125f, c0 = type == T_B4 ? 0.5f : 0.7978845608028654f;
      uint32_t yn[4][4];
      uint4 rn[4], gn[4];
#pragma unroll
      for (int i = 0; i < 4; i++) rn[i] = gn[i] = make_uint4(0, 0, 0, 0);
      auto fetch_res = [&](int grp) {
#pragma unroll
        for (int i = 0; i < 4; i++) {
          if (res) rn[i] = __ldcg(reinterpret_cast<const uint4*>(rp + (grp * 4 + i) * cfg::D));
          if (type == T_O) gn[i] = __ldcg(reinterpret_cast<const uint4*>(gp + (grp * 4 + i) * cfg::D));
        }
      };
      auto fetch_y = [&](int grp) {
#pragma unroll
        for (int i = 0; i < 4; i++) lds128(yn[i], base + OUTB + (grp * 4 + i) * 512 + ((lane ^ ((grp * 4 + i) & 7)) << 4));
      };
      if (type == T_B4) wait_count(&g_cnt[T_B2][mb], 4 * NEW);
      if (type >= T_B4 && warp > 8) for (int r = tid - 288; r < 128; r += 96) l2_prefetch(rp - lane * 8 + r * cfg::D, 512);
      fetch_res(ew);
      mbar_wait(base + B_FILL, q & 1);
      fetch_y(ew);
      next = get_item(q + 1);
      const int stride = (next & 7) == T_END ? NEW + 8 : NEW;
#pragma unroll 1
      for (int grp = ew; grp < 32; grp += stride) {
        uint32_t y[4][4];
#pragma unroll
        for (int i = 0; i < 4; i++) {
#pragma unroll
          for (int k = 0; k < 4; k++) y[i][k] = yn[i][k];
          if (type == T_O) {
            y[i][0] = mul_bf16x2(y[i][0], gn[i].x); y[i][1] = mul_bf16x2(y[i][1], gn[i].y);
            y[i][2] = mul_bf16x2(y[i][2], gn[i].z); y[i][3] = mul_bf16x2(y[i][3], gn[i].w);
          }
          if (res) {
            y[i][0] = add_bf16x2(y[i][0], rn[i].x); y[i][1] = add_bf16x2(y[i][1], rn[i].y);
            y[i][2] = add_bf16x2(y[i][2], rn[i].z); y[i][3] = add_bf16x2(y[i][3], rn[i].w);
          }
        }
        const int nx = grp + stride;
        if (nx < 32) {
          fetch_res(nx);
          if (nx >= 16 && grp < 16) {
            __syncwarp();
            if (lane == 0 && warp > 8) mbar_arrive(base + B_FREE);
            mbar_wait(base + B_FILL + 8, q & 1);
          }
          fetch_y(nx);
        }
        if (act) {
#pragma unroll
          for (int i = 0; i < 4; i++)
#pragma unroll
            for (int k = 0; k < 4; k++) {
              const float v0 = bf_lo(y[i][k]), v1 = bf_hi(y[i][k]);
              const float t0 = tanh_approx(v0 * fmaf(v0 * c1, v0, c0)), t1 = tanh_approx(v1 * fmaf(v1 * c1, v1, c0));
              const float h0 = 0.5f * v0, h1 = 0.5f * v1;
              y[i][k] = pack_bf16(fmaf(h0, t0, h0), fmaf(h1, t1, h1));
            }
        }
#pragma unroll
        for (int i = 0; i < 4; i++)
          *reinterpret_cast<uint4*>(cp + (size_t)(grp * 4 + i) * ldc) = make_uint4(y[i][0], y[i][1], y[i][2], y[i][3]);
      }
      __syncwarp();
      if (lane == 0 && warp > 8) mbar_arrive(base + B_FREE + 8);
      if (stride != NEW) named_bar_sync(2, 352);
      if (type != T_O && lane == 0 && warp > 8) asm volatile("red.release.gpu.global.add.u32 [%0], 1;" ::"l"(&g_cnt[type][mb]) : "memory");
      __syncwarp();
      if (tid == 288) ILOG(7);
      kill_acc();
    }
    KT_END(2);
  }
  __syncwarp();
  if (warp >= 8) {
   named_bar_sync(1, 128);
   const bool late = lds32(base + ITEMS + 32);
   if (late) pdl_wait();
#pragma unroll 1
   for (int c = blockIdx.x; late && c < 96; c += gridDim.x) {
     if (__ldcg(&g_tfix[c]) == 0) continue;
     const int hh = c / 3, mb = TAIL_MB0 + 3 * (hh >> 4) + c % 3;
     wait_count(&g_cnt[T_B4][mb], GATE_CNT);
#pragma unroll 1
     for (int i = tid - 256; i < 1024; i += 128) {
       const size_t off = (size_t)(mb * 128 + (i >> 3)) * cfg::D + (hh & 15) * 64 + (i & 7) * 8;
       const uint4 sv = __ldcg(reinterpret_cast<const uint4*>(P.c[T_O] + off)), gv = __ldcg(reinterpret_cast<const uint4*>(P.c[T_B4] + off)),
                   xv = __ldcg(reinterpret_cast<const uint4*>(P.r[T_O] + off));
       *reinterpret_cast<uint4*>(P.c[T_O] + off) = make_uint4(add_bf16x2(xv.x, mul_bf16x2(sv.x, gv.x)), add_bf16x2(xv.y, mul_bf16x2(sv.y, gv.y)),
                                                              add_bf16x2(xv.z, mul_bf16x2(sv.z, gv.z)), add_bf16x2(xv.w, mul_bf16x2(sv.w, gv.w)));
     }
   }
  }
  if (GCL > 1) cluster_sync();
}

__device__ bf16 g_xn[cfg::S * cfg::D];
__device__ bf16 g_xn2[cfg::S * cfg::D];
__device__ bf16 g_h[cfg::S * cfg::D];
__device__ bf16 g_x1[cfg::S * cfg::D];
__device__ bf16 g_x1n[cfg::S * cfg::D];
__device__ bf16 g_u[cfg::S * cfg::F];
__device__ bf16 g_g[cfg::S * cfg::D];
__device__ bf16 g_o[cfg::S * cfg::HD];

typedef CUresult (*PFN_encodeTiled)(CUtensorMap*, CUtensorMapDataType, cuuint32_t, void*, const cuuint64_t*,
                                    const cuuint64_t*, const cuuint32_t*, const cuuint32_t*, CUtensorMapInterleave,
                                    CUtensorMapSwizzle, CUtensorMapL2promotion, CUtensorMapFloatOOBfill);

static PFN_encodeTiled get_encoder() {
  static PFN_encodeTiled fn = nullptr;
  if (!fn) {
    void* p = nullptr;
    cudaDriverEntryPointQueryResult st;
    cudaGetDriverEntryPoint("cuTensorMapEncodeTiled", &p, cudaEnableDefault, &st);
    fn = (PFN_encodeTiled)p;
  }
  return fn;
}
static CUtensorMap make_map(const void* ptr, int rows, int cols, int box_rows, int box_cols, int swizzle_bytes) {
  CUtensorMap m;
  cuuint64_t dims[2] = {(cuuint64_t)cols, (cuuint64_t)rows};
  cuuint64_t strides[1] = {(cuuint64_t)cols * 2};
  cuuint32_t box[2] = {(cuuint32_t)box_cols, (cuuint32_t)box_rows};
  cuuint32_t estr[2] = {1, 1};
  CUtensorMapSwizzle sw = swizzle_bytes == 128 ? CU_TENSOR_MAP_SWIZZLE_128B
                        : swizzle_bytes == 64 ? CU_TENSOR_MAP_SWIZZLE_64B
                        : swizzle_bytes == 32 ? CU_TENSOR_MAP_SWIZZLE_32B : CU_TENSOR_MAP_SWIZZLE_NONE;
  get_encoder()(&m, CU_TENSOR_MAP_DATA_TYPE_BFLOAT16, 2, const_cast<void*>(ptr), dims, strides, box, estr,
                CU_TENSOR_MAP_INTERLEAVE_NONE, sw, CU_TENSOR_MAP_L2_PROMOTION_L2_128B, CU_TENSOR_MAP_FLOAT_OOB_FILL_NONE);
  return m;
}
static CUtensorMap make_map3(const void* ptr, int rows, int cols, int box_rows, int nblk) {
  CUtensorMap m;
  cuuint64_t dims[3] = {64, (cuuint64_t)rows, (cuuint64_t)(cols / 64)};
  cuuint64_t strides[2] = {(cuuint64_t)cols * 2, 128};
  cuuint32_t box[3] = {64, (cuuint32_t)box_rows, (cuuint32_t)nblk};
  cuuint32_t estr[3] = {1, 1, 1};
  get_encoder()(&m, CU_TENSOR_MAP_DATA_TYPE_BFLOAT16, 3, const_cast<void*>(ptr), dims, strides, box, estr,
                CU_TENSOR_MAP_INTERLEAVE_NONE, CU_TENSOR_MAP_SWIZZLE_128B, CU_TENSOR_MAP_L2_PROMOTION_L2_128B,
                CU_TENSOR_MAP_FLOAT_OOB_FILL_NONE);
  return m;
}
template <class T> static T* sym(T& s) { void* p = nullptr; cudaGetSymbolAddress(&p, s); return (T*)p; }
#define SYM(name) ((bf16*)[] { void* p = nullptr; cudaGetSymbolAddress(&p, name); return p; }())

#define G_CTAS 36
#define B4_FIRST (GCL == 1 ? 9 : 16)
#define O_FIRST 2
#define LN_POS 63
static int build_items(uint16_t* it) {
  using namespace gk;
  int n = 0;
  auto add = [&](int type, int nrows, int ncols, int row0 = 0) {
    for (int mb = row0; mb < nrows; mb += GCL) for (int nt = 0; nt < ncols; nt++) it[n++] = (uint16_t)(type | mb << 3 | nt << 7);
  };
  add(T_B1, 16, 4); add(T_B2, 16, 4); add(T_B3, 16, 14);
  add(T_B4, B4_FIRST, 4); add(T_O, O_FIRST, 4); add(T_B4, 16, 4, B4_FIRST); add(T_O, TAIL_MB0, 4, O_FIRST);
  return n;
}

extern "C" void kernel_launch(void* const* d_in, const int* in_sizes, int n_in, void* d_out, int out_size) {
  using namespace cfg;
  const bf16* x = (const bf16*)d_in[0];
  const bf16* mem0 = (const bf16*)d_in[1];
  const bf16* Wq = (const bf16*)d_in[2];
  const bf16* Wk = (const bf16*)d_in[3];
  const bf16* Wv = (const bf16*)d_in[4];
  const bf16* Wo = (const bf16*)d_in[5];
  const bf16* w1 = (const bf16*)d_in[8];
  const bf16* w2 = (const bf16*)d_in[9];
  const bf16* w3 = (const bf16*)d_in[10];
  const bf16* w4 = (const bf16*)d_in[11];
  bf16* out = (bf16*)d_out;
  cudaStream_t st = cudaStreamPerThread;

  bf16 *xn = SYM(g_xn), *xn2 = SYM(g_xn2), *hb = SYM(g_h), *x1 = SYM(g_x1), *x1n = SYM(g_x1n), *u = SYM(g_u),
       *g = SYM(g_g), *o = SYM(g_o);

  {
    cudaFuncSetAttribute(f_kernel, cudaFuncAttributeMaxDynamicSharedMemorySize, fk::SMEM);
    FParams P;
    P.wq = make_map(Wq, D, HD, 64, 64, 128); P.wk = make_map(Wk, D, HD, 64, 64, 128); P.wv = make_map(Wv, D, HD, 64, 64, 128);
    P.wo = make_map(Wo, HD, D, 128, 64, 128); P.wo16 = make_map(Wo, HD, D, 128, 16, 32); P.xn = make_map3(xn, S, D, 32, 4); P.xn12 = make_map3(xn, S, D, 32, 12); P.o = make_map3(o, S, HD, 32, 2);
    P.ta = make_map(o, S, HD, 128, 64, 128); P.tb = make_map(Wo, HD, D, 64, 64, 128); P.tx = make_map(x, S, D, 128, 64, 128);
    P.tg = make_map(g, S, D, 128, 64, 128); P.tout = make_map(out, S, D, 16, 64, 128);
    P.mem0 = mem0;
    P.nprobe = PROBE_N;
    P.x = x; P.w1 = w1; P.xn_ptr = xn; P.xn2 = xn2;
    P.xch = (char*)(((uintptr_t)SYM(g_xch) + 8191) & ~(uintptr_t)8191);
    cudaLaunchConfig_t cfg = {};
    cfg.gridDim = dim3(96); cfg.blockDim = dim3(256); cfg.dynamicSmemBytes = fk::SMEM; cfg.stream = st;
    cudaLaunchAttribute at[2];
    at[0].id = cudaLaunchAttributeClusterDimension;
    at[0].val.clusterDim.x = 3; at[0].val.clusterDim.y = 1; at[0].val.clusterDim.z = 1;
    cfg.attrs = at; cfg.numAttrs = 1;
    cudaLaunchKernelEx(&cfg, f_kernel, P);
  }
  {
    cudaFuncSetAttribute(g_kernel, cudaFuncAttributeMaxDynamicSharedMemorySize, gk::SMEM);
    GParams G;
    const bf16* as[5] = {xn2, hb, x1n, u, o};
    const bf16* bs[5] = {w1, w2, w3, w4, Wo};
    bf16* cs[5] = {hb, x1, u, g, out};
    const bf16* rs[5] = {xn, xn, xn, x1, x};
    const int ks[5] = {D, D, D, F, HD}, ns[5] = {D, D, F, D, D};
    for (int i = 0; i < 5; i++) {
      G.a[i] = make_map(as[i], S, ks[i], 128, 64, 128);
      G.b[i] = make_map3(bs[i], ks[i], ns[i], 64, 4 / GCL);
      G.c[i] = cs[i];
      G.r[i] = rs[i];
    }
    G.x1n = x1n;
    G.nitems = build_items(G.items);
    G.lnpos = LN_POS * 2 / GCL;
    cudaLaunchConfig_t cfg = {};
    cfg.gridDim = dim3(G_CTAS); cfg.blockDim = dim3(384); cfg.dynamicSmemBytes = gk::SMEM; cfg.stream = st;
    cudaLaunchAttribute at[2];
    at[0].id = cudaLaunchAttributeClusterDimension;
    at[0].val.clusterDim.x = GCL; at[0].val.clusterDim.y = 1; at[0].val.clusterDim.z = 1;
    at[1].id = cudaLaunchAttributeProgrammaticStreamSerialization;
    at[1].val.programmaticStreamSerializationAllowed = 1;
    cfg.attrs = at;
    cfg.numAttrs = 2;
    cudaLaunchKernelEx(&cfg, g_kernel, G);
  }
}
```

```cpp
#include <cuda_runtime.h>
#include <cuda_bf16.h>
#include <cuda.h>
#include <stdint.h>

typedef __nv_bfloat16 bf16;

namespace cfg {
constexpr int S = 2048;
constexpr int D = 1024;
constexpr int H = 32;
constexpr int DH = 128;
constexpr int HD = H * DH;
constexpr int M = 8;
constexpr int SEG = 32;
constexpr int NSEG = S / SEG;
constexpr int F = 3584;
}

__device__ __forceinline__ uint32_t smem_u32(const void* p) { return (uint32_t)__cvta_generic_to_shared(p); }

__device__ __forceinline__ void mbar_init(uint32_t bar, uint32_t count) {
  asm volatile("mbarrier.init.shared::cta.b64 [%0], %1;" ::"r"(bar), "r"(count) : "memory");
}
__device__ __forceinline__ void mbar_expect_tx(uint32_t bar, uint32_t bytes) {
  asm volatile("mbarrier.arrive.expect_tx.shared::cta.b64 _, [%0], %1;" ::"r"(bar), "r"(bytes) : "memory");
}
__device__ __forceinline__ void mbar_arrive(uint32_t bar) {
  asm volatile("mbarrier.arrive.shared::cta.b64 _, [%0];" ::"r"(bar) : "memory");
}
__device__ __forceinline__ bool mbar_try(uint32_t bar, uint32_t parity) {
  uint32_t done;
  asm volatile("{\n.reg .pred p;\nmbarrier.try_wait.parity.shared::cta.b64 p, [%1], %2, 20000;\nselp.u32 %0, 1, 0, p;\n}"
               : "=r"(done) : "r"(bar), "r"(parity) : "memory");
  return done != 0;
}
__device__ __forceinline__ bool mbar_try_nohint(uint32_t bar, uint32_t parity) {
  uint32_t done;
  asm volatile("{\n.reg .pred p;\nmbarrier.try_wait.parity.shared::cta.b64 p, [%1], %2;\nselp.u32 %0, 1, 0, p;\n}"
               : "=r"(done) : "r"(bar), "r"(parity) : "memory");
  return done != 0;
}
constexpr int MBAR_TRIES = 4096;
constexpr int POLL_TRIES = 1 << 16;
__device__ __forceinline__ void mbar_wait(uint32_t bar, uint32_t parity) {
#pragma unroll 1
  for (int n = 0; n < MBAR_TRIES; n++)
    if (mbar_try(bar, parity)) break;
}
__device__ __forceinline__ void mbar_wait_fast(uint32_t bar, uint32_t parity) {
#pragma unroll 1
  for (int n = 0; n < (POLL_TRIES << 4); n++)
    if (mbar_try_nohint(bar, parity)) break;
}
__device__ __forceinline__ void fence_barrier_init() { asm volatile("fence.mbarrier_init.release.cluster;" ::: "memory"); }
__device__ __forceinline__ void fence_proxy_async_smem() { asm volatile("fence.proxy.async.shared::cta;" ::: "memory"); }

__device__ __forceinline__ void tma_load_2d(uint32_t dst, const CUtensorMap* map, int x, int y, uint32_t bar) {
  asm volatile("cp.async.bulk.tensor.2d.shared::cluster.global.mbarrier::complete_tx::bytes [%0], [%1, {%3, %4}], [%2];"
               ::"r"(dst), "l"(map), "r"(bar), "r"(x), "r"(y) : "memory");
}
__device__ __forceinline__ void tma_load_3d(uint32_t dst, const CUtensorMap* map, int x, int y, int z, uint32_t bar) {
  asm volatile("cp.async.bulk.tensor.3d.shared::cluster.global.mbarrier::complete_tx::bytes [%0], [%1, {%3, %4, %5}], [%2];"
               ::"r"(dst), "l"(map), "r"(bar), "r"(x), "r"(y), "r"(z) : "memory");
}
__device__ __forceinline__ void tma_store_2d(const CUtensorMap* map, uint32_t src, int x, int y) {
  asm volatile("cp.async.bulk.tensor.2d.global.shared::cta.bulk_group [%0, {%2, %3}], [%1];"
               ::"l"(map), "r"(src), "r"(x), "r"(y) : "memory");
}
__device__ __forceinline__ void tma_store_commit() { asm volatile("cp.async.bulk.commit_group;" ::: "memory"); }
__device__ __forceinline__ void tma_store_wait_all() { asm volatile("cp.async.bulk.wait_group 0;" ::: "memory"); }
__device__ __forceinline__ void tma_store_wait_read() { asm volatile("cp.async.bulk.wait_group.read 0;" ::: "memory"); }
__device__ __forceinline__ void prefetch_tmap(const CUtensorMap* map) {
  asm volatile("prefetch.tensormap [%0];" ::"l"(map) : "memory");
}

__device__ __forceinline__ void wg_fence() { asm volatile("wgmma.fence.sync.aligned;" ::: "memory"); }
__device__ __forceinline__ void wg_commit() { asm volatile("wgmma.commit_group.sync.aligned;" ::: "memory"); }
template <int N> __device__ __forceinline__ void wg_wait() { asm volatile("wgmma.wait_group.sync.aligned %0;" ::"n"(N) : "memory"); }

#define named_bar_sync(id, n) asm volatile("bar.sync %0, %1;" ::"n"(id), "n"(n) : "memory")
#define named_bar_arrive(id, n) asm volatile("bar.arrive %0, %1;" ::"n"(id), "n"(n) : "memory")

__host__ __device__ __forceinline__ uint64_t make_desc(uint32_t addr, uint32_t lbo, uint32_t sbo) {
  return (uint64_t)((addr & 0x3FFFF) >> 4) | ((uint64_t)(lbo >> 4) << 16) | ((uint64_t)(sbo >> 4) << 32) | (1ull << 62);
}

__device__ __forceinline__ uint64_t make_desc0(uint32_t addr, uint32_t lbo, uint32_t sbo) {
  return (uint64_t)((addr & 0x3FFFF) >> 4) | ((uint64_t)(lbo >> 4) << 16) | ((uint64_t)(sbo >> 4) << 32);
}

__device__ __forceinline__ uint32_t pack_bf16(float lo, float hi) {
  uint32_t r;
  asm("cvt.rn.bf16x2.f32 %0, %1, %2;" : "=r"(r) : "f"(hi), "f"(lo));
  return r;
}
__device__ __forceinline__ float bf_lo(uint32_t v) { return __uint_as_float(v << 16); }
__device__ __forceinline__ float bf_hi(uint32_t v) { return __uint_as_float(v & 0xFFFF0000u); }
__device__ __forceinline__ float rbf(float v) { return __bfloat162float(__float2bfloat16_rn(v)); }

__device__ __forceinline__ void pdl_launch_dependents() { asm volatile("griddepcontrol.launch_dependents;" ::: "memory"); }
__device__ __forceinline__ void pdl_wait() { asm volatile("griddepcontrol.wait;" ::: "memory"); }

__device__ __forceinline__ float ex2_approx(float x) { float y; asm("ex2.approx.ftz.f32 %0, %1;" : "=f"(y) : "f"(x)); return y; }
__device__ __forceinline__ float rcp_approx(float x) { float y; asm("rcp.approx.ftz.f32 %0, %1;" : "=f"(y) : "f"(x)); return y; }

__device__ __forceinline__ void mul_sigmoid4(float (&v)[4], const float (&t)[4]) {
#pragma unroll
  for (int i = 0; i < 4; i += 2) {
    const float a = 1.0f + ex2_approx(fminf(t[i], 60.0f)), b = 1.0f + ex2_approx(fminf(t[i + 1], 60.0f));
    const float r = rcp_approx(a * b);
    v[i] *= b * r;
    v[i + 1] *= a * r;
  }
}
__device__ __forceinline__ void gelu4(float (&v)[4]) {
  float t[4];
#pragma unroll
  for (int i = 0; i < 4; i++) t[i] = v[i] * fmaf(v[i] * v[i], -0.10294324f, -2.30220819f);
  mul_sigmoid4(v, t);
}
__device__ __forceinline__ void silu4(float (&v)[4]) {
  float t[4];
#pragma unroll
  for (int i = 0; i < 4; i++) t[i] = v[i] * -1.4426950408889634f;
  mul_sigmoid4(v, t);
}

#define KT_START(id)
#define KT_END(id)

__device__ __forceinline__ void wgmma_ss_n256_tb(float (&d)[128], uint64_t da, uint64_t db, int scale_d) {
  asm volatile("{\n.reg .pred p;\nsetp.ne.b32 p, %130, 0;\n"
    "wgmma.mma_async.sync.aligned.m64n256k16.f32.bf16.bf16 "
    "{%0, %1, %2, %3, %4, %5, %6, %7, %8, %9, %10, %11, %12, %13, %14, %15, "
    "%16, %17, %18, %19, %20, %21, %22, %23, %24, %25, %26, %27, %28, %29, %30, %31, "
    "%32, %33, %34, %35, %36, %37, %38, %39, %40, %41, %42, %43, %44, %45, %46, %47, "
    "%48, %49, %50, %51, %52, %53, %54, %55, %56, %57, %58, %59, %60, %61, %62, %63, "
    "%64, %65, %66, %67, %68, %69, %70, %71, %72, %73, %74, %75, %76, %77, %78, %79, "
    "%80, %81, %82, %83, %84, %85, %86, %87, %88, %89, %90, %91, %92, %93, %94, %95, "
    "%96, %97, %98, %99, %100, %101, %102, %103, %104, %105, %106, %107, %108, %109, %110, %111, "
    "%112, %113, %114, %115, %116, %117, %118, %119, %120, %121, %122, %123, %124, %125, %126, %127}, "
    "%128, %129, p, 1, 1, 0, 1;\n}\n"
    : "+f"(d[0]), "+f"(d[1]), "+f"(d[2]), "+f"(d[3]), "+f"(d[4]), "+f"(d[5]), "+f"(d[6]), "+f"(d[7]),
      "+f"(d[8]), "+f"(d[9]), "+f"(d[10]), "+f"(d[11]), "+f"(d[12]), "+f"(d[13]), "+f"(d[14]), "+f"(d[15]),
      "+f"(d[16]), "+f"(d[17]), "+f"(d[18]), "+f"(d[19]), "+f"(d[20]), "+f"(d[21]), "+f"(d[22]), "+f"(d[23]),
      "+f"(d[24]), "+f"(d[25]), "+f"(d[26]), "+f"(d[27]), "+f"(d[28]), "+f"(d[29]), "+f"(d[30]), "+f"(d[31]),
      "+f"(d[32]), "+f"(d[33]), "+f"(d[34]), "+f"(d[35]), "+f"(d[36]), "+f"(d[37]), "+f"(d[38]), "+f"(d[39]),
      "+f"(d[40]), "+f"(d[41]), "+f"(d[42]), "+f"(d[43]), "+f"(d[44]), "+f"(d[45]), "+f"(d[46]), "+f"(d[47]),
      "+f"(d[48]), "+f"(d[49]), "+f"(d[50]), "+f"(d[51]), "+f"(d[52]), "+f"(d[53]), "+f"(d[54]), "+f"(d[55]),
      "+f"(d[56]), "+f"(d[57]), "+f"(d[58]), "+f"(d[59]), "+f"(d[60]), "+f"(d[61]), "+f"(d[62]), "+f"(d[63]),
      "+f"(d[64]), "+f"(d[65]), "+f"(d[66]), "+f"(d[67]), "+f"(d[68]), "+f"(d[69]), "+f"(d[70]), "+f"(d[71]),
      "+f"(d[72]), "+f"(d[73]), "+f"(d[74]), "+f"(d[75]), "+f"(d[76]), "+f"(d[77]), "+f"(d[78]), "+f"(d[79]),
      "+f"(d[80]), "+f"(d[81]), "+f"(d[82]), "+f"(d[83]), "+f"(d[84]), "+f"(d[85]), "+f"(d[86]), "+f"(d[87]),
      "+f"(d[88]), "+f"(d[89]), "+f"(d[90]), "+f"(d[91]), "+f"(d[92]), "+f"(d[93]), "+f"(d[94]), "+f"(d[95]),
      "+f"(d[96]), "+f"(d[97]), "+f"(d[98]), "+f"(d[99]), "+f"(d[100]), "+f"(d[101]), "+f"(d[102]), "+f"(d[103]),
      "+f"(d[104]), "+f"(d[105]), "+f"(d[106]), "+f"(d[107]), "+f"(d[108]), "+f"(d[109]), "+f"(d[110]), "+f"(d[111]),
      "+f"(d[112]), "+f"(d[113]), "+f"(d[114]), "+f"(d[115]), "+f"(d[116]), "+f"(d[117]), "+f"(d[118]), "+f"(d[119]),
      "+f"(d[120]), "+f"(d[121]), "+f"(d[122]), "+f"(d[123]), "+f"(d[124]), "+f"(d[125]), "+f"(d[126]), "+f"(d[127])
    : "l"(da), "l"(db), "r"(scale_d));
}
__device__ __forceinline__ void wgmma_rs_n32(float (&d)[16], const uint32_t* a, uint64_t db, int scale_d) {
  asm volatile("{\n.reg .pred p;\nsetp.ne.b32 p, %21, 0;\n"
    "wgmma.mma_async.sync.aligned.m64n32k16.f32.bf16.bf16 "
    "{%0, %1, %2, %3, %4, %5, %6, %7, %8, %9, %10, %11, %12, %13, %14, %15}, "
    "{%16, %17, %18, %19}, %20, p, 1, 1, 0;\n}\n"
    : "+f"(d[0]), "+f"(d[1]), "+f"(d[2]), "+f"(d[3]), "+f"(d[4]), "+f"(d[5]), "+f"(d[6]), "+f"(d[7]),
      "+f"(d[8]), "+f"(d[9]), "+f"(d[10]), "+f"(d[11]), "+f"(d[12]), "+f"(d[13]), "+f"(d[14]), "+f"(d[15])
    : "r"(a[0]), "r"(a[1]), "r"(a[2]), "r"(a[3]), "l"(db), "r"(scale_d));
}
__device__ __forceinline__ void wgmma_ss_n32_ta(float (&d)[16], uint64_t da, uint64_t db, int scale_d) {
  asm volatile("{\n.reg .pred p;\nsetp.ne.b32 p, %18, 0;\n"
    "wgmma.mma_async.sync.aligned.m64n32k16.f32.bf16.bf16 "
    "{%0, %1, %2, %3, %4, %5, %6, %7, %8, %9, %10, %11, %12, %13, %14, %15}, "
    "%16, %17, p, 1, 1, 1, 0;\n}\n"
    : "+f"(d[0]), "+f"(d[1]), "+f"(d[2]), "+f"(d[3]), "+f"(d[4]), "+f"(d[5]), "+f"(d[6]), "+f"(d[7]),
      "+f"(d[8]), "+f"(d[9]), "+f"(d[10]), "+f"(d[11]), "+f"(d[12]), "+f"(d[13]), "+f"(d[14]), "+f"(d[15])
    : "l"(da), "l"(db), "r"(scale_d));
}
__device__ __forceinline__ void wgmma_ss_n8_ta(float (&d)[4], uint64_t da, uint64_t db, int scale_d) {
  asm volatile("{\n.reg .pred p;\nsetp.ne.b32 p, %6, 0;\n"
    "wgmma.mma_async.sync.aligned.m64n8k16.f32.bf16.bf16 {%0, %1, %2, %3}, %4, %5, p, 1, 1, 1, 0;\n}\n"
    : "+f"(d[0]), "+f"(d[1]), "+f"(d[2]), "+f"(d[3]) : "l"(da), "l"(db), "r"(scale_d));
}
__device__ __forceinline__ void wgmma_ss_n48_tt(float (&d)[24], uint64_t da, uint64_t db, int scale_d) {
  asm volatile("{\n.reg .pred p;\nsetp.ne.b32 p, %26, 0;\n"
    "wgmma.mma_async.sync.aligned.m64n48k16.f32.bf16.bf16 "
    "{%0, %1, %2, %3, %4, %5, %6, %7, %8, %9, %10, %11, %12, %13, %14, %15, %16, %17, %18, %19, %20, %21, %22, %23}, "
    "%24, %25, p, 1, 1, 1, 1;\n}\n"
    : "+f"(d[0]), "+f"(d[1]), "+f"(d[2]), "+f"(d[3]), "+f"(d[4]), "+f"(d[5]), "+f"(d[6]), "+f"(d[7]), "+f"(d[8]), "+f"(d[9]), "+f"(d[10]), "+f"(d[11]), "+f"(d[12]), "+f"(d[13]), "+f"(d[14]), "+f"(d[15]), "+f"(d[16]), "+f"(d[17]), "+f"(d[18]), "+f"(d[19]), "+f"(d[20]), "+f"(d[21]), "+f"(d[22]), "+f"(d[23])
    : "l"(da), "l"(db), "r"(scale_d));
}
__device__ __forceinline__ void wgmma_ss_n32(float (&d)[16], uint64_t da, uint64_t db, int scale_d) {
  asm volatile("{\n.reg .pred p;\nsetp.ne.b32 p, %18, 0;\n"
    "wgmma.mma_async.sync.aligned.m64n32k16.f32.bf16.bf16 "
    "{%0, %1, %2, %3, %4, %5, %6, %7, %8, %9, %10, %11, %12, %13, %14, %15}, "
    "%16, %17, p, 1, 1, 0, 0;\n}\n"
    : "+f"(d[0]), "+f"(d[1]), "+f"(d[2]), "+f"(d[3]), "+f"(d[4]), "+f"(d[5]), "+f"(d[6]), "+f"(d[7]),
      "+f"(d[8]), "+f"(d[9]), "+f"(d[10]), "+f"(d[11]), "+f"(d[12]), "+f"(d[13]), "+f"(d[14]), "+f"(d[15])
    : "l"(da), "l"(db), "r"(scale_d));
}

__device__ __forceinline__ void tma_load_2d_mc(uint32_t dst, const CUtensorMap* map, int x, int y, uint32_t bar, uint16_t mask) {
  asm volatile("cp.async.bulk.tensor.2d.shared::cluster.global.mbarrier::complete_tx::bytes.multicast::cluster "
               "[%0], [%1, {%3, %4}], [%2], %5;"
               ::"r"(dst), "l"(map), "r"(bar), "r"(x), "r"(y), "h"(mask) : "memory");
}
__device__ __forceinline__ void mbar_arrive_cluster(uint32_t bar, uint32_t cta) {
  asm volatile("{\n.reg .b32 r;\nmapa.shared::cluster.u32 r, %0, %1;\nmbarrier.arrive.shared::cluster.b64 _, [r];\n}"
               ::"r"(bar), "r"(cta) : "memory");
}
__device__ __forceinline__ void cluster_sync() {
  asm volatile("barrier.cluster.arrive.release.aligned;\nbarrier.cluster.wait.acquire.aligned;" ::: "memory");
}
__device__ __forceinline__ void wait_count(const unsigned* p, unsigned need) {
#pragma unroll 1
  for (int tries = 0; tries < (1 << 18); tries++) {
    unsigned v;
    asm volatile("ld.acquire.gpu.global.u32 %0, [%1];" : "=r"(v) : "l"(p) : "memory");
    if (v >= need) break;
    __nanosleep(64);
  }
}
__device__ __forceinline__ uint32_t sub_bf16x2(uint32_t a, uint32_t b) {
  uint32_t d;
  asm("sub.rn.bf16x2 %0, %1, %2;" : "=r"(d) : "r"(a), "r"(b));
  return d;
}
__device__ __forceinline__ uint32_t add_bf16x2(uint32_t a, uint32_t b) {
  uint32_t d;
  asm("add.rn.bf16x2 %0, %1, %2;" : "=r"(d) : "r"(a), "r"(b));
  return d;
}
__device__ __forceinline__ uint32_t mul_bf16x2(uint32_t a, uint32_t b) {
  uint32_t d;
  asm("mul.rn.bf16x2 %0, %1, %2;" : "=r"(d) : "r"(a), "r"(b));
  return d;
}

template <int NR>
__device__ __forceinline__ void ln_regs(uint32_t (&raw)[NR][16]) {
  float m[NR], q[NR];
#pragma unroll
  for (int r = 0; r < NR; r++) {
    float s0 = 0.f, s1 = 0.f;
#pragma unroll
    for (int i = 0; i < 16; i++) { s0 += bf_lo(raw[r][i]); s1 += bf_hi(raw[r][i]); }
    m[r] = s0 + s1;
  }
#pragma unroll
  for (int o = 16; o > 0; o >>= 1)
#pragma unroll
    for (int r = 0; r < NR; r++) m[r] += __shfl_xor_sync(0xffffffffu, m[r], o);
#pragma unroll
  for (int r = 0; r < NR; r++) {
    m[r] *= 1.0f / 1024.0f;
    float s0 = 0.f, s1 = 0.f;
#pragma unroll
    for (int i = 0; i < 16; i++) {
      const float d0 = bf_lo(raw[r][i]) - m[r], d1 = bf_hi(raw[r][i]) - m[r];
      s0 = fmaf(d0, d0, s0); s1 = fmaf(d1, d1, s1);
    }
    q[r] = s0 + s1;
  }
#pragma unroll
  for (int o = 16; o > 0; o >>= 1)
#pragma unroll
    for (int r = 0; r < NR; r++) q[r] += __shfl_xor_sync(0xffffffffu, q[r], o);
#pragma unroll
  for (int r = 0; r < NR; r++) {
    const uint32_t mb = pack_bf16(m[r], m[r]);
    float sq;
    asm("sqrt.approx.f32 %0, %1;" : "=f"(sq) : "f"(rbf(rbf(q[r] * (1.0f / 1024.0f)) + 1e-5f)));
    const float inv = rcp_approx(rbf(sq));
#pragma unroll
    for (int i = 0; i < 16; i++) {
      const uint32_t d = sub_bf16x2(raw[r][i], mb);
      raw[r][i] = pack_bf16(bf_lo(d) * inv, bf_hi(d) * inv);
    }
  }
}
__device__ __forceinline__ void load_row16(uint32_t (&raw)[16], const bf16* src, int lane) {
#pragma unroll
  for (int j = 0; j < 4; j++) {
    const uint4 u = __ldcg(reinterpret_cast<const uint4*>(src + j * 256 + lane * 8));
    raw[4 * j] = u.x; raw[4 * j + 1] = u.y; raw[4 * j + 2] = u.z; raw[4 * j + 3] = u.w;
  }
}
__device__ __forceinline__ void store_row16(const uint32_t (&raw)[16], bf16* dst, int lane) {
#pragma unroll
  for (int j = 0; j < 4; j++)
    *reinterpret_cast<uint4*>(dst + j * 256 + lane * 8) = make_uint4(raw[4 * j], raw[4 * j + 1], raw[4 * j + 2], raw[4 * j + 3]);
}

namespace fk {
constexpr uint32_t SM0 = 1024;
constexpr uint32_t WO = SM0, WS = WO + 90112, XN = WS + 65536, VX = XN + 49152, QK = VX + 8192, PT = QK + 8192,
                   SP = PT + 4096, VM = SP + 2560, OB = VM + 2048, BAR = OB + 2048;
constexpr uint32_t MEMB = XN + 16384, RED = XN + 32768, VX2 = WO + 81920;
constexpr int SMEM = 232448;
static_assert(BAR + 512 == SM0 + SMEM, "shared memory layout");
constexpr uint32_t B_XN = BAR, B_H2 = BAR + 64, B_H1 = BAR + 120, ONES = BAR + 384, B_PF = BAR + 16, B_WO = BAR + 24, B_SM = BAR + 32, B_VM = BAR + 40, B_VX = BAR + 48, B_ST = BAR + 56, B_PB = BAR + 64, B_W = BAR + 112,
                   MASKS = BAR + 128, PROBE = BAR + 256;
constexpr int NB_M0 = 1, NB_M1 = 2, NB_C = 3, NB_O = 4, NB_ST = 5, NB_DU = 6, NB_CF = 7, NB_W1 = 8, NB_XE = 9, NB_HD = 10, NB_MX = 11, NB_O0 = 12;
#define D_H1 500
#define D_H2 1900
#define D_ST 100
#define SMQ 0x1E
#define SMV 0x1E
#define PRE_G 5
#define WO_AT 4
#define NS0 4
#define NS0V 4
#define NTA0 2
#define NTA1 1
#define PF0A 3
#define PF0 10
#define PF1A 0
#define PF1V 10
#define PF1 11
#define REFILL_EARLY 1
#define GATE_MX 0
#define GATE_Q 0
#define PF1Q 4
#define PACEQ 0x60
#define PACEV 0
#define PADD 1
#define VM_BULK 0
#define CF_AT 0
#define H2_AT 1
#define NPRE0 1
#define PROBE_N 4
#define SPACK 0
constexpr uint32_t SPW = SPACK ? 4 : 8, SP_SRC = 160 * SPW;
constexpr int H1_BYTES = 64 * 32768, H2_BYTES = 8 * 8192;
}

#define PROF(wg, i)
#define PROF2(i)
#define RETRY(i)
#define GTSYNC(i)
#define PRO(i)
#define TL(i)
#define TL2(t, i)

__device__ uint4 g_xch[(fk::H1_BYTES + fk::H2_BYTES + 8192) / 16];
__device__ __align__(16) unsigned g_mask[128];
__device__ unsigned g_cnt[6][16];
__device__ unsigned g_next;
constexpr int TAIL_MB0 = 10, GATE_CNT = 12;
__device__ __align__(16) unsigned g_tfix[96], g_lnok[4];
__device__ uint4 g_tpart[96][3][4][256];
__device__ unsigned g_oflag[16];

#define LD_POLL "ld.global.L1::no_allocate"
__device__ __forceinline__ uint4 ld_poll16(const void* p) {
  uint4 v;
  asm volatile(LD_POLL ".v4.u32 {%0,%1,%2,%3}, [%4];" : "=r"(v.x), "=r"(v.y), "=r"(v.z), "=r"(v.w) : "l"(p) : "memory");
  return v;
}
__device__ __forceinline__ uint2 ld_poll8(const void* p) {
  uint2 v;
  asm volatile(LD_POLL ".v2.u32 {%0,%1}, [%2];" : "=r"(v.x), "=r"(v.y) : "l"(p) : "memory");
  return v;
}
__device__ __forceinline__ uint4 ld_strong16(const void* p) {
  uint4 v;
  asm volatile("ld.relaxed.gpu.global.v4.u32 {%0,%1,%2,%3}, [%4];" : "=r"(v.x), "=r"(v.y), "=r"(v.z), "=r"(v.w) : "l"(p) : "memory");
  return v;
}
__device__ __forceinline__ uint2 ld_strong8(const void* p) {
  uint2 v;
  asm volatile("ld.relaxed.gpu.global.v2.u32 {%0,%1}, [%2];" : "=r"(v.x), "=r"(v.y) : "l"(p) : "memory");
  return v;
}
__device__ __forceinline__ void st_pub32(void* p, uint32_t v) { asm volatile("st.relaxed.gpu.global.u32 [%0], %1;" ::"l"(p), "r"(v) : "memory"); }
__device__ __forceinline__ void st_pub16(void* p, uint32_t v) {
  asm volatile("st.relaxed.gpu.global.u16 [%0], %1;" ::"l"(p), "h"((uint16_t)v) : "memory");
}
__device__ __forceinline__ uint32_t ld_strong4(const void* p) {
  uint32_t v;
  asm volatile("ld.relaxed.gpu.global.u32 %0, [%1];" : "=r"(v) : "l"(p) : "memory");
  return v;
}
__device__ __forceinline__ void st_pub64(void* p, uint32_t a, uint32_t b) {
  asm volatile("st.relaxed.gpu.global.v2.u32 [%0], {%1,%2};" ::"l"(p), "r"(a), "r"(b) : "memory");
}
__device__ __forceinline__ void st_pub128(void* p, uint32_t a) {
  asm volatile("st.relaxed.gpu.global.v4.u32 [%0], {%1,%1,%1,%1};" ::"l"(p), "r"(a) : "memory");
}
constexpr uint32_t EMPTY = 0xFFFFFFFFu;
__device__ __forceinline__ uint32_t umax4(const uint4& v) { return max(max(v.x, v.y), max(v.z, v.w)); }
__device__ __forceinline__ void sts128(uint32_t a, uint32_t x, uint32_t y, uint32_t z, uint32_t w) {
  asm volatile("st.shared.v4.u32 [%0], {%1,%2,%3,%4};" ::"r"(a), "r"(x), "r"(y), "r"(z), "r"(w) : "memory");
}
__device__ __forceinline__ void sts64(uint32_t a, uint32_t x, uint32_t y) {
  asm volatile("st.shared.v2.u32 [%0], {%1,%2};" ::"r"(a), "r"(x), "r"(y) : "memory");
}
__device__ __forceinline__ void sts32(uint32_t a, uint32_t x) { asm volatile("st.shared.u32 [%0], %1;" ::"r"(a), "r"(x) : "memory"); }
__device__ __forceinline__ void sts128f(uint32_t a, float x, float y, float z, float w) {
  asm volatile("st.shared.v4.f32 [%0], {%1,%2,%3,%4};" ::"r"(a), "f"(x), "f"(y), "f"(z), "f"(w) : "memory");
}
__device__ __forceinline__ void sts64f(uint32_t a, float x, float y) {
  asm volatile("st.shared.v2.f32 [%0], {%1,%2};" ::"r"(a), "f"(x), "f"(y) : "memory");
}
__device__ __forceinline__ float4 lds128f(uint32_t a) {
  float4 v;
  asm volatile("ld.shared.v4.f32 {%0,%1,%2,%3}, [%4];" : "=f"(v.x), "=f"(v.y), "=f"(v.z), "=f"(v.w) : "r"(a) : "memory");
  return v;
}
__device__ __forceinline__ float2 lds64f(uint32_t a) {
  float2 v;
  asm volatile("ld.shared.v2.f32 {%0,%1}, [%2];" : "=f"(v.x), "=f"(v.y) : "r"(a) : "memory");
  return v;
}
__device__ __forceinline__ float2 lds64f_if(uint32_t a, bool on, float other) {
  float2 v = make_float2(other, other);
  asm volatile("{\n.reg .pred p;\nsetp.ne.u32 p, %3, 0;\n@p ld.shared.v2.f32 {%0,%1}, [%2];\n}" : "+f"(v.x), "+f"(v.y) : "r"(a), "r"((uint32_t)on) : "memory");
  return v;
}
__device__ __forceinline__ void lds128(uint32_t* r, uint32_t a) {
  asm volatile("ld.shared.v4.u32 {%0,%1,%2,%3}, [%4];" : "=r"(r[0]), "=r"(r[1]), "=r"(r[2]), "=r"(r[3]) : "r"(a) : "memory");
}
__device__ __forceinline__ void lds64(uint32_t* r, uint32_t a) {
  asm volatile("ld.shared.v2.u32 {%0,%1}, [%2];" : "=r"(r[0]), "=r"(r[1]) : "r"(a) : "memory");
}
__device__ __forceinline__ uint32_t lds32(uint32_t a) {
  uint32_t v;
  asm volatile("ld.shared.u32 %0, [%1];" : "=r"(v) : "r"(a) : "memory");
  return v;
}
__device__ __forceinline__ void ldsm4(uint32_t* r, uint32_t a) {
  asm volatile("ldmatrix.sync.aligned.m8n8.x4.shared.b16 {%0,%1,%2,%3}, [%4];"
               : "=r"(r[0]), "=r"(r[1]), "=r"(r[2]), "=r"(r[3]) : "r"(a) : "memory");
}
__device__ __forceinline__ void ldsm4t(uint32_t* r, uint32_t a) {
  asm volatile("ldmatrix.sync.aligned.m8n8.x4.trans.shared.b16 {%0,%1,%2,%3}, [%4];"
               : "=r"(r[0]), "=r"(r[1]), "=r"(r[2]), "=r"(r[3]) : "r"(a) : "memory");
}
__device__ __forceinline__ void stsm4(uint32_t a, uint32_t r0, uint32_t r1, uint32_t r2, uint32_t r3) {
  asm volatile("stmatrix.sync.aligned.m8n8.x4.shared.b16 [%0], {%1,%2,%3,%4};"
               ::"r"(a), "r"(r0), "r"(r1), "r"(r2), "r"(r3) : "memory");
}
__device__ __forceinline__ void stsm4t(uint32_t a, uint32_t r0, uint32_t r1, uint32_t r2, uint32_t r3) {
  asm volatile("stmatrix.sync.aligned.m8n8.x4.trans.shared.b16 [%0], {%1,%2,%3,%4};"
               ::"r"(a), "r"(r0), "r"(r1), "r"(r2), "r"(r3) : "memory");
}
__device__ __forceinline__ void mma16816(float* d, const uint32_t* a, uint32_t b0, uint32_t b1) {
  asm volatile("mma.sync.aligned.m16n8k16.row.col.f32.bf16.bf16.f32 {%0,%1,%2,%3}, {%4,%5,%6,%7}, {%8,%9}, {%0,%1,%2,%3};"
               : "+f"(d[0]), "+f"(d[1]), "+f"(d[2]), "+f"(d[3])
               : "r"(a[0]), "r"(a[1]), "r"(a[2]), "r"(a[3]), "r"(b0), "r"(b1));
}
__device__ __forceinline__ void mma16816z(float* d, const uint32_t* a, uint32_t b0, uint32_t b1) {
  asm volatile("mma.sync.aligned.m16n8k16.row.col.f32.bf16.bf16.f32 {%0,%1,%2,%3}, {%4,%5,%6,%7}, {%8,%9}, {%10,%10,%10,%10};"
               : "=f"(d[0]), "=f"(d[1]), "=f"(d[2]), "=f"(d[3])
               : "r"(a[0]), "r"(a[1]), "r"(a[2]), "r"(a[3]), "r"(b0), "r"(b1), "f"(0.f));
}
__device__ __forceinline__ void mma1688(float* d, uint32_t a0, uint32_t a1, uint32_t b0) {
  asm volatile("mma.sync.aligned.m16n8k8.row.col.f32.bf16.bf16.f32 {%0,%1,%2,%3}, {%4,%5}, {%6}, {%0,%1,%2,%3};"
               : "+f"(d[0]), "+f"(d[1]), "+f"(d[2]), "+f"(d[3]) : "r"(a0), "r"(a1), "r"(b0));
}
__device__ __forceinline__ uint32_t movtrans(uint32_t a) {
  uint32_t d;
  asm volatile("movmatrix.sync.aligned.m8n8.trans.b16 %0, %1;" : "=r"(d) : "r"(a));
  return d;
}
__device__ __forceinline__ uint32_t mapa(uint32_t a, uint32_t rank) {
  uint32_t d;
  asm("mapa.shared::cluster.u32 %0, %1, %2;" : "=r"(d) : "r"(a), "r"(rank));
  return d;
}
__device__ __forceinline__ void st_async64(uint32_t a, uint32_t x, uint32_t y, uint32_t bar) {
  asm volatile("st.async.weak.shared::cluster.mbarrier::complete_tx::bytes.v2.b32 [%0], {%1,%2}, [%3];"
               ::"r"(a), "r"(x), "r"(y), "r"(bar) : "memory");
}
__device__ __forceinline__ void st_async64f(uint32_t a, float x, float y, uint32_t bar) {
  st_async64(a, __float_as_uint(x), __float_as_uint(y), bar);
}
__device__ __forceinline__ void bulk_s2s(uint32_t dst, uint32_t src, uint32_t bytes, uint32_t bar) {
  asm volatile("cp.async.bulk.shared::cluster.shared::cta.mbarrier::complete_tx::bytes [%0], [%1], %2, [%3];"
               ::"r"(dst), "r"(src), "r"(bytes), "r"(bar) : "memory");
}
__device__ __forceinline__ void tma_store_3d(const CUtensorMap* map, uint32_t src, int x, int y, int z) {
  asm volatile("cp.async.bulk.tensor.3d.global.shared::cta.bulk_group [%0, {%2, %3, %4}], [%1];"
               ::"l"(map), "r"(src), "r"(x), "r"(y), "r"(z) : "memory");
}
__device__ __forceinline__ void mbar_spin(uint32_t bar, uint32_t parity) {
  asm volatile("{\n.reg .pred p;\n.reg .b32 n;\nmov.u32 n, 0x100000;\nMW_L:\n"
               "mbarrier.try_wait.parity.shared::cta.b64 p, [%0], %1;\n@p bra.uni MW_D;\n"
               "add.s32 n, n, -1;\nsetp.ne.u32 p, n, 0;\n@p bra.uni MW_L;\nMW_D:\n}" ::"r"(bar), "r"(parity) : "memory");
}
__device__ __forceinline__ bool mbar_test(uint32_t bar, uint32_t parity) {
  uint32_t done;
  asm volatile("{\n.reg .pred p;\nmbarrier.test_wait.parity.shared::cta.b64 p, [%1], %2;\nselp.u32 %0, 1, 0, p;\n}"
               : "=r"(done) : "r"(bar), "r"(parity) : "memory");
  return done != 0;
}
__device__ __forceinline__ void mbar_arrive_remote(uint32_t bar) {
  asm volatile("mbarrier.arrive.shared::cluster.b64 _, [%0];" ::"r"(bar) : "memory");
}
__device__ __forceinline__ bool elect_one() {
  uint32_t r;
  asm volatile("{\n.reg .pred p;\nelect.sync _|p, 0xffffffff;\nselp.u32 %0, 1, 0, p;\n}" : "=r"(r));
  return r != 0;
}
__device__ __forceinline__ void st_async32(uint32_t a, uint32_t x, uint32_t bar) {
  asm volatile("st.async.weak.shared::cluster.mbarrier::complete_tx::bytes.b32 [%0], %1, [%2];" ::"r"(a), "r"(x), "r"(bar) : "memory");
}
#define named_bar_and(id, n, in, out) \
  asm volatile("{\n.reg .pred p, q;\nsetp.ne.u32 p, %1, 0;\nbar.red.and.pred q, %2, %3, p;\nselp.u32 %0, 1, 0, q;\n}" \
               : "=r"(out) : "r"(in), "n"(id), "n"(n) : "memory")
__device__ __forceinline__ void bulk_g2s(uint32_t dst, const void* src, uint32_t bytes, uint32_t bar) {
  asm volatile("cp.async.bulk.shared::cluster.global.mbarrier::complete_tx::bytes [%0], [%1], %2, [%3];"
               ::"r"(dst), "l"(src), "r"(bytes), "r"(bar) : "memory");
}
__device__ __forceinline__ void l2_prefetch(const void* p, uint32_t bytes) {
  asm volatile("cp.async.bulk.prefetch.L2.global [%0], %1;" ::"l"(p), "r"(bytes) : "memory");
}

__device__ __forceinline__ uint32_t clk32() { uint32_t c; asm volatile("mov.u32 %0, %%clock;" : "=r"(c)::"memory"); return c; }
__device__ __forceinline__ void spin_until(uint32_t t) { while ((int32_t)(clk32() - t) < 0) {} }
#define PIN(x) asm volatile("" : "+r"(x))
#define OPQ                                                                                     \
  int tid_o = tid;                                                                              \
  asm volatile("" : "+r"(tid_o));                                                               \
  const int lane = tid_o & 31, w = (tid_o >> 5) & 3, t7 = tid_o & 127, lg = lane >> 2,          \
            lq = lane & 3, mi = lane >> 3, mr = lane & 7;                                       \
  (void)w; (void)t7; (void)lg; (void)lq; (void)mi; (void)mr; (void)lane

#define SMAP                                                                                                          \
  const uint32_t SM0 = self + fk::SM0, WO = self + fk::WO, WS = self + fk::WS, XN = self + fk::XN, VX = self + fk::VX, \
                 QK = self + fk::QK, PT = self + fk::PT, SP = self + fk::SP, VM = self + fk::VM, OB = self + fk::OB,   \
                 RED = self + fk::RED, VX2 = self + fk::VX2, MEMB = self + fk::MEMB, B_XN = self + fk::B_XN, B_SM = self + fk::B_SM,       \
                 B_VM = self + fk::B_VM, B_VX = self + fk::B_VX, B_ST = self + fk::B_ST, B_PB = self + fk::B_PB,       \
                 B_W = self + fk::B_W, B_H2 = self + fk::B_H2, B_H1 = self + fk::B_H1, B_PF = self + fk::B_PF, B_WO = self + fk::B_WO, MASKS = self + fk::MASKS, PROBE = self + fk::PROBE;                             \
  (void)SM0; (void)WO; (void)WS; (void)XN; (void)VX; (void)QK; (void)PT; (void)SP; (void)VM; (void)OB; (void)RED; (void)VX2; \
  (void)MEMB; (void)B_XN; (void)B_SM; (void)B_VM; (void)B_VX; (void)B_ST; (void)B_PB; (void)B_W; (void)MASKS; (void)PROBE; (void)B_H2; (void)B_H1; (void)B_PF; (void)B_WO

struct FParams {
  CUtensorMap wq, wk, wv, wo, wo16, xn, xn12, o;
  CUtensorMap ta, tb, tx, tg, tout;
  const bf16 *mem0, *x, *w1;
  bf16 *xn_ptr, *xn2;
  uint64_t dxn;
  int nprobe;
  char* xch;
};

__device__ __forceinline__ uint2 probe_pair(char* p, uint32_t val, uint32_t dummy, int n) {
  uint2 best = make_uint2(0x7FFFFFFF, 0x7FFFFFFF);
  st_pub128(p, val); st_pub128(p + 16, val); st_pub128(p + 4096, val); st_pub128(p + 4112, val);
#pragma unroll 1
  for (int r = 0; r < n; r++) {
    uint32_t v;
    const uint32_t c0 = clk32();
    asm volatile("atom.relaxed.gpu.global.exch.b32 %0, [%1], %2;" : "=r"(v) : "l"(p + (r & 1) * 4096), "r"(val) : "memory");
    asm volatile("{\n.reg .pred p;\nsetp.eq.u32 p, %0, 0x12345678;\n@p st.shared.u32 [%1], %0;\n}" ::"r"(v), "r"(dummy) : "memory");
    const uint32_t d = clk32() - c0;
    if (r & 1) best.y = min(best.y, d); else best.x = min(best.x, d);
  }
  return best;
}

typedef uint32_t WRegs[6][2][4][4];

constexpr uint32_t nth_chunks(uint32_t mask) {
  uint32_t t = 0;
  for (int c = 0, n = 0; c < 10; c++) if ((mask >> c) & 1) t |= c << (4 * n++);
  return t;
}
constexpr uint64_t chunk_pos(uint32_t mask) {
  uint64_t t = 0;
  for (int c = 0, a = 0, b = 0; c < 10; c++) t |= (uint64_t)(((mask >> c) & 1) ? a++ : b++) << (4 * c);
  return t;
}
template <bool ISV> struct Chunks {
  static constexpr uint32_t MASK = ISV ? SMV : SMQ, SMT = nth_chunks(MASK), RFT = nth_chunks(~MASK & 1023);
  static_assert(!(MASK & 1), "the first chunk initialises the accumulators");
  static __device__ __forceinline__ constexpr int rf(int wg, int i) { return wg ? 10 + i : (RFT >> (4 * i)) & 15; }
  static __device__ __forceinline__ constexpr int sm(int i) { return (SMT >> (4 * i)) & 15; }
  static constexpr uint64_t IDX = chunk_pos(MASK);
  static __device__ __forceinline__ constexpr int idx(int c) { return (IDX >> (4 * c)) & 15; }
};

template <bool ISV, int WG> struct ProjCfg {
  static constexpr int N0 = ISV ? NS0V : NS0, NS = WG ? 8 - N0 : N0, P0 = WG ? N0 : 0, NTA = WG ? NTA1 : NTA0;
};
__device__ __forceinline__ void load_pair(uint32_t (&t)[4][4], uint32_t wsa, int pp) {
#pragma unroll
  for (int f = 0; f < 4; f++) ldsm4t(t[f], wsa + ((pp >> 1) * 2 + (f & 1)) * 8192 + ((pp & 1) * 2 + (f >> 1)) * 2048);
}
template <bool ISV, int WG>
__device__ __forceinline__ void proj_mem(const WRegs& wr, uint32_t (&ta)[ProjCfg<ISV, WG>::NTA][4][4], uint32_t wsa, uint32_t mba,
                                         float (&a0)[4], float (&a1)[4]) {
  constexpr int NS = ProjCfg<ISV, WG>::NS, P0 = ProjCfg<ISV, WG>::P0, NTA = ProjCfg<ISV, WG>::NTA, NP = 12 + NS;
  float acc[4][4];
  auto spos = [](int j) { return j < NTA ? j : j + (j - NTA + 1) * 12 / (NS - NTA > 0 ? NS - NTA : 1); };
  auto which = [&](int p) { int r = -1; for (int j = 0; j < NS; j++) if (spos(j) == p) r = j; return r; };
  auto nsm_before = [&](int p) { int n = 0; for (int j = 0; j < NS; j++) if (spos(j) < p) n++; return n; };
#pragma unroll
  for (int p = 0; p < NP; p++) {
    const int j = which(p), r = j >= 0 ? 0 : p - nsm_before(p);
    uint32_t bp[4], tl[4][4];
    ldsm4(bp, mba + (j >= 0 ? Chunks<ISV>::sm((P0 + (j >= 0 ? j : 0)) >> 1) * 1024 + ((P0 + j) & 1) * 512 : Chunks<ISV>::rf(WG, r >> 1) * 1024 + (r & 1) * 512));
    if (j >= NTA) load_pair(tl, wsa, P0 + j);
#pragma unroll
    for (int u = 0; u < 2; u++)
#pragma unroll
      for (int T = 0; T < 2; T++) {
        const uint32_t* a = j >= NTA ? tl[u * 2 + T] : j >= 0 ? ta[j >= 0 ? j % NTA : 0][u * 2 + T] : wr[r >> 1][T][(r & 1) * 2 + u];
        if (p == 0) mma16816z(acc[u * 2 + T], a, bp[2 * u], bp[2 * u + 1]);
        else mma16816(acc[u * 2 + T], a, bp[2 * u], bp[2 * u + 1]);
      }
  }
#pragma unroll
  for (int i = 0; i < 4; i++) { a0[i] = acc[0][i] + acc[2][i]; a1[i] = acc[1][i] + acc[3][i]; }
}
template <bool ISV, int WG, int J0, int J1>
__device__ __forceinline__ void proj_mem_prefetch(uint32_t (&ta)[ProjCfg<ISV, WG>::NTA][4][4], uint32_t wsa) {
#pragma unroll
  for (int j = J0; j < J1; j++) load_pair(ta[j], wsa, ProjCfg<ISV, WG>::P0 + j);
}

template <bool ISV, int WG>
__device__ __forceinline__ void proj_finish(const float (&a0)[4], const float (&a1)[4], uint32_t peer0, uint32_t peer1, uint32_t self, int tid, int warp,
                                            uint32_t (&vmo)[4]) {
  using namespace fk;
  SMAP;
  OPQ;
  if (!ISV) {
    stsm4(PT + mr * 16 + ((mi >> 1) ? WG * 1024 + w * 256 + (mi & 1) * 128 : 2048 + w * 512 + (mi & 1) * 256 + WG * 128),
          pack_bf16(a0[0], a0[1]), pack_bf16(a0[2], a0[3]), pack_bf16(a1[0], a1[1]), pack_bf16(a1[2], a1[3]));
    named_bar_sync(NB_C, 256);
  } else {
    if (WG == 0) sts128f(RED + t7 * 16, a1[0], a1[1], a1[2], a1[3]);
    else sts128f(RED + 2048 + t7 * 16, a0[0], a0[1], a0[2], a0[3]);
    if (WG == 1) { lds64(vmo, VM + t7 * 8); lds64(vmo + 2, VM + 1024 + t7 * 8); }
    named_bar_sync(NB_C, 256);
    const float4 p = lds128f(RED + (1 - WG) * 2048 + t7 * 16);
    const float* k = WG == 0 ? a0 : a1;
    const uint32_t v0 = pack_bf16(k[0] + p.x, k[1] + p.y), v1 = pack_bf16(k[2] + p.z, k[3] + p.w);
    const uint32_t off = VM + WG * 1024 + t7 * 8;
    if (VM_BULK) {
      sts64(off, v0, v1);
      fence_proxy_async_smem();
      __syncwarp();
      const uint32_t a = VM + WG * 1024 + warp * 256;
      if (elect_one()) {
        bulk_s2s(peer0 + a, a, 256, peer0 + B_VM);
        bulk_s2s(peer1 + a, a, 256, peer1 + B_VM);
        mbar_arrive(B_VM);
      }
    } else {
      st_async64(peer0 + off, v0, v1, peer0 + B_VM);
      st_async64(peer1 + off, v0, v1, peer1 + B_VM);
      sts64(off, v0, v1);
      __syncwarp();
      if (lane == 0) mbar_arrive(B_VM);
    }
  }
}

__device__ __forceinline__ void send_scores(float s0, float s1, uint32_t off, uint32_t peer0, uint32_t peer1, uint32_t bar, int lane) {
  if (SPACK) {
    const uint32_t v = pack_bf16(s0, s1);
    st_async32(peer0 + off, v, peer0 + bar);
    st_async32(peer1 + off, v, peer1 + bar);
    sts32(off, v);
  } else {
    st_async64f(peer0 + off, s0, s1, peer0 + bar);
    st_async64f(peer1 + off, s0, s1, peer1 + bar);
    sts64f(off, s0, s1);
  }
  __syncwarp();
  if (lane == 0) mbar_arrive(bar);
}

template <int MODE>
__device__ __forceinline__ void wo_load(uint32_t* r, int f, uint32_t woa, uint32_t wob, bool third) {
  constexpr int NT = MODE ? 3 : 2;
  if (MODE == 2 && f % 3 == 2)
    asm volatile("{\n.reg .pred p;\nsetp.ne.u32 p, %5, 0;\nmov.b32 %0, 0;\nmov.b32 %1, 0;\nmov.b32 %2, 0;\nmov.b32 %3, 0;\n"
                 "@p ldmatrix.sync.aligned.m8n8.x4.trans.shared.b16 {%0,%1,%2,%3}, [%4];\n}"
                 : "=r"(r[0]), "=r"(r[1]), "=r"(r[2]), "=r"(r[3]) : "r"(wob + (f / 3) * 512), "r"((uint32_t)third) : "memory");
  else ldsm4t(r, woa + (f % NT) * 32768 + (f / NT) * 2048);
}
template <int MODE, int PF>
__device__ __forceinline__ void wo_phase(uint32_t (&wf)[PF][4], uint32_t woa, uint32_t wob, bool third, uint32_t oba, char* h1p,
                                         uint32_t sel, uint32_t tag) {
  constexpr int NT = MODE ? 3 : 2;
  float c[NT][4];
  uint32_t of[2][4];
  ldsm4t(of[0], oba);
#pragma unroll
  for (int k = 0; k < 8; k++) {
    if ((k & 1) == 0 && k + 2 < 8) ldsm4t(of[((k >> 1) + 1) & 1], oba + ((k >> 1) + 1) * 512);
#pragma unroll
    for (int i = 0; i < NT; i++) {
      const int f = k * NT + i;
      const uint32_t b0 = of[(k >> 1) & 1][2 * (k & 1)], b1 = of[(k >> 1) & 1][2 * (k & 1) + 1];
      if (k == 0) mma16816z(c[i], wf[f % PF], b0, b1); else mma16816(c[i], wf[f % PF], b0, b1);
      if (f + PF < 8 * NT) wo_load<MODE>(wf[f % PF], f + PF, woa, wob, third);
    }
  }
#pragma unroll
  for (int i = 0; i < NT; i++) {
    char* p = h1p + i * (8 * 32768) + ((sel >> (2 * i)) & 3) * 2048;
    const uint32_t tm = (sel >> 10) & 1;
    if (MODE != 2 || i < 2 || third) {
      st_pub32(p, (pack_bf16(c[i][0], c[i][1]) & ~tm) | (tag & tm));
      st_pub32(p + 1024, (pack_bf16(c[i][2], c[i][3]) & ~tm) | (tag & tm));
    }
  }
}
template <int MODE, int F0, int F1, int PF>
__device__ __forceinline__ void wo_prefetch(uint32_t (&wf)[PF][4], uint32_t woa, uint32_t wob, bool third) {
#pragma unroll
  for (int f = F0; f < F1; f++) wo_load<MODE>(wf[f], f, woa, wob, third);
}

template <bool ISV> __device__ __forceinline__ uint32_t tok_addr(uint32_t base, int tid) {
  OPQ;
  return ISV ? base + w * 2048 + (mi & 1) * 1024 + (mi >> 1) * 128 + mr * 16 : base + (mi >> 1) * 1024 + w * 256 + (mi & 1) * 128 + mr * 16;
}
template <bool ISV> __device__ __forceinline__ constexpr uint32_t tok_off(int T, int i) { return ISV ? T * 512 + i * 256 : T * 4096 + i * 2048; }
template <bool ISV, int T, bool ADD>
__device__ __forceinline__ void tok_store(const float (&x)[16], uint32_t a, const uint32_t (&p)[2][4]) {
#pragma unroll
  for (int i = 0; i < 2; i++) {
    uint32_t r[4];
#pragma unroll
    for (int k = 0; k < 4; k++)
      r[k] = !ADD ? pack_bf16(x[8 * i + 2 * k], x[8 * i + 2 * k + 1])
           : PADD ? add_bf16x2(pack_bf16(x[8 * i + 2 * k], x[8 * i + 2 * k + 1]), p[i][k])
                  : pack_bf16(x[8 * i + 2 * k] + bf_lo(p[i][k]), x[8 * i + 2 * k + 1] + bf_hi(p[i][k]));
    stsm4(a + tok_off<ISV>(T, i), r[0], r[1], r[2], r[3]);
  }
}

__device__ __forceinline__ void load_xn(const FParams& P, int seg, uint32_t self) {
  SMAP;
  mbar_expect_tx(B_XN, 49152);
  tma_load_3d(XN, &P.xn12, 0, seg * 32, 0, B_XN);
}

#define xn_desc(slot, u) (P.dxn + ((slot) * 256 + (u) * 2))
#define xn_desc_c(slot, u) make_desc(fk::XN + (slot) * 4096 + (u) * 32, 16, 1024)

template <bool ISV>
__device__ __forceinline__ void f_wg0(const FParams& P, const WRegs& wr, const int h, const int rank, const uint32_t hw, int tid) {
  using namespace fk;
  const uint32_t self = mapa(0, (hw >> (2 * rank)) & 3), peer0 = mapa(0, (hw >> (ISV ? 0 : 2 * (rank ^ 1))) & 3) - self,
                 peer1 = mapa(0, (hw >> (ISV ? 2 : 4)) & 3) - self;
  SMAP;
  const int tile0 = rank * 22;
  const int warp = __shfl_sync(0xffffffffu, threadIdx.x >> 5, 0);
  const bool three = !ISV && warp < 2;
  uint32_t h2ph = 1;
  tid ^= 0x5500;
#pragma unroll 1
  for (int s = -1;;) {
    uint32_t ta[ProjCfg<ISV, 0>::NTA][4][4], wsa, mba;
    const char* src = P.xch + H1_BYTES + ((s & 1) * 4 + warp) * 8192 + __shfl_sync(0xffffffffu, (tid >> (16 + (s & 1))) & 1, 0) * 4096;
    {
      const uint32_t ph = (s + 1) & 1;
      float x0[16], x1[16];
      uint32_t t_pub = 0;
      wg_fence();
#pragma unroll
      for (int c = 0; c < 10; c++) {
        if (c == 9) named_bar_arrive(NB_ST, 256);
#pragma unroll
        for (int u = 0; u < 4; u++) {
          const int ci = Chunks<ISV>::idx(c);
          if ((Chunks<ISV>::MASK >> c) & 1) {
            wgmma_ss_n32_ta(x0, make_desc(fk::WS + ci * 16384 + u * 2048, 8192, 1024), xn_desc_c(c, u), 1);
            wgmma_ss_n32_ta(x1, make_desc(fk::WS + ci * 16384 + 8192 + u * 2048, 8192, 1024), xn_desc_c(c, u), 1);
          } else {
            wgmma_rs_n32(x0, wr[ci][0][u], xn_desc(c, u), (c | u) != 0);
            wgmma_rs_n32(x1, wr[ci][1][u], xn_desc(c, u), (c | u) != 0);
          }
          if (((ISV ? PACEV : PACEQ) >> c) & 1) { wg_commit(); wg_wait<2>(); wg_fence(); }
          if (c == 4 && u == 1) { wg_commit(); wg_wait<1>(); named_bar_arrive(NB_XE, 160); wg_fence(); }
        }
        if (c == 0) { t_pub = clk32() - 60; PROF(0, 8); PROF(0, 1); }
        if (c == 3) wg_commit();
      }
      wg_commit();
      wg_wait<0>();
      PROF(0, 10);
      const uint32_t tb = ISV ? (ph ? VX2 : VX) : QK;
      auto h2_issue = [&]() {
        spin_until(t_pub + D_H2);
        PROF(0, 13);
        if (elect_one()) { mbar_expect_tx(B_H2 + 8 * warp, 4096); bulk_g2s(MEMB + warp * 4096, src, 4096, B_H2 + 8 * warp); }
      };
      named_bar_sync(NB_CF, ISV ? 160 : 256);
      if (H2_AT == 0) h2_issue();
      const uint32_t none[2][4] = {}, tka = tok_addr<ISV>(tb, tid);
      tok_store<ISV, 0, false>(x0, tka, none);
      if (H2_AT == 1) h2_issue();
      tok_store<ISV, 1, false>(x1, tka, none);
      if (H2_AT == 2) h2_issue();
      named_bar_arrive(NB_DU, 256);
    }
    {
      OPQ;
      wsa = WS + ((mi >> 1) * 8 + mr) * 128 + (((2 * w + (mi & 1)) ^ mr) << 4);
      mba = MEMB + lane * 16;
      PIN(wsa); PIN(mba);
      {
        const uint32_t chk = MEMB + w * 4096 + lane * 32 + lg * 4, bar = B_H2 + 8 * warp;
        PROF(0, 11);
        proj_mem_prefetch<ISV, 0, 0, NPRE0>(ta, wsa);
#pragma unroll 1
        for (int tries = 0; tries < POLL_TRIES; tries++) {
          mbar_spin(bar, h2ph);
          h2ph ^= 1;
          const uint32_t mx = max(max(lds32(chk), lds32(chk + 1024)), max(lds32(chk + 2048), lds32(chk + 3072)));
          if (__all_sync(0xffffffffu, mx != EMPTY)) break;
          RETRY(1);
          if (elect_one()) { mbar_expect_tx(bar, 4096); bulk_g2s(MEMB + warp * 4096, src, 4096, bar); }
        }
      }
      if (s < 0) mbar_spin(B_WO, 0);
      PROF(0, 12);
      named_bar_arrive(NB_M1, 256);
      proj_mem_prefetch<ISV, 0, NPRE0, NTA0>(ta, wsa);
      named_bar_sync(NB_M0, 128);
    }
    s++;
    tid ^= 0x5500;
    {
      float a0[4], a1[4];
      proj_mem<ISV, 0>(wr, ta, wsa, mba, a0, a1);
      PROF(0, 2);
      uint32_t unused[4];
      proj_finish<ISV, 0>(a0, a1, peer0, peer1, self, tid, warp, unused);
      PROF(0, 3);
      if (s + 1 == cfg::NSEG) break;
      uint32_t wf[PF0][4], woa, wob;
      bool xn_ok;
      {
        OPQ;
        if (!ISV) {
          uint32_t qf[4][4], kf[2][4];
          const uint32_t qa = PT + 2048 + lane * 16, ka = QK + 4096 + w * 1024 + lane * 16;
          ldsm4t(qf[0], qa); ldsm4t(kf[0], ka); ldsm4t(qf[1], qa + 512);
          ldsm4t(qf[2], qa + 1024); ldsm4t(kf[1], ka + 512); ldsm4t(qf[3], qa + 1536);
          float c0[4], c1[4];
          mma16816z(c0, qf[0], kf[0][0], kf[0][1]);
          mma16816z(c1, qf[1], kf[0][2], kf[0][3]);
          mma16816(c0, qf[2], kf[1][0], kf[1][1]);
          mma16816(c1, qf[3], kf[1][2], kf[1][3]);
          const float s0 = (c0[0] + c0[2]) + (c1[0] + c1[2]), s1 = (c0[1] + c0[3]) + (c1[1] + c1[3]);
          send_scores(s0, s1, SP + rank * SP_SRC + t7 * SPW, peer0, peer1, B_SM, lane);
        }
        PROF(0, 4);
        woa = WO + 16384 + ((mi >> 1) * 8 + mr) * 128 + (((2 * w + (mi & 1)) ^ mr) << 4);
        wob = WO + 81920 + w * 4096 + ((mi >> 1) * 8 + mr) * 32 + (((mi & 1) ^ (mr >> 2)) << 4);
        uint32_t vf[2][2][4], vm[2][2];
        if (!ISV) mbar_spin(B_VX, s & 1);
        PROF(0, 14);
#pragma unroll
        for (int T = 0; T < 2; T++)
#pragma unroll
          for (int kk = 0; kk < 2; kk++) ldsm4(vf[T][kk], ((ISV && (s & 1)) ? VX2 : VX) + w * 2048 + (mi & 1) * 1024 + (mi >> 1) * 128 + mr * 16 + T * 512 + kk * 256);
        wo_prefetch<ISV ? 0 : 2, 0, PF0A>(wf, woa, wob, three);
        uint32_t spa = SP + lane * SPW, vma = VM + t7 * 8, oa = OB + (mi >> 1) * 1024 + w * 256 + (mi & 1) * 128 + mr * 16;
        PIN(spa); PIN(vma); PIN(oa);
        mbar_spin(B_SM, s & 1);
        PROF(0, 5);
        float sc[10];
#pragma unroll
        for (int j = 0; j < 5; j++) {
          if (SPACK) {
            const uint32_t x = lds32(spa + j * 128), y = lds32(spa + SP_SRC + j * 128);
            sc[2 * j] = bf_lo(x) + bf_lo(y); sc[2 * j + 1] = bf_hi(x) + bf_hi(y);
          } else {
            const float2 x = lds64f(spa + j * 256), y = lds64f(spa + SP_SRC + j * 256);
            sc[2 * j] = x.x + y.x; sc[2 * j + 1] = x.y + y.y;
          }
        }
        const bool vm_ok = mbar_test(B_VM, s & 1);
        lds64(vm[0], vma); lds64(vm[1], vma + 1024);
        float m = fmaxf(fmaxf(fmaxf(sc[0], sc[1]), fmaxf(sc[2], sc[3])), fmaxf(fmaxf(sc[4], sc[5]), fmaxf(sc[6], sc[7])));
        m = fmaxf(m, fmaxf(sc[8], sc[9]));
        const float cs = 0.08838834764831845f * 1.4426950408889634f;
        uint32_t pb[5];
        m = fmaxf(m, __shfl_xor_sync(0xffffffffu, m, 1));
        m = fmaxf(m, __shfl_xor_sync(0xffffffffu, m, 2));
        if (ISV ? GATE_MX : GATE_Q) named_bar_arrive(NB_MX, 256);
        const float mc = -m * cs;
#pragma unroll
        for (int j = 0; j < 5; j++) pb[j] = pack_bf16(ex2_approx(fmaf(sc[2 * j], cs, mc)), ex2_approx(fmaf(sc[2 * j + 1], cs, mc)));
        PROF(0, 15);
        if (!vm_ok) { mbar_spin(B_VM, s & 1); lds64(vm[0], vma); lds64(vm[1], vma + 1024); }
        PROF(0, 6);
        float o0[4], o1[4], rs[4];
        const uint32_t ones[4] = {0x3F803F80u, 0x3F803F80u, 0x3F803F80u, 0x3F803F80u};
        mma16816z(rs, ones, pb[0], pb[1]);
        mma16816z(o0, vf[0][0], pb[0], pb[1]);
        mma16816z(o1, vf[1][0], pb[0], pb[1]);
        mma16816(rs, ones, pb[2], pb[3]);
        mma16816(o0, vf[0][1], pb[2], pb[3]);
        mma16816(o1, vf[1][1], pb[2], pb[3]);
        mma1688(rs, ones[0], ones[0], pb[4]);
        mma1688(o0, vm[0][0], vm[0][1], pb[4]);
        mma1688(o1, vm[1][0], vm[1][1], pb[4]);
        const float i0 = rcp_approx(rs[0]), i1 = rcp_approx(rs[1]);
        stsm4(oa, pack_bf16(o0[0] * i0, o0[1] * i1), pack_bf16(o0[2] * i0, o0[3] * i1),
              pack_bf16(o1[0] * i0, o1[1] * i1), pack_bf16(o1[2] * i0, o1[3] * i1));
      }
      {
        OPQ;
        named_bar_arrive(NB_O, 256);
        wo_prefetch<ISV ? 0 : 2, PF0A, PF0>(wf, woa, wob, three);
        xn_ok = mbar_test(B_XN, (s + 1) & 1);
        char* h1p = P.xch + (tile0 + 4 + w) * 32768 + (h >> 3) * 8192 + (h & 7) * 128 + (((2 * lq + (lg & 1)) ^ (h & 7)) << 4) + (lg >> 1) * 4;
        uint32_t oba = OB + lane * 16;
        PIN(oba);
        PROF(0, 7);
        named_bar_sync(NB_O0, 128);
        const uint32_t tag = ((s >> 1) & 1) ^ 1;
        wo_phase<ISV ? 0 : 2>(wf, woa, wob, three, oba, h1p, tid >> 8, tag);
        PROF(0, 9);
        if (!xn_ok) mbar_spin(B_XN, (s + 1) & 1);
        named_bar_sync(NB_HD, 256);
      }
    }
  }
}

template <bool ISV>
__device__ __forceinline__ void f_wg1(const FParams& P, const WRegs& wr, const int h, const int rank, const uint32_t hw, int tid) {
  using namespace fk;
  const uint32_t self = mapa(0, (hw >> (2 * rank)) & 3), peer0 = mapa(0, (hw >> (ISV ? 0 : 2 * (rank ^ 1))) & 3) - self,
                 peer1 = mapa(0, (hw >> (ISV ? 2 : 4)) & 3) - self;
  SMAP;
  const int tile0 = rank * 22;
  const int warp = __shfl_sync(0xffffffffu, (threadIdx.x >> 5) & 3, 0);
  uint32_t h1ph = 0;
  auto o_done = [&](int mb) {
    tma_store_wait_all();
    asm volatile("fence.proxy.async.global;" ::: "memory");
    asm volatile("red.relaxed.gpu.global.add.u32 [%0], 1;" ::"l"(&g_oflag[mb]) : "memory");
  };
  uint32_t vmo[4] = {0, 0, 0, 0};
  if (ISV) {
    OPQ;
    sts32(PT + (t7 >> 2) * 128 + ((5 ^ lg) << 4) + lq * 4, 0);
    sts32(PT + (t7 >> 2) * 128 + ((6 ^ lg) << 4) + lq * 4, 0);
  }
  tid ^= 0x5500;
#pragma unroll 1
  for (int s = -1;;) {
    uint32_t ta[ProjCfg<ISV, 1>::NTA][4][4], wsa, mba;
    if (s + 1 < cfg::NSEG) mbar_spin(B_XN, (s + 1) & 1);
    const uint32_t t_pub = clk32();
    auto refill = [&]() {
      if (warp == 3) {
        named_bar_sync(NB_XE, 160);
        if (elect_one()) {
          mbar_expect_tx(B_XN + 8, 16384);
          tma_load_3d(XN, &P.xn, 0, (s + 1) * 32, 12, B_XN + 8);
        }
      }
    };
    auto arm = [&]() {
      if ((tid & 255) == 160) {
        if (s == 1) st_pub32(&g_mask[3 * h + rank], 0);
        if (s + 2 < cfg::NSEG) { mbar_expect_tx(B_SM, ISV ? 2 * SP_SRC : SP_SRC); if (!ISV) mbar_expect_tx(B_VX, 8192); }
        if (!ISV && s + 1 < cfg::NSEG) mbar_expect_tx(B_VM, 2048);
        if (ISV && s >= 1 && s < cfg::NSEG) mbar_expect_tx(B_ST, 7168);
      }
      if (ISV && s < cfg::NSEG && (tid & 254) == 192) mbar_arrive_remote(((tid & 1) ? peer1 : peer0) + B_ST);
      __syncwarp();
    };
    if (ISV) {
      if (s >= 0) arm();
      if (s >= 1) {
        OPQ;
        if (warp == 0 && (s & 3) == 1 && s > 1) { if (elect_one()) o_done((s - 2) >> 2); }
        const uint32_t vb = (s & 1) ? VX : VX2;
        float x0[16], x1[16];
        wg_fence();
        wgmma_rs_n32(x0, vmo, make_desc(fk::PT + 64, 16, 1024), 0);
        wgmma_rs_n32(x1, vmo, make_desc(fk::PT + 96, 16, 1024), 0);
#pragma unroll
        for (int kk = 0; kk < 2; kk++) {
          wgmma_ss_n32(x0, make_desc0(vb + kk * 256, 128, 1024), make_desc(fk::PT + kk * 32, 16, 1024), 1);
          wgmma_ss_n32(x1, make_desc0(vb + 512 + kk * 256, 128, 1024), make_desc(fk::PT + kk * 32, 16, 1024), 1);
        }
        wg_commit();
        wg_wait<0>();
        named_bar_sync(NB_W1, 128);
        PROF(1, 4);
        const uint32_t stg = vb + (8 * (mi >> 1) + mr) * 128 + (((2 * w + (mi & 1)) ^ mr) << 4);
#pragma unroll
        for (int T = 0; T < 2; T++) {
          const float* x = T ? x1 : x0;
#pragma unroll
          for (int jj = 0; jj < 4; jj += 2)
            stsm4t(stg + T * 4096 + jj * 1024, pack_bf16(x[4 * jj], x[4 * jj + 1]), pack_bf16(x[4 * jj + 2], x[4 * jj + 3]),
                   pack_bf16(x[4 * jj + 4], x[4 * jj + 5]), pack_bf16(x[4 * jj + 6], x[4 * jj + 7]));
        }
        fence_proxy_async_smem();
        named_bar_sync(NB_W1, 128);
        PROF(1, 10);
        if (warp == 0) {
          if (elect_one()) {
            tma_store_3d(&P.o, vb, 0, (s - 1) * 32, 2 * h);
            tma_store_commit();
          }
          __syncwarp();
        }
        if (s == cfg::NSEG) break;
      }
      if (s + 1 < cfg::NSEG) refill();
      PROF(1, 11);
    } else if (s < 0) {
      named_bar_arrive(NB_CF, 256);
      refill();
    } else {
      float x[24];
      wg_fence();
#pragma unroll
      for (int k = 0; k < 4; k++) wgmma_ss_n48_tt(x, make_desc0(fk::QK + k * 256, 128, 1024), make_desc0(fk::QK + 4096 + k * 256, 128, 1024), k != 0);
      wg_commit();
      arm();
      auto send_tok = [&]() {
        if (warp < 2) {
          OPQ;
          const uint32_t d0 = peer1 + QK + rank * 3584 + lane * 8 + w * 1280, d1 = d0 + 512 + w * 512, bar = peer1 + B_ST;
          mbar_spin(B_ST, s & 1);
          const float NEG = -500000000.0f / 0.08838834764831845f;
          const bool m0 = 2 * lq > lg, m1 = 2 * lq + 1 > lg;
          st_async64f(d0, x[16] + x[20], x[17] + x[21], bar);
          st_async64f(d1, x[18] + x[22], x[19] + x[23], bar);
          st_async64f(d1 + 256, x[2], x[3], bar);
          if (warp == 0) {
            st_async64f(d0 + 256, m0 ? NEG : x[0], m1 ? NEG : x[1], bar);
            st_async64f(d1 + 512, m0 ? NEG : x[6], m1 ? NEG : x[7], bar);
          } else {
            st_async64f(d0 + 256, x[0], x[1], bar);
            st_async64f(d1 + 512, x[6], x[7], bar);
            st_async64f(d0 + 512, x[4], x[5], bar);
            st_async64f(d0 + 768, m0 ? NEG : x[8], m1 ? NEG : x[9], bar);
            st_async64f(d1 + 768, x[10], x[11], bar);
            st_async64f(d1 + 1024, m0 ? NEG : x[14], m1 ? NEG : x[15], bar);
          }
        }
        PROF(1, 4);
      };
      const bool fin = s + 1 == cfg::NSEG;
      OPQ;
      const int j = 2 * h + rank;
      const char* src = P.xch + j * 32768 + warp * 8192 + __shfl_sync(0xffffffffu, (tid >> 14) & 3, 0) * 2048;
      char* dst = P.xch + H1_BYTES + (j >> 4) * 8192 + (lq >> 1) * 4096 + (j & 15) * 256 + (lq & 1) * 128 + (2 * w + (lg & 1)) * 16 + (lg >> 1) * 4;
      const uint32_t chk = VX + mi * 2048 + mr * 128 + (w ^ (mr >> 1)) * 32 + ((lane & 1) + 2 * mi) * 4;
      const uint32_t tmask = (s >> 1) & 1;
      if (!fin) {
        spin_until(t_pub + D_H1);
        if (elect_one()) { mbar_expect_tx(B_H1, 2048); bulk_g2s(VX + warp * 2048, src, 2048, B_H1); }
      }
      __syncwarp();
      wg_wait<0>();
      PROF(1, 6);
      send_tok();
      if (fin) { mbar_spin(B_VM, s & 1); break; }
      named_bar_arrive(NB_CF, 256);
      if (REFILL_EARLY) refill();
#pragma unroll 1
      for (int tries = 0; tries < POLL_TRIES; tries++) {
        float d0[4], d1[4], d2[4], d3[4];
        mbar_spin(B_H1, h1ph);
        h1ph ^= 1;
        PROF(1, 10);
        const uint32_t t0 = lds32(chk), t1 = lds32(chk + 1024);
        wg_fence();
        const uint64_t ones = (uint64_t)(fk::ONES >> 4);
        wgmma_ss_n8_ta(d0, make_desc(fk::VX, 8192, 2048), ones, 0);
        wgmma_ss_n8_ta(d1, make_desc(fk::VX + 1024, 8192, 2048), ones, 0);
        wgmma_ss_n8_ta(d2, make_desc(fk::VX + 4096, 8192, 2048), ones, 0);
        wgmma_ss_n8_ta(d3, make_desc(fk::VX + 5120, 8192, 2048), ones, 0);
        wg_commit();
        uint32_t tt;
        asm volatile("lop3.b32 %0, %1, %2, %3, 0x42;" : "=r"(tt) : "r"(t0), "r"(t1), "r"(tmask) : "memory");
        uint32_t ok;
        named_bar_and(NB_W1, 128, tt & 1, ok);
        if (!ok) { if (elect_one()) { mbar_expect_tx(B_H1, 2048); bulk_g2s(VX + warp * 2048, src, 2048, B_H1); } }
        wg_wait<0>();
        if (ok) {
          st_pub32(dst + (s & 1) * 32768, (lq & 1) ? pack_bf16(d1[0] + d3[0], d1[2] + d3[2]) : pack_bf16(d0[0] + d2[0], d0[2] + d2[2]));
          PROF(1, 12);
          st_pub32(dst + ((s & 1) ^ 1) * 32768, EMPTY);
          break;
        }
        RETRY(0);
      }
      named_bar_sync(NB_W1, 128);
      if ((tid & 255) == 192) mbar_arrive_remote(peer1 + B_PF);
      __syncwarp();
      if (!REFILL_EARLY) refill();
      PROF(1, 11);
    }
    if (!ISV || s + 1 < cfg::NSEG) {
      const uint32_t ph = (s + 1) & 1;
      float x0[16], x1[16];
      named_bar_sync(NB_ST, 256);
      wg_fence();
#pragma unroll
      for (int c = 0; c < 6; c++) {
        if (c == 2) { mbar_spin(B_XN + 8, ph); wg_fence(); }
        if (ISV && c == CF_AT) {
          if (warp == 0) {
            if (elect_one()) tma_store_wait_read();
            __syncwarp();
            named_bar_arrive(NB_CF, 160);
          }
          wg_fence();
        }
#pragma unroll
        for (int u = 0; u < 4; u++) {
          wgmma_rs_n32(x0, wr[c][0][u], xn_desc(c < 2 ? 10 + c : c - 2, u), (c | u) != 0);
          wgmma_rs_n32(x1, wr[c][1][u], xn_desc(c < 2 ? 10 + c : c - 2, u), (c | u) != 0);
        }
      }
      wg_commit();
      OPQ;
      const uint32_t tb = ISV ? (ph ? VX2 : VX) : QK, tka = tok_addr<ISV>(tb, tid);
      uint32_t p0[2][4], p1[2][4];
      named_bar_sync(NB_DU, 256);
      ldsm4(p1[0], tka + tok_off<ISV>(1, 0)); ldsm4(p1[1], tka + tok_off<ISV>(1, 1));
      ldsm4(p0[0], tka + tok_off<ISV>(0, 0)); ldsm4(p0[1], tka + tok_off<ISV>(0, 1));
      if (ISV && s >= 0) mbar_spin(B_PF, s & 1);
      wg_wait<0>();
      PROF(1, 13);
      tok_store<ISV, 1, true>(x1, tka, p1);
      tok_store<ISV, 0, true>(x0, tka, p0);
      if (ISV && s + 2 < cfg::NSEG) {
        fence_proxy_async_smem();
        __syncwarp();
        if (elect_one()) {
          bulk_s2s(peer0 + VX + warp * 2048, tb + warp * 2048, 2048, peer0 + B_VX);
          bulk_s2s(peer1 + VX + warp * 2048, tb + warp * 2048, 2048, peer1 + B_VX);
        }
      }
      wsa = WS + ((mi >> 1) * 8 + mr) * 128 + (((2 * w + (mi & 1)) ^ mr) << 4);
      mba = MEMB + lane * 16;
      PIN(wsa); PIN(mba);
      proj_mem_prefetch<ISV, 1, 0, NTA1>(ta, wsa);
      PROF(1, 14);
      named_bar_sync(NB_M1, 256);
      s++;
      PROF(1, 1);
      float a0[4], a1[4];
      proj_mem<ISV, 1>(wr, ta, wsa, mba, a0, a1);
      PROF(1, 2);
      proj_finish<ISV, 1>(a0, a1, peer0, peer1, self, tid, warp, vmo);
      PROF(1, 3);
    } else {
      OPQ;
      mbar_spin(B_VM, s & 1);
      lds64(vmo, VM + t7 * 8); lds64(vmo + 2, VM + 1024 + t7 * 8);
      s++;
    }
    tid ^= 0x5500;
    const bool last = s + 1 >= cfg::NSEG;
    constexpr int PFW = ISV ? PF1V : PF1;
    uint32_t wf[PFW][4], woa;
    if (ISV) {
      OPQ;
      woa = WO + ((mi >> 1) * 8 + mr) * 128 + (((2 * w + (mi & 1)) ^ mr) << 4);
      if (s >= 1) {
        const uint32_t sa = QK + ((w * (w + 3)) >> 1) * 256 + lane * 8;
        mbar_spin(B_ST, (s - 1) & 1);
        float sc[10];
        {
          const float NEG = -1000000000.0f / 0.08838834764831845f;
          float2 x[5], y[5];
#pragma unroll
          for (int b = 0; b < 5; b++) {
            x[b] = b < 2 ? lds64f(sa + b * 256) : lds64f_if(sa + b * 256, b <= w + 1, NEG);
            y[b] = b < 2 ? lds64f(sa + 3584 + b * 256) : lds64f_if(sa + 3584 + b * 256, b <= w + 1, 0.f);
          }
          wo_prefetch<1, 0, PF1A>(wf, woa, 0, true);
#pragma unroll
          for (int b = 0; b < 5; b++) { sc[2 * b] = x[b].x + y[b].x; sc[2 * b + 1] = x[b].y + y[b].y; }
        }
        float m = fmaxf(fmaxf(fmaxf(sc[0], sc[1]), fmaxf(sc[2], sc[3])), fmaxf(fmaxf(sc[4], sc[5]), fmaxf(sc[6], sc[7])));
        m = fmaxf(m, fmaxf(sc[8], sc[9]));
        m = fmaxf(m, __shfl_xor_sync(0xffffffffu, m, 1));
        m = fmaxf(m, __shfl_xor_sync(0xffffffffu, m, 2));
        const float cs = 0.08838834764831845f * 1.4426950408889634f;
#pragma unroll
        for (int i = 0; i < 10; i++) sc[i] = ex2_approx((sc[i] - m) * cs);
        float sum = ((sc[0] + sc[1]) + (sc[2] + sc[3])) + ((sc[4] + sc[5]) + (sc[6] + sc[7])) + (sc[8] + sc[9]);
        sum += __shfl_xor_sync(0xffffffffu, sum, 1);
        sum += __shfl_xor_sync(0xffffffffu, sum, 2);
        const float inv = rcp_approx(sum);
        const uint32_t pa = PT + (w * 8 + mr) * 128, pm = pack_bf16(sc[0] * inv, sc[1] * inv);
        stsm4(pa + ((mi ^ mr) << 4), pack_bf16(sc[2] * inv, sc[3] * inv), pack_bf16(sc[4] * inv, sc[5] * inv),
              pack_bf16(sc[6] * inv, sc[7] * inv), pack_bf16(sc[8] * inv, sc[9] * inv));
        asm volatile("stmatrix.sync.aligned.m8n8.x2.shared.b16 [%0], {%1,%1};" ::"r"(pa + ((((mi & 1) ? 7 : 4) ^ mr) << 4)), "r"(pm) : "memory");
      } else {
        wo_prefetch<1, 0, PF1A>(wf, woa, 0, true);
      }
      if (warp == 3 && !last) {
        mbar_spin(B_VM, s & 1);
        if (elect_one()) load_xn(P, s + 1, self);
      }
      PROF(1, 5);
    } else {
      if (warp == 0) {
        OPQ;
        uint32_t kf[4][4], qf[4][4];
        float c0[4], c1[4], d0[4], d1[4];
        const uint32_t ka = PT + (mi >> 1) * 1024 + (mi & 1) * 128 + mr * 16;
#pragma unroll
        for (int k = 0; k < 4; k++) { ldsm4t(qf[k], PT + 2048 + k * 512 + lane * 16); ldsm4t(kf[k], ka + k * 256); }
        mma16816z(c0, qf[0], kf[0][0], kf[0][1]); mma16816z(c1, qf[0], kf[0][2], kf[0][3]);
        mma16816z(d0, qf[1], kf[1][0], kf[1][1]); mma16816z(d1, qf[1], kf[1][2], kf[1][3]);
        mma16816(c0, qf[2], kf[2][0], kf[2][1]); mma16816(c1, qf[2], kf[2][2], kf[2][3]);
        mma16816(d0, qf[3], kf[3][0], kf[3][1]); mma16816(d1, qf[3], kf[3][2], kf[3][3]);
        const float s0 = ((c0[0] + c0[2]) + (c1[0] + c1[2])) + ((d0[0] + d0[2]) + (d1[0] + d1[2]));
        const float s1 = ((c0[1] + c0[3]) + (c1[1] + c1[3])) + ((d0[1] + d0[3]) + (d1[1] + d1[3]));
        if (!last) send_scores(s0, s1, SP + rank * SP_SRC + (128 + lane) * SPW, peer0, peer1, B_SM, lane);
        PROF(1, 5);
      } else {
        const uint32_t t_c = clk32() + lds32(B_XN) * 0;
        if (warp == 3 && !last) { if (elect_one()) load_xn(P, s + 1, self); }
        spin_until(t_c + D_ST);
      }
      OPQ;
      woa = WO + ((mi >> 1) * 8 + mr) * 128 + (((2 * w + (mi & 1)) ^ mr) << 4);
    }
    if (!last) {
      OPQ;
      uint32_t oba = OB + lane * 16;
      if (!ISV) wo_prefetch<1, 0, PF1Q>(wf, woa, 0, true);
      if (ISV ? GATE_MX : GATE_Q) named_bar_sync(NB_MX, 256);
      wo_prefetch<1, ISV ? PF1A : PF1Q, PFW>(wf, woa, 0, true);
      char* h1p = P.xch + (tile0 + w) * 32768 + (h >> 3) * 8192 + (h & 7) * 128 + (((2 * lq + (lg & 1)) ^ (h & 7)) << 4) + (lg >> 1) * 4;
      fence_proxy_async_smem();
      PROF(1, 7);
      named_bar_sync(NB_O, 256);
      PROF(1, 8);
      wo_phase<1>(wf, woa, 0, true, oba, h1p, tid >> 8, ((s >> 1) & 1) ^ 1);
      PROF(1, 9);
      named_bar_sync(NB_HD, 256);
    } else {
      fence_proxy_async_smem();
      named_bar_sync(NB_W1, 128);
    }
  }
  if (ISV && warp == 0) { if (elect_one()) o_done(15); }
}

template <bool ISV, int WG>
__device__ __forceinline__ void f_main(const FParams& P, const int h, const int rank, const uint32_t hw) {
  using namespace fk;
  const uint32_t self = mapa(0, (hw >> (2 * rank)) & 3);
  SMAP;
  const int tid = __shfl_sync(0xffffffffu, threadIdx.x, threadIdx.x & 31);
  const int tile0 = rank * 22, ntile = ISV ? 20 : 22;
  const CUtensorMap* m0 = ISV ? &P.wv : &P.wq;
  const CUtensorMap* m1 = ISV ? &P.wv : &P.wk;
  const int col0 = h * 128 + (ISV ? 0 : 64 * rank), col1 = h * 128 + (ISV ? 64 : 64 * rank);
  WRegs wr;
  uint32_t sel = 0;
  {
    OPQ;
    const uint32_t a = SM0 + WG * 16384 + ((mi >> 1) * 8 + mr) * 128 + (((2 * w + (mi & 1)) ^ mr) << 4);
#pragma unroll
    for (int i = 0; i < 6; i++) {
      mbar_wait(B_PB + 8 * i, 0);
      PRO(8 + i);
#pragma unroll
      for (int T = 0; T < 2; T++)
#pragma unroll
        for (int u = 0; u < 4; u++) ldsm4t(wr[i][T][u], a + i * 32768 + T * 8192 + u * 2048);
      named_bar_sync(NB_C, 256);
      if (WG == 1 && w == (i & 3)) {
        if (elect_one()) {
          if (i <= 2 && i + PRE_G < 6) {
#pragma unroll 1
            for (int n = 2 * (i + PRE_G); n < (i == 2 ? 12 : 2 * (i + PRE_G) + 2); n++) {
              const int ii = n >> 1, row = Chunks<ISV>::rf(n & 1, ii) * 64;
              if (!(n & 1)) mbar_expect_tx(B_PB + 8 * ii, 32768);
              tma_load_2d(SM0 + n * 16384, m0, col0, row, B_PB + 8 * ii);
              tma_load_2d(SM0 + n * 16384 + 8192, m1, col1, row, B_PB + 8 * ii);
            }
          }
          if (i == 3 || i == 4) {
            const int p0 = i == 3 ? 0 : 5, p1 = i == 3 ? 5 : 8;
            mbar_expect_tx(B_W, (p1 - p0) * 8192);
#pragma unroll 1
            for (int p = p0; p < p1; p++) tma_load_2d(WS + p * 8192, (p & 1) ? m1 : m0, (p & 1) ? col1 : col0, Chunks<ISV>::sm(p >> 1) * 64, B_W);
          }
          if (i == WO_AT) {
            mbar_expect_tx(B_WO, ntile * 4096);
#pragma unroll 1
            for (int t = 0; t < 5; t++) tma_load_2d(WO + t * 16384, &P.wo, tile0 * 16 + t * 64, h * 128, B_WO);
            if (!ISV) {
              tma_load_2d(WO + 81920, &P.wo16, tile0 * 16 + 320, h * 128, B_WO);
              tma_load_2d(WO + 86016, &P.wo16, tile0 * 16 + 336, h * 128, B_WO);
            }
          }
        }
      }
    }
    PROF2(1);
    uint2 m0 = make_uint2(0, 0);
    if (!ISV && WG == 1) m0 = *reinterpret_cast<const uint2*>(P.mem0 + ((lane >> 1) & 7) * cfg::D + (2 * h + rank) * 16 + (lane >> 4) * 8 + (lane & 1) * 4);
    if (WG == 0 && w == 1) {
      uint4 v;
#pragma unroll 1
      for (int tries = 0; tries < POLL_TRIES; tries++) {
        asm volatile("ld.acquire.gpu.global.v4.u32 {%0,%1,%2,%3}, [%4];" : "=r"(v.x), "=r"(v.y), "=r"(v.z), "=r"(v.w)
                     : "l"(&g_mask[4 * min(lane, 23)]) : "memory");
        if (__all_sync(0xffffffffu, v.x & v.y & v.z & v.w & 0x100)) break;
        __nanosleep(100);
      }
      if (elect_one()) {
        asm volatile("fence.proxy.async.global;" ::: "memory");
        load_xn(P, 0, self);
        if (blockIdx.x == 2) { __threadfence(); st_pub128(g_lnok, 0x100); }
      }
      sts128(OB + lane * 16, v.x, v.y, v.z, v.w);
    }
    named_bar_sync(NB_C, 256);
    if (!ISV && WG == 1 && w < 2) st_pub64(P.xch + H1_BYTES + 32768 + (h >> 3) * 8192 + w * 4096 + ((2 * h + rank) & 15) * 256 + lane * 8, m0.x, m0.y);
#pragma unroll
    for (int i = 0; i < 3; i++) {
      const int t = min(tile0 + 8 * i + w + (WG ? 0 : 4), 63);
      sel |= ((lds32(OB + ((t >> 1) * 3 + (t & 1)) * 4) >> (h >> 3)) & 1) << (2 * i + 1);
    }
    const uint32_t own = lds32(OB + (3 * h + rank) * 4) >> w, m2 = lds32(OB + (3 * h + 2) * 4) >> w;
    sel |= (own & 1) << 7 | (m2 & 1) << 8 | (m2 & 16) << 5;
    sel |= (((((lg ^ h) & 1) << 2) | (lg >> 1)) == (h & 1) + 2 * (h >> 3)) << 10;
  }
  asm volatile("barrier.cluster.wait.aligned;" ::: "memory");
  PRO(14);
  mbar_wait(B_W, 0);
  mbar_wait(B_XN, 0);
  PRO(15);
  PROF2(4);
  GTSYNC(0);
  PROF2(2);
  KT_END(8);
  if (WG == 0) f_wg0<ISV>(P, wr, h, rank, hw, tid | sel << 8); else f_wg1<ISV>(P, wr, h, rank, hw, tid | sel << 8);
}

__device__ __forceinline__ void f_tail(const FParams& P, const int h, const uint32_t rank, const bool isv) {
  using namespace fk;
  const uint32_t self = mapa(0, rank), base = self + SM0;
  const uint32_t FULL = self + SP, EMPT = FULL + 32, RES = FULL + 64, NOG = FULL + 72;
  const int tid = threadIdx.x, lane = tid & 31, wv = __shfl_sync(0xffffffffu, tid >> 5, 0), wg = wv >> 2;
  const int kq = h & 3, nt = (h >> 2) & 3, mb = TAIL_MB0 + 3 * (h >> 4) + rank;
  auto a_off = [](uint32_t st) { return (0x98685800u >> (8 * st) & 255) * 1024; };
  auto b_off = [](uint32_t st) { return (0xA8783010u >> (8 * st) & 255) * 1024; };
  static_assert(VX2 - SM0 == 80 * 1024 && VX - SM0 == 200 * 1024, "stage layout");
  auto load_b = [&](int kb) {
    const uint32_t sb = base + b_off(kb & 3), full = FULL + 8 * (kb & 3);
    mbar_expect_tx(full, 49152);
    tma_load_2d_mc(sb + rank * 8192, &P.tb, nt * 256 + ((rank + kq) & 3) * 64, (kq * 16 + kb) * 64, full, 7);
    if (kb % 3 == rank) tma_load_2d_mc(sb + 3 * 8192, &P.tb, nt * 256 + ((3 + kq) & 3) * 64, (kq * 16 + kb) * 64, full, 7);
  };
  auto load_a = [&](int kb) { tma_load_2d(base + a_off(kb & 3), &P.ta, (kq * 16 + kb) * 64, mb * 128, FULL + 8 * (kb & 3)); };
  TL(0);
  TL2(128, 10); TL2(160, 11);
  if (wv == 0) {
    if (elect_one()) {
      prefetch_tmap(&P.tb); prefetch_tmap(&P.ta);
      if (isv) mbar_spin(self + B_VM, (cfg::NSEG - 1) & 1);
      for (int i = 0; i < 4; i++) { mbar_init(FULL + 8 * i, 1); mbar_init(EMPT + 8 * i, 24); }
      mbar_init(RES, 1);
      fence_barrier_init();
      mbar_arrive_cluster(self + B_W, rank == 0 ? 1 : 0);
      mbar_arrive_cluster(self + B_W, rank == 2 ? 1 : 2);
      mbar_spin(self + B_W, 1);
#pragma unroll 1
      for (int kb = 0; kb < 4; kb++) load_b(kb);
      TL2(0, 12);
      wait_count(&g_oflag[mb], 32);
      asm volatile("fence.proxy.async.global;" ::: "memory");
      TL2(0, 13);
#pragma unroll 1
      for (int kb = 0; kb < 4; kb++) load_a(kb);
      TL2(0, 14);
    }
  }
  if (wv == 1) {
    if (lane == 0) {
      prefetch_tmap(&P.tx); prefetch_tmap(&P.tg); prefetch_tmap(&P.tout);
      uint32_t gc;
      asm volatile("ld.acquire.gpu.global.u32 %0, [%1];" : "=r"(gc) : "l"(&g_cnt[3][mb]) : "memory");
      const bool ng = gc < GATE_CNT && ld_strong4(&g_next) == 0;
      sts32(NOG, ng ? 1 : gc < GATE_CNT ? 2 : 0);
      if (ng) g_tfix[blockIdx.x] = 1;
      asm volatile("cp.async.bulk.prefetch.tensor.2d.L2.global [%0, {%1, %2}];" ::"l"(&P.tx), "r"(nt * 256 + kq * 64), "r"(mb * 128) : "memory");
    }
  } else if (wv == 2 || wv == 3) {
#pragma unroll 2
    for (int i = tid - 64; i < 3072; i += 64) st_pub128(&g_tpart[blockIdx.x][0][0][0] + i, EMPTY);
  }
  float acc[128];
  __syncthreads();
  KT_START(7);
  const uint32_t gate = lds32(NOG);
  const bool nog = gate == 1;
  if (gate) TL(15); else TL(15);
#pragma unroll 1
  for (int kb = 0; kb < 16; kb++) {
    const uint32_t st = kb & 3, sa = base + a_off(st) + wg * 8192, sb = base + b_off(st);
    mbar_spin(FULL + 8 * st, (kb >> 2) & 1);
    if (kb == 0) TL(2);
    if (kb == 4) TL(3);
    if (kb == 10) TL(4);
    wg_fence();
#pragma unroll
    for (int k = 0; k < 4; k++) {
      wgmma_ss_n256_tb(acc, make_desc(sa + k * 32, 16, 1024), make_desc(sb + k * 2048, 8192, 1024), (kb | k) != 0);
      if (k == 0) {
        wg_commit();
        wg_wait<1>();
        if (kb > 0 && kb <= 13 && lane < 3) mbar_arrive_cluster(EMPT + 8 * ((kb - 1) & 3), lane);
        wg_fence();
      }
    }
    wg_commit();
    if (kb >= 2 && kb < 15 && wv == ((kb & 1) << 2)) {
      if (elect_one()) {
        mbar_spin(EMPT + 8 * ((kb - 2) & 3), ((kb - 2) >> 2) & 1);
        if (kb < 14) {
          load_b(kb + 2);
          load_a(kb + 2);
        } else if (nog) {
          mbar_arrive(RES);
        } else {
          if (gate) wait_count(&g_cnt[3][mb], GATE_CNT);
          asm volatile("fence.proxy.async.global;" ::: "memory");
          mbar_expect_tx(RES, 32768);
          tma_load_2d(base, &P.tx, nt * 256 + kq * 64, mb * 128, RES);
          tma_load_2d(base + 16384, &P.tg, nt * 256 + kq * 64, mb * 128, RES);
        }
      }
      __syncwarp();
    }
  }
  wg_wait<0>();
  TL(5);
#pragma unroll
  for (int j = 1; j < 4; j++) {
    uint4* dst = &g_tpart[((h & ~3) + ((j + kq) & 3)) * 3 + rank][j - 1][0][tid];
#pragma unroll
    for (int i = 0; i < 4; i++) {
      const float* a = &acc[32 * j + 8 * i];
      asm volatile("st.relaxed.gpu.global.v4.u32 [%0], {%1,%2,%3,%4};" ::"l"(dst + i * 256), "r"(pack_bf16(a[0], a[1])),
                   "r"(pack_bf16(a[2], a[3])), "r"(pack_bf16(a[4], a[5])), "r"(pack_bf16(a[6], a[7])) : "memory");
    }
  }
  TL(6);
#pragma unroll 1
  for (int j = 0, tries = 0; j < 3 && tries < POLL_TRIES; tries++) {
    uint4 pt[4];
#pragma unroll
    for (int i = 0; i < 4; i++) pt[i] = ld_strong16(&g_tpart[blockIdx.x][j][i][tid]);
    if (!__all_sync(0xffffffffu, max(max(umax4(pt[0]), umax4(pt[1])), max(umax4(pt[2]), umax4(pt[3]))) != EMPTY)) continue;
#pragma unroll
    for (int i = 0; i < 16; i++) { acc[2 * i] += bf_lo((&pt[0].x)[i]); acc[2 * i + 1] += bf_hi((&pt[0].x)[i]); }
    j++;
  }
  mbar_spin(RES, 0);
  TL(7);
  const uint32_t xa = base + (wv * 16 + ((lane >> 3) & 1) * 8 + (lane & 7)) * 128 + (((lane >> 4) ^ (lane & 7)) << 4);
#pragma unroll
  for (int i = 0; i < 4; i++) {
    uint32_t x[4], g[4], o[4];
    ldsm4(x, xa ^ (i << 5));
    ldsm4(g, (xa ^ (i << 5)) + 16384);
#pragma unroll
    for (int k = 0; k < 4; k++) {
      const uint32_t sv = pack_bf16(acc[8 * i + 2 * k], acc[8 * i + 2 * k + 1]);
      o[k] = nog ? sv : add_bf16x2(x[k], mul_bf16x2(sv, g[k]));
    }
    stsm4(xa ^ (i << 5), o[0], o[1], o[2], o[3]);
  }
  TL(8);
  fence_proxy_async_smem();
  __syncwarp();
  if (elect_one()) {
    tma_store_2d(&P.tout, base + wv * 2048, nt * 256 + kq * 64, mb * 128 + wv * 16);
    tma_store_commit();
    tma_store_wait_read();
  }
  TL(9);
  KT_END(7);
}

__global__ void __launch_bounds__(256, 1) f_kernel(const __grid_constant__ FParams P) {
  using namespace fk;
  extern __shared__ __align__(1024) uint8_t smem_f[];
  uint32_t crank, rank, hw;
  asm("mov.u32 %0, %%cluster_ctarank;" : "=r"(crank));
  const int h = blockIdx.x / 3;
  if (smem_u32(smem_f) != mapa(0, crank) + SM0) return;
  PROF2(0);
  KT_START(1);
  KT_START(0);
  {
    const uint32_t self = mapa(0, crank);
    SMAP;
    const int tid = threadIdx.x, lane = tid & 31, wv = __shfl_sync(0xffffffffu, tid >> 5, 0);
    PRO(0);
    if (wv == 0) {
      uint32_t sm;
      asm("mov.u32 %0, %%smid;" : "=r"(sm));
      sts32(PROBE + 96, sm >> 1);
      asm volatile("fence.release.sync_restrict::shared::cta.cluster;" ::: "memory");
    }
    asm volatile("barrier.cluster.arrive.relaxed.aligned;" ::: "memory");
    if (wv == 7) {
      if (blockIdx.x == 2) {
#pragma unroll
        for (int i = 0; i < 3; i++) { (&g_cnt[0][0])[32 * i + lane] = 0; g_tfix[32 * i + lane] = 0; }
        if (lane < 16) g_oflag[lane] = 0;
        if (lane == 0) { g_next = 0; g_lnok[0] = 0; }
        __threadfence();
        __syncwarp();
      }
      pdl_launch_dependents();
    }
    const int row0 = blockIdx.x * 8 + wv;
    const bool third = row0 + 1536 < cfg::S;
    uint32_t cur[1][16], raw[2][16];
    load_row16(cur[0], P.x + (size_t)row0 * cfg::D, lane);
    load_row16(raw[0], P.x + (size_t)(row0 + 768) * cfg::D, lane);
    load_row16(raw[1], P.x + (size_t)(row0 + (third ? 1536 : 0)) * cfg::D, lane);
    {
      uint32_t tpc;
      asm volatile("barrier.cluster.wait.aligned;" ::: "memory");
      asm volatile("ld.shared::cluster.u32 %0, [%1];" : "=r"(tpc) : "r"(mapa(PROBE + 96, lane % 3)) : "memory");
      const uint32_t t0 = __shfl_sync(0xffffffffu, tpc, 0), t1 = __shfl_sync(0xffffffffu, tpc, 1), t2 = __shfl_sync(0xffffffffu, tpc, 2);
      hw = t1 == t2 ? 0x09 : t0 == t2 ? 0x18 : 0x24;
      rank = (hw & 3) == crank ? 0 : ((hw >> 2) & 3) == crank ? 1 : 2;
    }
    const bool isv = rank == 2;
    const CUtensorMap* m0 = isv ? &P.wv : &P.wq;
    const CUtensorMap* m1 = isv ? &P.wv : &P.wk;
    const int col0 = h * 128 + (isv ? 0 : 64 * rank), col1 = h * 128 + (isv ? 64 : 64 * rank);
    if (wv == 0) {
      if (elect_one()) {
        for (int i = 0; i < 2; i++) mbar_init(B_XN + 8 * i, 1);
        mbar_init(B_H1, 4);
        mbar_init(B_SM, isv ? 1 : 6);
        mbar_init(B_VM, isv ? 8 : 1);
        mbar_init(B_VX, 1);
        mbar_init(B_ST, 1);
        mbar_init(B_PF, 2);
        for (int i = 0; i < 6; i++) mbar_init(B_PB + 8 * i, 1);
        mbar_init(B_W, 2);
        mbar_init(B_WO, 1);
        fence_barrier_init();
        mbar_expect_tx(B_SM, isv ? 2 * SP_SRC : SP_SRC);
        if (isv) mbar_expect_tx(B_ST, 7168);
        else { mbar_expect_tx(B_VM, 2048); mbar_expect_tx(B_VX, 8192); }
      }
    }
    const int j = 2 * h + rank;
    if (lane == 0) {
      const uint2 b = probe_pair(P.xch + (isv ? H1_BYTES + wv * 8192 + h * 128 : j * 32768 + (wv & 3) * 8192 + (wv >> 2) * 128),
                                 isv ? EMPTY : 0, PROBE + 64, P.nprobe);
      sts64(PROBE + wv * 8, b.x, b.y);
    }
    PROF2(3);
    PRO(1);
    __syncwarp();
    if (wv == 1) {
      const uint32_t off = (blockIdx.x * 32 + lane) * 688;
      if (off < cfg::D * cfg::D * 2) l2_prefetch(reinterpret_cast<const char*>(P.w1) + off, min(688u, cfg::D * cfg::D * 2 - off));
    }
    if (wv == 0) {
      asm volatile("{\n.reg .pred p;\nsetp.eq.u32 p, %0, %1;\n@p st.shared.u32 [%2], %0;\n}" ::"r"(raw[1][15]), "r"(cur[0][0] ^ raw[0][15]), "r"(PROBE + 64) : "memory");
      if (elect_one()) {
#pragma unroll 1
        for (int n = 0; n < 2 * PRE_G; n++) {
          const int i = n >> 1, g = n & 1, row = (isv ? Chunks<true>::rf(g, i) : Chunks<false>::rf(g, i)) * 64;
          if (!g) mbar_expect_tx(B_PB + 8 * i, 32768);
          tma_load_2d(SM0 + n * 16384, m0, col0, row, B_PB + 8 * i);
          tma_load_2d(SM0 + n * 16384 + 8192, m1, col1, row, B_PB + 8 * i);
        }
      }
    }
    __syncthreads();
    PRO(2);
    asm volatile("barrier.cluster.arrive.relaxed.aligned;" ::: "memory");
    PRO(3);
    if (wv == 2) { sts32(self + ONES + lane * 4, 0x3F803F80u); fence_proxy_async_smem(); }
    uint32_t pb[2], pc[2];
    lds64(pb, PROBE + (lane & 7) * 8);
    lds64(pc, PROBE + ((lane & 7) ^ 4) * 8);
    const uint32_t mask = __ballot_sync(0xffffffffu, isv ? pb[1] < pb[0] : min(pb[1], pc[1]) < min(pb[0], pc[0])) & (isv ? 255 : 15);
    if (!isv) {
#pragma unroll
      for (int i = 0; i < 4; i++) st_pub128(P.xch + j * 32768 + i * 8192 + ((mask >> i) & 1) * 4096 + tid * 16, 0);
      if (wv < 4) st_pub64(P.xch + H1_BYTES + (wv >> 1) * 32768 + (j >> 4) * 8192 + (wv & 1) * 4096 + (j & 15) * 256 + lane * 8, EMPTY, EMPTY);
    }
#pragma unroll 1
    for (int it = 0; it < (third ? 6 : 4); it++) {
      ln_regs<1>(cur);
      store_row16(cur[0], ((it & 1) ? P.xn2 : P.xn_ptr) + (size_t)(row0 + (it >> 1) * 768) * cfg::D, lane);
      if (it == 0) PRO(4);
      if (it & 1) {
#pragma unroll
        for (int i = 0; i < 16; i++) { cur[0][i] = raw[0][i]; raw[0][i] = raw[1][i]; }
      }
    }
    PRO(5);
    __syncthreads();
    PRO(6);
    if (tid == 64) {
      __threadfence();
      PRO(7);
      st_pub32(&g_mask[3 * h + rank], 0x100 | mask);
    }
    KT_END(0);
    __syncwarp();
  }
  const int wg = __shfl_sync(0xffffffffu, threadIdx.x >> 7, 0);
  if (rank == 2) { if (wg == 0) f_main<true, 0>(P, h, 2, hw); else f_main<true, 1>(P, h, 2, hw); }
  else { if (wg == 0) f_main<false, 0>(P, h, rank, hw); else f_main<false, 1>(P, h, rank, hw); }
  PROF2(5);
  KT_END(1);
  __syncwarp();
  f_tail(P, h, crank, rank == 2);
}

#define GCL 1
namespace gk {
enum { T_B1 = 0, T_B2 = 1, T_B3 = 2, T_B4 = 3, T_O = 4, T_LN = 5, T_END = 7 };
constexpr int NST = 3, STAGE = 49152, MAXITEMS = 512, NEW = 3;
constexpr uint32_t OUTB = NST * STAGE, BARS = OUTB + 65536;
constexpr uint32_t B_FULL = BARS, B_EMPTY = BARS + 32, B_ITEM = BARS + 64, B_FILL = BARS + 128, B_FREE = BARS + 160, B_LN = BARS + 176, ITEMS = BARS + 192;
constexpr int SMEM = BARS + 256;
static_assert(GATE_CNT == 4 * NEW && T_B4 == 3, "gate counter");
}
struct GParams {
  CUtensorMap a[5], b[5];
  bf16* c[5];
  const bf16* r[5];
  bf16* x1n;
  int nitems, lnpos;
  uint16_t items[gk::MAXITEMS];
};
#define ILOG(i)

__device__ __forceinline__ void tma_load_3d_mc(uint32_t dst, const CUtensorMap* map, int x, int y, int z, uint32_t bar) {
  asm volatile("cp.async.bulk.tensor.3d.shared::cluster.global.mbarrier::complete_tx::bytes.multicast::cluster "
               "[%0], [%1, {%3, %4, %5}], [%2], %6;"
               ::"r"(dst), "l"(map), "r"(bar), "r"(x), "r"(y), "r"(z), "h"((uint16_t)3) : "memory");
}
__device__ __forceinline__ float tanh_approx(float x) { float y; asm("tanh.approx.f32 %0, %1;" : "=f"(y) : "f"(x)); return y; }
__global__ void __launch_bounds__(384, 1) g_kernel(const __grid_constant__ GParams P) {
  using namespace gk;
  extern __shared__ __align__(1024) uint8_t smem_g[];
  const uint32_t base = smem_u32(smem_g);
  const int tid = threadIdx.x, warp = __shfl_sync(0xffffffffu, tid >> 5, 0), lane = tid & 31;
  const int rank = blockIdx.x % GCL;
  KT_START(2);
  if (tid == 0) {
    for (int s = 0; s < NST; s++) { mbar_init(base + B_FULL + 8 * s, 1); mbar_init(base + B_EMPTY + 8 * s, 8 * GCL); }
    for (int s = 0; s < 8; s++) mbar_init(base + B_ITEM + 8 * s, 1);
    for (int s = 0; s < 2; s++) { mbar_init(base + B_FILL + 8 * s, 4); mbar_init(base + B_FREE + 8 * s, NEW); }
    mbar_init(base + B_LN, 1);
    fence_barrier_init();
  }
  __syncthreads();
  if (GCL > 1) cluster_sync();
  auto release = [&](uint32_t st) {
    if (GCL > 1) { if (lane < GCL) mbar_arrive_cluster(base + B_EMPTY + 8 * st, lane); }
    else if (lane == 0) mbar_arrive(base + B_EMPTY + 8 * st);
  };
  auto get_item = [&](int q) {
    mbar_wait(base + B_ITEM + 8 * (q & 7), (q >> 3) & 1);
    return lds32(base + ITEMS + 4 * (q & 7));
  };

  if (warp == 8) {
    if (lane < 10) prefetch_tmap(&P.a[0] + lane);
    if (lane == 0) {
      uint32_t st = 0, ph = 1;
#pragma unroll 1
      for (int q = 0;; q++) {
        if (GCL > 1) mbar_expect_tx(base + B_ITEM + 8 * (q & 7), 4);
        if (rank == 0) {
          const unsigned idx = atomicAdd(&g_next, 1), ln = idx - P.lnpos;
          const uint32_t v = (idx < (unsigned)P.nitems ? P.items[idx] : T_END) | (ln < 64 / GCL ? (ln + 1) << 16 : 0);
          if (GCL > 1) {
#pragma unroll
            for (int r = 0; r < GCL; r++) st_async32(mapa(base + ITEMS + 4 * (q & 7), r), v, mapa(base + B_ITEM + 8 * (q & 7), r));
          } else {
            sts32(base + ITEMS + 4 * (q & 7), v);
            mbar_arrive(base + B_ITEM + 8 * (q & 7));
          }
        }
        const uint32_t item = get_item(q);
        const int type = item & 7, mb = ((item >> 3) & 15) + rank, nt = (item >> 7) & 15;
        ILOG(1);
        if (q == 0) { __threadfence(); sts32(base + ITEMS + 32, ld_strong4(&g_oflag[14]) >= 32); }
        if (type == T_END) break;
        if (type == T_B2) {
          wait_count(&g_cnt[T_B1][max(mb - 1, 0)], 4 * NEW); wait_count(&g_cnt[T_B1][mb], 4 * NEW); wait_count(&g_cnt[T_B1][min(mb + 1, 15)], 4 * NEW);
        } else if (type == T_B3) wait_count(&g_cnt[T_LN][mb], 32);
        else if (type == T_B4) wait_count(&g_cnt[T_B3][mb], 14 * NEW);
        else if (type == T_O) wait_count(&g_oflag[mb], 32);
        asm volatile("fence.proxy.async.global;" ::: "memory");
        ILOG(2);
        const CUtensorMap *ma = &P.a[type], *mbm = &P.b[type];
        const int nkb = type == T_B4 ? cfg::F / 64 : type == T_O ? cfg::HD / 64 : cfg::D / 64;
#pragma unroll 1
        for (int kb = 0; kb < nkb; kb++) {
          mbar_wait(base + B_EMPTY + 8 * st, ph);
          const uint32_t sa = base + st * STAGE, full = base + B_FULL + 8 * st;
          mbar_expect_tx(full, STAGE);
          int arow = mb * 128;
          if (type == T_B2) { const int qd = kb >> 2; arow += (qd == 0) ? -1 : (qd == 1) ? 1 : (qd == 2) ? -2 : 2; }
          if (GCL > 1) tma_load_3d_mc(sa + 16384 + rank * 16384, mbm, 0, kb * 64, nt * 4 + rank * 2, full);
          else tma_load_3d(sa + 16384, mbm, 0, kb * 64, nt * 4, full);
          if (q == 0 && kb == 0) { mbar_wait(base + B_LN, 0); asm volatile("fence.proxy.async.global;" ::: "memory"); }
          tma_load_2d(sa, ma, kb * 64, arow, full);
          if (++st == NST) { st = 0; ph ^= 1; }
        }
      }
    }
  } else {
    const int wg = warp >> 2, ew = warp > 8 ? warp - 9 : warp + NEW;
    const uint32_t outa = base + OUTB + (warp * 16 + ((lane >> 3) & 1) * 8 + (lane & 7)) * 512 + (((lane >> 4) ^ (lane & 7)) << 4);
    uint32_t st = 0, ph = 0;
    float acc[128];
    auto kill_acc = [&]() {
#pragma unroll
      for (int i = 0; i < 128; i++) acc[i] = 0.f;
    };
    if (warp == 9) {
#pragma unroll 1
      for (int tries = 0; tries < POLL_TRIES; tries++) {
        uint4 v;
        asm volatile("ld.acquire.gpu.global.v4.u32 {%0,%1,%2,%3}, [%4];" : "=r"(v.x), "=r"(v.y), "=r"(v.z), "=r"(v.w)
                     : "l"(lane < 24 ? &g_mask[4 * lane] : &g_lnok[0]) : "memory");
        const uint32_t ok = __ballot_sync(0xffffffffu, v.x & v.y & v.z & v.w & 0x100);
        if ((ok & 0xFFFFFF) == 0xFFFFFF || (ok >> 24)) break;
        __nanosleep(200);
      }
      if (lane == 0) mbar_arrive(base + B_LN);
    }
    uint32_t next = get_item(0);
#pragma unroll 1
    for (int q = 0;; q++) {
      const uint32_t item = next;
      const int type = item & 7, mb = ((item >> 3) & 15) + rank, nt = (item >> 7) & 15;
      if (type == T_END) break;
      if (warp < 8) {
      if (item >> 16) {
        const int ln = (item >> 16) - 1, lb = (ln >> 2) * GCL + rank;
        const size_t row = (size_t)(lb * 128 + (ln & 3) * 32 + warp * 4) * cfg::D;
        wait_count(&g_cnt[T_B2][lb], 4 * NEW);
        uint32_t cur[2][16], nxt[2][16];
#pragma unroll
        for (int r = 0; r < 2; r++) {
          load_row16(cur[r], P.c[T_B2] + row + r * cfg::D, lane);
          load_row16(nxt[r], P.c[T_B2] + row + (r + 2) * cfg::D, lane);
        }
#pragma unroll 1
        for (int r2 = 0; r2 < 4; r2 += 2) {
          ln_regs<2>(cur);
#pragma unroll
          for (int r = 0; r < 2; r++) {
            store_row16(cur[r], P.x1n + row + (r2 + r) * cfg::D, lane);
#pragma unroll
            for (int i = 0; i < 16; i++) cur[r][i] = nxt[r][i];
          }
        }
        __syncwarp();
        if (lane == 0) asm volatile("red.release.gpu.global.add.u32 [%0], 1;" ::"l"(&g_cnt[T_LN][lb]) : "memory");
        __syncwarp();
        if (tid == 0) ILOG(6);
        kill_acc();
      }
      const int nkb = type == T_B4 ? cfg::F / 64 : type == T_O ? cfg::HD / 64 : cfg::D / 64;
      uint32_t prev = 0;
      mbar_wait(base + B_FULL + 8 * st, ph);
#pragma unroll 1
      for (int kb = 0; kb < nkb; kb++) {
        mbar_spin(base + B_FULL + 8 * st, ph);
        if (kb == 0 && tid == 0) ILOG(3);
        const uint64_t da = make_desc(base + wg * 8192, 16, 1024) + st * (STAGE >> 4), db = make_desc(base + 16384, 8192, 1024) + st * (STAGE >> 4);
        wg_fence();
#pragma unroll
        for (int k = 0; k < 4; k++) {
          wgmma_ss_n256_tb(acc, da + k * 2, db + k * 128, (kb | k) != 0);
          if (k == 0) {
            wg_commit();
            wg_wait<1>();
            if (kb > 0) release(prev);
            wg_fence();
          }
        }
        wg_commit();
        prev = st;
        if (++st == NST) { st = 0; ph ^= 1; }
      }
      next = get_item(q + 1);
      if (q > 0) mbar_wait(base + B_FREE + 8 * wg, (q - 1) & 1);
      wg_wait<0>();
      if (tid == 0) ILOG(4);
      release(prev);
#pragma unroll
      for (int j = 0; j < 16; j++)
        stsm4((outa ^ ((j & 3) << 5)) + (j >> 2) * 128, pack_bf16(acc[8 * j], acc[8 * j + 1]), pack_bf16(acc[8 * j + 2], acc[8 * j + 3]),
              pack_bf16(acc[8 * j + 4], acc[8 * j + 5]), pack_bf16(acc[8 * j + 6], acc[8 * j + 7]));
      __syncwarp();
      if (lane == 0) mbar_arrive(base + B_FILL + 8 * wg);
      if (tid == 0) ILOG(5);
      if ((next & 7) != T_END) continue;
      }
      if (type == T_O) wait_count(&g_cnt[T_B4][mb], 4 * NEW);
      const int ldc = type == T_B3 ? cfg::F : cfg::D;
      bf16* cp = P.c[type] + (size_t)mb * 128 * ldc + nt * 256 + lane * 8;
      const size_t roff = (size_t)mb * 128 * cfg::D + nt * 256 + lane * 8;
      const bf16 *rp = P.r[type] + roff, *gp = P.c[T_B4] + roff;
      const bool res = type == T_B2 || type >= T_B4, act = type != T_B2 && type != T_O;
      const float c1 = type == T_B4 ? 0.f : 0.035677408136300125f, c0 = type == T_B4 ? 0.5f : 0.7978845608028654f;
      uint32_t yn[4][4];
      uint4 rn[4], gn[4];
#pragma unroll
      for (int i = 0; i < 4; i++) rn[i] = gn[i] = make_uint4(0, 0, 0, 0);
      auto fetch_res = [&](int grp) {
#pragma unroll
        for (int i = 0; i < 4; i++) {
          if (res) rn[i] = __ldcg(reinterpret_cast<const uint4*>(rp + (grp * 4 + i) * cfg::D));
          if (type == T_O) gn[i] = __ldcg(reinterpret_cast<const uint4*>(gp + (grp * 4 + i) * cfg::D));
        }
      };
      auto fetch_y = [&](int grp) {
#pragma unroll
        for (int i = 0; i < 4; i++) lds128(yn[i], base + OUTB + (grp * 4 + i) * 512 + ((lane ^ ((grp * 4 + i) & 7)) << 4));
      };
      if (type == T_B4) wait_count(&g_cnt[T_B2][mb], 4 * NEW);
      if (type >= T_B4 && warp > 8) for (int r = tid - 288; r < 128; r += 96) l2_prefetch(rp - lane * 8 + r * cfg::D, 512);
      fetch_res(ew);
      mbar_wait(base + B_FILL, q & 1);
      fetch_y(ew);
      next = get_item(q + 1);
      const int stride = (next & 7) == T_END ? NEW + 8 : NEW;
#pragma unroll 1
      for (int grp = ew; grp < 32; grp += stride) {
        uint32_t y[4][4];
#pragma unroll
        for (int i = 0; i < 4; i++) {
#pragma unroll
          for (int k = 0; k < 4; k++) y[i][k] = yn[i][k];
          if (type == T_O) {
            y[i][0] = mul_bf16x2(y[i][0], gn[i].x); y[i][1] = mul_bf16x2(y[i][1], gn[i].y);
            y[i][2] = mul_bf16x2(y[i][2], gn[i].z); y[i][3] = mul_bf16x2(y[i][3], gn[i].w);
          }
          if (res) {
            y[i][0] = add_bf16x2(y[i][0], rn[i].x); y[i][1] = add_bf16x2(y[i][1], rn[i].y);
            y[i][2] = add_bf16x2(y[i][2], rn[i].z); y[i][3] = add_bf16x2(y[i][3], rn[i].w);
          }
        }
        const int nx = grp + stride;
        if (nx < 32) {
          fetch_res(nx);
          if (nx >= 16 && grp < 16) {
            __syncwarp();
            if (lane == 0 && warp > 8) mbar_arrive(base + B_FREE);
            mbar_wait(base + B_FILL + 8, q & 1);
          }
          fetch_y(nx);
        }
        if (act) {
#pragma unroll
          for (int i = 0; i < 4; i++)
#pragma unroll
            for (int k = 0; k < 4; k++) {
              const float v0 = bf_lo(y[i][k]), v1 = bf_hi(y[i][k]);
              const float t0 = tanh_approx(v0 * fmaf(v0 * c1, v0, c0)), t1 = tanh_approx(v1 * fmaf(v1 * c1, v1, c0));
              const float h0 = 0.5f * v0, h1 = 0.5f * v1;
              y[i][k] = pack_bf16(fmaf(h0, t0, h0), fmaf(h1, t1, h1));
            }
        }
#pragma unroll
        for (int i = 0; i < 4; i++)
          *reinterpret_cast<uint4*>(cp + (size_t)(grp * 4 + i) * ldc) = make_uint4(y[i][0], y[i][1], y[i][2], y[i][3]);
      }
      __syncwarp();
      if (lane == 0 && warp > 8) mbar_arrive(base + B_FREE + 8);
      if (stride != NEW) named_bar_sync(2, 352);
      if (type != T_O && lane == 0 && warp > 8) asm volatile("red.release.gpu.global.add.u32 [%0], 1;" ::"l"(&g_cnt[type][mb]) : "memory");
      __syncwarp();
      if (tid == 288) ILOG(7);
      kill_acc();
    }
    KT_END(2);
  }
  __syncwarp();
  if (warp >= 8) {
   named_bar_sync(1, 128);
   const bool late = lds32(base + ITEMS + 32);
   if (late) pdl_wait();
#pragma unroll 1
   for (int c = blockIdx.x; late && c < 96; c += gridDim.x) {
     if (__ldcg(&g_tfix[c]) == 0) continue;
     const int hh = c / 3, mb = TAIL_MB0 + 3 * (hh >> 4) + c % 3;
     wait_count(&g_cnt[T_B4][mb], GATE_CNT);
#pragma unroll 1
     for (int i = tid - 256; i < 1024; i += 128) {
       const size_t off = (size_t)(mb * 128 + (i >> 3)) * cfg::D + (hh & 15) * 64 + (i & 7) * 8;
       const uint4 sv = __ldcg(reinterpret_cast<const uint4*>(P.c[T_O] + off)), gv = __ldcg(reinterpret_cast<const uint4*>(P.c[T_B4] + off)),
                   xv = __ldcg(reinterpret_cast<const uint4*>(P.r[T_O] + off));
       *reinterpret_cast<uint4*>(P.c[T_O] + off) = make_uint4(add_bf16x2(xv.x, mul_bf16x2(sv.x, gv.x)), add_bf16x2(xv.y, mul_bf16x2(sv.y, gv.y)),
                                                              add_bf16x2(xv.z, mul_bf16x2(sv.z, gv.z)), add_bf16x2(xv.w, mul_bf16x2(sv.w, gv.w)));
     }
   }
  }
  if (GCL > 1) cluster_sync();
}

__device__ bf16 g_xn[cfg::S * cfg::D];
__device__ bf16 g_xn2[cfg::S * cfg::D];
__device__ bf16 g_h[cfg::S * cfg::D];
__device__ bf16 g_x1[cfg::S * cfg::D];
__device__ bf16 g_x1n[cfg::S * cfg::D];
__device__ bf16 g_u[cfg::S * cfg::F];
__device__ bf16 g_g[cfg::S * cfg::D];
__device__ bf16 g_o[cfg::S * cfg::HD];

typedef CUresult (*PFN_encodeTiled)(CUtensorMap*, CUtensorMapDataType, cuuint32_t, void*, const cuuint64_t*,
                                    const cuuint64_t*, const cuuint32_t*, const cuuint32_t*, CUtensorMapInterleave,
                                    CUtensorMapSwizzle, CUtensorMapL2promotion, CUtensorMapFloatOOBfill);

static PFN_encodeTiled get_encoder() {
  static PFN_encodeTiled fn = nullptr;
  if (!fn) {
    void* p = nullptr;
    cudaDriverEntryPointQueryResult st;
    cudaGetDriverEntryPoint("cuTensorMapEncodeTiled", &p, cudaEnableDefault, &st);
    fn = (PFN_encodeTiled)p;
  }
  return fn;
}
static CUtensorMap make_map(const void* ptr, int rows, int cols, int box_rows, int box_cols, int swizzle_bytes) {
  CUtensorMap m;
  cuuint64_t dims[2] = {(cuuint64_t)cols, (cuuint64_t)rows};
  cuuint64_t strides[1] = {(cuuint64_t)cols * 2};
  cuuint32_t box[2] = {(cuuint32_t)box_cols, (cuuint32_t)box_rows};
  cuuint32_t estr[2] = {1, 1};
  CUtensorMapSwizzle sw = swizzle_bytes == 128 ? CU_TENSOR_MAP_SWIZZLE_128B
                        : swizzle_bytes == 64 ? CU_TENSOR_MAP_SWIZZLE_64B
                        : swizzle_bytes == 32 ? CU_TENSOR_MAP_SWIZZLE_32B : CU_TENSOR_MAP_SWIZZLE_NONE;
  get_encoder()(&m, CU_TENSOR_MAP_DATA_TYPE_BFLOAT16, 2, const_cast<void*>(ptr), dims, strides, box, estr,
                CU_TENSOR_MAP_INTERLEAVE_NONE, sw, CU_TENSOR_MAP_L2_PROMOTION_L2_128B, CU_TENSOR_MAP_FLOAT_OOB_FILL_NONE);
  return m;
}
static CUtensorMap make_map3(const void* ptr, int rows, int cols, int box_rows, int nblk) {
  CUtensorMap m;
  cuuint64_t dims[3] = {64, (cuuint64_t)rows, (cuuint64_t)(cols / 64)};
  cuuint64_t strides[2] = {(cuuint64_t)cols * 2, 128};
  cuuint32_t box[3] = {64, (cuuint32_t)box_rows, (cuuint32_t)nblk};
  cuuint32_t estr[3] = {1, 1, 1};
  get_encoder()(&m, CU_TENSOR_MAP_DATA_TYPE_BFLOAT16, 3, const_cast<void*>(ptr), dims, strides, box, estr,
                CU_TENSOR_MAP_INTERLEAVE_NONE, CU_TENSOR_MAP_SWIZZLE_128B, CU_TENSOR_MAP_L2_PROMOTION_L2_128B,
                CU_TENSOR_MAP_FLOAT_OOB_FILL_NONE);
  return m;
}
template <class T> static T* sym(T& s) { void* p = nullptr; cudaGetSymbolAddress(&p, s); return (T*)p; }
#define SYM(name) ((bf16*)[] { void* p = nullptr; cudaGetSymbolAddress(&p, name); return p; }())

#define G_CTAS 36
#define B4_FIRST (GCL == 1 ? 9 : 16)
#define O_FIRST 2
#define LN_POS 63
static int build_items(uint16_t* it) {
  using namespace gk;
  int n = 0;
  auto add = [&](int type, int nrows, int ncols, int row0 = 0) {
    for (int mb = row0; mb < nrows; mb += GCL) for (int nt = 0; nt < ncols; nt++) it[n++] = (uint16_t)(type | mb << 3 | nt << 7);
  };
  add(T_B1, 16, 4); add(T_B2, 16, 4); add(T_B3, 16, 14);
  add(T_B4, B4_FIRST, 4); add(T_O, O_FIRST, 4); add(T_B4, 16, 4, B4_FIRST); add(T_O, TAIL_MB0, 4, O_FIRST);
  return n;
}

extern "C" void kernel_launch(void* const* d_in, const int* in_sizes, int n_in, void* d_out, int out_size) {
  using namespace cfg;
  const bf16* x = (const bf16*)d_in[0];
  const bf16* mem0 = (const bf16*)d_in[1];
  const bf16* Wq = (const bf16*)d_in[2];
  const bf16* Wk = (const bf16*)d_in[3];
  const bf16* Wv = (const bf16*)d_in[4];
  const bf16* Wo = (const bf16*)d_in[5];
  const bf16* w1 = (const bf16*)d_in[8];
  const bf16* w2 = (const bf16*)d_in[9];
  const bf16* w3 = (const bf16*)d_in[10];
  const bf16* w4 = (const bf16*)d_in[11];
  bf16* out = (bf16*)d_out;
  cudaStream_t st = cudaStreamPerThread;

  bf16 *xn = SYM(g_xn), *xn2 = SYM(g_xn2), *hb = SYM(g_h), *x1 = SYM(g_x1), *x1n = SYM(g_x1n), *u = SYM(g_u),
       *g = SYM(g_g), *o = SYM(g_o);

  {
    cudaFuncSetAttribute(f_kernel, cudaFuncAttributeMaxDynamicSharedMemorySize, fk::SMEM);
    FParams P;
    P.wq = make_map(Wq, D, HD, 64, 64, 128); P.wk = make_map(Wk, D, HD, 64, 64, 128); P.wv = make_map(Wv, D, HD, 64, 64, 128);
    P.wo = make_map(Wo, HD, D, 128, 64, 128); P.wo16 = make_map(Wo, HD, D, 128, 16, 32); P.xn = make_map3(xn, S, D, 32, 4); P.xn12 = make_map3(xn, S, D, 32, 12); P.o = make_map3(o, S, HD, 32, 2);
    P.ta = make_map(o, S, HD, 128, 64, 128); P.tb = make_map(Wo, HD, D, 64, 64, 128); P.tx = make_map(x, S, D, 128, 64, 128);
    P.tg = make_map(g, S, D, 128, 64, 128); P.tout = make_map(out, S, D, 16, 64, 128);
    P.mem0 = mem0;
    P.nprobe = PROBE_N;
    P.dxn = make_desc(fk::XN, 16, 1024);
    P.x = x; P.w1 = w1; P.xn_ptr = xn; P.xn2 = xn2;
    P.xch = (char*)(((uintptr_t)SYM(g_xch) + 8191) & ~(uintptr_t)8191);
    cudaLaunchConfig_t cfg = {};
    cfg.gridDim = dim3(96); cfg.blockDim = dim3(256); cfg.dynamicSmemBytes = fk::SMEM; cfg.stream = st;
    cudaLaunchAttribute at[2];
    at[0].id = cudaLaunchAttributeClusterDimension;
    at[0].val.clusterDim.x = 3; at[0].val.clusterDim.y = 1; at[0].val.clusterDim.z = 1;
    cfg.attrs = at; cfg.numAttrs = 1;
    cudaLaunchKernelEx(&cfg, f_kernel, P);
  }
  {
    cudaFuncSetAttribute(g_kernel, cudaFuncAttributeMaxDynamicSharedMemorySize, gk::SMEM);
    GParams G;
    const bf16* as[5] = {xn2, hb, x1n, u, o};
    const bf16* bs[5] = {w1, w2, w3, w4, Wo};
    bf16* cs[5] = {hb, x1, u, g, out};
    const bf16* rs[5] = {xn, xn, xn, x1, x};
    const int ks[5] = {D, D, D, F, HD}, ns[5] = {D, D, F, D, D};
    for (int i = 0; i < 5; i++) {
      G.a[i] = make_map(as[i], S, ks[i], 128, 64, 128);
      G.b[i] = make_map3(bs[i], ks[i], ns[i], 64, 4 / GCL);
      G.c[i] = cs[i];
      G.r[i] = rs[i];
    }
    G.x1n = x1n;
    G.nitems = build_items(G.items);
    G.lnpos = LN_POS * 2 / GCL;
    cudaLaunchConfig_t cfg = {};
    cfg.gridDim = dim3(G_CTAS); cfg.blockDim = dim3(384); cfg.dynamicSmemBytes = gk::SMEM; cfg.stream = st;
    cudaLaunchAttribute at[2];
    at[0].id = cudaLaunchAttributeClusterDimension;
    at[0].val.clusterDim.x = GCL; at[0].val.clusterDim.y = 1; at[0].val.clusterDim.z = 1;
    at[1].id = cudaLaunchAttributeProgrammaticStreamSerialization;
    at[1].val.programmaticStreamSerializationAllowed = 1;
    cfg.attrs = at;
    cfg.numAttrs = 2;
    cudaLaunchKernelEx(&cfg, g_kernel, G);
  }
}
```

```cpp
#include <cuda_runtime.h>
#include <cuda_bf16.h>
#include <cuda.h>
#include <stdint.h>

typedef __nv_bfloat16 bf16;

namespace cfg {
constexpr int S = 2048;
constexpr int D = 1024;
constexpr int H = 32;
constexpr int DH = 128;
constexpr int HD = H * DH;
constexpr int M = 8;
constexpr int SEG = 32;
constexpr int NSEG = S / SEG;
constexpr int F = 3584;
}

__device__ __forceinline__ uint32_t smem_u32(const void* p) { return (uint32_t)__cvta_generic_to_shared(p); }

__device__ __forceinline__ void mbar_init(uint32_t bar, uint32_t count) {
  asm volatile("mbarrier.init.shared::cta.b64 [%0], %1;" ::"r"(bar), "r"(count) : "memory");
}
__device__ __forceinline__ void mbar_expect_tx(uint32_t bar, uint32_t bytes) {
  asm volatile("mbarrier.arrive.expect_tx.shared::cta.b64 _, [%0], %1;" ::"r"(bar), "r"(bytes) : "memory");
}
__device__ __forceinline__ void mbar_arrive(uint32_t bar) {
  asm volatile("mbarrier.arrive.shared::cta.b64 _, [%0];" ::"r"(bar) : "memory");
}
__device__ __forceinline__ bool mbar_try(uint32_t bar, uint32_t parity) {
  uint32_t done;
  asm volatile("{\n.reg .pred p;\nmbarrier.try_wait.parity.shared::cta.b64 p, [%1], %2, 20000;\nselp.u32 %0, 1, 0, p;\n}"
               : "=r"(done) : "r"(bar), "r"(parity) : "memory");
  return done != 0;
}
__device__ __forceinline__ bool mbar_try_nohint(uint32_t bar, uint32_t parity) {
  uint32_t done;
  asm volatile("{\n.reg .pred p;\nmbarrier.try_wait.parity.shared::cta.b64 p, [%1], %2;\nselp.u32 %0, 1, 0, p;\n}"
               : "=r"(done) : "r"(bar), "r"(parity) : "memory");
  return done != 0;
}
constexpr int MBAR_TRIES = 4096;
constexpr int POLL_TRIES = 1 << 16;
__device__ __forceinline__ void mbar_wait(uint32_t bar, uint32_t parity) {
#pragma unroll 1
  for (int n = 0; n < MBAR_TRIES; n++)
    if (mbar_try(bar, parity)) break;
}
__device__ __forceinline__ void mbar_wait_fast(uint32_t bar, uint32_t parity) {
#pragma unroll 1
  for (int n = 0; n < (POLL_TRIES << 4); n++)
    if (mbar_try_nohint(bar, parity)) break;
}
__device__ __forceinline__ void fence_barrier_init() { asm volatile("fence.mbarrier_init.release.cluster;" ::: "memory"); }
__device__ __forceinline__ void fence_proxy_async_smem() { asm volatile("fence.proxy.async.shared::cta;" ::: "memory"); }

__device__ __forceinline__ void tma_load_2d(uint32_t dst, const CUtensorMap* map, int x, int y, uint32_t bar) {
  asm volatile("cp.async.bulk.tensor.2d.shared::cluster.global.mbarrier::complete_tx::bytes [%0], [%1, {%3, %4}], [%2];"
               ::"r"(dst), "l"(map), "r"(bar), "r"(x), "r"(y) : "memory");
}
__device__ __forceinline__ void tma_load_3d(uint32_t dst, const CUtensorMap* map, int x, int y, int z, uint32_t bar) {
  asm volatile("cp.async.bulk.tensor.3d.shared::cluster.global.mbarrier::complete_tx::bytes [%0], [%1, {%3, %4, %5}], [%2];"
               ::"r"(dst), "l"(map), "r"(bar), "r"(x), "r"(y), "r"(z) : "memory");
}
__device__ __forceinline__ void tma_store_2d(const CUtensorMap* map, uint32_t src, int x, int y) {
  asm volatile("cp.async.bulk.tensor.2d.global.shared::cta.bulk_group [%0, {%2, %3}], [%1];"
               ::"l"(map), "r"(src), "r"(x), "r"(y) : "memory");
}
__device__ __forceinline__ void tma_store_commit() { asm volatile("cp.async.bulk.commit_group;" ::: "memory"); }
__device__ __forceinline__ void tma_store_wait_all() { asm volatile("cp.async.bulk.wait_group 0;" ::: "memory"); }
__device__ __forceinline__ void tma_store_wait_read() { asm volatile("cp.async.bulk.wait_group.read 0;" ::: "memory"); }
__device__ __forceinline__ void prefetch_tmap(const CUtensorMap* map) {
  asm volatile("prefetch.tensormap [%0];" ::"l"(map) : "memory");
}

__device__ __forceinline__ void wg_fence() { asm volatile("wgmma.fence.sync.aligned;" ::: "memory"); }
__device__ __forceinline__ void wg_commit() { asm volatile("wgmma.commit_group.sync.aligned;" ::: "memory"); }
template <int N> __device__ __forceinline__ void wg_wait() { asm volatile("wgmma.wait_group.sync.aligned %0;" ::"n"(N) : "memory"); }

#define named_bar_sync(id, n) asm volatile("bar.sync %0, %1;" ::"n"(id), "n"(n) : "memory")
#define named_bar_arrive(id, n) asm volatile("bar.arrive %0, %1;" ::"n"(id), "n"(n) : "memory")

__host__ __device__ __forceinline__ uint64_t make_desc(uint32_t addr, uint32_t lbo, uint32_t sbo) {
  return (uint64_t)((addr & 0x3FFFF) >> 4) | ((uint64_t)(lbo >> 4) << 16) | ((uint64_t)(sbo >> 4) << 32) | (1ull << 62);
}

__device__ __forceinline__ uint64_t make_desc0(uint32_t addr, uint32_t lbo, uint32_t sbo) {
  return (uint64_t)((addr & 0x3FFFF) >> 4) | ((uint64_t)(lbo >> 4) << 16) | ((uint64_t)(sbo >> 4) << 32);
}

__device__ __forceinline__ uint32_t pack_bf16(float lo, float hi) {
  uint32_t r;
  asm("cvt.rn.bf16x2.f32 %0, %1, %2;" : "=r"(r) : "f"(hi), "f"(lo));
  return r;
}
__device__ __forceinline__ float bf_lo(uint32_t v) { return __uint_as_float(v << 16); }
__device__ __forceinline__ float bf_hi(uint32_t v) { return __uint_as_float(v & 0xFFFF0000u); }
__device__ __forceinline__ float rbf(float v) { return __bfloat162float(__float2bfloat16_rn(v)); }

__device__ __forceinline__ void pdl_launch_dependents() { asm volatile("griddepcontrol.launch_dependents;" ::: "memory"); }
__device__ __forceinline__ void pdl_wait() { asm volatile("griddepcontrol.wait;" ::: "memory"); }

__device__ __forceinline__ float ex2_approx(float x) { float y; asm("ex2.approx.ftz.f32 %0, %1;" : "=f"(y) : "f"(x)); return y; }
__device__ __forceinline__ float rcp_approx(float x) { float y; asm("rcp.approx.ftz.f32 %0, %1;" : "=f"(y) : "f"(x)); return y; }

__device__ __forceinline__ void mul_sigmoid4(float (&v)[4], const float (&t)[4]) {
#pragma unroll
  for (int i = 0; i < 4; i += 2) {
    const float a = 1.0f + ex2_approx(fminf(t[i], 60.0f)), b = 1.0f + ex2_approx(fminf(t[i + 1], 60.0f));
    const float r = rcp_approx(a * b);
    v[i] *= b * r;
    v[i + 1] *= a * r;
  }
}
__device__ __forceinline__ void gelu4(float (&v)[4]) {
  float t[4];
#pragma unroll
  for (int i = 0; i < 4; i++) t[i] = v[i] * fmaf(v[i] * v[i], -0.10294324f, -2.30220819f);
  mul_sigmoid4(v, t);
}
__device__ __forceinline__ void silu4(float (&v)[4]) {
  float t[4];
#pragma unroll
  for (int i = 0; i < 4; i++) t[i] = v[i] * -1.4426950408889634f;
  mul_sigmoid4(v, t);
}

#define KT_START(id)
#define KT_END(id)

__device__ __forceinline__ void wgmma_ss_n256_tb(float (&d)[128], uint64_t da, uint64_t db, int scale_d) {
  asm volatile("{\n.reg .pred p;\nsetp.ne.b32 p, %130, 0;\n"
    "wgmma.mma_async.sync.aligned.m64n256k16.f32.bf16.bf16 "
    "{%0, %1, %2, %3, %4, %5, %6, %7, %8, %9, %10, %11, %12, %13, %14, %15, "
    "%16, %17, %18, %19, %20, %21, %22, %23, %24, %25, %26, %27, %28, %29, %30, %31, "
    "%32, %33, %34, %35, %36, %37, %38, %39, %40, %41, %42, %43, %44, %45, %46, %47, "
    "%48, %49, %50, %51, %52, %53, %54, %55, %56, %57, %58, %59, %60, %61, %62, %63, "
    "%64, %65, %66, %67, %68, %69, %70, %71, %72, %73, %74, %75, %76, %77, %78, %79, "
    "%80, %81, %82, %83, %84, %85, %86, %87, %88, %89, %90, %91, %92, %93, %94, %95, "
    "%96, %97, %98, %99, %100, %101, %102, %103, %104, %105, %106, %107, %108, %109, %110, %111, "
    "%112, %113, %114, %115, %116, %117, %118, %119, %120, %121, %122, %123, %124, %125, %126, %127}, "
    "%128, %129, p, 1, 1, 0, 1;\n}\n"
    : "+f"(d[0]), "+f"(d[1]), "+f"(d[2]), "+f"(d[3]), "+f"(d[4]), "+f"(d[5]), "+f"(d[6]), "+f"(d[7]),
      "+f"(d[8]), "+f"(d[9]), "+f"(d[10]), "+f"(d[11]), "+f"(d[12]), "+f"(d[13]), "+f"(d[14]), "+f"(d[15]),
      "+f"(d[16]), "+f"(d[17]), "+f"(d[18]), "+f"(d[19]), "+f"(d[20]), "+f"(d[21]), "+f"(d[22]), "+f"(d[23]),
      "+f"(d[24]), "+f"(d[25]), "+f"(d[26]), "+f"(d[27]), "+f"(d[28]), "+f"(d[29]), "+f"(d[30]), "+f"(d[31]),
      "+f"(d[32]), "+f"(d[33]), "+f"(d[34]), "+f"(d[35]), "+f"(d[36]), "+f"(d[37]), "+f"(d[38]), "+f"(d[39]),
      "+f"(d[40]), "+f"(d[41]), "+f"(d[42]), "+f"(d[43]), "+f"(d[44]), "+f"(d[45]), "+f"(d[46]), "+f"(d[47]),
      "+f"(d[48]), "+f"(d[49]), "+f"(d[50]), "+f"(d[51]), "+f"(d[52]), "+f"(d[53]), "+f"(d[54]), "+f"(d[55]),
      "+f"(d[56]), "+f"(d[57]), "+f"(d[58]), "+f"(d[59]), "+f"(d[60]), "+f"(d[61]), "+f"(d[62]), "+f"(d[63]),
      "+f"(d[64]), "+f"(d[65]), "+f"(d[66]), "+f"(d[67]), "+f"(d[68]), "+f"(d[69]), "+f"(d[70]), "+f"(d[71]),
      "+f"(d[72]), "+f"(d[73]), "+f"(d[74]), "+f"(d[75]), "+f"(d[76]), "+f"(d[77]), "+f"(d[78]), "+f"(d[79]),
      "+f"(d[80]), "+f"(d[81]), "+f"(d[82]), "+f"(d[83]), "+f"(d[84]), "+f"(d[85]), "+f"(d[86]), "+f"(d[87]),
      "+f"(d[88]), "+f"(d[89]), "+f"(d[90]), "+f"(d[91]), "+f"(d[92]), "+f"(d[93]), "+f"(d[94]), "+f"(d[95]),
      "+f"(d[96]), "+f"(d[97]), "+f"(d[98]), "+f"(d[99]), "+f"(d[100]), "+f"(d[101]), "+f"(d[102]), "+f"(d[103]),
      "+f"(d[104]), "+f"(d[105]), "+f"(d[106]), "+f"(d[107]), "+f"(d[108]), "+f"(d[109]), "+f"(d[110]), "+f"(d[111]),
      "+f"(d[112]), "+f"(d[113]), "+f"(d[114]), "+f"(d[115]), "+f"(d[116]), "+f"(d[117]), "+f"(d[118]), "+f"(d[119]),
      "+f"(d[120]), "+f"(d[121]), "+f"(d[122]), "+f"(d[123]), "+f"(d[124]), "+f"(d[125]), "+f"(d[126]), "+f"(d[127])
    : "l"(da), "l"(db), "r"(scale_d));
}
__device__ __forceinline__ void wgmma_rs_n32(float (&d)[16], const uint32_t* a, uint64_t db, int scale_d) {
  asm volatile("{\n.reg .pred p;\nsetp.ne.b32 p, %21, 0;\n"
    "wgmma.mma_async.sync.aligned.m64n32k16.f32.bf16.bf16 "
    "{%0, %1, %2, %3, %4, %5, %6, %7, %8, %9, %10, %11, %12, %13, %14, %15}, "
    "{%16, %17, %18, %19}, %20, p, 1, 1, 0;\n}\n"
    : "+f"(d[0]), "+f"(d[1]), "+f"(d[2]), "+f"(d[3]), "+f"(d[4]), "+f"(d[5]), "+f"(d[6]), "+f"(d[7]),
      "+f"(d[8]), "+f"(d[9]), "+f"(d[10]), "+f"(d[11]), "+f"(d[12]), "+f"(d[13]), "+f"(d[14]), "+f"(d[15])
    : "r"(a[0]), "r"(a[1]), "r"(a[2]), "r"(a[3]), "l"(db), "r"(scale_d));
}
__device__ __forceinline__ void wgmma_ss_n32_ta(float (&d)[16], uint64_t da, uint64_t db, int scale_d) {
  asm volatile("{\n.reg .pred p;\nsetp.ne.b32 p, %18, 0;\n"
    "wgmma.mma_async.sync.aligned.m64n32k16.f32.bf16.bf16 "
    "{%0, %1, %2, %3, %4, %5, %6, %7, %8, %9, %10, %11, %12, %13, %14, %15}, "
    "%16, %17, p, 1, 1, 1, 0;\n}\n"
    : "+f"(d[0]), "+f"(d[1]), "+f"(d[2]), "+f"(d[3]), "+f"(d[4]), "+f"(d[5]), "+f"(d[6]), "+f"(d[7]),
      "+f"(d[8]), "+f"(d[9]), "+f"(d[10]), "+f"(d[11]), "+f"(d[12]), "+f"(d[13]), "+f"(d[14]), "+f"(d[15])
    : "l"(da), "l"(db), "r"(scale_d));
}
__device__ __forceinline__ void wgmma_ss_n8_ta(float (&d)[4], uint64_t da, uint64_t db, int scale_d) {
  asm volatile("{\n.reg .pred p;\nsetp.ne.b32 p, %6, 0;\n"
    "wgmma.mma_async.sync.aligned.m64n8k16.f32.bf16.bf16 {%0, %1, %2, %3}, %4, %5, p, 1, 1, 1, 0;\n}\n"
    : "+f"(d[0]), "+f"(d[1]), "+f"(d[2]), "+f"(d[3]) : "l"(da), "l"(db), "r"(scale_d));
}
__device__ __forceinline__ void wgmma_ss_n48_tt(float (&d)[24], uint64_t da, uint64_t db, int scale_d) {
  asm volatile("{\n.reg .pred p;\nsetp.ne.b32 p, %26, 0;\n"
    "wgmma.mma_async.sync.aligned.m64n48k16.f32.bf16.bf16 "
    "{%0, %1, %2, %3, %4, %5, %6, %7, %8, %9, %10, %11, %12, %13, %14, %15, %16, %17, %18, %19, %20, %21, %22, %23}, "
    "%24, %25, p, 1, 1, 1, 1;\n}\n"
    : "+f"(d[0]), "+f"(d[1]), "+f"(d[2]), "+f"(d[3]), "+f"(d[4]), "+f"(d[5]), "+f"(d[6]), "+f"(d[7]), "+f"(d[8]), "+f"(d[9]), "+f"(d[10]), "+f"(d[11]), "+f"(d[12]), "+f"(d[13]), "+f"(d[14]), "+f"(d[15]), "+f"(d[16]), "+f"(d[17]), "+f"(d[18]), "+f"(d[19]), "+f"(d[20]), "+f"(d[21]), "+f"(d[22]), "+f"(d[23])
    : "l"(da), "l"(db), "r"(scale_d));
}
__device__ __forceinline__ void wgmma_ss_n32(float (&d)[16], uint64_t da, uint64_t db, int scale_d) {
  asm volatile("{\n.reg .pred p;\nsetp.ne.b32 p, %18, 0;\n"
    "wgmma.mma_async.sync.aligned.m64n32k16.f32.bf16.bf16 "
    "{%0, %1, %2, %3, %4, %5, %6, %7, %8, %9, %10, %11, %12, %13, %14, %15}, "
    "%16, %17, p, 1, 1, 0, 0;\n}\n"
    : "+f"(d[0]), "+f"(d[1]), "+f"(d[2]), "+f"(d[3]), "+f"(d[4]), "+f"(d[5]), "+f"(d[6]), "+f"(d[7]),
      "+f"(d[8]), "+f"(d[9]), "+f"(d[10]), "+f"(d[11]), "+f"(d[12]), "+f"(d[13]), "+f"(d[14]), "+f"(d[15])
    : "l"(da), "l"(db), "r"(scale_d));
}

__device__ __forceinline__ void tma_load_2d_mc(uint32_t dst, const CUtensorMap* map, int x, int y, uint32_t bar, uint16_t mask) {
  asm volatile("cp.async.bulk.tensor.2d.shared::cluster.global.mbarrier::complete_tx::bytes.multicast::cluster "
               "[%0], [%1, {%3, %4}], [%2], %5;"
               ::"r"(dst), "l"(map), "r"(bar), "r"(x), "r"(y), "h"(mask) : "memory");
}
__device__ __forceinline__ void mbar_arrive_cluster(uint32_t bar, uint32_t cta) {
  asm volatile("{\n.reg .b32 r;\nmapa.shared::cluster.u32 r, %0, %1;\nmbarrier.arrive.shared::cluster.b64 _, [r];\n}"
               ::"r"(bar), "r"(cta) : "memory");
}
__device__ __forceinline__ void cluster_sync() {
  asm volatile("barrier.cluster.arrive.release.aligned;\nbarrier.cluster.wait.acquire.aligned;" ::: "memory");
}
__device__ __forceinline__ void wait_count(const unsigned* p, unsigned need) {
#pragma unroll 1
  for (int tries = 0; tries < (1 << 18); tries++) {
    unsigned v;
    asm volatile("ld.acquire.gpu.global.u32 %0, [%1];" : "=r"(v) : "l"(p) : "memory");
    if (v >= need) break;
    __nanosleep(64);
  }
}
__device__ __forceinline__ uint32_t sub_bf16x2(uint32_t a, uint32_t b) {
  uint32_t d;
  asm("sub.rn.bf16x2 %0, %1, %2;" : "=r"(d) : "r"(a), "r"(b));
  return d;
}
__device__ __forceinline__ uint32_t add_bf16x2(uint32_t a, uint32_t b) {
  uint32_t d;
  asm("add.rn.bf16x2 %0, %1, %2;" : "=r"(d) : "r"(a), "r"(b));
  return d;
}
__device__ __forceinline__ uint32_t mul_bf16x2(uint32_t a, uint32_t b) {
  uint32_t d;
  asm("mul.rn.bf16x2 %0, %1, %2;" : "=r"(d) : "r"(a), "r"(b));
  return d;
}

template <int NR>
__device__ __forceinline__ void ln_regs(uint32_t (&raw)[NR][16]) {
  float m[NR], q[NR];
#pragma unroll
  for (int r = 0; r < NR; r++) {
    float s0 = 0.f, s1 = 0.f;
#pragma unroll
    for (int i = 0; i < 16; i++) { s0 += bf_lo(raw[r][i]); s1 += bf_hi(raw[r][i]); }
    m[r] = s0 + s1;
  }
#pragma unroll
  for (int o = 16; o > 0; o >>= 1)
#pragma unroll
    for (int r = 0; r < NR; r++) m[r] += __shfl_xor_sync(0xffffffffu, m[r], o);
#pragma unroll
  for (int r = 0; r < NR; r++) {
    m[r] *= 1.0f / 1024.0f;
    float s0 = 0.f, s1 = 0.f;
#pragma unroll
    for (int i = 0; i < 16; i++) {
      const float d0 = bf_lo(raw[r][i]) - m[r], d1 = bf_hi(raw[r][i]) - m[r];
      s0 = fmaf(d0, d0, s0); s1 = fmaf(d1, d1, s1);
    }
    q[r] = s0 + s1;
  }
#pragma unroll
  for (int o = 16; o > 0; o >>= 1)
#pragma unroll
    for (int r = 0; r < NR; r++) q[r] += __shfl_xor_sync(0xffffffffu, q[r], o);
#pragma unroll
  for (int r = 0; r < NR; r++) {
    const uint32_t mb = pack_bf16(m[r], m[r]);
    float sq;
    asm("sqrt.approx.f32 %0, %1;" : "=f"(sq) : "f"(rbf(rbf(q[r] * (1.0f / 1024.0f)) + 1e-5f)));
    const float inv = rcp_approx(rbf(sq));
#pragma unroll
    for (int i = 0; i < 16; i++) {
      const uint32_t d = sub_bf16x2(raw[r][i], mb);
      raw[r][i] = pack_bf16(bf_lo(d) * inv, bf_hi(d) * inv);
    }
  }
}
__device__ __forceinline__ void load_row16(uint32_t (&raw)[16], const bf16* src, int lane) {
#pragma unroll
  for (int j = 0; j < 4; j++) {
    const uint4 u = __ldcg(reinterpret_cast<const uint4*>(src + j * 256 + lane * 8));
    raw[4 * j] = u.x; raw[4 * j + 1] = u.y; raw[4 * j + 2] = u.z; raw[4 * j + 3] = u.w;
  }
}
__device__ __forceinline__ void store_row16(const uint32_t (&raw)[16], bf16* dst, int lane) {
#pragma unroll
  for (int j = 0; j < 4; j++)
    *reinterpret_cast<uint4*>(dst + j * 256 + lane * 8) = make_uint4(raw[4 * j], raw[4 * j + 1], raw[4 * j + 2], raw[4 * j + 3]);
}

namespace fk {
constexpr uint32_t SM0 = 1024;
constexpr uint32_t WO = SM0, WS = WO + 90112, XN = WS + 65536, VX = XN + 49152, QK = VX + 8192, PT = QK + 8192,
                   SP = PT + 4096, VM = SP + 2560, OB = VM + 2048, BAR = OB + 2048;
constexpr uint32_t MEMB = XN + 16384, RED = XN + 32768, VX2 = WO + 81920;
constexpr int SMEM = 232448;
static_assert(BAR + 512 == SM0 + SMEM, "shared memory layout");
constexpr uint32_t B_XN = BAR, B_H2 = BAR + 64, B_H1 = BAR + 120, ONES = BAR + 384, B_PF = BAR + 16, B_WO = BAR + 24, B_SM = BAR + 32, B_VM = BAR + 40, B_VX = BAR + 48, B_ST = BAR + 56, B_PB = BAR + 64, B_W = BAR + 112,
                   MASKS = BAR + 128, PROBE = BAR + 256;
constexpr int NB_M0 = 1, NB_M1 = 2, NB_C = 3, NB_O = 4, NB_ST = 5, NB_DU = 6, NB_CF = 7, NB_W1 = 8, NB_XE = 9, NB_HD = 10, NB_MX = 11, NB_O0 = 12;
#define D_H1 500
#define D_H2 1800
#define D_ST 200
#define SMQ 0x1E
#define SMV 0x1E
#define PRE_G 5
#define WO_AT 4
#define NS0 4
#define NS0V 4
#define NTA0 2
#define NTA1 1
#define PF0A 3
#define PF0 10
#define PF1A 0
#define PF1V 10
#define PF1 11
#define REFILL_EARLY 1
#define GATE_MX 0
#define GATE_Q 0
#define PF1Q 4
#define PACEQ 0x60
#define PACEV 0
#define PADD 1
#define D_H2V 1950
#define H2_ATV 1
#define VM_BULK 0
#define CF_AT 0
#define H2_AT 0
#define NPRE0 1
#define PROBE_N 4
#define SPACK 1
constexpr uint32_t SPW = SPACK ? 4 : 8, SP_SRC = 160 * SPW;
constexpr int H1_BYTES = 64 * 32768, H2_BYTES = 8 * 8192;
}

#define PROF(wg, i)
#define PROF2(i)
#define RETRY(i)
#define GTSYNC(i)
#define PRO(i)
#define TL(i)
#define TL2(t, i)

__device__ uint4 g_xch[(fk::H1_BYTES + fk::H2_BYTES + 8192) / 16];
__device__ __align__(16) unsigned g_mask[128];
__device__ unsigned g_cnt[6][16];
__device__ unsigned g_next;
constexpr int TAIL_MB0 = 10, GATE_CNT = 12;
__device__ __align__(16) unsigned g_tfix[96], g_lnok[4];
__device__ uint4 g_tpart[96][3][4][256];
__device__ unsigned g_oflag[16];

#define LD_POLL "ld.global.L1::no_allocate"
__device__ __forceinline__ uint4 ld_poll16(const void* p) {
  uint4 v;
  asm volatile(LD_POLL ".v4.u32 {%0,%1,%2,%3}, [%4];" : "=r"(v.x), "=r"(v.y), "=r"(v.z), "=r"(v.w) : "l"(p) : "memory");
  return v;
}
__device__ __forceinline__ uint2 ld_poll8(const void* p) {
  uint2 v;
  asm volatile(LD_POLL ".v2.u32 {%0,%1}, [%2];" : "=r"(v.x), "=r"(v.y) : "l"(p) : "memory");
  return v;
}
__device__ __forceinline__ uint4 ld_strong16(const void* p) {
  uint4 v;
  asm volatile("ld.relaxed.gpu.global.v4.u32 {%0,%1,%2,%3}, [%4];" : "=r"(v.x), "=r"(v.y), "=r"(v.z), "=r"(v.w) : "l"(p) : "memory");
  return v;
}
__device__ __forceinline__ uint2 ld_strong8(const void* p) {
  uint2 v;
  asm volatile("ld.relaxed.gpu.global.v2.u32 {%0,%1}, [%2];" : "=r"(v.x), "=r"(v.y) : "l"(p) : "memory");
  return v;
}
__device__ __forceinline__ void st_pub32(void* p, uint32_t v) { asm volatile("st.relaxed.gpu.global.u32 [%0], %1;" ::"l"(p), "r"(v) : "memory"); }
__device__ __forceinline__ void st_pub16(void* p, uint32_t v) {
  asm volatile("st.relaxed.gpu.global.u16 [%0], %1;" ::"l"(p), "h"((uint16_t)v) : "memory");
}
__device__ __forceinline__ uint32_t ld_strong4(const void* p) {
  uint32_t v;
  asm volatile("ld.relaxed.gpu.global.u32 %0, [%1];" : "=r"(v) : "l"(p) : "memory");
  return v;
}
__device__ __forceinline__ void st_pub64(void* p, uint32_t a, uint32_t b) {
  asm volatile("st.relaxed.gpu.global.v2.u32 [%0], {%1,%2};" ::"l"(p), "r"(a), "r"(b) : "memory");
}
__device__ __forceinline__ void st_pub128(void* p, uint32_t a) {
  asm volatile("st.relaxed.gpu.global.v4.u32 [%0], {%1,%1,%1,%1};" ::"l"(p), "r"(a) : "memory");
}
constexpr uint32_t EMPTY = 0xFFFFFFFFu;
__device__ __forceinline__ uint32_t umax4(const uint4& v) { return max(max(v.x, v.y), max(v.z, v.w)); }
__device__ __forceinline__ void sts128(uint32_t a, uint32_t x, uint32_t y, uint32_t z, uint32_t w) {
  asm volatile("st.shared.v4.u32 [%0], {%1,%2,%3,%4};" ::"r"(a), "r"(x), "r"(y), "r"(z), "r"(w) : "memory");
}
__device__ __forceinline__ void sts64(uint32_t a, uint32_t x, uint32_t y) {
  asm volatile("st.shared.v2.u32 [%0], {%1,%2};" ::"r"(a), "r"(x), "r"(y) : "memory");
}
__device__ __forceinline__ void sts32(uint32_t a, uint32_t x) { asm volatile("st.shared.u32 [%0], %1;" ::"r"(a), "r"(x) : "memory"); }
__device__ __forceinline__ void sts128f(uint32_t a, float x, float y, float z, float w) {
  asm volatile("st.shared.v4.f32 [%0], {%1,%2,%3,%4};" ::"r"(a), "f"(x), "f"(y), "f"(z), "f"(w) : "memory");
}
__device__ __forceinline__ void sts64f(uint32_t a, float x, float y) {
  asm volatile("st.shared.v2.f32 [%0], {%1,%2};" ::"r"(a), "f"(x), "f"(y) : "memory");
}
__device__ __forceinline__ float4 lds128f(uint32_t a) {
  float4 v;
  asm volatile("ld.shared.v4.f32 {%0,%1,%2,%3}, [%4];" : "=f"(v.x), "=f"(v.y), "=f"(v.z), "=f"(v.w) : "r"(a) : "memory");
  return v;
}
__device__ __forceinline__ float2 lds64f(uint32_t a) {
  float2 v;
  asm volatile("ld.shared.v2.f32 {%0,%1}, [%2];" : "=f"(v.x), "=f"(v.y) : "r"(a) : "memory");
  return v;
}
__device__ __forceinline__ float2 lds64f_if(uint32_t a, bool on, float other) {
  float2 v = make_float2(other, other);
  asm volatile("{\n.reg .pred p;\nsetp.ne.u32 p, %3, 0;\n@p ld.shared.v2.f32 {%0,%1}, [%2];\n}" : "+f"(v.x), "+f"(v.y) : "r"(a), "r"((uint32_t)on) : "memory");
  return v;
}
__device__ __forceinline__ void lds128(uint32_t* r, uint32_t a) {
  asm volatile("ld.shared.v4.u32 {%0,%1,%2,%3}, [%4];" : "=r"(r[0]), "=r"(r[1]), "=r"(r[2]), "=r"(r[3]) : "r"(a) : "memory");
}
__device__ __forceinline__ void lds64(uint32_t* r, uint32_t a) {
  asm volatile("ld.shared.v2.u32 {%0,%1}, [%2];" : "=r"(r[0]), "=r"(r[1]) : "r"(a) : "memory");
}
__device__ __forceinline__ uint32_t lds32(uint32_t a) {
  uint32_t v;
  asm volatile("ld.shared.u32 %0, [%1];" : "=r"(v) : "r"(a) : "memory");
  return v;
}
__device__ __forceinline__ void ldsm4(uint32_t* r, uint32_t a) {
  asm volatile("ldmatrix.sync.aligned.m8n8.x4.shared.b16 {%0,%1,%2,%3}, [%4];"
               : "=r"(r[0]), "=r"(r[1]), "=r"(r[2]), "=r"(r[3]) : "r"(a) : "memory");
}
__device__ __forceinline__ void ldsm4t(uint32_t* r, uint32_t a) {
  asm volatile("ldmatrix.sync.aligned.m8n8.x4.trans.shared.b16 {%0,%1,%2,%3}, [%4];"
               : "=r"(r[0]), "=r"(r[1]), "=r"(r[2]), "=r"(r[3]) : "r"(a) : "memory");
}
__device__ __forceinline__ void stsm4(uint32_t a, uint32_t r0, uint32_t r1, uint32_t r2, uint32_t r3) {
  asm volatile("stmatrix.sync.aligned.m8n8.x4.shared.b16 [%0], {%1,%2,%3,%4};"
               ::"r"(a), "r"(r0), "r"(r1), "r"(r2), "r"(r3) : "memory");
}
__device__ __forceinline__ void stsm4t(uint32_t a, uint32_t r0, uint32_t r1, uint32_t r2, uint32_t r3) {
  asm volatile("stmatrix.sync.aligned.m8n8.x4.trans.shared.b16 [%0], {%1,%2,%3,%4};"
               ::"r"(a), "r"(r0), "r"(r1), "r"(r2), "r"(r3) : "memory");
}
__device__ __forceinline__ void mma16816(float* d, const uint32_t* a, uint32_t b0, uint32_t b1) {
  asm volatile("mma.sync.aligned.m16n8k16.row.col.f32.bf16.bf16.f32 {%0,%1,%2,%3}, {%4,%5,%6,%7}, {%8,%9}, {%0,%1,%2,%3};"
               : "+f"(d[0]), "+f"(d[1]), "+f"(d[2]), "+f"(d[3])
               : "r"(a[0]), "r"(a[1]), "r"(a[2]), "r"(a[3]), "r"(b0), "r"(b1));
}
__device__ __forceinline__ void mma16816z(float* d, const uint32_t* a, uint32_t b0, uint32_t b1) {
  asm volatile("mma.sync.aligned.m16n8k16.row.col.f32.bf16.bf16.f32 {%0,%1,%2,%3}, {%4,%5,%6,%7}, {%8,%9}, {%10,%10,%10,%10};"
               : "=f"(d[0]), "=f"(d[1]), "=f"(d[2]), "=f"(d[3])
               : "r"(a[0]), "r"(a[1]), "r"(a[2]), "r"(a[3]), "r"(b0), "r"(b1), "f"(0.f));
}
__device__ __forceinline__ void mma1688(float* d, uint32_t a0, uint32_t a1, uint32_t b0) {
  asm volatile("mma.sync.aligned.m16n8k8.row.col.f32.bf16.bf16.f32 {%0,%1,%2,%3}, {%4,%5}, {%6}, {%0,%1,%2,%3};"
               : "+f"(d[0]), "+f"(d[1]), "+f"(d[2]), "+f"(d[3]) : "r"(a0), "r"(a1), "r"(b0));
}
__device__ __forceinline__ uint32_t movtrans(uint32_t a) {
  uint32_t d;
  asm volatile("movmatrix.sync.aligned.m8n8.trans.b16 %0, %1;" : "=r"(d) : "r"(a));
  return d;
}
__device__ __forceinline__ uint32_t mapa(uint32_t a, uint32_t rank) {
  uint32_t d;
  asm("mapa.shared::cluster.u32 %0, %1, %2;" : "=r"(d) : "r"(a), "r"(rank));
  return d;
}
__device__ __forceinline__ void st_async64(uint32_t a, uint32_t x, uint32_t y, uint32_t bar) {
  asm volatile("st.async.weak.shared::cluster.mbarrier::complete_tx::bytes.v2.b32 [%0], {%1,%2}, [%3];"
               ::"r"(a), "r"(x), "r"(y), "r"(bar) : "memory");
}
__device__ __forceinline__ void st_async64f(uint32_t a, float x, float y, uint32_t bar) {
  st_async64(a, __float_as_uint(x), __float_as_uint(y), bar);
}
__device__ __forceinline__ void bulk_s2s(uint32_t dst, uint32_t src, uint32_t bytes, uint32_t bar) {
  asm volatile("cp.async.bulk.shared::cluster.shared::cta.mbarrier::complete_tx::bytes [%0], [%1], %2, [%3];"
               ::"r"(dst), "r"(src), "r"(bytes), "r"(bar) : "memory");
}
__device__ __forceinline__ void tma_store_3d(const CUtensorMap* map, uint32_t src, int x, int y, int z) {
  asm volatile("cp.async.bulk.tensor.3d.global.shared::cta.bulk_group [%0, {%2, %3, %4}], [%1];"
               ::"l"(map), "r"(src), "r"(x), "r"(y), "r"(z) : "memory");
}
__device__ __forceinline__ void mbar_spin(uint32_t bar, uint32_t parity) {
  asm volatile("{\n.reg .pred p;\n.reg .b32 n;\nmov.u32 n, 0x100000;\nMW_L:\n"
               "mbarrier.try_wait.parity.shared::cta.b64 p, [%0], %1;\n@p bra.uni MW_D;\n"
               "add.s32 n, n, -1;\nsetp.ne.u32 p, n, 0;\n@p bra.uni MW_L;\nMW_D:\n}" ::"r"(bar), "r"(parity) : "memory");
}
__device__ __forceinline__ bool mbar_test(uint32_t bar, uint32_t parity) {
  uint32_t done;
  asm volatile("{\n.reg .pred p;\nmbarrier.test_wait.parity.shared::cta.b64 p, [%1], %2;\nselp.u32 %0, 1, 0, p;\n}"
               : "=r"(done) : "r"(bar), "r"(parity) : "memory");
  return done != 0;
}
__device__ __forceinline__ void mbar_arrive_remote(uint32_t bar) {
  asm volatile("mbarrier.arrive.shared::cluster.b64 _, [%0];" ::"r"(bar) : "memory");
}
__device__ __forceinline__ bool elect_one() {
  uint32_t r;
  asm volatile("{\n.reg .pred p;\nelect.sync _|p, 0xffffffff;\nselp.u32 %0, 1, 0, p;\n}" : "=r"(r));
  return r != 0;
}
__device__ __forceinline__ void st_async32(uint32_t a, uint32_t x, uint32_t bar) {
  asm volatile("st.async.weak.shared::cluster.mbarrier::complete_tx::bytes.b32 [%0], %1, [%2];" ::"r"(a), "r"(x), "r"(bar) : "memory");
}
#define named_bar_and(id, n, in, out) \
  asm volatile("{\n.reg .pred p, q;\nsetp.ne.u32 p, %1, 0;\nbar.red.and.pred q, %2, %3, p;\nselp.u32 %0, 1, 0, q;\n}" \
               : "=r"(out) : "r"(in), "n"(id), "n"(n) : "memory")
__device__ __forceinline__ void bulk_g2s(uint32_t dst, const void* src, uint32_t bytes, uint32_t bar) {
  asm volatile("cp.async.bulk.shared::cluster.global.mbarrier::complete_tx::bytes [%0], [%1], %2, [%3];"
               ::"r"(dst), "l"(src), "r"(bytes), "r"(bar) : "memory");
}
__device__ __forceinline__ void l2_prefetch(const void* p, uint32_t bytes) {
  asm volatile("cp.async.bulk.prefetch.L2.global [%0], %1;" ::"l"(p), "r"(bytes) : "memory");
}

__device__ __forceinline__ uint32_t clk32() { uint32_t c; asm volatile("mov.u32 %0, %%clock;" : "=r"(c)::"memory"); return c; }
__device__ __forceinline__ void spin_until(uint32_t t) { while ((int32_t)(clk32() - t) < 0) {} }
#define PIN(x) asm volatile("" : "+r"(x))
#define OPQ                                                                                     \
  int tid_o = tid;                                                                              \
  asm volatile("" : "+r"(tid_o));                                                               \
  const int lane = tid_o & 31, w = (tid_o >> 5) & 3, t7 = tid_o & 127, lg = lane >> 2,          \
            lq = lane & 3, mi = lane >> 3, mr = lane & 7;                                       \
  (void)w; (void)t7; (void)lg; (void)lq; (void)mi; (void)mr; (void)lane

#define SMAP                                                                                                          \
  const uint32_t SM0 = self + fk::SM0, WO = self + fk::WO, WS = self + fk::WS, XN = self + fk::XN, VX = self + fk::VX, \
                 QK = self + fk::QK, PT = self + fk::PT, SP = self + fk::SP, VM = self + fk::VM, OB = self + fk::OB,   \
                 RED = self + fk::RED, VX2 = self + fk::VX2, MEMB = self + fk::MEMB, B_XN = self + fk::B_XN, B_SM = self + fk::B_SM,       \
                 B_VM = self + fk::B_VM, B_VX = self + fk::B_VX, B_ST = self + fk::B_ST, B_PB = self + fk::B_PB,       \
                 B_W = self + fk::B_W, B_H2 = self + fk::B_H2, B_H1 = self + fk::B_H1, B_PF = self + fk::B_PF, B_WO = self + fk::B_WO, MASKS = self + fk::MASKS, PROBE = self + fk::PROBE;                             \
  (void)SM0; (void)WO; (void)WS; (void)XN; (void)VX; (void)QK; (void)PT; (void)SP; (void)VM; (void)OB; (void)RED; (void)VX2; \
  (void)MEMB; (void)B_XN; (void)B_SM; (void)B_VM; (void)B_VX; (void)B_ST; (void)B_PB; (void)B_W; (void)MASKS; (void)PROBE; (void)B_H2; (void)B_H1; (void)B_PF; (void)B_WO

struct FParams {
  CUtensorMap wq, wk, wv, wo, wo16, xn, xn12, o;
  CUtensorMap ta, tb, tx, tg, tout;
  const bf16 *mem0, *x, *w1;
  bf16 *xn_ptr, *xn2;
  uint64_t dxn;
  int nprobe;
  char* xch;
};

__device__ __forceinline__ uint2 probe_pair(char* p, uint32_t val, uint32_t dummy, int n) {
  uint2 best = make_uint2(0x7FFFFFFF, 0x7FFFFFFF);
  st_pub128(p, val); st_pub128(p + 16, val); st_pub128(p + 4096, val); st_pub128(p + 4112, val);
#pragma unroll 1
  for (int r = 0; r < n; r++) {
    uint32_t v;
    const uint32_t c0 = clk32();
    asm volatile("atom.relaxed.gpu.global.exch.b32 %0, [%1], %2;" : "=r"(v) : "l"(p + (r & 1) * 4096), "r"(val) : "memory");
    asm volatile("{\n.reg .pred p;\nsetp.eq.u32 p, %0, 0x12345678;\n@p st.shared.u32 [%1], %0;\n}" ::"r"(v), "r"(dummy) : "memory");
    const uint32_t d = clk32() - c0;
    if (r & 1) best.y = min(best.y, d); else best.x = min(best.x, d);
  }
  return best;
}

typedef uint32_t WRegs[6][2][4][4];

constexpr uint32_t nth_chunks(uint32_t mask) {
  uint32_t t = 0;
  for (int c = 0, n = 0; c < 10; c++) if ((mask >> c) & 1) t |= c << (4 * n++);
  return t;
}
constexpr uint64_t chunk_pos(uint32_t mask) {
  uint64_t t = 0;
  for (int c = 0, a = 0, b = 0; c < 10; c++) t |= (uint64_t)(((mask >> c) & 1) ? a++ : b++) << (4 * c);
  return t;
}
template <bool ISV> struct Chunks {
  static constexpr uint32_t MASK = ISV ? SMV : SMQ, SMT = nth_chunks(MASK), RFT = nth_chunks(~MASK & 1023);
  static_assert(!(MASK & 1), "the first chunk initialises the accumulators");
  static __device__ __forceinline__ constexpr int rf(int wg, int i) { return wg ? 10 + i : (RFT >> (4 * i)) & 15; }
  static __device__ __forceinline__ constexpr int sm(int i) { return (SMT >> (4 * i)) & 15; }
  static constexpr uint64_t IDX = chunk_pos(MASK);
  static __device__ __forceinline__ constexpr int idx(int c) { return (IDX >> (4 * c)) & 15; }
};

template <bool ISV, int WG> struct ProjCfg {
  static constexpr int N0 = ISV ? NS0V : NS0, NS = WG ? 8 - N0 : N0, P0 = WG ? N0 : 0, NTA = WG ? NTA1 : NTA0;
};
__device__ __forceinline__ void load_pair(uint32_t (&t)[4][4], uint32_t wsa, int pp) {
#pragma unroll
  for (int f = 0; f < 4; f++) ldsm4t(t[f], wsa + ((pp >> 1) * 2 + (f & 1)) * 8192 + ((pp & 1) * 2 + (f >> 1)) * 2048);
}
template <bool ISV, int WG>
__device__ __forceinline__ void proj_mem(const WRegs& wr, uint32_t (&ta)[ProjCfg<ISV, WG>::NTA][4][4], uint32_t wsa, uint32_t mba,
                                         float (&a0)[4], float (&a1)[4]) {
  constexpr int NS = ProjCfg<ISV, WG>::NS, P0 = ProjCfg<ISV, WG>::P0, NTA = ProjCfg<ISV, WG>::NTA, NP = 12 + NS;
  float acc[4][4];
  auto spos = [](int j) { return j < NTA ? j : j + (j - NTA + 1) * 12 / (NS - NTA > 0 ? NS - NTA : 1); };
  auto which = [&](int p) { int r = -1; for (int j = 0; j < NS; j++) if (spos(j) == p) r = j; return r; };
  auto nsm_before = [&](int p) { int n = 0; for (int j = 0; j < NS; j++) if (spos(j) < p) n++; return n; };
#pragma unroll
  for (int p = 0; p < NP; p++) {
    const int j = which(p), r = j >= 0 ? 0 : p - nsm_before(p);
    uint32_t bp[4], tl[4][4];
    ldsm4(bp, mba + (j >= 0 ? Chunks<ISV>::sm((P0 + (j >= 0 ? j : 0)) >> 1) * 1024 + ((P0 + j) & 1) * 512 : Chunks<ISV>::rf(WG, r >> 1) * 1024 + (r & 1) * 512));
    if (j >= NTA) load_pair(tl, wsa, P0 + j);
#pragma unroll
    for (int u = 0; u < 2; u++)
#pragma unroll
      for (int T = 0; T < 2; T++) {
        const uint32_t* a = j >= NTA ? tl[u * 2 + T] : j >= 0 ? ta[j >= 0 ? j % NTA : 0][u * 2 + T] : wr[r >> 1][T][(r & 1) * 2 + u];
        if (p == 0) mma16816z(acc[u * 2 + T], a, bp[2 * u], bp[2 * u + 1]);
        else mma16816(acc[u * 2 + T], a, bp[2 * u], bp[2 * u + 1]);
      }
  }
#pragma unroll
  for (int i = 0; i < 4; i++) { a0[i] = acc[0][i] + acc[2][i]; a1[i] = acc[1][i] + acc[3][i]; }
}
template <bool ISV, int WG, int J0, int J1>
__device__ __forceinline__ void proj_mem_prefetch(uint32_t (&ta)[ProjCfg<ISV, WG>::NTA][4][4], uint32_t wsa) {
#pragma unroll
  for (int j = J0; j < J1; j++) load_pair(ta[j], wsa, ProjCfg<ISV, WG>::P0 + j);
}

template <bool ISV, int WG>
__device__ __forceinline__ void proj_finish(const float (&a0)[4], const float (&a1)[4], uint32_t peer0, uint32_t peer1, uint32_t self, int tid, int warp,
                                            uint32_t (&vmo)[4]) {
  using namespace fk;
  SMAP;
  OPQ;
  if (!ISV) {
    stsm4(PT + mr * 16 + ((mi >> 1) ? WG * 1024 + w * 256 + (mi & 1) * 128 : 2048 + w * 512 + (mi & 1) * 256 + WG * 128),
          pack_bf16(a0[0], a0[1]), pack_bf16(a0[2], a0[3]), pack_bf16(a1[0], a1[1]), pack_bf16(a1[2], a1[3]));
    named_bar_sync(NB_C, 256);
  } else {
    if (WG == 0) sts128f(RED + t7 * 16, a1[0], a1[1], a1[2], a1[3]);
    else sts128f(RED + 2048 + t7 * 16, a0[0], a0[1], a0[2], a0[3]);
    if (WG == 1) { lds64(vmo, VM + t7 * 8); lds64(vmo + 2, VM + 1024 + t7 * 8); }
    named_bar_sync(NB_C, 256);
    const float4 p = lds128f(RED + (1 - WG) * 2048 + t7 * 16);
    const float* k = WG == 0 ? a0 : a1;
    const uint32_t v0 = pack_bf16(k[0] + p.x, k[1] + p.y), v1 = pack_bf16(k[2] + p.z, k[3] + p.w);
    const uint32_t off = VM + WG * 1024 + t7 * 8;
    if (VM_BULK) {
      sts64(off, v0, v1);
      fence_proxy_async_smem();
      __syncwarp();
      const uint32_t a = VM + WG * 1024 + warp * 256;
      if (elect_one()) {
        bulk_s2s(peer0 + a, a, 256, peer0 + B_VM);
        bulk_s2s(peer1 + a, a, 256, peer1 + B_VM);
        mbar_arrive(B_VM);
      }
    } else {
      st_async64(peer0 + off, v0, v1, peer0 + B_VM);
      st_async64(peer1 + off, v0, v1, peer1 + B_VM);
      sts64(off, v0, v1);
      __syncwarp();
      if (lane == 0) mbar_arrive(B_VM);
    }
  }
}

__device__ __forceinline__ void send_scores(float s0, float s1, uint32_t off, uint32_t peer0, uint32_t peer1, uint32_t bar, int lane) {
  if (SPACK) {
    const uint32_t v = pack_bf16(s0, s1);
    st_async32(peer0 + off, v, peer0 + bar);
    st_async32(peer1 + off, v, peer1 + bar);
    sts32(off, v);
  } else {
    st_async64f(peer0 + off, s0, s1, peer0 + bar);
    st_async64f(peer1 + off, s0, s1, peer1 + bar);
    sts64f(off, s0, s1);
  }
  __syncwarp();
  if (lane == 0) mbar_arrive(bar);
}

template <int MODE>
__device__ __forceinline__ void wo_load(uint32_t* r, int f, uint32_t woa, uint32_t wob, bool third) {
  constexpr int NT = MODE ? 3 : 2;
  if (MODE >= 2 && f % 3 == 2)
    asm volatile("{\n.reg .pred p;\nsetp.ne.u32 p, %5, 0;\nmov.b32 %0, 0;\nmov.b32 %1, 0;\nmov.b32 %2, 0;\nmov.b32 %3, 0;\n"
                 "@p ldmatrix.sync.aligned.m8n8.x4.trans.shared.b16 {%0,%1,%2,%3}, [%4];\n}"
                 : "=r"(r[0]), "=r"(r[1]), "=r"(r[2]), "=r"(r[3]) : "r"(wob + (f / 3) * 512), "r"((uint32_t)third) : "memory");
  else ldsm4t(r, woa + (f % NT) * 32768 + (f / NT) * 2048);
}
template <int MODE, int PF>
__device__ __forceinline__ void wo_phase(uint32_t (&wf)[PF][4], uint32_t woa, uint32_t wob, bool third, uint32_t oba, char* h1p,
                                         uint32_t sel, uint32_t tag) {
  constexpr int NT = MODE ? 3 : 2;
  float c[NT][4];
  uint32_t of[2][4];
  ldsm4t(of[0], oba);
#pragma unroll
  for (int k = 0; k < 8; k++) {
    if ((k & 1) == 0 && k + 2 < 8) ldsm4t(of[((k >> 1) + 1) & 1], oba + ((k >> 1) + 1) * 512);
#pragma unroll
    for (int i = 0; i < NT; i++) {
      const int f = k * NT + i;
      const uint32_t b0 = of[(k >> 1) & 1][2 * (k & 1)], b1 = of[(k >> 1) & 1][2 * (k & 1) + 1];
      if (k == 0) mma16816z(c[i], wf[f % PF], b0, b1); else mma16816(c[i], wf[f % PF], b0, b1);
      if (f + PF < 8 * NT) wo_load<MODE>(wf[f % PF], f + PF, woa, wob, third);
    }
  }
#pragma unroll
  for (int i = 0; i < NT; i++) {
    char* p = h1p + i * (8 * 32768) + ((sel >> (2 * i)) & 3) * 2048;
    const uint32_t tm = (sel >> 10) & 1;
    if (MODE < 2 || i < 2 || third) {
      st_pub32(p, (pack_bf16(c[i][0], c[i][1]) & ~tm) | (tag & tm));
      st_pub32(p + 1024, (pack_bf16(c[i][2], c[i][3]) & ~tm) | (tag & tm));
    }
  }
}
template <int MODE, int F0, int F1, int PF>
__device__ __forceinline__ void wo_prefetch(uint32_t (&wf)[PF][4], uint32_t woa, uint32_t wob, bool third) {
#pragma unroll
  for (int f = F0; f < F1; f++) wo_load<MODE>(wf[f], f, woa, wob, third);
}

template <bool ISV> __device__ __forceinline__ uint32_t tok_addr(uint32_t base, int tid) {
  OPQ;
  return ISV ? base + w * 2048 + (mi & 1) * 1024 + (mi >> 1) * 128 + mr * 16 : base + (mi >> 1) * 1024 + w * 256 + (mi & 1) * 128 + mr * 16;
}
template <bool ISV> __device__ __forceinline__ constexpr uint32_t tok_off(int T, int i) { return ISV ? T * 512 + i * 256 : T * 4096 + i * 2048; }
template <bool ISV, int T, bool ADD>
__device__ __forceinline__ void tok_store(const float (&x)[16], uint32_t a, const uint32_t (&p)[2][4]) {
#pragma unroll
  for (int i = 0; i < 2; i++) {
    uint32_t r[4];
#pragma unroll
    for (int k = 0; k < 4; k++)
      r[k] = !ADD ? pack_bf16(x[8 * i + 2 * k], x[8 * i + 2 * k + 1])
           : PADD ? add_bf16x2(pack_bf16(x[8 * i + 2 * k], x[8 * i + 2 * k + 1]), p[i][k])
                  : pack_bf16(x[8 * i + 2 * k] + bf_lo(p[i][k]), x[8 * i + 2 * k + 1] + bf_hi(p[i][k]));
    stsm4(a + tok_off<ISV>(T, i), r[0], r[1], r[2], r[3]);
  }
}

__device__ __forceinline__ void load_xn(const FParams& P, int seg, uint32_t self) {
  SMAP;
  mbar_expect_tx(B_XN, 49152);
  tma_load_3d(XN, &P.xn12, 0, seg * 32, 0, B_XN);
}

#define DESC_ADD(d, n) asm volatile("add.s64 %0, %0, %1;" : "+l"(d) : "n"(n))

template <bool ISV>
__device__ __forceinline__ void f_wg0(const FParams& P, const WRegs& wr, const int h, const int rank, const uint32_t hw, int tid) {
  using namespace fk;
  const uint32_t self = mapa(0, (hw >> (2 * rank)) & 3), peer0 = mapa(0, (hw >> (ISV ? 0 : 2 * (rank ^ 1))) & 3) - self,
                 peer1 = mapa(0, (hw >> (ISV ? 2 : 4)) & 3) - self;
  SMAP;
  const int tile0 = rank * 22;
  const uint32_t usel = __shfl_sync(0xffffffffu, tid, 0);
  const int warp = __shfl_sync(0xffffffffu, threadIdx.x >> 5, 0);
  constexpr int WMODE = ISV ? 0 : 2;
  const bool three = warp < 2;
  uint32_t h2ph = 1;
  tid ^= 0x5500;
#pragma unroll 1
  for (int s = -1;;) {
    uint32_t ta[ProjCfg<ISV, 0>::NTA][4][4], wsa, mba;
    const char* src = P.xch + H1_BYTES + ((s & 1) * 4 + warp) * 8192 + ((usel >> (16 + (s & 1))) & 1) * 4096;
    {
      const uint32_t ph = (s + 1) & 1;
      float x0[16], x1[16];
      uint32_t t_pub = 0;
      wg_fence();
      static_assert(Chunks<ISV>::MASK == 0x1E, "chunks 1 .. 4 are in shared memory");
      uint64_t db = P.dxn;
      auto rs_chunk = [&](int ci, bool pace) {
#pragma unroll
        for (int u = 0; u < 4; u++) {
          wgmma_rs_n32(x0, wr[ci][0][u], db, (ci | u) != 0);
          wgmma_rs_n32(x1, wr[ci][1][u], db, (ci | u) != 0);
          if (u < 3) DESC_ADD(db, 2); else DESC_ADD(db, 250);
          if (pace) { wg_commit(); wg_wait<2>(); wg_fence(); }
        }
      };
      rs_chunk(0, false);
      t_pub = clk32() - 60;
      PROF(0, 8); PROF(0, 1);
#pragma unroll
      for (int c = 1; c <= 4; c++) {
#pragma unroll
        for (int u = 0; u < 4; u++) {
          const uint64_t dx = make_desc(fk::XN + c * 4096 + u * 32, 16, 1024);
          wgmma_ss_n32_ta(x0, make_desc(fk::WS + (c - 1) * 16384 + u * 2048, 8192, 1024), dx, 1);
          wgmma_ss_n32_ta(x1, make_desc(fk::WS + (c - 1) * 16384 + 8192 + u * 2048, 8192, 1024), dx, 1);
          if (c == 4 && u == 1) { wg_commit(); wg_wait<1>(); named_bar_arrive(NB_XE, 160); wg_fence(); }
        }
        if (c == 3) wg_commit();
      }
      DESC_ADD(db, 1024);
#pragma unroll
      for (int c = 5; c < 10; c++) {
        if (c == 9) named_bar_arrive(NB_ST, 256);
        rs_chunk(c - 4, ((ISV ? PACEV : PACEQ) >> c) & 1);
      }
      wg_commit();
      wg_wait<0>();
      PROF(0, 10);
      const uint32_t tb = ISV ? (ph ? VX2 : VX) : QK;
      auto h2_issue = [&]() {
        spin_until(t_pub + (ISV ? D_H2V : D_H2));
        PROF(0, 13);
        if (elect_one()) { mbar_expect_tx(B_H2 + 8 * warp, 4096); bulk_g2s(MEMB + warp * 4096, src, 4096, B_H2 + 8 * warp); }
      };
      named_bar_sync(NB_CF, ISV ? 160 : 256);
      if ((ISV ? H2_ATV : H2_AT) == 0) h2_issue();
      const uint32_t none[2][4] = {}, tka = tok_addr<ISV>(tb, tid);
      tok_store<ISV, 0, false>(x0, tka, none);
      if ((ISV ? H2_ATV : H2_AT) == 1) h2_issue();
      tok_store<ISV, 1, false>(x1, tka, none);
      if ((ISV ? H2_ATV : H2_AT) == 2) h2_issue();
      named_bar_arrive(NB_DU, 256);
    }
    {
      OPQ;
      wsa = WS + ((mi >> 1) * 8 + mr) * 128 + (((2 * w + (mi & 1)) ^ mr) << 4);
      mba = MEMB + lane * 16;
      PIN(wsa); PIN(mba);
      {
        const uint32_t chk = MEMB + w * 4096 + lane * 32 + lg * 4, bar = B_H2 + 8 * warp;
        PROF(0, 11);
        proj_mem_prefetch<ISV, 0, 0, NPRE0>(ta, wsa);
#pragma unroll 1
        for (int tries = 0; tries < POLL_TRIES; tries++) {
          mbar_spin(bar, h2ph);
          h2ph ^= 1;
          const uint32_t mx = max(max(lds32(chk), lds32(chk + 1024)), max(lds32(chk + 2048), lds32(chk + 3072)));
          if (__all_sync(0xffffffffu, mx != EMPTY)) break;
          RETRY(1);
          if (elect_one()) { mbar_expect_tx(bar, 4096); bulk_g2s(MEMB + warp * 4096, src, 4096, bar); }
        }
      }
      if (s < 0) mbar_spin(B_WO, 0);
      PROF(0, 12);
      named_bar_arrive(NB_M1, 256);
      proj_mem_prefetch<ISV, 0, NPRE0, NTA0>(ta, wsa);
      named_bar_sync(NB_M0, 128);
    }
    s++;
    tid ^= 0x5500;
    {
      float a0[4], a1[4];
      proj_mem<ISV, 0>(wr, ta, wsa, mba, a0, a1);
      PROF(0, 2);
      uint32_t unused[4];
      proj_finish<ISV, 0>(a0, a1, peer0, peer1, self, tid, warp, unused);
      PROF(0, 3);
      if (s + 1 == cfg::NSEG) break;
      uint32_t wf[PF0][4], woa, wob;
      bool xn_ok;
      {
        OPQ;
        if (!ISV) {
          uint32_t qf[4][4], kf[2][4];
          const uint32_t qa = PT + 2048 + lane * 16, ka = QK + 4096 + w * 1024 + lane * 16;
          ldsm4t(qf[0], qa); ldsm4t(kf[0], ka); ldsm4t(qf[1], qa + 512);
          ldsm4t(qf[2], qa + 1024); ldsm4t(kf[1], ka + 512); ldsm4t(qf[3], qa + 1536);
          float c0[4], c1[4];
          mma16816z(c0, qf[0], kf[0][0], kf[0][1]);
          mma16816z(c1, qf[1], kf[0][2], kf[0][3]);
          mma16816(c0, qf[2], kf[1][0], kf[1][1]);
          mma16816(c1, qf[3], kf[1][2], kf[1][3]);
          const float s0 = (c0[0] + c0[2]) + (c1[0] + c1[2]), s1 = (c0[1] + c0[3]) + (c1[1] + c1[3]);
          send_scores(s0, s1, SP + rank * SP_SRC + t7 * SPW, peer0, peer1, B_SM, lane);
        }
        PROF(0, 4);
        woa = WO + 16384 + ((mi >> 1) * 8 + mr) * 128 + (((2 * w + (mi & 1)) ^ mr) << 4);
        wob = WO + 81920 + w * 4096 + ((mi >> 1) * 8 + mr) * 32 + (((mi & 1) ^ (mr >> 2)) << 4);
        uint32_t vf[2][2][4], vm[2][2];
        if (!ISV) mbar_spin(B_VX, s & 1);
        PROF(0, 14);
#pragma unroll
        for (int T = 0; T < 2; T++)
#pragma unroll
          for (int kk = 0; kk < 2; kk++) ldsm4(vf[T][kk], ((ISV && (s & 1)) ? VX2 : VX) + w * 2048 + (mi & 1) * 1024 + (mi >> 1) * 128 + mr * 16 + T * 512 + kk * 256);
        wo_prefetch<WMODE, 0, PF0A>(wf, woa, wob, three);
        uint32_t spa = SP + lane * SPW, vma = VM + t7 * 8, oa = OB + (mi >> 1) * 1024 + w * 256 + (mi & 1) * 128 + mr * 16;
        PIN(spa); PIN(vma); PIN(oa);
        mbar_spin(B_SM, s & 1);
        PROF(0, 5);
        float sc[10];
#pragma unroll
        for (int j = 0; j < 5; j++) {
          if (SPACK) {
            const uint32_t x = lds32(spa + j * 128), y = lds32(spa + SP_SRC + j * 128);
            sc[2 * j] = bf_lo(x) + bf_lo(y); sc[2 * j + 1] = bf_hi(x) + bf_hi(y);
          } else {
            const float2 x = lds64f(spa + j * 256), y = lds64f(spa + SP_SRC + j * 256);
            sc[2 * j] = x.x + y.x; sc[2 * j + 1] = x.y + y.y;
          }
        }
        const bool vm_ok = mbar_test(B_VM, s & 1);
        lds64(vm[0], vma); lds64(vm[1], vma + 1024);
        float m = fmaxf(fmaxf(fmaxf(sc[0], sc[1]), fmaxf(sc[2], sc[3])), fmaxf(fmaxf(sc[4], sc[5]), fmaxf(sc[6], sc[7])));
        m = fmaxf(m, fmaxf(sc[8], sc[9]));
        const float cs = 0.08838834764831845f * 1.4426950408889634f;
        uint32_t pb[5];
        m = fmaxf(m, __shfl_xor_sync(0xffffffffu, m, 1));
        m = fmaxf(m, __shfl_xor_sync(0xffffffffu, m, 2));
        if (ISV ? GATE_MX : GATE_Q) named_bar_arrive(NB_MX, 256);
        const float mc = -m * cs;
#pragma unroll
        for (int j = 0; j < 5; j++) pb[j] = pack_bf16(ex2_approx(fmaf(sc[2 * j], cs, mc)), ex2_approx(fmaf(sc[2 * j + 1], cs, mc)));
        PROF(0, 15);
        if (!vm_ok) { mbar_spin(B_VM, s & 1); lds64(vm[0], vma); lds64(vm[1], vma + 1024); }
        PROF(0, 6);
        float o0[4], o1[4], rs[4];
        const uint32_t ones[4] = {0x3F803F80u, 0x3F803F80u, 0x3F803F80u, 0x3F803F80u};
        mma16816z(rs, ones, pb[0], pb[1]);
        mma16816z(o0, vf[0][0], pb[0], pb[1]);
        mma16816z(o1, vf[1][0], pb[0], pb[1]);
        mma16816(rs, ones, pb[2], pb[3]);
        mma16816(o0, vf[0][1], pb[2], pb[3]);
        mma16816(o1, vf[1][1], pb[2], pb[3]);
        mma1688(rs, ones[0], ones[0], pb[4]);
        mma1688(o0, vm[0][0], vm[0][1], pb[4]);
        mma1688(o1, vm[1][0], vm[1][1], pb[4]);
        const float i0 = rcp_approx(rs[0]), i1 = rcp_approx(rs[1]);
        stsm4(oa, pack_bf16(o0[0] * i0, o0[1] * i1), pack_bf16(o0[2] * i0, o0[3] * i1),
              pack_bf16(o1[0] * i0, o1[1] * i1), pack_bf16(o1[2] * i0, o1[3] * i1));
      }
      {
        OPQ;
        named_bar_arrive(NB_O, 256);
        wo_prefetch<WMODE, PF0A, PF0>(wf, woa, wob, three);
        xn_ok = mbar_test(B_XN, (s + 1) & 1);
        char* h1p = P.xch + (tile0 + 4 + w) * 32768 + (h >> 3) * 8192 + (h & 7) * 128 + (((2 * lq + (lg & 1)) ^ (h & 7)) << 4) + (lg >> 1) * 4;
        uint32_t oba = OB + lane * 16;
        PIN(oba);
        PROF(0, 7);
        named_bar_sync(NB_O0, 128);
        const uint32_t tag = ((s >> 1) & 1) ^ 1;
        wo_phase<WMODE>(wf, woa, wob, three, oba, h1p, tid >> 8, tag);
        PROF(0, 9);
        if (!xn_ok) mbar_spin(B_XN, (s + 1) & 1);
        named_bar_sync(NB_HD, 256);
      }
    }
  }
}

template <bool ISV>
__device__ __forceinline__ void f_wg1(const FParams& P, const WRegs& wr, const int h, const int rank, const uint32_t hw, int tid) {
  using namespace fk;
  const uint32_t self = mapa(0, (hw >> (2 * rank)) & 3), peer0 = mapa(0, (hw >> (ISV ? 0 : 2 * (rank ^ 1))) & 3) - self,
                 peer1 = mapa(0, (hw >> (ISV ? 2 : 4)) & 3) - self;
  SMAP;
  const int tile0 = rank * 22;
  const uint32_t usel = __shfl_sync(0xffffffffu, tid, 0);
  const int warp = __shfl_sync(0xffffffffu, (threadIdx.x >> 5) & 3, 0);
  constexpr int WMODE = 1;
  uint32_t h1ph = 0;
  auto o_done = [&](int mb) {
    tma_store_wait_all();
    asm volatile("fence.proxy.async.global;" ::: "memory");
    asm volatile("red.relaxed.gpu.global.add.u32 [%0], 1;" ::"l"(&g_oflag[mb]) : "memory");
  };
  uint32_t vmo[4] = {0, 0, 0, 0};
  if (ISV) {
    OPQ;
    sts32(PT + (t7 >> 2) * 128 + ((5 ^ lg) << 4) + lq * 4, 0);
    sts32(PT + (t7 >> 2) * 128 + ((6 ^ lg) << 4) + lq * 4, 0);
  }
  tid ^= 0x5500;
#pragma unroll 1
  for (int s = -1;;) {
    uint32_t ta[ProjCfg<ISV, 1>::NTA][4][4], wsa, mba;
    if (s + 1 < cfg::NSEG) mbar_spin(B_XN, (s + 1) & 1);
    const uint32_t t_pub = clk32();
    auto refill = [&]() {
      if (warp == 3) {
        named_bar_sync(NB_XE, 160);
        if (elect_one()) {
          mbar_expect_tx(B_XN + 8, 16384);
          tma_load_3d(XN, &P.xn, 0, (s + 1) * 32, 12, B_XN + 8);
        }
      }
    };
    auto arm = [&]() {
      if ((tid & 255) == 160) {
        if (s == 1) st_pub32(&g_mask[3 * h + rank], 0);
        if (s + 2 < cfg::NSEG) { mbar_expect_tx(B_SM, ISV ? 2 * SP_SRC : SP_SRC); if (!ISV) mbar_expect_tx(B_VX, 8192); }
        if (!ISV && s + 1 < cfg::NSEG) mbar_expect_tx(B_VM, 2048);
        if (ISV && s >= 1 && s < cfg::NSEG) mbar_expect_tx(B_ST, 7168);
      }
      if (ISV && s < cfg::NSEG && (tid & 254) == 192) mbar_arrive_remote(((tid & 1) ? peer1 : peer0) + B_ST);
      __syncwarp();
    };
    if (ISV) {
      if (s >= 0) arm();
      if (s >= 1) {
        OPQ;
        if (warp == 0 && (s & 3) == 1 && s > 1) { if (elect_one()) o_done((s - 2) >> 2); }
        const uint32_t vb = (s & 1) ? VX : VX2;
        float x0[16], x1[16];
        wg_fence();
        wgmma_rs_n32(x0, vmo, make_desc(fk::PT + 64, 16, 1024), 0);
        wgmma_rs_n32(x1, vmo, make_desc(fk::PT + 96, 16, 1024), 0);
#pragma unroll
        for (int kk = 0; kk < 2; kk++) {
          wgmma_ss_n32(x0, make_desc0(vb + kk * 256, 128, 1024), make_desc(fk::PT + kk * 32, 16, 1024), 1);
          wgmma_ss_n32(x1, make_desc0(vb + 512 + kk * 256, 128, 1024), make_desc(fk::PT + kk * 32, 16, 1024), 1);
        }
        wg_commit();
        wg_wait<0>();
        named_bar_sync(NB_W1, 128);
        PROF(1, 4);
        const uint32_t stg = vb + (8 * (mi >> 1) + mr) * 128 + (((2 * w + (mi & 1)) ^ mr) << 4);
#pragma unroll
        for (int T = 0; T < 2; T++) {
          const float* x = T ? x1 : x0;
#pragma unroll
          for (int jj = 0; jj < 4; jj += 2)
            stsm4t(stg + T * 4096 + jj * 1024, pack_bf16(x[4 * jj], x[4 * jj + 1]), pack_bf16(x[4 * jj + 2], x[4 * jj + 3]),
                   pack_bf16(x[4 * jj + 4], x[4 * jj + 5]), pack_bf16(x[4 * jj + 6], x[4 * jj + 7]));
        }
        fence_proxy_async_smem();
        named_bar_sync(NB_W1, 128);
        PROF(1, 10);
        if (warp == 0) {
          if (elect_one()) {
            tma_store_3d(&P.o, vb, 0, (s - 1) * 32, 2 * h);
            tma_store_commit();
          }
          __syncwarp();
        }
        if (s == cfg::NSEG) break;
      }
      if (s + 1 < cfg::NSEG) refill();
      PROF(1, 11);
    } else if (s < 0) {
      named_bar_arrive(NB_CF, 256);
      refill();
    } else {
      float x[24];
      wg_fence();
#pragma unroll
      for (int k = 0; k < 4; k++) wgmma_ss_n48_tt(x, make_desc0(fk::QK + k * 256, 128, 1024), make_desc0(fk::QK + 4096 + k * 256, 128, 1024), k != 0);
      wg_commit();
      arm();
      auto send_tok = [&]() {
        if (warp < 2) {
          OPQ;
          const uint32_t d0 = peer1 + QK + rank * 3584 + lane * 8 + w * 1280, d1 = d0 + 512 + w * 512, bar = peer1 + B_ST;
          mbar_spin(B_ST, s & 1);
          const float NEG = -500000000.0f / 0.08838834764831845f;
          const bool m0 = 2 * lq > lg, m1 = 2 * lq + 1 > lg;
          st_async64f(d0, x[16] + x[20], x[17] + x[21], bar);
          st_async64f(d1, x[18] + x[22], x[19] + x[23], bar);
          st_async64f(d1 + 256, x[2], x[3], bar);
          if (warp == 0) {
            st_async64f(d0 + 256, m0 ? NEG : x[0], m1 ? NEG : x[1], bar);
            st_async64f(d1 + 512, m0 ? NEG : x[6], m1 ? NEG : x[7], bar);
          } else {
            st_async64f(d0 + 256, x[0], x[1], bar);
            st_async64f(d1 + 512, x[6], x[7], bar);
            st_async64f(d0 + 512, x[4], x[5], bar);
            st_async64f(d0 + 768, m0 ? NEG : x[8], m1 ? NEG : x[9], bar);
            st_async64f(d1 + 768, x[10], x[11], bar);
            st_async64f(d1 + 1024, m0 ? NEG : x[14], m1 ? NEG : x[15], bar);
          }
        }
        PROF(1, 4);
      };
      const bool fin = s + 1 == cfg::NSEG;
      OPQ;
      const int j = 2 * h + rank;
      const char* src = P.xch + j * 32768 + warp * 8192 + (((usel >> 14) & 2) + (s & 1)) * 2048;
      char* dst = P.xch + H1_BYTES + (j >> 4) * 8192 + (lq >> 1) * 4096 + (j & 15) * 256 + (lq & 1) * 128 + (2 * w + (lg & 1)) * 16 + (lg >> 1) * 4;
      const uint32_t chk = VX + mi * 2048 + mr * 128 + (w ^ (mr >> 1)) * 32 + ((lane & 1) + 2 * mi) * 4;
      const uint32_t tmask = (s >> 1) & 1;
      if (!fin) {
        spin_until(t_pub + D_H1);
        if (elect_one()) { mbar_expect_tx(B_H1, 2048); bulk_g2s(VX + warp * 2048, src, 2048, B_H1); }
      }
      __syncwarp();
      wg_wait<0>();
      PROF(1, 6);
      send_tok();
      if (fin) { mbar_spin(B_VM, s & 1); break; }
      named_bar_arrive(NB_CF, 256);
      if (REFILL_EARLY) refill();
#pragma unroll 1
      for (int tries = 0; tries < POLL_TRIES; tries++) {
        float d0[4], d1[4], d2[4], d3[4];
        mbar_spin(B_H1, h1ph);
        h1ph ^= 1;
        PROF(1, 10);
        const uint32_t t0 = lds32(chk), t1 = lds32(chk + 1024);
        wg_fence();
        const uint64_t ones = (uint64_t)(fk::ONES >> 4);
        wgmma_ss_n8_ta(d0, make_desc(fk::VX, 8192, 2048), ones, 0);
        wgmma_ss_n8_ta(d1, make_desc(fk::VX + 1024, 8192, 2048), ones, 0);
        wgmma_ss_n8_ta(d2, make_desc(fk::VX + 4096, 8192, 2048), ones, 0);
        wgmma_ss_n8_ta(d3, make_desc(fk::VX + 5120, 8192, 2048), ones, 0);
        wg_commit();
        uint32_t tt;
        asm volatile("lop3.b32 %0, %1, %2, %3, 0x42;" : "=r"(tt) : "r"(t0), "r"(t1), "r"(tmask) : "memory");
        uint32_t ok;
        named_bar_and(NB_W1, 128, tt & 1, ok);
        if (!ok) { if (elect_one()) { mbar_expect_tx(B_H1, 2048); bulk_g2s(VX + warp * 2048, src, 2048, B_H1); } }
        wg_wait<0>();
        if (ok) {
          st_pub32(dst + (s & 1) * 32768, (lq & 1) ? pack_bf16(d1[0] + d3[0], d1[2] + d3[2]) : pack_bf16(d0[0] + d2[0], d0[2] + d2[2]));
          PROF(1, 12);
          st_pub32(dst + ((s & 1) ^ 1) * 32768, EMPTY);
          break;
        }
        RETRY(0);
      }
      named_bar_sync(NB_W1, 128);
      if ((tid & 255) == 192) mbar_arrive_remote(peer1 + B_PF);
      __syncwarp();
      if (!REFILL_EARLY) refill();
      PROF(1, 11);
    }
    if (!ISV || s + 1 < cfg::NSEG) {
      const uint32_t ph = (s + 1) & 1;
      float x0[16], x1[16];
      uint64_t db = P.dxn + 10 * 256;
      named_bar_sync(NB_ST, 256);
      wg_fence();
#pragma unroll
      for (int c = 0; c < 6; c++) {
        if (c == 2) { mbar_spin(B_XN + 8, ph); wg_fence(); }
        if (ISV && c == CF_AT) {
          if (warp == 0) {
            if (elect_one()) tma_store_wait_read();
            __syncwarp();
            named_bar_arrive(NB_CF, 160);
          }
          wg_fence();
        }
#pragma unroll
        for (int u = 0; u < 4; u++) {
          wgmma_rs_n32(x0, wr[c][0][u], db, (c | u) != 0);
          wgmma_rs_n32(x1, wr[c][1][u], db, (c | u) != 0);
          if (u < 3) DESC_ADD(db, 2); else if (c == 1) DESC_ADD(db, 250 - 12 * 256); else DESC_ADD(db, 250);
        }
      }
      wg_commit();
      OPQ;
      const uint32_t tb = ISV ? (ph ? VX2 : VX) : QK, tka = tok_addr<ISV>(tb, tid);
      uint32_t p0[2][4], p1[2][4];
      named_bar_sync(NB_DU, 256);
      ldsm4(p1[0], tka + tok_off<ISV>(1, 0)); ldsm4(p1[1], tka + tok_off<ISV>(1, 1));
      ldsm4(p0[0], tka + tok_off<ISV>(0, 0)); ldsm4(p0[1], tka + tok_off<ISV>(0, 1));
      if (ISV && s >= 0) mbar_spin(B_PF, s & 1);
      wg_wait<0>();
      PROF(1, 13);
      tok_store<ISV, 1, true>(x1, tka, p1);
      tok_store<ISV, 0, true>(x0, tka, p0);
      if (ISV && s + 2 < cfg::NSEG) {
        fence_proxy_async_smem();
        __syncwarp();
        if (elect_one()) {
          bulk_s2s(peer0 + VX + warp * 2048, tb + warp * 2048, 2048, peer0 + B_VX);
          bulk_s2s(peer1 + VX + warp * 2048, tb + warp * 2048, 2048, peer1 + B_VX);
        }
      }
      wsa = WS + ((mi >> 1) * 8 + mr) * 128 + (((2 * w + (mi & 1)) ^ mr) << 4);
      mba = MEMB + lane * 16;
      PIN(wsa); PIN(mba);
      proj_mem_prefetch<ISV, 1, 0, NTA1>(ta, wsa);
      PROF(1, 14);
      named_bar_sync(NB_M1, 256);
      s++;
      PROF(1, 1);
      float a0[4], a1[4];
      proj_mem<ISV, 1>(wr, ta, wsa, mba, a0, a1);
      PROF(1, 2);
      proj_finish<ISV, 1>(a0, a1, peer0, peer1, self, tid, warp, vmo);
      PROF(1, 3);
    } else {
      OPQ;
      mbar_spin(B_VM, s & 1);
      lds64(vmo, VM + t7 * 8); lds64(vmo + 2, VM + 1024 + t7 * 8);
      s++;
    }
    tid ^= 0x5500;
    const bool last = s + 1 >= cfg::NSEG;
    constexpr int PFW = ISV ? PF1V : PF1;
    uint32_t wf[PFW][4], woa;
    if (ISV) {
      OPQ;
      woa = WO + ((mi >> 1) * 8 + mr) * 128 + (((2 * w + (mi & 1)) ^ mr) << 4);
      if (s >= 1) {
        const uint32_t sa = QK + ((w * (w + 3)) >> 1) * 256 + lane * 8;
        mbar_spin(B_ST, (s - 1) & 1);
        float sc[10];
        {
          const float NEG = -1000000000.0f / 0.08838834764831845f;
          float2 x[5], y[5];
#pragma unroll
          for (int b = 0; b < 5; b++) {
            x[b] = b < 2 ? lds64f(sa + b * 256) : lds64f_if(sa + b * 256, b <= w + 1, NEG);
            y[b] = b < 2 ? lds64f(sa + 3584 + b * 256) : lds64f_if(sa + 3584 + b * 256, b <= w + 1, 0.f);
          }
          wo_prefetch<WMODE, 0, PF1A>(wf, woa, 0, true);
#pragma unroll
          for (int b = 0; b < 5; b++) { sc[2 * b] = x[b].x + y[b].x; sc[2 * b + 1] = x[b].y + y[b].y; }
        }
        float m = fmaxf(fmaxf(fmaxf(sc[0], sc[1]), fmaxf(sc[2], sc[3])), fmaxf(fmaxf(sc[4], sc[5]), fmaxf(sc[6], sc[7])));
        m = fmaxf(m, fmaxf(sc[8], sc[9]));
        m = fmaxf(m, __shfl_xor_sync(0xffffffffu, m, 1));
        m = fmaxf(m, __shfl_xor_sync(0xffffffffu, m, 2));
        const float cs = 0.08838834764831845f * 1.4426950408889634f;
#pragma unroll
        for (int i = 0; i < 10; i++) sc[i] = ex2_approx((sc[i] - m) * cs);
        float sum = ((sc[0] + sc[1]) + (sc[2] + sc[3])) + ((sc[4] + sc[5]) + (sc[6] + sc[7])) + (sc[8] + sc[9]);
        sum += __shfl_xor_sync(0xffffffffu, sum, 1);
        sum += __shfl_xor_sync(0xffffffffu, sum, 2);
        const float inv = rcp_approx(sum);
        const uint32_t pa = PT + (w * 8 + mr) * 128, pm = pack_bf16(sc[0] * inv, sc[1] * inv);
        stsm4(pa + ((mi ^ mr) << 4), pack_bf16(sc[2] * inv, sc[3] * inv), pack_bf16(sc[4] * inv, sc[5] * inv),
              pack_bf16(sc[6] * inv, sc[7] * inv), pack_bf16(sc[8] * inv, sc[9] * inv));
        asm volatile("stmatrix.sync.aligned.m8n8.x2.shared.b16 [%0], {%1,%1};" ::"r"(pa + ((((mi & 1) ? 7 : 4) ^ mr) << 4)), "r"(pm) : "memory");
      } else {
        wo_prefetch<WMODE, 0, PF1A>(wf, woa, 0, true);
      }
      if (warp == 3 && !last) {
        mbar_spin(B_VM, s & 1);
        if (elect_one()) load_xn(P, s + 1, self);
      }
      PROF(1, 5);
    } else {
      if (warp == 0) {
        OPQ;
        uint32_t kf[4][4], qf[4][4];
        float c0[4], c1[4], d0[4], d1[4];
        const uint32_t ka = PT + (mi >> 1) * 1024 + (mi & 1) * 128 + mr * 16;
#pragma unroll
        for (int k = 0; k < 4; k++) { ldsm4t(qf[k], PT + 2048 + k * 512 + lane * 16); ldsm4t(kf[k], ka + k * 256); }
        mma16816z(c0, qf[0], kf[0][0], kf[0][1]); mma16816z(c1, qf[0], kf[0][2], kf[0][3]);
        mma16816z(d0, qf[1], kf[1][0], kf[1][1]); mma16816z(d1, qf[1], kf[1][2], kf[1][3]);
        mma16816(c0, qf[2], kf[2][0], kf[2][1]); mma16816(c1, qf[2], kf[2][2], kf[2][3]);
        mma16816(d0, qf[3], kf[3][0], kf[3][1]); mma16816(d1, qf[3], kf[3][2], kf[3][3]);
        const float s0 = ((c0[0] + c0[2]) + (c1[0] + c1[2])) + ((d0[0] + d0[2]) + (d1[0] + d1[2]));
        const float s1 = ((c0[1] + c0[3]) + (c1[1] + c1[3])) + ((d0[1] + d0[3]) + (d1[1] + d1[3]));
        if (!last) send_scores(s0, s1, SP + rank * SP_SRC + (128 + lane) * SPW, peer0, peer1, B_SM, lane);
        PROF(1, 5);
      } else {
        const uint32_t t_c = clk32() + lds32(B_XN) * 0;
        if (warp == 3 && !last) { if (elect_one()) load_xn(P, s + 1, self); }
        spin_until(t_c + D_ST);
      }
      OPQ;
      woa = WO + ((mi >> 1) * 8 + mr) * 128 + (((2 * w + (mi & 1)) ^ mr) << 4);
    }
    if (!last) {
      OPQ;
      uint32_t oba = OB + lane * 16;
      if (!ISV) wo_prefetch<WMODE, 0, PF1Q>(wf, woa, 0, true);
      if (ISV ? GATE_MX : GATE_Q) named_bar_sync(NB_MX, 256);
      wo_prefetch<WMODE, ISV ? PF1A : PF1Q, PFW>(wf, woa, 0, true);
      char* h1p = P.xch + (tile0 + w) * 32768 + (h >> 3) * 8192 + (h & 7) * 128 + (((2 * lq + (lg & 1)) ^ (h & 7)) << 4) + (lg >> 1) * 4;
      fence_proxy_async_smem();
      PROF(1, 7);
      named_bar_sync(NB_O, 256);
      PROF(1, 8);
      wo_phase<WMODE>(wf, woa, 0, true, oba, h1p, tid >> 8, ((s >> 1) & 1) ^ 1);
      PROF(1, 9);
      named_bar_sync(NB_HD, 256);
    } else {
      fence_proxy_async_smem();
      named_bar_sync(NB_W1, 128);
    }
  }
  if (ISV && warp == 0) { if (elect_one()) o_done(15); }
}

template <bool ISV, int WG>
__device__ __forceinline__ void f_main(const FParams& P, const int h, const int rank, const uint32_t hw) {
  using namespace fk;
  const uint32_t self = mapa(0, (hw >> (2 * rank)) & 3);
  SMAP;
  const int tid = __shfl_sync(0xffffffffu, threadIdx.x, threadIdx.x & 31);
  const int tile0 = rank * 22, ntile = ISV ? 20 : 22;
  const CUtensorMap* m0 = ISV ? &P.wv : &P.wq;
  const CUtensorMap* m1 = ISV ? &P.wv : &P.wk;
  const int col0 = h * 128 + (ISV ? 0 : 64 * rank), col1 = h * 128 + (ISV ? 64 : 64 * rank);
  WRegs wr;
  uint32_t sel = 0;
  {
    OPQ;
    const uint32_t a = SM0 + WG * 16384 + ((mi >> 1) * 8 + mr) * 128 + (((2 * w + (mi & 1)) ^ mr) << 4);
#pragma unroll
    for (int i = 0; i < 6; i++) {
      mbar_wait(B_PB + 8 * i, 0);
      PRO(8 + i);
#pragma unroll
      for (int T = 0; T < 2; T++)
#pragma unroll
        for (int u = 0; u < 4; u++) ldsm4t(wr[i][T][u], a + i * 32768 + T * 8192 + u * 2048);
      named_bar_sync(NB_C, 256);
      if (WG == 1 && w == (i & 3)) {
        if (elect_one()) {
          if (i <= 2 && i + PRE_G < 6) {
#pragma unroll 1
            for (int n = 2 * (i + PRE_G); n < (i == 2 ? 12 : 2 * (i + PRE_G) + 2); n++) {
              const int ii = n >> 1, row = Chunks<ISV>::rf(n & 1, ii) * 64;
              if (!(n & 1)) mbar_expect_tx(B_PB + 8 * ii, 32768);
              tma_load_2d(SM0 + n * 16384, m0, col0, row, B_PB + 8 * ii);
              tma_load_2d(SM0 + n * 16384 + 8192, m1, col1, row, B_PB + 8 * ii);
            }
          }
          if (i == 3 || i == 4) {
            const int p0 = i == 3 ? 0 : 5, p1 = i == 3 ? 5 : 8;
            mbar_expect_tx(B_W, (p1 - p0) * 8192);
#pragma unroll 1
            for (int p = p0; p < p1; p++) tma_load_2d(WS + p * 8192, (p & 1) ? m1 : m0, (p & 1) ? col1 : col0, Chunks<ISV>::sm(p >> 1) * 64, B_W);
          }
          if (i == WO_AT) {
            mbar_expect_tx(B_WO, ntile * 4096);
#pragma unroll 1
            for (int t = 0; t < 5; t++) tma_load_2d(WO + t * 16384, &P.wo, tile0 * 16 + t * 64, h * 128, B_WO);
            if (!ISV) {
              tma_load_2d(WO + 81920, &P.wo16, tile0 * 16 + 320, h * 128, B_WO);
              tma_load_2d(WO + 86016, &P.wo16, tile0 * 16 + 336, h * 128, B_WO);
            }
          }
        }
      }
    }
    PROF2(1);
    uint2 m0 = make_uint2(0, 0);
    if (!ISV && WG == 1) m0 = *reinterpret_cast<const uint2*>(P.mem0 + ((lane >> 1) & 7) * cfg::D + (2 * h + rank) * 16 + (lane >> 4) * 8 + (lane & 1) * 4);
    if (WG == 0 && w == 1) {
      uint4 v;
#pragma unroll 1
      for (int tries = 0; tries < POLL_TRIES; tries++) {
        asm volatile("ld.acquire.gpu.global.v4.u32 {%0,%1,%2,%3}, [%4];" : "=r"(v.x), "=r"(v.y), "=r"(v.z), "=r"(v.w)
                     : "l"(&g_mask[4 * min(lane, 23)]) : "memory");
        if (__all_sync(0xffffffffu, v.x & v.y & v.z & v.w & 0x100)) break;
        __nanosleep(100);
      }
      if (elect_one()) {
        asm volatile("fence.proxy.async.global;" ::: "memory");
        load_xn(P, 0, self);
        if (blockIdx.x == 2) { __threadfence(); st_pub128(g_lnok, 0x100); }
      }
      sts128(OB + lane * 16, v.x, v.y, v.z, v.w);
    }
    named_bar_sync(NB_C, 256);
    if (!ISV && WG == 1 && w < 2) st_pub64(P.xch + H1_BYTES + 32768 + (h >> 3) * 8192 + w * 4096 + ((2 * h + rank) & 15) * 256 + lane * 8, m0.x, m0.y);
#pragma unroll
    for (int i = 0; i < 3; i++) {
      const int t = min(tile0 + 8 * i + w + (WG ? 0 : 4), 63);
      sel |= ((lds32(OB + ((t >> 1) * 3 + (t & 1)) * 4) >> (h >> 3)) & 1) << (2 * i + 1);
    }
    const uint32_t own = lds32(OB + (3 * h + rank) * 4) >> w, m2 = lds32(OB + (3 * h + 2) * 4) >> w;
    sel |= (own & 1) << 7 | (m2 & 1) << 8 | (m2 & 16) << 5;
    sel |= (((((lg ^ h) & 1) << 2) | (lg >> 1)) == (h & 1) + 2 * (h >> 3)) << 10;
  }
  asm volatile("barrier.cluster.wait.aligned;" ::: "memory");
  PRO(14);
  mbar_wait(B_W, 0);
  mbar_wait(B_XN, 0);
  PRO(15);
  PROF2(4);
  GTSYNC(0);
  PROF2(2);
  KT_END(8);
  if (WG == 0) f_wg0<ISV>(P, wr, h, rank, hw, tid | sel << 8); else f_wg1<ISV>(P, wr, h, rank, hw, tid | sel << 8);
}

__device__ __forceinline__ void f_tail(const FParams& P, const int h, const uint32_t rank, const bool isv) {
  using namespace fk;
  const uint32_t self = mapa(0, rank), base = self + SM0;
  const uint32_t FULL = self + SP, EMPT = FULL + 32, RES = FULL + 64, NOG = FULL + 72;
  const int tid = threadIdx.x, lane = tid & 31, wv = __shfl_sync(0xffffffffu, tid >> 5, 0), wg = wv >> 2;
  const int kq = h & 3, nt = (h >> 2) & 3, mb = TAIL_MB0 + 3 * (h >> 4) + rank;
  auto a_off = [](uint32_t st) { return (0x98685800u >> (8 * st) & 255) * 1024; };
  auto b_off = [](uint32_t st) { return (0xA8783010u >> (8 * st) & 255) * 1024; };
  static_assert(VX2 - SM0 == 80 * 1024 && VX - SM0 == 200 * 1024, "stage layout");
  auto load_b = [&](int kb) {
    const uint32_t sb = base + b_off(kb & 3), full = FULL + 8 * (kb & 3);
    mbar_expect_tx(full, 49152);
    tma_load_2d_mc(sb + rank * 8192, &P.tb, nt * 256 + ((rank + kq) & 3) * 64, (kq * 16 + kb) * 64, full, 7);
    if (kb % 3 == rank) tma_load_2d_mc(sb + 3 * 8192, &P.tb, nt * 256 + ((3 + kq) & 3) * 64, (kq * 16 + kb) * 64, full, 7);
  };
  auto load_a = [&](int kb) { tma_load_2d(base + a_off(kb & 3), &P.ta, (kq * 16 + kb) * 64, mb * 128, FULL + 8 * (kb & 3)); };
  TL(0);
  TL2(128, 10); TL2(160, 11);
  if (wv == 0) {
    if (elect_one()) {
      prefetch_tmap(&P.tb); prefetch_tmap(&P.ta);
      if (isv) mbar_spin(self + B_VM, (cfg::NSEG - 1) & 1);
      for (int i = 0; i < 4; i++) { mbar_init(FULL + 8 * i, 1); mbar_init(EMPT + 8 * i, 24); }
      mbar_init(RES, 1);
      fence_barrier_init();
      mbar_arrive_cluster(self + B_W, rank == 0 ? 1 : 0);
      mbar_arrive_cluster(self + B_W, rank == 2 ? 1 : 2);
      mbar_spin(self + B_W, 1);
#pragma unroll 1
      for (int kb = 0; kb < 4; kb++) load_b(kb);
      TL2(0, 12);
      wait_count(&g_oflag[mb], 32);
      asm volatile("fence.proxy.async.global;" ::: "memory");
      TL2(0, 13);
#pragma unroll 1
      for (int kb = 0; kb < 4; kb++) load_a(kb);
      TL2(0, 14);
    }
  }
  if (wv == 1) {
    if (lane == 0) {
      prefetch_tmap(&P.tx); prefetch_tmap(&P.tg); prefetch_tmap(&P.tout);
      uint32_t gc;
      asm volatile("ld.acquire.gpu.global.u32 %0, [%1];" : "=r"(gc) : "l"(&g_cnt[3][mb]) : "memory");
      const bool ng = gc < GATE_CNT && ld_strong4(&g_next) == 0;
      sts32(NOG, ng ? 1 : gc < GATE_CNT ? 2 : 0);
      if (ng) g_tfix[blockIdx.x] = 1;
      asm volatile("cp.async.bulk.prefetch.tensor.2d.L2.global [%0, {%1, %2}];" ::"l"(&P.tx), "r"(nt * 256 + kq * 64), "r"(mb * 128) : "memory");
    }
  } else if (wv == 2 || wv == 3) {
#pragma unroll 2
    for (int i = tid - 64; i < 3072; i += 64) st_pub128(&g_tpart[blockIdx.x][0][0][0] + i, EMPTY);
  }
  float acc[128];
  __syncthreads();
  KT_START(7);
  const uint32_t gate = lds32(NOG);
  const bool nog = gate == 1;
  if (gate) TL(15); else TL(15);
#pragma unroll 1
  for (int kb = 0; kb < 16; kb++) {
    const uint32_t st = kb & 3, sa = base + a_off(st) + wg * 8192, sb = base + b_off(st);
    mbar_spin(FULL + 8 * st, (kb >> 2) & 1);
    if (kb == 0) TL(2);
    if (kb == 4) TL(3);
    if (kb == 10) TL(4);
    wg_fence();
#pragma unroll
    for (int k = 0; k < 4; k++) {
      wgmma_ss_n256_tb(acc, make_desc(sa + k * 32, 16, 1024), make_desc(sb + k * 2048, 8192, 1024), (kb | k) != 0);
      if (k == 0) {
        wg_commit();
        wg_wait<1>();
        if (kb > 0 && kb <= 13 && lane < 3) mbar_arrive_cluster(EMPT + 8 * ((kb - 1) & 3), lane);
        wg_fence();
      }
    }
    wg_commit();
    if (kb >= 2 && kb < 15 && wv == ((kb & 1) << 2)) {
      if (elect_one()) {
        mbar_spin(EMPT + 8 * ((kb - 2) & 3), ((kb - 2) >> 2) & 1);
        if (kb < 14) {
          load_b(kb + 2);
          load_a(kb + 2);
        } else if (nog) {
          mbar_arrive(RES);
        } else {
          if (gate) wait_count(&g_cnt[3][mb], GATE_CNT);
          asm volatile("fence.proxy.async.global;" ::: "memory");
          mbar_expect_tx(RES, 32768);
          tma_load_2d(base, &P.tx, nt * 256 + kq * 64, mb * 128, RES);
          tma_load_2d(base + 16384, &P.tg, nt * 256 + kq * 64, mb * 128, RES);
        }
      }
      __syncwarp();
    }
  }
  wg_wait<0>();
  TL(5);
#pragma unroll
  for (int j = 1; j < 4; j++) {
    uint4* dst = &g_tpart[((h & ~3) + ((j + kq) & 3)) * 3 + rank][j - 1][0][tid];
#pragma unroll
    for (int i = 0; i < 4; i++) {
      const float* a = &acc[32 * j + 8 * i];
      asm volatile("st.relaxed.gpu.global.v4.u32 [%0], {%1,%2,%3,%4};" ::"l"(dst + i * 256), "r"(pack_bf16(a[0], a[1])),
                   "r"(pack_bf16(a[2], a[3])), "r"(pack_bf16(a[4], a[5])), "r"(pack_bf16(a[6], a[7])) : "memory");
    }
  }
  TL(6);
#pragma unroll 1
  for (int j = 0, tries = 0; j < 3 && tries < POLL_TRIES; tries++) {
    uint4 pt[4];
#pragma unroll
    for (int i = 0; i < 4; i++) pt[i] = ld_strong16(&g_tpart[blockIdx.x][j][i][tid]);
    if (!__all_sync(0xffffffffu, max(max(umax4(pt[0]), umax4(pt[1])), max(umax4(pt[2]), umax4(pt[3]))) != EMPTY)) continue;
#pragma unroll
    for (int i = 0; i < 16; i++) { acc[2 * i] += bf_lo((&pt[0].x)[i]); acc[2 * i + 1] += bf_hi((&pt[0].x)[i]); }
    j++;
  }
  mbar_spin(RES, 0);
  TL(7);
  const uint32_t xa = base + (wv * 16 + ((lane >> 3) & 1) * 8 + (lane & 7)) * 128 + (((lane >> 4) ^ (lane & 7)) << 4);
#pragma unroll
  for (int i = 0; i < 4; i++) {
    uint32_t x[4], g[4], o[4];
    ldsm4(x, xa ^ (i << 5));
    ldsm4(g, (xa ^ (i << 5)) + 16384);
#pragma unroll
    for (int k = 0; k < 4; k++) {
      const uint32_t sv = pack_bf16(acc[8 * i + 2 * k], acc[8 * i + 2 * k + 1]);
      o[k] = nog ? sv : add_bf16x2(x[k], mul_bf16x2(sv, g[k]));
    }
    stsm4(xa ^ (i << 5), o[0], o[1], o[2], o[3]);
  }
  TL(8);
  fence_proxy_async_smem();
  __syncwarp();
  if (elect_one()) {
    tma_store_2d(&P.tout, base + wv * 2048, nt * 256 + kq * 64, mb * 128 + wv * 16);
    tma_store_commit();
    tma_store_wait_read();
  }
  TL(9);
  KT_END(7);
}

__global__ void __launch_bounds__(256, 1) f_kernel(const __grid_constant__ FParams P) {
  using namespace fk;
  extern __shared__ __align__(1024) uint8_t smem_f[];
  uint32_t crank, rank, hw;
  asm("mov.u32 %0, %%cluster_ctarank;" : "=r"(crank));
  const int h = blockIdx.x / 3;
  if (smem_u32(smem_f) != mapa(0, crank) + SM0) return;
  PROF2(0);
  KT_START(1);
  KT_START(0);
  {
    const uint32_t self = mapa(0, crank);
    SMAP;
    const int tid = threadIdx.x, lane = tid & 31, wv = __shfl_sync(0xffffffffu, tid >> 5, 0);
    PRO(0);
    if (wv == 0) {
      uint32_t sm;
      asm("mov.u32 %0, %%smid;" : "=r"(sm));
      sts32(PROBE + 96, sm >> 1);
      asm volatile("fence.release.sync_restrict::shared::cta.cluster;" ::: "memory");
    }
    asm volatile("barrier.cluster.arrive.relaxed.aligned;" ::: "memory");
    if (wv == 7) {
      if (blockIdx.x == 2) {
#pragma unroll
        for (int i = 0; i < 3; i++) { (&g_cnt[0][0])[32 * i + lane] = 0; g_tfix[32 * i + lane] = 0; }
        if (lane < 16) g_oflag[lane] = 0;
        if (lane == 0) { g_next = 0; g_lnok[0] = 0; }
        __threadfence();
        __syncwarp();
      }
      pdl_launch_dependents();
    }
    const int row0 = blockIdx.x * 8 + wv;
    const bool third = row0 + 1536 < cfg::S;
    uint32_t cur[1][16], raw[2][16];
    load_row16(cur[0], P.x + (size_t)row0 * cfg::D, lane);
    load_row16(raw[0], P.x + (size_t)(row0 + 768) * cfg::D, lane);
    load_row16(raw[1], P.x + (size_t)(row0 + (third ? 1536 : 0)) * cfg::D, lane);
    {
      uint32_t tpc;
      asm volatile("barrier.cluster.wait.aligned;" ::: "memory");
      asm volatile("ld.shared::cluster.u32 %0, [%1];" : "=r"(tpc) : "r"(mapa(PROBE + 96, lane % 3)) : "memory");
      const uint32_t t0 = __shfl_sync(0xffffffffu, tpc, 0), t1 = __shfl_sync(0xffffffffu, tpc, 1), t2 = __shfl_sync(0xffffffffu, tpc, 2);
      hw = t1 == t2 ? 0x09 : t0 == t2 ? 0x18 : 0x24;
      rank = (hw & 3) == crank ? 0 : ((hw >> 2) & 3) == crank ? 1 : 2;
    }
    const bool isv = rank == 2;
    const CUtensorMap* m0 = isv ? &P.wv : &P.wq;
    const CUtensorMap* m1 = isv ? &P.wv : &P.wk;
    const int col0 = h * 128 + (isv ? 0 : 64 * rank), col1 = h * 128 + (isv ? 64 : 64 * rank);
    if (wv == 0) {
      if (elect_one()) {
        for (int i = 0; i < 2; i++) mbar_init(B_XN + 8 * i, 1);
        mbar_init(B_H1, 4);
        mbar_init(B_SM, isv ? 1 : 6);
        mbar_init(B_VM, isv ? 8 : 1);
        mbar_init(B_VX, 1);
        mbar_init(B_ST, 1);
        mbar_init(B_PF, 2);
        for (int i = 0; i < 6; i++) mbar_init(B_PB + 8 * i, 1);
        mbar_init(B_W, 2);
        mbar_init(B_WO, 1);
        fence_barrier_init();
        mbar_expect_tx(B_SM, isv ? 2 * SP_SRC : SP_SRC);
        if (isv) mbar_expect_tx(B_ST, 7168);
        else { mbar_expect_tx(B_VM, 2048); mbar_expect_tx(B_VX, 8192); }
      }
    }
    const int j = 2 * h + rank;
    if (lane == 0) {
      const uint2 b = probe_pair(P.xch + (isv ? H1_BYTES + wv * 8192 + h * 128 : j * 32768 + (wv & 3) * 8192 + (wv >> 2) * 128),
                                 isv ? EMPTY : 0, PROBE + 64, P.nprobe);
      sts64(PROBE + wv * 8, b.x, b.y);
    }
    PROF2(3);
    PRO(1);
    __syncwarp();
    if (wv == 1) {
      const uint32_t off = (blockIdx.x * 32 + lane) * 688;
      if (off < cfg::D * cfg::D * 2) l2_prefetch(reinterpret_cast<const char*>(P.w1) + off, min(688u, cfg::D * cfg::D * 2 - off));
    }
    if (wv == 0) {
      asm volatile("{\n.reg .pred p;\nsetp.eq.u32 p, %0, %1;\n@p st.shared.u32 [%2], %0;\n}" ::"r"(raw[1][15]), "r"(cur[0][0] ^ raw[0][15]), "r"(PROBE + 64) : "memory");
      if (elect_one()) {
#pragma unroll 1
        for (int n = 0; n < 2 * PRE_G; n++) {
          const int i = n >> 1, g = n & 1, row = (isv ? Chunks<true>::rf(g, i) : Chunks<false>::rf(g, i)) * 64;
          if (!g) mbar_expect_tx(B_PB + 8 * i, 32768);
          tma_load_2d(SM0 + n * 16384, m0, col0, row, B_PB + 8 * i);
          tma_load_2d(SM0 + n * 16384 + 8192, m1, col1, row, B_PB + 8 * i);
        }
      }
    }
    __syncthreads();
    PRO(2);
    asm volatile("barrier.cluster.arrive.relaxed.aligned;" ::: "memory");
    PRO(3);
    if (wv == 2) { sts32(self + ONES + lane * 4, 0x3F803F80u); fence_proxy_async_smem(); }
    uint32_t pb[2], pc[2];
    lds64(pb, PROBE + (lane & 7) * 8);
    lds64(pc, PROBE + ((lane & 7) ^ 4) * 8);
    const uint32_t mask = __ballot_sync(0xffffffffu, isv ? pb[1] < pb[0] : min(pb[1], pc[1]) < min(pb[0], pc[0])) & (isv ? 255 : 15);
    if (!isv) {
#pragma unroll
      for (int i = 0; i < 4; i++) st_pub128(P.xch + j * 32768 + i * 8192 + ((mask >> i) & 1) * 4096 + tid * 16, 0);
      if (wv < 4) st_pub64(P.xch + H1_BYTES + (wv >> 1) * 32768 + (j >> 4) * 8192 + (wv & 1) * 4096 + (j & 15) * 256 + lane * 8, EMPTY, EMPTY);
    }
#pragma unroll 1
    for (int it = 0; it < (third ? 6 : 4); it++) {
      ln_regs<1>(cur);
      store_row16(cur[0], ((it & 1) ? P.xn2 : P.xn_ptr) + (size_t)(row0 + (it >> 1) * 768) * cfg::D, lane);
      if (it == 0) PRO(4);
      if (it & 1) {
#pragma unroll
        for (int i = 0; i < 16; i++) { cur[0][i] = raw[0][i]; raw[0][i] = raw[1][i]; }
      }
    }
    PRO(5);
    __syncthreads();
    PRO(6);
    if (tid == 64) {
      __threadfence();
      PRO(7);
      st_pub32(&g_mask[3 * h + rank], 0x100 | mask);
    }
    KT_END(0);
    __syncwarp();
  }
  const int wg = __shfl_sync(0xffffffffu, threadIdx.x >> 7, 0);
  if (rank == 2) { if (wg == 0) f_main<true, 0>(P, h, 2, hw); else f_main<true, 1>(P, h, 2, hw); }
  else { if (wg == 0) f_main<false, 0>(P, h, rank, hw); else f_main<false, 1>(P, h, rank, hw); }
  PROF2(5);
  KT_END(1);
  __syncwarp();
  f_tail(P, h, crank, rank == 2);
}

#define GCL 1
namespace gk {
enum { T_B1 = 0, T_B2 = 1, T_B3 = 2, T_B4 = 3, T_O = 4, T_LN = 5, T_END = 7 };
constexpr int NST = 3, STAGE = 49152, MAXITEMS = 512, NEW = 3;
constexpr uint32_t OUTB = NST * STAGE, BARS = OUTB + 65536;
constexpr uint32_t B_FULL = BARS, B_EMPTY = BARS + 32, B_ITEM = BARS + 64, B_FILL = BARS + 128, B_FREE = BARS + 160, B_LN = BARS + 176, ITEMS = BARS + 192;
constexpr int SMEM = BARS + 256;
static_assert(GATE_CNT == 4 * NEW && T_B4 == 3, "gate counter");
}
struct GParams {
  CUtensorMap a[5], b[5];
  bf16* c[5];
  const bf16* r[5];
  bf16* x1n;
  int nitems, lnpos;
  uint16_t items[gk::MAXITEMS];
};
#define ILOG(i)

__device__ __forceinline__ void tma_load_3d_mc(uint32_t dst, const CUtensorMap* map, int x, int y, int z, uint32_t bar) {
  asm volatile("cp.async.bulk.tensor.3d.shared::cluster.global.mbarrier::complete_tx::bytes.multicast::cluster "
               "[%0], [%1, {%3, %4, %5}], [%2], %6;"
               ::"r"(dst), "l"(map), "r"(bar), "r"(x), "r"(y), "r"(z), "h"((uint16_t)3) : "memory");
}
__device__ __forceinline__ float tanh_approx(float x) { float y; asm("tanh.approx.f32 %0, %1;" : "=f"(y) : "f"(x)); return y; }
__global__ void __launch_bounds__(384, 1) g_kernel(const __grid_constant__ GParams P) {
  using namespace gk;
  extern __shared__ __align__(1024) uint8_t smem_g[];
  const uint32_t base = smem_u32(smem_g);
  const int tid = threadIdx.x, warp = __shfl_sync(0xffffffffu, tid >> 5, 0), lane = tid & 31;
  const int rank = blockIdx.x % GCL;
  KT_START(2);
  if (tid == 0) {
    for (int s = 0; s < NST; s++) { mbar_init(base + B_FULL + 8 * s, 1); mbar_init(base + B_EMPTY + 8 * s, 8 * GCL); }
    for (int s = 0; s < 8; s++) mbar_init(base + B_ITEM + 8 * s, 1);
    for (int s = 0; s < 2; s++) { mbar_init(base + B_FILL + 8 * s, 4); mbar_init(base + B_FREE + 8 * s, NEW); }
    mbar_init(base + B_LN, 1);
    fence_barrier_init();
  }
  __syncthreads();
  if (GCL > 1) cluster_sync();
  auto release = [&](uint32_t st) {
    if (GCL > 1) { if (lane < GCL) mbar_arrive_cluster(base + B_EMPTY + 8 * st, lane); }
    else if (lane == 0) mbar_arrive(base + B_EMPTY + 8 * st);
  };
  auto get_item = [&](int q) {
    mbar_wait(base + B_ITEM + 8 * (q & 7), (q >> 3) & 1);
    return lds32(base + ITEMS + 4 * (q & 7));
  };

  if (warp == 8) {
    if (lane < 10) prefetch_tmap(&P.a[0] + lane);
    if (lane == 0) {
      uint32_t st = 0, ph = 1;
#pragma unroll 1
      for (int q = 0;; q++) {
        if (GCL > 1) mbar_expect_tx(base + B_ITEM + 8 * (q & 7), 4);
        if (rank == 0) {
          const unsigned idx = atomicAdd(&g_next, 1), ln = idx - P.lnpos;
          const uint32_t v = (idx < (unsigned)P.nitems ? P.items[idx] : T_END) | (ln < 64 / GCL ? (ln + 1) << 16 : 0);
          if (GCL > 1) {
#pragma unroll
            for (int r = 0; r < GCL; r++) st_async32(mapa(base + ITEMS + 4 * (q & 7), r), v, mapa(base + B_ITEM + 8 * (q & 7), r));
          } else {
            sts32(base + ITEMS + 4 * (q & 7), v);
            mbar_arrive(base + B_ITEM + 8 * (q & 7));
          }
        }
        const uint32_t item = get_item(q);
        const int type = item & 7, mb = ((item >> 3) & 15) + rank, nt = (item >> 7) & 15;
        ILOG(1);
        if (q == 0) { __threadfence(); sts32(base + ITEMS + 32, ld_strong4(&g_oflag[14]) >= 32); }
        if (type == T_END) break;
        if (type == T_B2) {
          wait_count(&g_cnt[T_B1][max(mb - 1, 0)], 4 * NEW); wait_count(&g_cnt[T_B1][mb], 4 * NEW); wait_count(&g_cnt[T_B1][min(mb + 1, 15)], 4 * NEW);
        } else if (type == T_B3) wait_count(&g_cnt[T_LN][mb], 32);
        else if (type == T_B4) wait_count(&g_cnt[T_B3][mb], 14 * NEW);
        else if (type == T_O) wait_count(&g_oflag[mb], 32);
        asm volatile("fence.proxy.async.global;" ::: "memory");
        ILOG(2);
        const CUtensorMap *ma = &P.a[type], *mbm = &P.b[type];
        const int nkb = type == T_B4 ? cfg::F / 64 : type == T_O ? cfg::HD / 64 : cfg::D / 64;
#pragma unroll 1
        for (int kb = 0; kb < nkb; kb++) {
          mbar_wait(base + B_EMPTY + 8 * st, ph);
          const uint32_t sa = base + st * STAGE, full = base + B_FULL + 8 * st;
          mbar_expect_tx(full, STAGE);
          int arow = mb * 128;
          if (type == T_B2) { const int qd = kb >> 2; arow += (qd == 0) ? -1 : (qd == 1) ? 1 : (qd == 2) ? -2 : 2; }
          if (GCL > 1) tma_load_3d_mc(sa + 16384 + rank * 16384, mbm, 0, kb * 64, nt * 4 + rank * 2, full);
          else tma_load_3d(sa + 16384, mbm, 0, kb * 64, nt * 4, full);
          if (q == 0 && kb == 0) { mbar_wait(base + B_LN, 0); asm volatile("fence.proxy.async.global;" ::: "memory"); }
          tma_load_2d(sa, ma, kb * 64, arow, full);
          if (++st == NST) { st = 0; ph ^= 1; }
        }
      }
    }
  } else {
    const int wg = warp >> 2, ew = warp > 8 ? warp - 9 : warp + NEW;
    const uint32_t outa = base + OUTB + (warp * 16 + ((lane >> 3) & 1) * 8 + (lane & 7)) * 512 + (((lane >> 4) ^ (lane & 7)) << 4);
    uint32_t st = 0, ph = 0;
    float acc[128];
    auto kill_acc = [&]() {
#pragma unroll
      for (int i = 0; i < 128; i++) acc[i] = 0.f;
    };
    if (warp == 9) {
#pragma unroll 1
      for (int tries = 0; tries < POLL_TRIES; tries++) {
        uint4 v;
        asm volatile("ld.acquire.gpu.global.v4.u32 {%0,%1,%2,%3}, [%4];" : "=r"(v.x), "=r"(v.y), "=r"(v.z), "=r"(v.w)
                     : "l"(lane < 24 ? &g_mask[4 * lane] : &g_lnok[0]) : "memory");
        const uint32_t ok = __ballot_sync(0xffffffffu, v.x & v.y & v.z & v.w & 0x100);
        if ((ok & 0xFFFFFF) == 0xFFFFFF || (ok >> 24)) break;
        __nanosleep(200);
      }
      if (lane == 0) mbar_arrive(base + B_LN);
    }
    uint32_t next = get_item(0);
#pragma unroll 1
    for (int q = 0;; q++) {
      const uint32_t item = next;
      const int type = item & 7, mb = ((item >> 3) & 15) + rank, nt = (item >> 7) & 15;
      if (type == T_END) break;
      if (warp < 8) {
      if (item >> 16) {
        const int ln = (item >> 16) - 1, lb = (ln >> 2) * GCL + rank;
        const size_t row = (size_t)(lb * 128 + (ln & 3) * 32 + warp * 4) * cfg::D;
        wait_count(&g_cnt[T_B2][lb], 4 * NEW);
        uint32_t cur[2][16], nxt[2][16];
#pragma unroll
        for (int r = 0; r < 2; r++) {
          load_row16(cur[r], P.c[T_B2] + row + r * cfg::D, lane);
          load_row16(nxt[r], P.c[T_B2] + row + (r + 2) * cfg::D, lane);
        }
#pragma unroll 1
        for (int r2 = 0; r2 < 4; r2 += 2) {
          ln_regs<2>(cur);
#pragma unroll
          for (int r = 0; r < 2; r++) {
            store_row16(cur[r], P.x1n + row + (r2 + r) * cfg::D, lane);
#pragma unroll
            for (int i = 0; i < 16; i++) cur[r][i] = nxt[r][i];
          }
        }
        __syncwarp();
        if (lane == 0) asm volatile("red.release.gpu.global.add.u32 [%0], 1;" ::"l"(&g_cnt[T_LN][lb]) : "memory");
        __syncwarp();
        if (tid == 0) ILOG(6);
        kill_acc();
      }
      const int nkb = type == T_B4 ? cfg::F / 64 : type == T_O ? cfg::HD / 64 : cfg::D / 64;
      uint32_t prev = 0;
      mbar_wait(base + B_FULL + 8 * st, ph);
#pragma unroll 1
      for (int kb = 0; kb < nkb; kb++) {
        mbar_spin(base + B_FULL + 8 * st, ph);
        if (kb == 0 && tid == 0) ILOG(3);
        const uint64_t da = make_desc(base + wg * 8192, 16, 1024) + st * (STAGE >> 4), db = make_desc(base + 16384, 8192, 1024) + st * (STAGE >> 4);
        wg_fence();
#pragma unroll
        for (int k = 0; k < 4; k++) {
          wgmma_ss_n256_tb(acc, da + k * 2, db + k * 128, (kb | k) != 0);
          if (k == 0) {
            wg_commit();
            wg_wait<1>();
            if (kb > 0) release(prev);
            wg_fence();
          }
        }
        wg_commit();
        prev = st;
        if (++st == NST) { st = 0; ph ^= 1; }
      }
      next = get_item(q + 1);
      if (q > 0) mbar_wait(base + B_FREE + 8 * wg, (q - 1) & 1);
      wg_wait<0>();
      if (tid == 0) ILOG(4);
      release(prev);
#pragma unroll
      for (int j = 0; j < 16; j++)
        stsm4((outa ^ ((j & 3) << 5)) + (j >> 2) * 128, pack_bf16(acc[8 * j], acc[8 * j + 1]), pack_bf16(acc[8 * j + 2], acc[8 * j + 3]),
              pack_bf16(acc[8 * j + 4], acc[8 * j + 5]), pack_bf16(acc[8 * j + 6], acc[8 * j + 7]));
      __syncwarp();
      if (lane == 0) mbar_arrive(base + B_FILL + 8 * wg);
      if (tid == 0) ILOG(5);
      if ((next & 7) != T_END) continue;
      }
      if (type == T_O) wait_count(&g_cnt[T_B4][mb], 4 * NEW);
      const int ldc = type == T_B3 ? cfg::F : cfg::D;
      bf16* cp = P.c[type] + (size_t)mb * 128 * ldc + nt * 256 + lane * 8;
      const size_t roff = (size_t)mb * 128 * cfg::D + nt * 256 + lane * 8;
      const bf16 *rp = P.r[type] + roff, *gp = P.c[T_B4] + roff;
      const bool res = type == T_B2 || type >= T_B4, act = type != T_B2 && type != T_O;
      const float c1 = type == T_B4 ? 0.f : 0.035677408136300125f, c0 = type == T_B4 ? 0.5f : 0.7978845608028654f;
      uint32_t yn[4][4];
      uint4 rn[4], gn[4];
#pragma unroll
      for (int i = 0; i < 4; i++) rn[i] = gn[i] = make_uint4(0, 0, 0, 0);
      auto fetch_res = [&](int grp) {
#pragma unroll
        for (int i = 0; i < 4; i++) {
          if (res) rn[i] = __ldcg(reinterpret_cast<const uint4*>(rp + (grp * 4 + i) * cfg::D));
          if (type == T_O) gn[i] = __ldcg(reinterpret_cast<const uint4*>(gp + (grp * 4 + i) * cfg::D));
        }
      };
      auto fetch_y = [&](int grp) {
#pragma unroll
        for (int i = 0; i < 4; i++) lds128(yn[i], base + OUTB + (grp * 4 + i) * 512 + ((lane ^ ((grp * 4 + i) & 7)) << 4));
      };
      if (type == T_B4) wait_count(&g_cnt[T_B2][mb], 4 * NEW);
      if (type >= T_B4 && warp > 8) for (int r = tid - 288; r < 128; r += 96) l2_prefetch(rp - lane * 8 + r * cfg::D, 512);
      fetch_res(ew);
      mbar_wait(base + B_FILL, q & 1);
      fetch_y(ew);
      next = get_item(q + 1);
      const int stride = (next & 7) == T_END ? NEW + 8 : NEW;
#pragma unroll 1
      for (int grp = ew; grp < 32; grp += stride) {
        uint32_t y[4][4];
#pragma unroll
        for (int i = 0; i < 4; i++) {
#pragma unroll
          for (int k = 0; k < 4; k++) y[i][k] = yn[i][k];
          if (type == T_O) {
            y[i][0] = mul_bf16x2(y[i][0], gn[i].x); y[i][1] = mul_bf16x2(y[i][1], gn[i].y);
            y[i][2] = mul_bf16x2(y[i][2], gn[i].z); y[i][3] = mul_bf16x2(y[i][3], gn[i].w);
          }
          if (res) {
            y[i][0] = add_bf16x2(y[i][0], rn[i].x); y[i][1] = add_bf16x2(y[i][1], rn[i].y);
            y[i][2] = add_bf16x2(y[i][2], rn[i].z); y[i][3] = add_bf16x2(y[i][3], rn[i].w);
          }
        }
        const int nx = grp + stride;
        if (nx < 32) {
          fetch_res(nx);
          if (nx >= 16 && grp < 16) {
            __syncwarp();
            if (lane == 0 && warp > 8) mbar_arrive(base + B_FREE);
            mbar_wait(base + B_FILL + 8, q & 1);
          }
          fetch_y(nx);
        }
        if (act) {
#pragma unroll
          for (int i = 0; i < 4; i++)
#pragma unroll
            for (int k = 0; k < 4; k++) {
              const float v0 = bf_lo(y[i][k]), v1 = bf_hi(y[i][k]);
              const float t0 = tanh_approx(v0 * fmaf(v0 * c1, v0, c0)), t1 = tanh_approx(v1 * fmaf(v1 * c1, v1, c0));
              const float h0 = 0.5f * v0, h1 = 0.5f * v1;
              y[i][k] = pack_bf16(fmaf(h0, t0, h0), fmaf(h1, t1, h1));
            }
        }
#pragma unroll
        for (int i = 0; i < 4; i++)
          *reinterpret_cast<uint4*>(cp + (size_t)(grp * 4 + i) * ldc) = make_uint4(y[i][0], y[i][1], y[i][2], y[i][3]);
      }
      __syncwarp();
      if (lane == 0 && warp > 8) mbar_arrive(base + B_FREE + 8);
      if (stride != NEW) named_bar_sync(2, 352);
      if (type != T_O && lane == 0 && warp > 8) asm volatile("red.release.gpu.global.add.u32 [%0], 1;" ::"l"(&g_cnt[type][mb]) : "memory");
      __syncwarp();
      if (tid == 288) ILOG(7);
      kill_acc();
    }
    KT_END(2);
  }
  __syncwarp();
  if (warp >= 8) {
   named_bar_sync(1, 128);
   const bool late = lds32(base + ITEMS + 32);
   if (late) pdl_wait();
#pragma unroll 1
   for (int c = blockIdx.x; late && c < 96; c += gridDim.x) {
     if (__ldcg(&g_tfix[c]) == 0) continue;
     const int hh = c / 3, mb = TAIL_MB0 + 3 * (hh >> 4) + c % 3;
     wait_count(&g_cnt[T_B4][mb], GATE_CNT);
#pragma unroll 1
     for (int i = tid - 256; i < 1024; i += 128) {
       const size_t off = (size_t)(mb * 128 + (i >> 3)) * cfg::D + (hh & 15) * 64 + (i & 7) * 8;
       const uint4 sv = __ldcg(reinterpret_cast<const uint4*>(P.c[T_O] + off)), gv = __ldcg(reinterpret_cast<const uint4*>(P.c[T_B4] + off)),
                   xv = __ldcg(reinterpret_cast<const uint4*>(P.r[T_O] + off));
       *reinterpret_cast<uint4*>(P.c[T_O] + off) = make_uint4(add_bf16x2(xv.x, mul_bf16x2(sv.x, gv.x)), add_bf16x2(xv.y, mul_bf16x2(sv.y, gv.y)),
                                                              add_bf16x2(xv.z, mul_bf16x2(sv.z, gv.z)), add_bf16x2(xv.w, mul_bf16x2(sv.w, gv.w)));
     }
   }
  }
  if (GCL > 1) cluster_sync();
}

__device__ bf16 g_xn[cfg::S * cfg::D];
__device__ bf16 g_xn2[cfg::S * cfg::D];
__device__ bf16 g_h[cfg::S * cfg::D];
__device__ bf16 g_x1[cfg::S * cfg::D];
__device__ bf16 g_x1n[cfg::S * cfg::D];
__device__ bf16 g_u[cfg::S * cfg::F];
__device__ bf16 g_g[cfg::S * cfg::D];
__device__ bf16 g_o[cfg::S * cfg::HD];

typedef CUresult (*PFN_encodeTiled)(CUtensorMap*, CUtensorMapDataType, cuuint32_t, void*, const cuuint64_t*,
                                    const cuuint64_t*, const cuuint32_t*, const cuuint32_t*, CUtensorMapInterleave,
                                    CUtensorMapSwizzle, CUtensorMapL2promotion, CUtensorMapFloatOOBfill);

static PFN_encodeTiled get_encoder() {
  static PFN_encodeTiled fn = nullptr;
  if (!fn) {
    void* p = nullptr;
    cudaDriverEntryPointQueryResult st;
    cudaGetDriverEntryPoint("cuTensorMapEncodeTiled", &p, cudaEnableDefault, &st);
    fn = (PFN_encodeTiled)p;
  }
  return fn;
}
static CUtensorMap make_map(const void* ptr, int rows, int cols, int box_rows, int box_cols, int swizzle_bytes) {
  CUtensorMap m;
  cuuint64_t dims[2] = {(cuuint64_t)cols, (cuuint64_t)rows};
  cuuint64_t strides[1] = {(cuuint64_t)cols * 2};
  cuuint32_t box[2] = {(cuuint32_t)box_cols, (cuuint32_t)box_rows};
  cuuint32_t estr[2] = {1, 1};
  CUtensorMapSwizzle sw = swizzle_bytes == 128 ? CU_TENSOR_MAP_SWIZZLE_128B
                        : swizzle_bytes == 64 ? CU_TENSOR_MAP_SWIZZLE_64B
                        : swizzle_bytes == 32 ? CU_TENSOR_MAP_SWIZZLE_32B : CU_TENSOR_MAP_SWIZZLE_NONE;
  get_encoder()(&m, CU_TENSOR_MAP_DATA_TYPE_BFLOAT16, 2, const_cast<void*>(ptr), dims, strides, box, estr,
                CU_TENSOR_MAP_INTERLEAVE_NONE, sw, CU_TENSOR_MAP_L2_PROMOTION_L2_128B, CU_TENSOR_MAP_FLOAT_OOB_FILL_NONE);
  return m;
}
static CUtensorMap make_map3(const void* ptr, int rows, int cols, int box_rows, int nblk) {
  CUtensorMap m;
  cuuint64_t dims[3] = {64, (cuuint64_t)rows, (cuuint64_t)(cols / 64)};
  cuuint64_t strides[2] = {(cuuint64_t)cols * 2, 128};
  cuuint32_t box[3] = {64, (cuuint32_t)box_rows, (cuuint32_t)nblk};
  cuuint32_t estr[3] = {1, 1, 1};
  get_encoder()(&m, CU_TENSOR_MAP_DATA_TYPE_BFLOAT16, 3, const_cast<void*>(ptr), dims, strides, box, estr,
                CU_TENSOR_MAP_INTERLEAVE_NONE, CU_TENSOR_MAP_SWIZZLE_128B, CU_TENSOR_MAP_L2_PROMOTION_L2_128B,
                CU_TENSOR_MAP_FLOAT_OOB_FILL_NONE);
  return m;
}
template <class T> static T* sym(T& s) { void* p = nullptr; cudaGetSymbolAddress(&p, s); return (T*)p; }
#define SYM(name) ((bf16*)[] { void* p = nullptr; cudaGetSymbolAddress(&p, name); return p; }())

#define G_CTAS 36
#define B4_FIRST (GCL == 1 ? 9 : 16)
#define O_FIRST 2
#define LN_POS 63
static int build_items(uint16_t* it) {
  using namespace gk;
  int n = 0;
  auto add = [&](int type, int nrows, int ncols, int row0 = 0) {
    for (int mb = row0; mb < nrows; mb += GCL) for (int nt = 0; nt < ncols; nt++) it[n++] = (uint16_t)(type | mb << 3 | nt << 7);
  };
  add(T_B1, 16, 4); add(T_B2, 16, 4); add(T_B3, 16, 14);
  add(T_B4, B4_FIRST, 4); add(T_O, O_FIRST, 4); add(T_B4, 16, 4, B4_FIRST); add(T_O, TAIL_MB0, 4, O_FIRST);
  return n;
}

extern "C" void kernel_launch(void* const* d_in, const int* in_sizes, int n_in, void* d_out, int out_size) {
  using namespace cfg;
  const bf16* x = (const bf16*)d_in[0];
  const bf16* mem0 = (const bf16*)d_in[1];
  const bf16* Wq = (const bf16*)d_in[2];
  const bf16* Wk = (const bf16*)d_in[3];
  const bf16* Wv = (const bf16*)d_in[4];
  const bf16* Wo = (const bf16*)d_in[5];
  const bf16* w1 = (const bf16*)d_in[8];
  const bf16* w2 = (const bf16*)d_in[9];
  const bf16* w3 = (const bf16*)d_in[10];
  const bf16* w4 = (const bf16*)d_in[11];
  bf16* out = (bf16*)d_out;
  cudaStream_t st = cudaStreamPerThread;

  bf16 *xn = SYM(g_xn), *xn2 = SYM(g_xn2), *hb = SYM(g_h), *x1 = SYM(g_x1), *x1n = SYM(g_x1n), *u = SYM(g_u),
       *g = SYM(g_g), *o = SYM(g_o);

  {
    cudaFuncSetAttribute(f_kernel, cudaFuncAttributeMaxDynamicSharedMemorySize, fk::SMEM);
    FParams P;
    P.wq = make_map(Wq, D, HD, 64, 64, 128); P.wk = make_map(Wk, D, HD, 64, 64, 128); P.wv = make_map(Wv, D, HD, 64, 64, 128);
    P.wo = make_map(Wo, HD, D, 128, 64, 128); P.wo16 = make_map(Wo, HD, D, 128, 16, 32); P.xn = make_map3(xn, S, D, 32, 4); P.xn12 = make_map3(xn, S, D, 32, 12); P.o = make_map3(o, S, HD, 32, 2);
    P.ta = make_map(o, S, HD, 128, 64, 128); P.tb = make_map(Wo, HD, D, 64, 64, 128); P.tx = make_map(x, S, D, 128, 64, 128);
    P.tg = make_map(g, S, D, 128, 64, 128); P.tout = make_map(out, S, D, 16, 64, 128);
    P.mem0 = mem0;
    P.nprobe = PROBE_N;
    P.dxn = make_desc(fk::XN, 16, 1024);
    P.x = x; P.w1 = w1; P.xn_ptr = xn; P.xn2 = xn2;
    P.xch = (char*)(((uintptr_t)SYM(g_xch) + 8191) & ~(uintptr_t)8191);
    cudaLaunchConfig_t cfg = {};
    cfg.gridDim = dim3(96); cfg.blockDim = dim3(256); cfg.dynamicSmemBytes = fk::SMEM; cfg.stream = st;
    cudaLaunchAttribute at[2];
    at[0].id = cudaLaunchAttributeClusterDimension;
    at[0].val.clusterDim.x = 3; at[0].val.clusterDim.y = 1; at[0].val.clusterDim.z = 1;
    cfg.attrs = at; cfg.numAttrs = 1;
    cudaLaunchKernelEx(&cfg, f_kernel, P);
  }
  {
    cudaFuncSetAttribute(g_kernel, cudaFuncAttributeMaxDynamicSharedMemorySize, gk::SMEM);
    GParams G;
    const bf16* as[5] = {xn2, hb, x1n, u, o};
    const bf16* bs[5] = {w1, w2, w3, w4, Wo};
    bf16* cs[5] = {hb, x1, u, g, out};
    const bf16* rs[5] = {xn, xn, xn, x1, x};
    const int ks[5] = {D, D, D, F, HD}, ns[5] = {D, D, F, D, D};
    for (int i = 0; i < 5; i++) {
      G.a[i] = make_map(as[i], S, ks[i], 128, 64, 128);
      G.b[i] = make_map3(bs[i], ks[i], ns[i], 64, 4 / GCL);
      G.c[i] = cs[i];
      G.r[i] = rs[i];
    }
    G.x1n = x1n;
    G.nitems = build_items(G.items);
    G.lnpos = LN_POS * 2 / GCL;
    cudaLaunchConfig_t cfg = {};
    cfg.gridDim = dim3(G_CTAS); cfg.blockDim = dim3(384); cfg.dynamicSmemBytes = gk::SMEM; cfg.stream = st;
    cudaLaunchAttribute at[2];
    at[0].id = cudaLaunchAttributeClusterDimension;
    at[0].val.clusterDim.x = GCL; at[0].val.clusterDim.y = 1; at[0].val.clusterDim.z = 1;
    at[1].id = cudaLaunchAttributeProgrammaticStreamSerialization;
    at[1].val.programmaticStreamSerializationAllowed = 1;
    cfg.attrs = at;
    cfg.numAttrs = 2;
    cudaLaunchKernelEx(&cfg, g_kernel, G);
  }
}
```

```cpp
#include <cuda_runtime.h>
#include <cuda_bf16.h>
#include <cuda.h>
#include <stdint.h>

typedef __nv_bfloat16 bf16;

namespace cfg {
constexpr int S = 2048;
constexpr int D = 1024;
constexpr int H = 32;
constexpr int DH = 128;
constexpr int HD = H * DH;
constexpr int M = 8;
constexpr int SEG = 32;
constexpr int NSEG = S / SEG;
constexpr int F = 3584;
}

__device__ __forceinline__ uint32_t smem_u32(const void* p) { return (uint32_t)__cvta_generic_to_shared(p); }

__device__ __forceinline__ void mbar_init(uint32_t bar, uint32_t count) {
  asm volatile("mbarrier.init.shared::cta.b64 [%0], %1;" ::"r"(bar), "r"(count) : "memory");
}
__device__ __forceinline__ void mbar_expect_tx(uint32_t bar, uint32_t bytes) {
  asm volatile("mbarrier.arrive.expect_tx.shared::cta.b64 _, [%0], %1;" ::"r"(bar), "r"(bytes) : "memory");
}
__device__ __forceinline__ void mbar_arrive(uint32_t bar) {
  asm volatile("mbarrier.arrive.shared::cta.b64 _, [%0];" ::"r"(bar) : "memory");
}
__device__ __forceinline__ bool mbar_try(uint32_t bar, uint32_t parity) {
  uint32_t done;
  asm volatile("{\n.reg .pred p;\nmbarrier.try_wait.parity.shared::cta.b64 p, [%1], %2, 20000;\nselp.u32 %0, 1, 0, p;\n}"
               : "=r"(done) : "r"(bar), "r"(parity) : "memory");
  return done != 0;
}
__device__ __forceinline__ bool mbar_try_nohint(uint32_t bar, uint32_t parity) {
  uint32_t done;
  asm volatile("{\n.reg .pred p;\nmbarrier.try_wait.parity.shared::cta.b64 p, [%1], %2;\nselp.u32 %0, 1, 0, p;\n}"
               : "=r"(done) : "r"(bar), "r"(parity) : "memory");
  return done != 0;
}
constexpr int MBAR_TRIES = 4096;
constexpr int POLL_TRIES = 1 << 16;
__device__ __forceinline__ void mbar_wait(uint32_t bar, uint32_t parity) {
#pragma unroll 1
  for (int n = 0; n < MBAR_TRIES; n++)
    if (mbar_try(bar, parity)) break;
}
__device__ __forceinline__ void mbar_wait_fast(uint32_t bar, uint32_t parity) {
#pragma unroll 1
  for (int n = 0; n < (POLL_TRIES << 4); n++)
    if (mbar_try_nohint(bar, parity)) break;
}
__device__ __forceinline__ void fence_barrier_init() { asm volatile("fence.mbarrier_init.release.cluster;" ::: "memory"); }
__device__ __forceinline__ void fence_proxy_async_smem() { asm volatile("fence.proxy.async.shared::cta;" ::: "memory"); }

__device__ __forceinline__ void tma_load_2d(uint32_t dst, const CUtensorMap* map, int x, int y, uint32_t bar) {
  asm volatile("cp.async.bulk.tensor.2d.shared::cluster.global.mbarrier::complete_tx::bytes [%0], [%1, {%3, %4}], [%2];"
               ::"r"(dst), "l"(map), "r"(bar), "r"(x), "r"(y) : "memory");
}
__device__ __forceinline__ void tma_load_3d(uint32_t dst, const CUtensorMap* map, int x, int y, int z, uint32_t bar) {
  asm volatile("cp.async.bulk.tensor.3d.shared::cluster.global.mbarrier::complete_tx::bytes [%0], [%1, {%3, %4, %5}], [%2];"
               ::"r"(dst), "l"(map), "r"(bar), "r"(x), "r"(y), "r"(z) : "memory");
}
__device__ __forceinline__ void tma_store_2d(const CUtensorMap* map, uint32_t src, int x, int y) {
  asm volatile("cp.async.bulk.tensor.2d.global.shared::cta.bulk_group [%0, {%2, %3}], [%1];"
               ::"l"(map), "r"(src), "r"(x), "r"(y) : "memory");
}
__device__ __forceinline__ void tma_store_commit() { asm volatile("cp.async.bulk.commit_group;" ::: "memory"); }
__device__ __forceinline__ void tma_store_wait_all() { asm volatile("cp.async.bulk.wait_group 0;" ::: "memory"); }
__device__ __forceinline__ void tma_store_wait_read() { asm volatile("cp.async.bulk.wait_group.read 0;" ::: "memory"); }
__device__ __forceinline__ void prefetch_tmap(const CUtensorMap* map) {
  asm volatile("prefetch.tensormap [%0];" ::"l"(map) : "memory");
}

__device__ __forceinline__ void wg_fence() { asm volatile("wgmma.fence.sync.aligned;" ::: "memory"); }
__device__ __forceinline__ void wg_commit() { asm volatile("wgmma.commit_group.sync.aligned;" ::: "memory"); }
template <int N> __device__ __forceinline__ void wg_wait() { asm volatile("wgmma.wait_group.sync.aligned %0;" ::"n"(N) : "memory"); }

#define named_bar_sync(id, n) asm volatile("bar.sync %0, %1;" ::"n"(id), "n"(n) : "memory")
#define named_bar_arrive(id, n) asm volatile("bar.arrive %0, %1;" ::"n"(id), "n"(n) : "memory")

__host__ __device__ __forceinline__ uint64_t make_desc(uint32_t addr, uint32_t lbo, uint32_t sbo) {
  return (uint64_t)((addr & 0x3FFFF) >> 4) | ((uint64_t)(lbo >> 4) << 16) | ((uint64_t)(sbo >> 4) << 32) | (1ull << 62);
}

__device__ __forceinline__ uint64_t make_desc0(uint32_t addr, uint32_t lbo, uint32_t sbo) {
  return (uint64_t)((addr & 0x3FFFF) >> 4) | ((uint64_t)(lbo >> 4) << 16) | ((uint64_t)(sbo >> 4) << 32);
}

__device__ __forceinline__ uint32_t pack_bf16(float lo, float hi) {
  uint32_t r;
  asm("cvt.rn.bf16x2.f32 %0, %1, %2;" : "=r"(r) : "f"(hi), "f"(lo));
  return r;
}
__device__ __forceinline__ float bf_lo(uint32_t v) { return __uint_as_float(v << 16); }
__device__ __forceinline__ float bf_hi(uint32_t v) { return __uint_as_float(v & 0xFFFF0000u); }
__device__ __forceinline__ float rbf(float v) { return __bfloat162float(__float2bfloat16_rn(v)); }

__device__ __forceinline__ void pdl_launch_dependents() { asm volatile("griddepcontrol.launch_dependents;" ::: "memory"); }
__device__ __forceinline__ void pdl_wait() { asm volatile("griddepcontrol.wait;" ::: "memory"); }

__device__ __forceinline__ float ex2_approx(float x) { float y; asm("ex2.approx.ftz.f32 %0, %1;" : "=f"(y) : "f"(x)); return y; }
__device__ __forceinline__ float rcp_approx(float x) { float y; asm("rcp.approx.ftz.f32 %0, %1;" : "=f"(y) : "f"(x)); return y; }

__device__ __forceinline__ void mul_sigmoid4(float (&v)[4], const float (&t)[4]) {
#pragma unroll
  for (int i = 0; i < 4; i += 2) {
    const float a = 1.0f + ex2_approx(fminf(t[i], 60.0f)), b = 1.0f + ex2_approx(fminf(t[i + 1], 60.0f));
    const float r = rcp_approx(a * b);
    v[i] *= b * r;
    v[i + 1] *= a * r;
  }
}
__device__ __forceinline__ void gelu4(float (&v)[4]) {
  float t[4];
#pragma unroll
  for (int i = 0; i < 4; i++) t[i] = v[i] * fmaf(v[i] * v[i], -0.10294324f, -2.30220819f);
  mul_sigmoid4(v, t);
}
__device__ __forceinline__ void silu4(float (&v)[4]) {
  float t[4];
#pragma unroll
  for (int i = 0; i < 4; i++) t[i] = v[i] * -1.4426950408889634f;
  mul_sigmoid4(v, t);
}

#define KT_START(id)
#define KT_END(id)

__device__ __forceinline__ void wgmma_ss_n256_tb(float (&d)[128], uint64_t da, uint64_t db, int scale_d) {
  asm volatile("{\n.reg .pred p;\nsetp.ne.b32 p, %130, 0;\n"
    "wgmma.mma_async.sync.aligned.m64n256k16.f32.bf16.bf16 "
    "{%0, %1, %2, %3, %4, %5, %6, %7, %8, %9, %10, %11, %12, %13, %14, %15, "
    "%16, %17, %18, %19, %20, %21, %22, %23, %24, %25, %26, %27, %28, %29, %30, %31, "
    "%32, %33, %34, %35, %36, %37, %38, %39, %40, %41, %42, %43, %44, %45, %46, %47, "
    "%48, %49, %50, %51, %52, %53, %54, %55, %56, %57, %58, %59, %60, %61, %62, %63, "
    "%64, %65, %66, %67, %68, %69, %70, %71, %72, %73, %74, %75, %76, %77, %78, %79, "
    "%80, %81, %82, %83, %84, %85, %86, %87, %88, %89, %90, %91, %92, %93, %94, %95, "
    "%96, %97, %98, %99, %100, %101, %102, %103, %104, %105, %106, %107, %108, %109, %110, %111, "
    "%112, %113, %114, %115, %116, %117, %118, %119, %120, %121, %122, %123, %124, %125, %126, %127}, "
    "%128, %129, p, 1, 1, 0, 1;\n}\n"
    : "+f"(d[0]), "+f"(d[1]), "+f"(d[2]), "+f"(d[3]), "+f"(d[4]), "+f"(d[5]), "+f"(d[6]), "+f"(d[7]),
      "+f"(d[8]), "+f"(d[9]), "+f"(d[10]), "+f"(d[11]), "+f"(d[12]), "+f"(d[13]), "+f"(d[14]), "+f"(d[15]),
      "+f"(d[16]), "+f"(d[17]), "+f"(d[18]), "+f"(d[19]), "+f"(d[20]), "+f"(d[21]), "+f"(d[22]), "+f"(d[23]),
      "+f"(d[24]), "+f"(d[25]), "+f"(d[26]), "+f"(d[27]), "+f"(d[28]), "+f"(d[29]), "+f"(d[30]), "+f"(d[31]),
      "+f"(d[32]), "+f"(d[33]), "+f"(d[34]), "+f"(d[35]), "+f"(d[36]), "+f"(d[37]), "+f"(d[38]), "+f"(d[39]),
      "+f"(d[40]), "+f"(d[41]), "+f"(d[42]), "+f"(d[43]), "+f"(d[44]), "+f"(d[45]), "+f"(d[46]), "+f"(d[47]),
      "+f"(d[48]), "+f"(d[49]), "+f"(d[50]), "+f"(d[51]), "+f"(d[52]), "+f"(d[53]), "+f"(d[54]), "+f"(d[55]),
      "+f"(d[56]), "+f"(d[57]), "+f"(d[58]), "+f"(d[59]), "+f"(d[60]), "+f"(d[61]), "+f"(d[62]), "+f"(d[63]),
      "+f"(d[64]), "+f"(d[65]), "+f"(d[66]), "+f"(d[67]), "+f"(d[68]), "+f"(d[69]), "+f"(d[70]), "+f"(d[71]),
      "+f"(d[72]), "+f"(d[73]), "+f"(d[74]), "+f"(d[75]), "+f"(d[76]), "+f"(d[77]), "+f"(d[78]), "+f"(d[79]),
      "+f"(d[80]), "+f"(d[81]), "+f"(d[82]), "+f"(d[83]), "+f"(d[84]), "+f"(d[85]), "+f"(d[86]), "+f"(d[87]),
      "+f"(d[88]), "+f"(d[89]), "+f"(d[90]), "+f"(d[91]), "+f"(d[92]), "+f"(d[93]), "+f"(d[94]), "+f"(d[95]),
      "+f"(d[96]), "+f"(d[97]), "+f"(d[98]), "+f"(d[99]), "+f"(d[100]), "+f"(d[101]), "+f"(d[102]), "+f"(d[103]),
      "+f"(d[104]), "+f"(d[105]), "+f"(d[106]), "+f"(d[107]), "+f"(d[108]), "+f"(d[109]), "+f"(d[110]), "+f"(d[111]),
      "+f"(d[112]), "+f"(d[113]), "+f"(d[114]), "+f"(d[115]), "+f"(d[116]), "+f"(d[117]), "+f"(d[118]), "+f"(d[119]),
      "+f"(d[120]), "+f"(d[121]), "+f"(d[122]), "+f"(d[123]), "+f"(d[124]), "+f"(d[125]), "+f"(d[126]), "+f"(d[127])
    : "l"(da), "l"(db), "r"(scale_d));
}
__device__ __forceinline__ void wgmma_rs_n32(float (&d)[16], const uint32_t* a, uint64_t db, int scale_d) {
  asm volatile("{\n.reg .pred p;\nsetp.ne.b32 p, %21, 0;\n"
    "wgmma.mma_async.sync.aligned.m64n32k16.f32.bf16.bf16 "
    "{%0, %1, %2, %3, %4, %5, %6, %7, %8, %9, %10, %11, %12, %13, %14, %15}, "
    "{%16, %17, %18, %19}, %20, p, 1, 1, 0;\n}\n"
    : "+f"(d[0]), "+f"(d[1]), "+f"(d[2]), "+f"(d[3]), "+f"(d[4]), "+f"(d[5]), "+f"(d[6]), "+f"(d[7]),
      "+f"(d[8]), "+f"(d[9]), "+f"(d[10]), "+f"(d[11]), "+f"(d[12]), "+f"(d[13]), "+f"(d[14]), "+f"(d[15])
    : "r"(a[0]), "r"(a[1]), "r"(a[2]), "r"(a[3]), "l"(db), "r"(scale_d));
}
__device__ __forceinline__ void wgmma_ss_n32_ta(float (&d)[16], uint64_t da, uint64_t db, int scale_d) {
  asm volatile("{\n.reg .pred p;\nsetp.ne.b32 p, %18, 0;\n"
    "wgmma.mma_async.sync.aligned.m64n32k16.f32.bf16.bf16 "
    "{%0, %1, %2, %3, %4, %5, %6, %7, %8, %9, %10, %11, %12, %13, %14, %15}, "
    "%16, %17, p, 1, 1, 1, 0;\n}\n"
    : "+f"(d[0]), "+f"(d[1]), "+f"(d[2]), "+f"(d[3]), "+f"(d[4]), "+f"(d[5]), "+f"(d[6]), "+f"(d[7]),
      "+f"(d[8]), "+f"(d[9]), "+f"(d[10]), "+f"(d[11]), "+f"(d[12]), "+f"(d[13]), "+f"(d[14]), "+f"(d[15])
    : "l"(da), "l"(db), "r"(scale_d));
}
__device__ __forceinline__ void wgmma_ss_n8_ta(float (&d)[4], uint64_t da, uint64_t db, int scale_d) {
  asm volatile("{\n.reg .pred p;\nsetp.ne.b32 p, %6, 0;\n"
    "wgmma.mma_async.sync.aligned.m64n8k16.f32.bf16.bf16 {%0, %1, %2, %3}, %4, %5, p, 1, 1, 1, 0;\n}\n"
    : "+f"(d[0]), "+f"(d[1]), "+f"(d[2]), "+f"(d[3]) : "l"(da), "l"(db), "r"(scale_d));
}
__device__ __forceinline__ void wgmma_ss_n48_tt(float (&d)[24], uint64_t da, uint64_t db, int scale_d) {
  asm volatile("{\n.reg .pred p;\nsetp.ne.b32 p, %26, 0;\n"
    "wgmma.mma_async.sync.aligned.m64n48k16.f32.bf16.bf16 "
    "{%0, %1, %2, %3, %4, %5, %6, %7, %8, %9, %10, %11, %12, %13, %14, %15, %16, %17, %18, %19, %20, %21, %22, %23}, "
    "%24, %25, p, 1, 1, 1, 1;\n}\n"
    : "+f"(d[0]), "+f"(d[1]), "+f"(d[2]), "+f"(d[3]), "+f"(d[4]), "+f"(d[5]), "+f"(d[6]), "+f"(d[7]), "+f"(d[8]), "+f"(d[9]), "+f"(d[10]), "+f"(d[11]), "+f"(d[12]), "+f"(d[13]), "+f"(d[14]), "+f"(d[15]), "+f"(d[16]), "+f"(d[17]), "+f"(d[18]), "+f"(d[19]), "+f"(d[20]), "+f"(d[21]), "+f"(d[22]), "+f"(d[23])
    : "l"(da), "l"(db), "r"(scale_d));
}
__device__ __forceinline__ void wgmma_ss_n32(float (&d)[16], uint64_t da, uint64_t db, int scale_d) {
  asm volatile("{\n.reg .pred p;\nsetp.ne.b32 p, %18, 0;\n"
    "wgmma.mma_async.sync.aligned.m64n32k16.f32.bf16.bf16 "
    "{%0, %1, %2, %3, %4, %5, %6, %7, %8, %9, %10, %11, %12, %13, %14, %15}, "
    "%16, %17, p, 1, 1, 0, 0;\n}\n"
    : "+f"(d[0]), "+f"(d[1]), "+f"(d[2]), "+f"(d[3]), "+f"(d[4]), "+f"(d[5]), "+f"(d[6]), "+f"(d[7]),
      "+f"(d[8]), "+f"(d[9]), "+f"(d[10]), "+f"(d[11]), "+f"(d[12]), "+f"(d[13]), "+f"(d[14]), "+f"(d[15])
    : "l"(da), "l"(db), "r"(scale_d));
}

__device__ __forceinline__ void tma_load_2d_mc(uint32_t dst, const CUtensorMap* map, int x, int y, uint32_t bar, uint16_t mask) {
  asm volatile("cp.async.bulk.tensor.2d.shared::cluster.global.mbarrier::complete_tx::bytes.multicast::cluster "
               "[%0], [%1, {%3, %4}], [%2], %5;"
               ::"r"(dst), "l"(map), "r"(bar), "r"(x), "r"(y), "h"(mask) : "memory");
}
__device__ __forceinline__ void mbar_arrive_cluster(uint32_t bar, uint32_t cta) {
  asm volatile("{\n.reg .b32 r;\nmapa.shared::cluster.u32 r, %0, %1;\nmbarrier.arrive.shared::cluster.b64 _, [r];\n}"
               ::"r"(bar), "r"(cta) : "memory");
}
__device__ __forceinline__ void cluster_sync() {
  asm volatile("barrier.cluster.arrive.release.aligned;\nbarrier.cluster.wait.acquire.aligned;" ::: "memory");
}
__device__ __forceinline__ void wait_count(const unsigned* p, unsigned need) {
#pragma unroll 1
  for (int tries = 0; tries < (1 << 18); tries++) {
    unsigned v;
    asm volatile("ld.acquire.gpu.global.u32 %0, [%1];" : "=r"(v) : "l"(p) : "memory");
    if (v >= need) break;
    __nanosleep(64);
  }
}
__device__ __forceinline__ uint32_t sub_bf16x2(uint32_t a, uint32_t b) {
  uint32_t d;
  asm("sub.rn.bf16x2 %0, %1, %2;" : "=r"(d) : "r"(a), "r"(b));
  return d;
}
__device__ __forceinline__ uint32_t add_bf16x2(uint32_t a, uint32_t b) {
  uint32_t d;
  asm("add.rn.bf16x2 %0, %1, %2;" : "=r"(d) : "r"(a), "r"(b));
  return d;
}
__device__ __forceinline__ uint32_t mul_bf16x2(uint32_t a, uint32_t b) {
  uint32_t d;
  asm("mul.rn.bf16x2 %0, %1, %2;" : "=r"(d) : "r"(a), "r"(b));
  return d;
}

template <int NR>
__device__ __forceinline__ void ln_regs(uint32_t (&raw)[NR][16]) {
  float m[NR], q[NR];
#pragma unroll
  for (int r = 0; r < NR; r++) {
    float s0 = 0.f, s1 = 0.f;
#pragma unroll
    for (int i = 0; i < 16; i++) { s0 += bf_lo(raw[r][i]); s1 += bf_hi(raw[r][i]); }
    m[r] = s0 + s1;
  }
#pragma unroll
  for (int o = 16; o > 0; o >>= 1)
#pragma unroll
    for (int r = 0; r < NR; r++) m[r] += __shfl_xor_sync(0xffffffffu, m[r], o);
#pragma unroll
  for (int r = 0; r < NR; r++) {
    m[r] *= 1.0f / 1024.0f;
    float s0 = 0.f, s1 = 0.f;
#pragma unroll
    for (int i = 0; i < 16; i++) {
      const float d0 = bf_lo(raw[r][i]) - m[r], d1 = bf_hi(raw[r][i]) - m[r];
      s0 = fmaf(d0, d0, s0); s1 = fmaf(d1, d1, s1);
    }
    q[r] = s0 + s1;
  }
#pragma unroll
  for (int o = 16; o > 0; o >>= 1)
#pragma unroll
    for (int r = 0; r < NR; r++) q[r] += __shfl_xor_sync(0xffffffffu, q[r], o);
#pragma unroll
  for (int r = 0; r < NR; r++) {
    const uint32_t mb = pack_bf16(m[r], m[r]);
    float sq;
    asm("sqrt.approx.f32 %0, %1;" : "=f"(sq) : "f"(rbf(rbf(q[r] * (1.0f / 1024.0f)) + 1e-5f)));
    const float inv = rcp_approx(rbf(sq));
#pragma unroll
    for (int i = 0; i < 16; i++) {
      const uint32_t d = sub_bf16x2(raw[r][i], mb);
      raw[r][i] = pack_bf16(bf_lo(d) * inv, bf_hi(d) * inv);
    }
  }
}
__device__ __forceinline__ void load_row16(uint32_t (&raw)[16], const bf16* src, int lane) {
#pragma unroll
  for (int j = 0; j < 4; j++) {
    const uint4 u = __ldcg(reinterpret_cast<const uint4*>(src + j * 256 + lane * 8));
    raw[4 * j] = u.x; raw[4 * j + 1] = u.y; raw[4 * j + 2] = u.z; raw[4 * j + 3] = u.w;
  }
}
__device__ __forceinline__ void store_row16(const uint32_t (&raw)[16], bf16* dst, int lane) {
#pragma unroll
  for (int j = 0; j < 4; j++)
    *reinterpret_cast<uint4*>(dst + j * 256 + lane * 8) = make_uint4(raw[4 * j], raw[4 * j + 1], raw[4 * j + 2], raw[4 * j + 3]);
}

namespace fk {
constexpr uint32_t SM0 = 1024;
constexpr uint32_t WO = SM0, WS = WO + 90112, XN = WS + 65536, VX = XN + 49152, QK = VX + 8192, PT = QK + 8192,
                   SP = PT + 4096, VM = SP + 2560, OB = VM + 2048, BAR = OB + 2048;
constexpr uint32_t MEMB = XN + 16384, RED = XN + 32768, VX2 = WO + 81920;
constexpr int SMEM = 232448;
static_assert(BAR + 512 == SM0 + SMEM, "shared memory layout");
constexpr uint32_t B_XN = BAR, B_H2 = BAR + 64, B_H1 = BAR + 120, ONES = BAR + 384, B_PF = BAR + 16, B_WO = BAR + 24, B_SM = BAR + 32, B_VM = BAR + 40, B_VX = BAR + 48, B_ST = BAR + 56, B_PB = BAR + 64, B_W = BAR + 112,
                   MASKS = BAR + 128, PROBE = BAR + 256;
constexpr int NB_M0 = 1, NB_M1 = 2, NB_C = 3, NB_O = 4, NB_ST = 5, NB_DU = 6, NB_CF = 7, NB_W1 = 8, NB_XE = 9, NB_HD = 10, NB_MX = 11, NB_O0 = 12;
#define D_H1 500
#define D_H2 1800
#define D_ST 200
#define SMQ 0x1E
#define SMV 0x1E
#define PRE_G 5
#define WO_AT 4
#define NS0 4
#define NS0V 4
#define NTA0 2
#define NTA1 1
#define PF0A 3
#define PF0 10
#define PF1A 0
#define PF1V 10
#define PF1 11
#define REFILL_EARLY 1
#define GATE_MX 0
#define GATE_Q 0
#define PF1Q 4
#define PACEQ 0x60
#define PACEV 0
#define PADD 1
#define D_H2V 1950
#define H2_ATV 1
#define VM_BULK 0
#define CF_AT 0
#define H2_AT 0
#define NPRE0 1
#define PROBE_N 4
#define SPACK 1
constexpr uint32_t SPW = SPACK ? 4 : 8, SP_SRC = 160 * SPW;
constexpr int H1_BYTES = 64 * 32768, H2_BYTES = 8 * 8192;
}

#define PROF(wg, i)
#define PROF2(i)
#define RETRY(i)
#define GTSYNC(i)
#define PRO(i)
#define TL(i)
#define TL2(t, i)

__device__ uint4 g_xch[(fk::H1_BYTES + fk::H2_BYTES + 8192) / 16];
__device__ __align__(16) unsigned g_mask[128];
__device__ unsigned g_cnt[6][16];
__device__ unsigned g_next;
constexpr int TAIL_MB0 = 10, GATE_CNT = 12;
__device__ __align__(16) unsigned g_tfix[96], g_lnok[4];
__device__ uint4 g_tpart[96][3][4][256];
__device__ unsigned g_oflag[16];

#define LD_POLL "ld.global.L1::no_allocate"
__device__ __forceinline__ uint4 ld_poll16(const void* p) {
  uint4 v;
  asm volatile(LD_POLL ".v4.u32 {%0,%1,%2,%3}, [%4];" : "=r"(v.x), "=r"(v.y), "=r"(v.z), "=r"(v.w) : "l"(p) : "memory");
  return v;
}
__device__ __forceinline__ uint2 ld_poll8(const void* p) {
  uint2 v;
  asm volatile(LD_POLL ".v2.u32 {%0,%1}, [%2];" : "=r"(v.x), "=r"(v.y) : "l"(p) : "memory");
  return v;
}
__device__ __forceinline__ uint4 ld_strong16(const void* p) {
  uint4 v;
  asm volatile("ld.relaxed.gpu.global.v4.u32 {%0,%1,%2,%3}, [%4];" : "=r"(v.x), "=r"(v.y), "=r"(v.z), "=r"(v.w) : "l"(p) : "memory");
  return v;
}
__device__ __forceinline__ uint2 ld_strong8(const void* p) {
  uint2 v;
  asm volatile("ld.relaxed.gpu.global.v2.u32 {%0,%1}, [%2];" : "=r"(v.x), "=r"(v.y) : "l"(p) : "memory");
  return v;
}
__device__ __forceinline__ void st_pub32(void* p, uint32_t v) { asm volatile("st.relaxed.gpu.global.u32 [%0], %1;" ::"l"(p), "r"(v) : "memory"); }
__device__ __forceinline__ void st_pub16(void* p, uint32_t v) {
  asm volatile("st.relaxed.gpu.global.u16 [%0], %1;" ::"l"(p), "h"((uint16_t)v) : "memory");
}
__device__ __forceinline__ uint32_t ld_strong4(const void* p) {
  uint32_t v;
  asm volatile("ld.relaxed.gpu.global.u32 %0, [%1];" : "=r"(v) : "l"(p) : "memory");
  return v;
}
__device__ __forceinline__ void st_pub64(void* p, uint32_t a, uint32_t b) {
  asm volatile("st.relaxed.gpu.global.v2.u32 [%0], {%1,%2};" ::"l"(p), "r"(a), "r"(b) : "memory");
}
__device__ __forceinline__ void st_pub128(void* p, uint32_t a) {
  asm volatile("st.relaxed.gpu.global.v4.u32 [%0], {%1,%1,%1,%1};" ::"l"(p), "r"(a) : "memory");
}
constexpr uint32_t EMPTY = 0xFFFFFFFFu;
__device__ __forceinline__ uint32_t umax4(const uint4& v) { return max(max(v.x, v.y), max(v.z, v.w)); }
__device__ __forceinline__ void sts128(uint32_t a, uint32_t x, uint32_t y, uint32_t z, uint32_t w) {
  asm volatile("st.shared.v4.u32 [%0], {%1,%2,%3,%4};" ::"r"(a), "r"(x), "r"(y), "r"(z), "r"(w) : "memory");
}
__device__ __forceinline__ void sts64(uint32_t a, uint32_t x, uint32_t y) {
  asm volatile("st.shared.v2.u32 [%0], {%1,%2};" ::"r"(a), "r"(x), "r"(y) : "memory");
}
__device__ __forceinline__ void sts32(uint32_t a, uint32_t x) { asm volatile("st.shared.u32 [%0], %1;" ::"r"(a), "r"(x) : "memory"); }
__device__ __forceinline__ void sts128f(uint32_t a, float x, float y, float z, float w) {
  asm volatile("st.shared.v4.f32 [%0], {%1,%2,%3,%4};" ::"r"(a), "f"(x), "f"(y), "f"(z), "f"(w) : "memory");
}
__device__ __forceinline__ void sts64f(uint32_t a, float x, float y) {
  asm volatile("st.shared.v2.f32 [%0], {%1,%2};" ::"r"(a), "f"(x), "f"(y) : "memory");
}
__device__ __forceinline__ float4 lds128f(uint32_t a) {
  float4 v;
  asm volatile("ld.shared.v4.f32 {%0,%1,%2,%3}, [%4];" : "=f"(v.x), "=f"(v.y), "=f"(v.z), "=f"(v.w) : "r"(a) : "memory");
  return v;
}
__device__ __forceinline__ float2 lds64f(uint32_t a) {
  float2 v;
  asm volatile("ld.shared.v2.f32 {%0,%1}, [%2];" : "=f"(v.x), "=f"(v.y) : "r"(a) : "memory");
  return v;
}
__device__ __forceinline__ float2 lds64f_if(uint32_t a, bool on, float other) {
  float2 v = make_float2(other, other);
  asm volatile("{\n.reg .pred p;\nsetp.ne.u32 p, %3, 0;\n@p ld.shared.v2.f32 {%0,%1}, [%2];\n}" : "+f"(v.x), "+f"(v.y) : "r"(a), "r"((uint32_t)on) : "memory");
  return v;
}
__device__ __forceinline__ void lds128(uint32_t* r, uint32_t a) {
  asm volatile("ld.shared.v4.u32 {%0,%1,%2,%3}, [%4];" : "=r"(r[0]), "=r"(r[1]), "=r"(r[2]), "=r"(r[3]) : "r"(a) : "memory");
}
__device__ __forceinline__ void lds64(uint32_t* r, uint32_t a) {
  asm volatile("ld.shared.v2.u32 {%0,%1}, [%2];" : "=r"(r[0]), "=r"(r[1]) : "r"(a) : "memory");
}
__device__ __forceinline__ uint32_t lds32(uint32_t a) {
  uint32_t v;
  asm volatile("ld.shared.u32 %0, [%1];" : "=r"(v) : "r"(a) : "memory");
  return v;
}
__device__ __forceinline__ void ldsm4(uint32_t* r, uint32_t a) {
  asm volatile("ldmatrix.sync.aligned.m8n8.x4.shared.b16 {%0,%1,%2,%3}, [%4];"
               : "=r"(r[0]), "=r"(r[1]), "=r"(r[2]), "=r"(r[3]) : "r"(a) : "memory");
}
__device__ __forceinline__ void ldsm4t(uint32_t* r, uint32_t a) {
  asm volatile("ldmatrix.sync.aligned.m8n8.x4.trans.shared.b16 {%0,%1,%2,%3}, [%4];"
               : "=r"(r[0]), "=r"(r[1]), "=r"(r[2]), "=r"(r[3]) : "r"(a) : "memory");
}
__device__ __forceinline__ void stsm4(uint32_t a, uint32_t r0, uint32_t r1, uint32_t r2, uint32_t r3) {
  asm volatile("stmatrix.sync.aligned.m8n8.x4.shared.b16 [%0], {%1,%2,%3,%4};"
               ::"r"(a), "r"(r0), "r"(r1), "r"(r2), "r"(r3) : "memory");
}
__device__ __forceinline__ void stsm4t(uint32_t a, uint32_t r0, uint32_t r1, uint32_t r2, uint32_t r3) {
  asm volatile("stmatrix.sync.aligned.m8n8.x4.trans.shared.b16 [%0], {%1,%2,%3,%4};"
               ::"r"(a), "r"(r0), "r"(r1), "r"(r2), "r"(r3) : "memory");
}
__device__ __forceinline__ void mma16816(float* d, const uint32_t* a, uint32_t b0, uint32_t b1) {
  asm volatile("mma.sync.aligned.m16n8k16.row.col.f32.bf16.bf16.f32 {%0,%1,%2,%3}, {%4,%5,%6,%7}, {%8,%9}, {%0,%1,%2,%3};"
               : "+f"(d[0]), "+f"(d[1]), "+f"(d[2]), "+f"(d[3])
               : "r"(a[0]), "r"(a[1]), "r"(a[2]), "r"(a[3]), "r"(b0), "r"(b1));
}
__device__ __forceinline__ void mma16816z(float* d, const uint32_t* a, uint32_t b0, uint32_t b1) {
  asm volatile("mma.sync.aligned.m16n8k16.row.col.f32.bf16.bf16.f32 {%0,%1,%2,%3}, {%4,%5,%6,%7}, {%8,%9}, {%10,%10,%10,%10};"
               : "=f"(d[0]), "=f"(d[1]), "=f"(d[2]), "=f"(d[3])
               : "r"(a[0]), "r"(a[1]), "r"(a[2]), "r"(a[3]), "r"(b0), "r"(b1), "f"(0.f));
}
__device__ __forceinline__ void mma1688(float* d, uint32_t a0, uint32_t a1, uint32_t b0) {
  asm volatile("mma.sync.aligned.m16n8k8.row.col.f32.bf16.bf16.f32 {%0,%1,%2,%3}, {%4,%5}, {%6}, {%0,%1,%2,%3};"
               : "+f"(d[0]), "+f"(d[1]), "+f"(d[2]), "+f"(d[3]) : "r"(a0), "r"(a1), "r"(b0));
}
__device__ __forceinline__ uint32_t movtrans(uint32_t a) {
  uint32_t d;
  asm volatile("movmatrix.sync.aligned.m8n8.trans.b16 %0, %1;" : "=r"(d) : "r"(a));
  return d;
}
__device__ __forceinline__ uint32_t mapa(uint32_t a, uint32_t rank) {
  uint32_t d;
  asm("mapa.shared::cluster.u32 %0, %1, %2;" : "=r"(d) : "r"(a), "r"(rank));
  return d;
}
__device__ __forceinline__ void st_async64(uint32_t a, uint32_t x, uint32_t y, uint32_t bar) {
  asm volatile("st.async.weak.shared::cluster.mbarrier::complete_tx::bytes.v2.b32 [%0], {%1,%2}, [%3];"
               ::"r"(a), "r"(x), "r"(y), "r"(bar) : "memory");
}
__device__ __forceinline__ void st_async64f(uint32_t a, float x, float y, uint32_t bar) {
  st_async64(a, __float_as_uint(x), __float_as_uint(y), bar);
}
__device__ __forceinline__ void bulk_s2s(uint32_t dst, uint32_t src, uint32_t bytes, uint32_t bar) {
  asm volatile("cp.async.bulk.shared::cluster.shared::cta.mbarrier::complete_tx::bytes [%0], [%1], %2, [%3];"
               ::"r"(dst), "r"(src), "r"(bytes), "r"(bar) : "memory");
}
__device__ __forceinline__ void tma_store_3d(const CUtensorMap* map, uint32_t src, int x, int y, int z) {
  asm volatile("cp.async.bulk.tensor.3d.global.shared::cta.bulk_group [%0, {%2, %3, %4}], [%1];"
               ::"l"(map), "r"(src), "r"(x), "r"(y), "r"(z) : "memory");
}
__device__ __forceinline__ void mbar_spin(uint32_t bar, uint32_t parity) {
  asm volatile("{\n.reg .pred p;\n.reg .b32 n;\nmov.u32 n, 0x100000;\nMW_L:\n"
               "mbarrier.try_wait.parity.shared::cta.b64 p, [%0], %1;\n@p bra.uni MW_D;\n"
               "add.s32 n, n, -1;\nsetp.ne.u32 p, n, 0;\n@p bra.uni MW_L;\nMW_D:\n}" ::"r"(bar), "r"(parity) : "memory");
}
__device__ __forceinline__ bool mbar_test(uint32_t bar, uint32_t parity) {
  uint32_t done;
  asm volatile("{\n.reg .pred p;\nmbarrier.test_wait.parity.shared::cta.b64 p, [%1], %2;\nselp.u32 %0, 1, 0, p;\n}"
               : "=r"(done) : "r"(bar), "r"(parity) : "memory");
  return done != 0;
}
__device__ __forceinline__ void mbar_arrive_remote(uint32_t bar) {
  asm volatile("mbarrier.arrive.shared::cluster.b64 _, [%0];" ::"r"(bar) : "memory");
}
__device__ __forceinline__ bool elect_one() {
  uint32_t r;
  asm volatile("{\n.reg .pred p;\nelect.sync _|p, 0xffffffff;\nselp.u32 %0, 1, 0, p;\n}" : "=r"(r));
  return r != 0;
}
__device__ __forceinline__ void st_async32(uint32_t a, uint32_t x, uint32_t bar) {
  asm volatile("st.async.weak.shared::cluster.mbarrier::complete_tx::bytes.b32 [%0], %1, [%2];" ::"r"(a), "r"(x), "r"(bar) : "memory");
}
#define named_bar_and(id, n, in, out) \
  asm volatile("{\n.reg .pred p, q;\nsetp.ne.u32 p, %1, 0;\nbar.red.and.pred q, %2, %3, p;\nselp.u32 %0, 1, 0, q;\n}" \
               : "=r"(out) : "r"(in), "n"(id), "n"(n) : "memory")
__device__ __forceinline__ void bulk_g2s(uint32_t dst, const void* src, uint32_t bytes, uint32_t bar) {
  asm volatile("cp.async.bulk.shared::cluster.global.mbarrier::complete_tx::bytes [%0], [%1], %2, [%3];"
               ::"r"(dst), "l"(src), "r"(bytes), "r"(bar) : "memory");
}
__device__ __forceinline__ void l2_prefetch(const void* p, uint32_t bytes) {
  asm volatile("cp.async.bulk.prefetch.L2.global [%0], %1;" ::"l"(p), "r"(bytes) : "memory");
}

__device__ __forceinline__ uint32_t clk32() { uint32_t c; asm volatile("mov.u32 %0, %%clock;" : "=r"(c)::"memory"); return c; }
__device__ __forceinline__ void spin_until(uint32_t t) { while ((int32_t)(clk32() - t) < 0) {} }
#define PIN(x) asm volatile("" : "+r"(x))
#define OPQ                                                                                     \
  int tid_o = tid;                                                                              \
  asm volatile("" : "+r"(tid_o));                                                               \
  const int lane = tid_o & 31, w = (tid_o >> 5) & 3, t7 = tid_o & 127, lg = lane >> 2,          \
            lq = lane & 3, mi = lane >> 3, mr = lane & 7;                                       \
  (void)w; (void)t7; (void)lg; (void)lq; (void)mi; (void)mr; (void)lane

#define SMAP                                                                                                          \
  const uint32_t SM0 = self + fk::SM0, WO = self + fk::WO, WS = self + fk::WS, XN = self + fk::XN, VX = self + fk::VX, \
                 QK = self + fk::QK, PT = self + fk::PT, SP = self + fk::SP, VM = self + fk::VM, OB = self + fk::OB,   \
                 RED = self + fk::RED, VX2 = self + fk::VX2, MEMB = self + fk::MEMB, B_XN = self + fk::B_XN, B_SM = self + fk::B_SM,       \
                 B_VM = self + fk::B_VM, B_VX = self + fk::B_VX, B_ST = self + fk::B_ST, B_PB = self + fk::B_PB,       \
                 B_W = self + fk::B_W, B_H2 = self + fk::B_H2, B_H1 = self + fk::B_H1, B_PF = self + fk::B_PF, B_WO = self + fk::B_WO, MASKS = self + fk::MASKS, PROBE = self + fk::PROBE;                             \
  (void)SM0; (void)WO; (void)WS; (void)XN; (void)VX; (void)QK; (void)PT; (void)SP; (void)VM; (void)OB; (void)RED; (void)VX2; \
  (void)MEMB; (void)B_XN; (void)B_SM; (void)B_VM; (void)B_VX; (void)B_ST; (void)B_PB; (void)B_W; (void)MASKS; (void)PROBE; (void)B_H2; (void)B_H1; (void)B_PF; (void)B_WO

struct FParams {
  CUtensorMap wq, wk, wv, wo, wo16, xn, xn12, o;
  CUtensorMap ta, tb, tx, tg, tout;
  const bf16 *mem0, *x, *w1;
  bf16 *xn_ptr, *xn2;
  uint64_t dxn;
  int nprobe;
  char* xch;
};

__device__ __forceinline__ uint2 probe_pair(char* p, uint32_t val, uint32_t dummy, int n) {
  uint2 best = make_uint2(0x7FFFFFFF, 0x7FFFFFFF);
  st_pub128(p, val); st_pub128(p + 16, val); st_pub128(p + 4096, val); st_pub128(p + 4112, val);
#pragma unroll 1
  for (int r = 0; r < n; r++) {
    uint32_t v;
    const uint32_t c0 = clk32();
    asm volatile("atom.relaxed.gpu.global.exch.b32 %0, [%1], %2;" : "=r"(v) : "l"(p + (r & 1) * 4096), "r"(val) : "memory");
    asm volatile("{\n.reg .pred p;\nsetp.eq.u32 p, %0, 0x12345678;\n@p st.shared.u32 [%1], %0;\n}" ::"r"(v), "r"(dummy) : "memory");
    const uint32_t d = clk32() - c0;
    if (r & 1) best.y = min(best.y, d); else best.x = min(best.x, d);
  }
  return best;
}

typedef uint32_t WRegs[6][2][4][4];

constexpr uint32_t nth_chunks(uint32_t mask) {
  uint32_t t = 0;
  for (int c = 0, n = 0; c < 10; c++) if ((mask >> c) & 1) t |= c << (4 * n++);
  return t;
}
constexpr uint64_t chunk_pos(uint32_t mask) {
  uint64_t t = 0;
  for (int c = 0, a = 0, b = 0; c < 10; c++) t |= (uint64_t)(((mask >> c) & 1) ? a++ : b++) << (4 * c);
  return t;
}
template <bool ISV> struct Chunks {
  static constexpr uint32_t MASK = ISV ? SMV : SMQ, SMT = nth_chunks(MASK), RFT = nth_chunks(~MASK & 1023);
  static_assert(!(MASK & 1), "the first chunk initialises the accumulators");
  static __device__ __forceinline__ constexpr int rf(int wg, int i) { return wg ? 10 + i : (RFT >> (4 * i)) & 15; }
  static __device__ __forceinline__ constexpr int sm(int i) { return (SMT >> (4 * i)) & 15; }
  static constexpr uint64_t IDX = chunk_pos(MASK);
  static __device__ __forceinline__ constexpr int idx(int c) { return (IDX >> (4 * c)) & 15; }
};

template <bool ISV, int WG> struct ProjCfg {
  static constexpr int N0 = ISV ? NS0V : NS0, NS = WG ? 8 - N0 : N0, P0 = WG ? N0 : 0, NTA = WG ? NTA1 : NTA0;
};
__device__ __forceinline__ void load_pair(uint32_t (&t)[4][4], uint32_t wsa, int pp) {
#pragma unroll
  for (int f = 0; f < 4; f++) ldsm4t(t[f], wsa + ((pp >> 1) * 2 + (f & 1)) * 8192 + ((pp & 1) * 2 + (f >> 1)) * 2048);
}
template <bool ISV, int WG>
__device__ __forceinline__ void proj_mem(const WRegs& wr, uint32_t (&ta)[ProjCfg<ISV, WG>::NTA][4][4], uint32_t wsa, uint32_t mba,
                                         float (&a0)[4], float (&a1)[4]) {
  constexpr int NS = ProjCfg<ISV, WG>::NS, P0 = ProjCfg<ISV, WG>::P0, NTA = ProjCfg<ISV, WG>::NTA, NP = 12 + NS;
  float acc[4][4];
  auto spos = [](int j) { return j < NTA ? j : j + (j - NTA + 1) * 12 / (NS - NTA > 0 ? NS - NTA : 1); };
  auto which = [&](int p) { int r = -1; for (int j = 0; j < NS; j++) if (spos(j) == p) r = j; return r; };
  auto nsm_before = [&](int p) { int n = 0; for (int j = 0; j < NS; j++) if (spos(j) < p) n++; return n; };
#pragma unroll
  for (int p = 0; p < NP; p++) {
    const int j = which(p), r = j >= 0 ? 0 : p - nsm_before(p);
    uint32_t bp[4], tl[4][4];
    ldsm4(bp, mba + (j >= 0 ? Chunks<ISV>::sm((P0 + (j >= 0 ? j : 0)) >> 1) * 1024 + ((P0 + j) & 1) * 512 : Chunks<ISV>::rf(WG, r >> 1) * 1024 + (r & 1) * 512));
    if (j >= NTA) load_pair(tl, wsa, P0 + j);
#pragma unroll
    for (int u = 0; u < 2; u++)
#pragma unroll
      for (int T = 0; T < 2; T++) {
        const uint32_t* a = j >= NTA ? tl[u * 2 + T] : j >= 0 ? ta[j >= 0 ? j % NTA : 0][u * 2 + T] : wr[r >> 1][T][(r & 1) * 2 + u];
        if (p == 0) mma16816z(acc[u * 2 + T], a, bp[2 * u], bp[2 * u + 1]);
        else mma16816(acc[u * 2 + T], a, bp[2 * u], bp[2 * u + 1]);
      }
  }
#pragma unroll
  for (int i = 0; i < 4; i++) { a0[i] = acc[0][i] + acc[2][i]; a1[i] = acc[1][i] + acc[3][i]; }
}
template <bool ISV, int WG, int J0, int J1>
__device__ __forceinline__ void proj_mem_prefetch(uint32_t (&ta)[ProjCfg<ISV, WG>::NTA][4][4], uint32_t wsa) {
#pragma unroll
  for (int j = J0; j < J1; j++) load_pair(ta[j], wsa, ProjCfg<ISV, WG>::P0 + j);
}

template <bool ISV, int WG>
__device__ __forceinline__ void proj_finish(const float (&a0)[4], const float (&a1)[4], uint32_t peer0, uint32_t peer1, uint32_t self, int tid, int warp,
                                            uint32_t (&vmo)[4]) {
  using namespace fk;
  SMAP;
  OPQ;
  if (!ISV) {
    stsm4(PT + mr * 16 + ((mi >> 1) ? WG * 1024 + w * 256 + (mi & 1) * 128 : 2048 + w * 512 + (mi & 1) * 256 + WG * 128),
          pack_bf16(a0[0], a0[1]), pack_bf16(a0[2], a0[3]), pack_bf16(a1[0], a1[1]), pack_bf16(a1[2], a1[3]));
    named_bar_sync(NB_C, 256);
  } else {
    if (WG == 0) sts128f(RED + t7 * 16, a1[0], a1[1], a1[2], a1[3]);
    else sts128f(RED + 2048 + t7 * 16, a0[0], a0[1], a0[2], a0[3]);
    if (WG == 1) { lds64(vmo, VM + t7 * 8); lds64(vmo + 2, VM + 1024 + t7 * 8); }
    named_bar_sync(NB_C, 256);
    const float4 p = lds128f(RED + (1 - WG) * 2048 + t7 * 16);
    const float* k = WG == 0 ? a0 : a1;
    const uint32_t v0 = pack_bf16(k[0] + p.x, k[1] + p.y), v1 = pack_bf16(k[2] + p.z, k[3] + p.w);
    const uint32_t off = VM + WG * 1024 + t7 * 8;
    if (VM_BULK) {
      sts64(off, v0, v1);
      fence_proxy_async_smem();
      __syncwarp();
      const uint32_t a = VM + WG * 1024 + warp * 256;
      if (elect_one()) {
        bulk_s2s(peer0 + a, a, 256, peer0 + B_VM);
        bulk_s2s(peer1 + a, a, 256, peer1 + B_VM);
        mbar_arrive(B_VM);
      }
    } else {
      st_async64(peer0 + off, v0, v1, peer0 + B_VM);
      st_async64(peer1 + off, v0, v1, peer1 + B_VM);
      sts64(off, v0, v1);
      __syncwarp();
      if (lane == 0) mbar_arrive(B_VM);
    }
  }
}

__device__ __forceinline__ void send_scores(float s0, float s1, uint32_t off, uint32_t peer0, uint32_t peer1, uint32_t bar, int lane) {
  if (SPACK) {
    const uint32_t v = pack_bf16(s0, s1);
    st_async32(peer0 + off, v, peer0 + bar);
    st_async32(peer1 + off, v, peer1 + bar);
    sts32(off, v);
  } else {
    st_async64f(peer0 + off, s0, s1, peer0 + bar);
    st_async64f(peer1 + off, s0, s1, peer1 + bar);
    sts64f(off, s0, s1);
  }
  __syncwarp();
  if (lane == 0) mbar_arrive(bar);
}

template <int MODE>
__device__ __forceinline__ void wo_load(uint32_t* r, int f, uint32_t woa, uint32_t wob, bool third) {
  constexpr int NT = MODE ? 3 : 2;
  if (MODE >= 2 && f % 3 == 2)
    asm volatile("{\n.reg .pred p;\nsetp.ne.u32 p, %5, 0;\nmov.b32 %0, 0;\nmov.b32 %1, 0;\nmov.b32 %2, 0;\nmov.b32 %3, 0;\n"
                 "@p ldmatrix.sync.aligned.m8n8.x4.trans.shared.b16 {%0,%1,%2,%3}, [%4];\n}"
                 : "=r"(r[0]), "=r"(r[1]), "=r"(r[2]), "=r"(r[3]) : "r"(wob + (f / 3) * 512), "r"((uint32_t)third) : "memory");
  else ldsm4t(r, woa + (f % NT) * 32768 + (f / NT) * 2048);
}
template <int MODE, int PF>
__device__ __forceinline__ void wo_phase(uint32_t (&wf)[PF][4], uint32_t woa, uint32_t wob, bool third, uint32_t oba, char* h1p,
                                         uint32_t sel, uint32_t tag) {
  constexpr int NT = MODE ? 3 : 2;
  float c[NT][4];
  uint32_t of[2][4];
  ldsm4t(of[0], oba);
#pragma unroll
  for (int k = 0; k < 8; k++) {
    if ((k & 1) == 0 && k + 2 < 8) ldsm4t(of[((k >> 1) + 1) & 1], oba + ((k >> 1) + 1) * 512);
#pragma unroll
    for (int i = 0; i < NT; i++) {
      const int f = k * NT + i;
      const uint32_t b0 = of[(k >> 1) & 1][2 * (k & 1)], b1 = of[(k >> 1) & 1][2 * (k & 1) + 1];
      if (k == 0) mma16816z(c[i], wf[f % PF], b0, b1); else mma16816(c[i], wf[f % PF], b0, b1);
      if (f + PF < 8 * NT) wo_load<MODE>(wf[f % PF], f + PF, woa, wob, third);
    }
  }
#pragma unroll
  for (int i = 0; i < NT; i++) {
    char* p = h1p + i * (8 * 32768) + ((sel >> (2 * i)) & 3) * 2048;
    const uint32_t tm = (sel >> 10) & 1;
    if (MODE < 2 || i < 2 || third) {
      st_pub32(p, (pack_bf16(c[i][0], c[i][1]) & ~tm) | (tag & tm));
      st_pub32(p + 1024, (pack_bf16(c[i][2], c[i][3]) & ~tm) | (tag & tm));
    }
  }
}
template <int MODE, int F0, int F1, int PF>
__device__ __forceinline__ void wo_prefetch(uint32_t (&wf)[PF][4], uint32_t woa, uint32_t wob, bool third) {
#pragma unroll
  for (int f = F0; f < F1; f++) wo_load<MODE>(wf[f], f, woa, wob, third);
}

template <bool ISV> __device__ __forceinline__ uint32_t tok_addr(uint32_t base, int tid) {
  OPQ;
  return ISV ? base + w * 2048 + (mi & 1) * 1024 + (mi >> 1) * 128 + mr * 16 : base + (mi >> 1) * 1024 + w * 256 + (mi & 1) * 128 + mr * 16;
}
template <bool ISV> __device__ __forceinline__ constexpr uint32_t tok_off(int T, int i) { return ISV ? T * 512 + i * 256 : T * 4096 + i * 2048; }
template <bool ISV, int T, bool ADD>
__device__ __forceinline__ void tok_store(const float (&x)[16], uint32_t a, const uint32_t (&p)[2][4]) {
#pragma unroll
  for (int i = 0; i < 2; i++) {
    uint32_t r[4];
#pragma unroll
    for (int k = 0; k < 4; k++)
      r[k] = !ADD ? pack_bf16(x[8 * i + 2 * k], x[8 * i + 2 * k + 1])
           : PADD ? add_bf16x2(pack_bf16(x[8 * i + 2 * k], x[8 * i + 2 * k + 1]), p[i][k])
                  : pack_bf16(x[8 * i + 2 * k] + bf_lo(p[i][k]), x[8 * i + 2 * k + 1] + bf_hi(p[i][k]));
    stsm4(a + tok_off<ISV>(T, i), r[0], r[1], r[2], r[3]);
  }
}

__device__ __forceinline__ void load_xn(const FParams& P, int seg, uint32_t self) {
  SMAP;
  mbar_expect_tx(B_XN, 49152);
  tma_load_3d(XN, &P.xn12, 0, seg * 32, 0, B_XN);
}

#define DESC_ADD(d, n) asm volatile("add.s64 %0, %0, %1;" : "+l"(d) : "n"(n))

template <bool ISV>
__device__ __forceinline__ void f_wg0(const FParams& P, const WRegs& wr, const int h, const int rank, const uint32_t hw, int tid) {
  using namespace fk;
  const uint32_t self = mapa(0, (hw >> (2 * rank)) & 3), peer0 = mapa(0, (hw >> (ISV ? 0 : 2 * (rank ^ 1))) & 3) - self,
                 peer1 = mapa(0, (hw >> (ISV ? 2 : 4)) & 3) - self;
  SMAP;
  const int tile0 = rank * 22;
  const uint32_t usel = __shfl_sync(0xffffffffu, tid, 0);
  const int warp = __shfl_sync(0xffffffffu, threadIdx.x >> 5, 0);
  constexpr int WMODE = ISV ? 0 : 2;
  const bool three = warp < 2;
  uint32_t h2ph = 1;
  tid ^= 0x5500;
#pragma unroll 1
  for (int s = -1;;) {
    uint32_t ta[ProjCfg<ISV, 0>::NTA][4][4], wsa, mba;
    const char* src = P.xch + H1_BYTES + ((s & 1) * 4 + warp) * 8192 + ((usel >> (16 + (s & 1))) & 1) * 4096;
    {
      const uint32_t ph = (s + 1) & 1;
      float x0[16], x1[16];
      uint32_t t_pub = 0;
      wg_fence();
      static_assert(Chunks<ISV>::MASK == 0x1E, "chunks 1 .. 4 are in shared memory");
      uint64_t db = P.dxn;
      auto rs_chunk = [&](int ci, bool pace) {
#pragma unroll
        for (int u = 0; u < 4; u++) {
          wgmma_rs_n32(x0, wr[ci][0][u], db, (ci | u) != 0);
          wgmma_rs_n32(x1, wr[ci][1][u], db, (ci | u) != 0);
          if (u < 3) DESC_ADD(db, 2); else DESC_ADD(db, 250);
          if (pace) { wg_commit(); wg_wait<2>(); wg_fence(); }
        }
      };
      rs_chunk(0, false);
      t_pub = clk32() - 60;
      PROF(0, 8); PROF(0, 1);
#pragma unroll
      for (int c = 1; c <= 4; c++) {
#pragma unroll
        for (int u = 0; u < 4; u++) {
          const uint64_t dx = make_desc(fk::XN + c * 4096 + u * 32, 16, 1024);
          wgmma_ss_n32_ta(x0, make_desc(fk::WS + (c - 1) * 16384 + u * 2048, 8192, 1024), dx, 1);
          wgmma_ss_n32_ta(x1, make_desc(fk::WS + (c - 1) * 16384 + 8192 + u * 2048, 8192, 1024), dx, 1);
          if (c == 4 && u == 1) { wg_commit(); wg_wait<1>(); named_bar_arrive(NB_XE, 160); wg_fence(); }
        }
        if (c == 3) wg_commit();
      }
      DESC_ADD(db, 1024);
#pragma unroll
      for (int c = 5; c < 10; c++) {
        if (c == 9) named_bar_arrive(NB_ST, 256);
        rs_chunk(c - 4, ((ISV ? PACEV : PACEQ) >> c) & 1);
      }
      wg_commit();
      wg_wait<0>();
      PROF(0, 10);
      const uint32_t tb = ISV ? (ph ? VX2 : VX) : QK;
      auto h2_issue = [&]() {
        spin_until(t_pub + (ISV ? D_H2V : D_H2));
        PROF(0, 13);
        if (elect_one()) { mbar_expect_tx(B_H2 + 8 * warp, 4096); bulk_g2s(MEMB + warp * 4096, src, 4096, B_H2 + 8 * warp); }
      };
      named_bar_sync(NB_CF, ISV ? 160 : 256);
      if ((ISV ? H2_ATV : H2_AT) == 0) h2_issue();
      const uint32_t none[2][4] = {}, tka = tok_addr<ISV>(tb, tid);
      tok_store<ISV, 0, false>(x0, tka, none);
      if ((ISV ? H2_ATV : H2_AT) == 1) h2_issue();
      tok_store<ISV, 1, false>(x1, tka, none);
      if ((ISV ? H2_ATV : H2_AT) == 2) h2_issue();
      named_bar_arrive(NB_DU, 256);
    }
    {
      OPQ;
      wsa = WS + ((mi >> 1) * 8 + mr) * 128 + (((2 * w + (mi & 1)) ^ mr) << 4);
      mba = MEMB + lane * 16;
      PIN(wsa); PIN(mba);
      {
        const uint32_t chk = MEMB + w * 4096 + lane * 32 + lg * 4, bar = B_H2 + 8 * warp;
        PROF(0, 11);
        proj_mem_prefetch<ISV, 0, 0, NPRE0>(ta, wsa);
#pragma unroll 1
        for (int tries = 0; tries < POLL_TRIES; tries++) {
          mbar_spin(bar, h2ph);
          h2ph ^= 1;
          const uint32_t mx = max(max(lds32(chk), lds32(chk + 1024)), max(lds32(chk + 2048), lds32(chk + 3072)));
          if (__all_sync(0xffffffffu, mx != EMPTY)) break;
          RETRY(1);
          if (elect_one()) { mbar_expect_tx(bar, 4096); bulk_g2s(MEMB + warp * 4096, src, 4096, bar); }
        }
      }
      if (s < 0) mbar_spin(B_WO, 0);
      PROF(0, 12);
      named_bar_arrive(NB_M1, 256);
      proj_mem_prefetch<ISV, 0, NPRE0, NTA0>(ta, wsa);
      named_bar_sync(NB_M0, 128);
    }
    s++;
    tid ^= 0x5500;
    {
      float a0[4], a1[4];
      proj_mem<ISV, 0>(wr, ta, wsa, mba, a0, a1);
      PROF(0, 2);
      uint32_t unused[4];
      proj_finish<ISV, 0>(a0, a1, peer0, peer1, self, tid, warp, unused);
      PROF(0, 3);
      if (s + 1 == cfg::NSEG) break;
      uint32_t wf[PF0][4], woa, wob;
      bool xn_ok;
      {
        OPQ;
        if (!ISV) {
          uint32_t qf[4][4], kf[2][4];
          const uint32_t qa = PT + 2048 + lane * 16, ka = QK + 4096 + w * 1024 + lane * 16;
          ldsm4t(qf[0], qa); ldsm4t(kf[0], ka); ldsm4t(qf[1], qa + 512);
          ldsm4t(qf[2], qa + 1024); ldsm4t(kf[1], ka + 512); ldsm4t(qf[3], qa + 1536);
          float c0[4], c1[4];
          mma16816z(c0, qf[0], kf[0][0], kf[0][1]);
          mma16816z(c1, qf[1], kf[0][2], kf[0][3]);
          mma16816(c0, qf[2], kf[1][0], kf[1][1]);
          mma16816(c1, qf[3], kf[1][2], kf[1][3]);
          const float s0 = (c0[0] + c0[2]) + (c1[0] + c1[2]), s1 = (c0[1] + c0[3]) + (c1[1] + c1[3]);
          send_scores(s0, s1, SP + rank * SP_SRC + t7 * SPW, peer0, peer1, B_SM, lane);
        }
        PROF(0, 4);
        woa = WO + 16384 + ((mi >> 1) * 8 + mr) * 128 + (((2 * w + (mi & 1)) ^ mr) << 4);
        wob = WO + 81920 + w * 4096 + ((mi >> 1) * 8 + mr) * 32 + (((mi & 1) ^ (mr >> 2)) << 4);
        uint32_t vf[2][2][4], vm[2][2];
        if (!ISV) mbar_spin(B_VX, s & 1);
        PROF(0, 14);
#pragma unroll
        for (int T = 0; T < 2; T++)
#pragma unroll
          for (int kk = 0; kk < 2; kk++) ldsm4(vf[T][kk], ((ISV && (s & 1)) ? VX2 : VX) + w * 2048 + (mi & 1) * 1024 + (mi >> 1) * 128 + mr * 16 + T * 512 + kk * 256);
        wo_prefetch<WMODE, 0, PF0A>(wf, woa, wob, three);
        uint32_t spa = SP + lane * SPW, vma = VM + t7 * 8, oa = OB + (mi >> 1) * 1024 + w * 256 + (mi & 1) * 128 + mr * 16;
        PIN(spa); PIN(vma); PIN(oa);
        mbar_spin(B_SM, s & 1);
        PROF(0, 5);
        float sc[10];
#pragma unroll
        for (int j = 0; j < 5; j++) {
          if (SPACK) {
            const uint32_t x = lds32(spa + j * 128), y = lds32(spa + SP_SRC + j * 128);
            sc[2 * j] = bf_lo(x) + bf_lo(y); sc[2 * j + 1] = bf_hi(x) + bf_hi(y);
          } else {
            const float2 x = lds64f(spa + j * 256), y = lds64f(spa + SP_SRC + j * 256);
            sc[2 * j] = x.x + y.x; sc[2 * j + 1] = x.y + y.y;
          }
        }
        const bool vm_ok = mbar_test(B_VM, s & 1);
        lds64(vm[0], vma); lds64(vm[1], vma + 1024);
        float m = fmaxf(fmaxf(fmaxf(sc[0], sc[1]), fmaxf(sc[2], sc[3])), fmaxf(fmaxf(sc[4], sc[5]), fmaxf(sc[6], sc[7])));
        m = fmaxf(m, fmaxf(sc[8], sc[9]));
        const float cs = 0.08838834764831845f * 1.4426950408889634f;
        uint32_t pb[5];
        m = fmaxf(m, __shfl_xor_sync(0xffffffffu, m, 1));
        m = fmaxf(m, __shfl_xor_sync(0xffffffffu, m, 2));
        if (ISV ? GATE_MX : GATE_Q) named_bar_arrive(NB_MX, 256);
        const float mc = -m * cs;
#pragma unroll
        for (int j = 0; j < 5; j++) pb[j] = pack_bf16(ex2_approx(fmaf(sc[2 * j], cs, mc)), ex2_approx(fmaf(sc[2 * j + 1], cs, mc)));
        PROF(0, 15);
        if (!vm_ok) { mbar_spin(B_VM, s & 1); lds64(vm[0], vma); lds64(vm[1], vma + 1024); }
        PROF(0, 6);
        float o0[4], o1[4], rs[4];
        const uint32_t ones[4] = {0x3F803F80u, 0x3F803F80u, 0x3F803F80u, 0x3F803F80u};
        mma16816z(rs, ones, pb[0], pb[1]);
        mma16816z(o0, vf[0][0], pb[0], pb[1]);
        mma16816z(o1, vf[1][0], pb[0], pb[1]);
        mma16816(rs, ones, pb[2], pb[3]);
        mma16816(o0, vf[0][1], pb[2], pb[3]);
        mma16816(o1, vf[1][1], pb[2], pb[3]);
        mma1688(rs, ones[0], ones[0], pb[4]);
        mma1688(o0, vm[0][0], vm[0][1], pb[4]);
        mma1688(o1, vm[1][0], vm[1][1], pb[4]);
        const float i0 = rcp_approx(rs[0]), i1 = rcp_approx(rs[1]);
        stsm4(oa, pack_bf16(o0[0] * i0, o0[1] * i1), pack_bf16(o0[2] * i0, o0[3] * i1),
              pack_bf16(o1[0] * i0, o1[1] * i1), pack_bf16(o1[2] * i0, o1[3] * i1));
      }
      {
        OPQ;
        named_bar_arrive(NB_O, 256);
        wo_prefetch<WMODE, PF0A, PF0>(wf, woa, wob, three);
        xn_ok = mbar_test(B_XN, (s + 1) & 1);
        char* h1p = P.xch + (tile0 + 4 + w) * 32768 + (h >> 3) * 8192 + (h & 7) * 128 + (((2 * lq + (lg & 1)) ^ (h & 7)) << 4) + (lg >> 1) * 4;
        uint32_t oba = OB + lane * 16;
        PIN(oba);
        PROF(0, 7);
        named_bar_sync(NB_O0, 128);
        const uint32_t tag = ((s >> 1) & 1) ^ 1;
        wo_phase<WMODE>(wf, woa, wob, three, oba, h1p, tid >> 8, tag);
        PROF(0, 9);
        if (!xn_ok) mbar_spin(B_XN, (s + 1) & 1);
        named_bar_sync(NB_HD, 256);
      }
    }
  }
}

template <bool ISV>
__device__ __forceinline__ void f_wg1(const FParams& P, const WRegs& wr, const int h, const int rank, const uint32_t hw, int tid) {
  using namespace fk;
  const uint32_t self = mapa(0, (hw >> (2 * rank)) & 3), peer0 = mapa(0, (hw >> (ISV ? 0 : 2 * (rank ^ 1))) & 3) - self,
                 peer1 = mapa(0, (hw >> (ISV ? 2 : 4)) & 3) - self;
  SMAP;
  const int tile0 = rank * 22;
  const uint32_t usel = __shfl_sync(0xffffffffu, tid, 0);
  const int warp = __shfl_sync(0xffffffffu, (threadIdx.x >> 5) & 3, 0);
  constexpr int WMODE = 1;
  uint32_t h1ph = 0;
  auto o_done = [&](int mb) {
    tma_store_wait_all();
    asm volatile("fence.proxy.async.global;" ::: "memory");
    asm volatile("red.relaxed.gpu.global.add.u32 [%0], 1;" ::"l"(&g_oflag[mb]) : "memory");
  };
  uint32_t vmo[4] = {0, 0, 0, 0};
  if (ISV) {
    OPQ;
    sts32(PT + (t7 >> 2) * 128 + ((5 ^ lg) << 4) + lq * 4, 0);
    sts32(PT + (t7 >> 2) * 128 + ((6 ^ lg) << 4) + lq * 4, 0);
  }
  tid ^= 0x5500;
#pragma unroll 1
  for (int s = -1;;) {
    uint32_t ta[ProjCfg<ISV, 1>::NTA][4][4], wsa, mba;
    if (s + 1 < cfg::NSEG) mbar_spin(B_XN, (s + 1) & 1);
    const uint32_t t_pub = clk32();
    auto refill = [&]() {
      if (warp == 3) {
        named_bar_sync(NB_XE, 160);
        if (elect_one()) {
          mbar_expect_tx(B_XN + 8, 16384);
          tma_load_3d(XN, &P.xn, 0, (s + 1) * 32, 12, B_XN + 8);
        }
      }
    };
    auto arm = [&]() {
      if ((tid & 255) == 160) {
        if (s == 1) st_pub32(&g_mask[3 * h + rank], 0);
        if (s + 2 < cfg::NSEG) { mbar_expect_tx(B_SM, ISV ? 2 * SP_SRC : SP_SRC); if (!ISV) mbar_expect_tx(B_VX, 8192); }
        if (!ISV && s + 1 < cfg::NSEG) mbar_expect_tx(B_VM, 2048);
        if (ISV && s >= 1 && s < cfg::NSEG) mbar_expect_tx(B_ST, 7168);
      }
      if (ISV && s < cfg::NSEG && (tid & 254) == 192) mbar_arrive_remote(((tid & 1) ? peer1 : peer0) + B_ST);
      __syncwarp();
    };
    if (ISV) {
      if (s >= 0) arm();
      if (s >= 1) {
        OPQ;
        if (warp == 0 && (s & 3) == 1 && s > 1) { if (elect_one()) o_done((s - 2) >> 2); }
        const uint32_t vb = (s & 1) ? VX : VX2;
        float x0[16], x1[16];
        wg_fence();
        wgmma_rs_n32(x0, vmo, make_desc(fk::PT + 64, 16, 1024), 0);
        wgmma_rs_n32(x1, vmo, make_desc(fk::PT + 96, 16, 1024), 0);
#pragma unroll
        for (int kk = 0; kk < 2; kk++) {
          wgmma_ss_n32(x0, make_desc0(vb + kk * 256, 128, 1024), make_desc(fk::PT + kk * 32, 16, 1024), 1);
          wgmma_ss_n32(x1, make_desc0(vb + 512 + kk * 256, 128, 1024), make_desc(fk::PT + kk * 32, 16, 1024), 1);
        }
        wg_commit();
        wg_wait<0>();
        named_bar_sync(NB_W1, 128);
        PROF(1, 4);
        const uint32_t stg = vb + (8 * (mi >> 1) + mr) * 128 + (((2 * w + (mi & 1)) ^ mr) << 4);
#pragma unroll
        for (int T = 0; T < 2; T++) {
          const float* x = T ? x1 : x0;
#pragma unroll
          for (int jj = 0; jj < 4; jj += 2)
            stsm4t(stg + T * 4096 + jj * 1024, pack_bf16(x[4 * jj], x[4 * jj + 1]), pack_bf16(x[4 * jj + 2], x[4 * jj + 3]),
                   pack_bf16(x[4 * jj + 4], x[4 * jj + 5]), pack_bf16(x[4 * jj + 6], x[4 * jj + 7]));
        }
        fence_proxy_async_smem();
        named_bar_sync(NB_W1, 128);
        PROF(1, 10);
        if (warp == 0) {
          if (elect_one()) {
            tma_store_3d(&P.o, vb, 0, (s - 1) * 32, 2 * h);
            tma_store_commit();
          }
          __syncwarp();
        }
        if (s == cfg::NSEG) break;
      }
      if (s + 1 < cfg::NSEG) refill();
      PROF(1, 11);
    } else if (s < 0) {
      named_bar_arrive(NB_CF, 256);
      refill();
    } else {
      float x[24];
      wg_fence();
#pragma unroll
      for (int k = 0; k < 4; k++) wgmma_ss_n48_tt(x, make_desc0(fk::QK + k * 256, 128, 1024), make_desc0(fk::QK + 4096 + k * 256, 128, 1024), k != 0);
      wg_commit();
      arm();
      auto send_tok = [&]() {
        if (warp < 2) {
          OPQ;
          const uint32_t d0 = peer1 + QK + rank * 3584 + lane * 8 + w * 1280, d1 = d0 + 512 + w * 512, bar = peer1 + B_ST;
          mbar_spin(B_ST, s & 1);
          const float NEG = -500000000.0f / 0.08838834764831845f;
          const bool m0 = 2 * lq > lg, m1 = 2 * lq + 1 > lg;
          st_async64f(d0, x[16] + x[20], x[17] + x[21], bar);
          st_async64f(d1, x[18] + x[22], x[19] + x[23], bar);
          st_async64f(d1 + 256, x[2], x[3], bar);
          if (warp == 0) {
            st_async64f(d0 + 256, m0 ? NEG : x[0], m1 ? NEG : x[1], bar);
            st_async64f(d1 + 512, m0 ? NEG : x[6], m1 ? NEG : x[7], bar);
          } else {
            st_async64f(d0 + 256, x[0], x[1], bar);
            st_async64f(d1 + 512, x[6], x[7], bar);
            st_async64f(d0 + 512, x[4], x[5], bar);
            st_async64f(d0 + 768, m0 ? NEG : x[8], m1 ? NEG : x[9], bar);
            st_async64f(d1 + 768, x[10], x[11], bar);
            st_async64f(d1 + 1024, m0 ? NEG : x[14], m1 ? NEG : x[15], bar);
          }
        }
        PROF(1, 4);
      };
      const bool fin = s + 1 == cfg::NSEG;
      OPQ;
      const int j = 2 * h + rank;
      const char* src = P.xch + j * 32768 + warp * 8192 + (((usel >> 14) & 2) + (s & 1)) * 2048;
      char* dst = P.xch + H1_BYTES + (j >> 4) * 8192 + (lq >> 1) * 4096 + (j & 15) * 256 + (lq & 1) * 128 + (2 * w + (lg & 1)) * 16 + (lg >> 1) * 4;
      const uint32_t chk = VX + mi * 2048 + mr * 128 + (w ^ (mr >> 1)) * 32 + ((lane & 1) + 2 * mi) * 4;
      const uint32_t tmask = (s >> 1) & 1;
      if (!fin) {
        spin_until(t_pub + D_H1);
        if (elect_one()) { mbar_expect_tx(B_H1, 2048); bulk_g2s(VX + warp * 2048, src, 2048, B_H1); }
      }
      __syncwarp();
      wg_wait<0>();
      PROF(1, 6);
      send_tok();
      if (fin) { mbar_spin(B_VM, s & 1); break; }
      named_bar_arrive(NB_CF, 256);
      if (REFILL_EARLY) refill();
#pragma unroll 1
      for (int tries = 0; tries < POLL_TRIES; tries++) {
        float d0[4], d1[4], d2[4], d3[4];
        mbar_spin(B_H1, h1ph);
        h1ph ^= 1;
        PROF(1, 10);
        const uint32_t t0 = lds32(chk), t1 = lds32(chk + 1024);
        wg_fence();
        const uint64_t ones = (uint64_t)(fk::ONES >> 4);
        wgmma_ss_n8_ta(d0, make_desc(fk::VX, 8192, 2048), ones, 0);
        wgmma_ss_n8_ta(d1, make_desc(fk::VX + 1024, 8192, 2048), ones, 0);
        wgmma_ss_n8_ta(d2, make_desc(fk::VX + 4096, 8192, 2048), ones, 0);
        wgmma_ss_n8_ta(d3, make_desc(fk::VX + 5120, 8192, 2048), ones, 0);
        wg_commit();
        uint32_t tt;
        asm volatile("lop3.b32 %0, %1, %2, %3, 0x42;" : "=r"(tt) : "r"(t0), "r"(t1), "r"(tmask) : "memory");
        uint32_t ok;
        named_bar_and(NB_W1, 128, tt & 1, ok);
        if (!ok) { if (elect_one()) { mbar_expect_tx(B_H1, 2048); bulk_g2s(VX + warp * 2048, src, 2048, B_H1); } }
        wg_wait<0>();
        if (ok) {
          st_pub32(dst + (s & 1) * 32768, (lq & 1) ? pack_bf16(d1[0] + d3[0], d1[2] + d3[2]) : pack_bf16(d0[0] + d2[0], d0[2] + d2[2]));
          PROF(1, 12);
          st_pub32(dst + ((s & 1) ^ 1) * 32768, EMPTY);
          break;
        }
        RETRY(0);
      }
      named_bar_sync(NB_W1, 128);
      if ((tid & 255) == 192) mbar_arrive_remote(peer1 + B_PF);
      __syncwarp();
      if (!REFILL_EARLY) refill();
      PROF(1, 11);
    }
    if (!ISV || s + 1 < cfg::NSEG) {
      const uint32_t ph = (s + 1) & 1;
      float x0[16], x1[16];
      uint64_t db = P.dxn + 10 * 256;
      named_bar_sync(NB_ST, 256);
      wg_fence();
#pragma unroll
      for (int c = 0; c < 6; c++) {
        if (c == 2) { mbar_spin(B_XN + 8, ph); wg_fence(); }
        if (ISV && c == CF_AT) {
          if (warp == 0) {
            if (elect_one()) tma_store_wait_read();
            __syncwarp();
            named_bar_arrive(NB_CF, 160);
          }
          wg_fence();
        }
#pragma unroll
        for (int u = 0; u < 4; u++) {
          wgmma_rs_n32(x0, wr[c][0][u], db, (c | u) != 0);
          wgmma_rs_n32(x1, wr[c][1][u], db, (c | u) != 0);
          if (u < 3) DESC_ADD(db, 2); else if (c == 1) DESC_ADD(db, 250 - 12 * 256); else DESC_ADD(db, 250);
        }
      }
      wg_commit();
      OPQ;
      const uint32_t tb = ISV ? (ph ? VX2 : VX) : QK, tka = tok_addr<ISV>(tb, tid);
      uint32_t p0[2][4], p1[2][4];
      named_bar_sync(NB_DU, 256);
      ldsm4(p1[0], tka + tok_off<ISV>(1, 0)); ldsm4(p1[1], tka + tok_off<ISV>(1, 1));
      ldsm4(p0[0], tka + tok_off<ISV>(0, 0)); ldsm4(p0[1], tka + tok_off<ISV>(0, 1));
      if (ISV && s >= 0) mbar_spin(B_PF, s & 1);
      wg_wait<0>();
      PROF(1, 13);
      tok_store<ISV, 1, true>(x1, tka, p1);
      tok_store<ISV, 0, true>(x0, tka, p0);
      if (ISV && s + 2 < cfg::NSEG) {
        fence_proxy_async_smem();
        __syncwarp();
        if (elect_one()) {
          bulk_s2s(peer0 + VX + warp * 2048, tb + warp * 2048, 2048, peer0 + B_VX);
          bulk_s2s(peer1 + VX + warp * 2048, tb + warp * 2048, 2048, peer1 + B_VX);
        }
      }
      wsa = WS + ((mi >> 1) * 8 + mr) * 128 + (((2 * w + (mi & 1)) ^ mr) << 4);
      mba = MEMB + lane * 16;
      PIN(wsa); PIN(mba);
      proj_mem_prefetch<ISV, 1, 0, NTA1>(ta, wsa);
      PROF(1, 14);
      named_bar_sync(NB_M1, 256);
      s++;
      PROF(1, 1);
      float a0[4], a1[4];
      proj_mem<ISV, 1>(wr, ta, wsa, mba, a0, a1);
      PROF(1, 2);
      proj_finish<ISV, 1>(a0, a1, peer0, peer1, self, tid, warp, vmo);
      PROF(1, 3);
    } else {
      OPQ;
      mbar_spin(B_VM, s & 1);
      lds64(vmo, VM + t7 * 8); lds64(vmo + 2, VM + 1024 + t7 * 8);
      s++;
    }
    tid ^= 0x5500;
    const bool last = s + 1 >= cfg::NSEG;
    constexpr int PFW = ISV ? PF1V : PF1;
    uint32_t wf[PFW][4], woa;
    if (ISV) {
      OPQ;
      woa = WO + ((mi >> 1) * 8 + mr) * 128 + (((2 * w + (mi & 1)) ^ mr) << 4);
      if (s >= 1) {
        const uint32_t sa = QK + ((w * (w + 3)) >> 1) * 256 + lane * 8;
        mbar_spin(B_ST, (s - 1) & 1);
        float sc[10];
        {
          const float NEG = -1000000000.0f / 0.08838834764831845f;
          float2 x[5], y[5];
#pragma unroll
          for (int b = 0; b < 5; b++) {
            x[b] = b < 2 ? lds64f(sa + b * 256) : lds64f_if(sa + b * 256, b <= w + 1, NEG);
            y[b] = b < 2 ? lds64f(sa + 3584 + b * 256) : lds64f_if(sa + 3584 + b * 256, b <= w + 1, 0.f);
          }
          wo_prefetch<WMODE, 0, PF1A>(wf, woa, 0, true);
#pragma unroll
          for (int b = 0; b < 5; b++) { sc[2 * b] = x[b].x + y[b].x; sc[2 * b + 1] = x[b].y + y[b].y; }
        }
        float m = fmaxf(fmaxf(fmaxf(sc[0], sc[1]), fmaxf(sc[2], sc[3])), fmaxf(fmaxf(sc[4], sc[5]), fmaxf(sc[6], sc[7])));
        m = fmaxf(m, fmaxf(sc[8], sc[9]));
        m = fmaxf(m, __shfl_xor_sync(0xffffffffu, m, 1));
        m = fmaxf(m, __shfl_xor_sync(0xffffffffu, m, 2));
        const float cs = 0.08838834764831845f * 1.4426950408889634f;
#pragma unroll
        for (int i = 0; i < 10; i++) sc[i] = ex2_approx((sc[i] - m) * cs);
        float sum = ((sc[0] + sc[1]) + (sc[2] + sc[3])) + ((sc[4] + sc[5]) + (sc[6] + sc[7])) + (sc[8] + sc[9]);
        sum += __shfl_xor_sync(0xffffffffu, sum, 1);
        sum += __shfl_xor_sync(0xffffffffu, sum, 2);
        const float inv = rcp_approx(sum);
        const uint32_t pa = PT + (w * 8 + mr) * 128, pm = pack_bf16(sc[0] * inv, sc[1] * inv);
        stsm4(pa + ((mi ^ mr) << 4), pack_bf16(sc[2] * inv, sc[3] * inv), pack_bf16(sc[4] * inv, sc[5] * inv),
              pack_bf16(sc[6] * inv, sc[7] * inv), pack_bf16(sc[8] * inv, sc[9] * inv));
        asm volatile("stmatrix.sync.aligned.m8n8.x2.shared.b16 [%0], {%1,%1};" ::"r"(pa + ((((mi & 1) ? 7 : 4) ^ mr) << 4)), "r"(pm) : "memory");
      } else {
        wo_prefetch<WMODE, 0, PF1A>(wf, woa, 0, true);
      }
      if (warp == 3 && !last) {
        mbar_spin(B_VM, s & 1);
        if (elect_one()) load_xn(P, s + 1, self);
      }
      PROF(1, 5);
    } else {
      if (warp == 0) {
        OPQ;
        uint32_t kf[4][4], qf[4][4];
        float c0[4], c1[4], d0[4], d1[4];
        const uint32_t ka = PT + (mi >> 1) * 1024 + (mi & 1) * 128 + mr * 16;
#pragma unroll
        for (int k = 0; k < 4; k++) { ldsm4t(qf[k], PT + 2048 + k * 512 + lane * 16); ldsm4t(kf[k], ka + k * 256); }
        mma16816z(c0, qf[0], kf[0][0], kf[0][1]); mma16816z(c1, qf[0], kf[0][2], kf[0][3]);
        mma16816z(d0, qf[1], kf[1][0], kf[1][1]); mma16816z(d1, qf[1], kf[1][2], kf[1][3]);
        mma16816(c0, qf[2], kf[2][0], kf[2][1]); mma16816(c1, qf[2], kf[2][2], kf[2][3]);
        mma16816(d0, qf[3], kf[3][0], kf[3][1]); mma16816(d1, qf[3], kf[3][2], kf[3][3]);
        const float s0 = ((c0[0] + c0[2]) + (c1[0] + c1[2])) + ((d0[0] + d0[2]) + (d1[0] + d1[2]));
        const float s1 = ((c0[1] + c0[3]) + (c1[1] + c1[3])) + ((d0[1] + d0[3]) + (d1[1] + d1[3]));
        if (!last) send_scores(s0, s1, SP + rank * SP_SRC + (128 + lane) * SPW, peer0, peer1, B_SM, lane);
        PROF(1, 5);
      } else {
        const uint32_t t_c = clk32() + lds32(B_XN) * 0;
        if (warp == 3 && !last) { if (elect_one()) load_xn(P, s + 1, self); }
        spin_until(t_c + D_ST);
      }
      OPQ;
      woa = WO + ((mi >> 1) * 8 + mr) * 128 + (((2 * w + (mi & 1)) ^ mr) << 4);
    }
    if (!last) {
      OPQ;
      uint32_t oba = OB + lane * 16;
      if (!ISV) wo_prefetch<WMODE, 0, PF1Q>(wf, woa, 0, true);
      if (ISV ? GATE_MX : GATE_Q) named_bar_sync(NB_MX, 256);
      wo_prefetch<WMODE, ISV ? PF1A : PF1Q, PFW>(wf, woa, 0, true);
      char* h1p = P.xch + (tile0 + w) * 32768 + (h >> 3) * 8192 + (h & 7) * 128 + (((2 * lq + (lg & 1)) ^ (h & 7)) << 4) + (lg >> 1) * 4;
      fence_proxy_async_smem();
      PROF(1, 7);
      named_bar_sync(NB_O, 256);
      PROF(1, 8);
      wo_phase<WMODE>(wf, woa, 0, true, oba, h1p, tid >> 8, ((s >> 1) & 1) ^ 1);
      PROF(1, 9);
      named_bar_sync(NB_HD, 256);
    } else {
      fence_proxy_async_smem();
      named_bar_sync(NB_W1, 128);
    }
  }
  if (ISV && warp == 0) { if (elect_one()) o_done(15); }
}

template <bool ISV, int WG>
__device__ __forceinline__ void f_main(const FParams& P, const int h, const int rank, const uint32_t hw) {
  using namespace fk;
  const uint32_t self = mapa(0, (hw >> (2 * rank)) & 3);
  SMAP;
  const int tid = __shfl_sync(0xffffffffu, threadIdx.x, threadIdx.x & 31);
  const int tile0 = rank * 22, ntile = ISV ? 20 : 22;
  const CUtensorMap* m0 = ISV ? &P.wv : &P.wq;
  const CUtensorMap* m1 = ISV ? &P.wv : &P.wk;
  const int col0 = h * 128 + (ISV ? 0 : 64 * rank), col1 = h * 128 + (ISV ? 64 : 64 * rank);
  WRegs wr;
  uint32_t sel = 0;
  {
    OPQ;
    const uint32_t a = SM0 + WG * 16384 + ((mi >> 1) * 8 + mr) * 128 + (((2 * w + (mi & 1)) ^ mr) << 4);
#pragma unroll
    for (int i = 0; i < 6; i++) {
      mbar_wait(B_PB + 8 * i, 0);
      PRO(8 + i);
#pragma unroll
      for (int T = 0; T < 2; T++)
#pragma unroll
        for (int u = 0; u < 4; u++) ldsm4t(wr[i][T][u], a + i * 32768 + T * 8192 + u * 2048);
      named_bar_sync(NB_C, 256);
      if (WG == 1 && w == (i & 3)) {
        if (elect_one()) {
          if (i <= 2 && i + PRE_G < 6) {
#pragma unroll 1
            for (int n = 2 * (i + PRE_G); n < (i == 2 ? 12 : 2 * (i + PRE_G) + 2); n++) {
              const int ii = n >> 1, row = Chunks<ISV>::rf(n & 1, ii) * 64;
              if (!(n & 1)) mbar_expect_tx(B_PB + 8 * ii, 32768);
              tma_load_2d(SM0 + n * 16384, m0, col0, row, B_PB + 8 * ii);
              tma_load_2d(SM0 + n * 16384 + 8192, m1, col1, row, B_PB + 8 * ii);
            }
          }
          if (i == 3 || i == 4) {
            const int p0 = i == 3 ? 0 : 5, p1 = i == 3 ? 5 : 8;
            mbar_expect_tx(B_W, (p1 - p0) * 8192);
#pragma unroll 1
            for (int p = p0; p < p1; p++) tma_load_2d(WS + p * 8192, (p & 1) ? m1 : m0, (p & 1) ? col1 : col0, Chunks<ISV>::sm(p >> 1) * 64, B_W);
          }
          if (i == WO_AT) {
            mbar_expect_tx(B_WO, ntile * 4096);
#pragma unroll 1
            for (int t = 0; t < 5; t++) tma_load_2d(WO + t * 16384, &P.wo, tile0 * 16 + t * 64, h * 128, B_WO);
            if (!ISV) {
              tma_load_2d(WO + 81920, &P.wo16, tile0 * 16 + 320, h * 128, B_WO);
              tma_load_2d(WO + 86016, &P.wo16, tile0 * 16 + 336, h * 128, B_WO);
            }
          }
        }
      }
    }
    PROF2(1);
    uint2 m0 = make_uint2(0, 0);
    if (!ISV && WG == 1) m0 = *reinterpret_cast<const uint2*>(P.mem0 + ((lane >> 1) & 7) * cfg::D + (2 * h + rank) * 16 + (lane >> 4) * 8 + (lane & 1) * 4);
    if (WG == 0 && w == 1) {
      uint4 v;
#pragma unroll 1
      for (int tries = 0; tries < POLL_TRIES; tries++) {
        asm volatile("ld.acquire.gpu.global.v4.u32 {%0,%1,%2,%3}, [%4];" : "=r"(v.x), "=r"(v.y), "=r"(v.z), "=r"(v.w)
                     : "l"(&g_mask[4 * min(lane, 23)]) : "memory");
        if (__all_sync(0xffffffffu, v.x & v.y & v.z & v.w & 0x100)) break;
        __nanosleep(100);
      }
      if (elect_one()) {
        asm volatile("fence.proxy.async.global;" ::: "memory");
        load_xn(P, 0, self);
        if (blockIdx.x == 2) { __threadfence(); st_pub128(g_lnok, 0x100); }
      }
      sts128(OB + lane * 16, v.x, v.y, v.z, v.w);
    }
    named_bar_sync(NB_C, 256);
    if (!ISV && WG == 1 && w < 2) st_pub64(P.xch + H1_BYTES + 32768 + (h >> 3) * 8192 + w * 4096 + ((2 * h + rank) & 15) * 256 + lane * 8, m0.x, m0.y);
#pragma unroll
    for (int i = 0; i < 3; i++) {
      const int t = min(tile0 + 8 * i + w + (WG ? 0 : 4), 63);
      sel |= ((lds32(OB + ((t >> 1) * 3 + (t & 1)) * 4) >> (h >> 3)) & 1) << (2 * i + 1);
    }
    const uint32_t own = lds32(OB + (3 * h + rank) * 4) >> w, m2 = lds32(OB + (3 * h + 2) * 4) >> w;
    sel |= (own & 1) << 7 | (m2 & 1) << 8 | (m2 & 16) << 5;
    sel |= (((((lg ^ h) & 1) << 2) | (lg >> 1)) == (h & 1) + 2 * (h >> 3)) << 10;
  }
  asm volatile("barrier.cluster.wait.aligned;" ::: "memory");
  PRO(14);
  mbar_wait(B_W, 0);
  mbar_wait(B_XN, 0);
  PRO(15);
  PROF2(4);
  GTSYNC(0);
  PROF2(2);
  KT_END(8);
  if (WG == 0) f_wg0<ISV>(P, wr, h, rank, hw, tid | sel << 8); else f_wg1<ISV>(P, wr, h, rank, hw, tid | sel << 8);
}

__device__ __forceinline__ void f_tail(const FParams& P, const int h, const uint32_t rank, const bool isv) {
  using namespace fk;
  const uint32_t self = mapa(0, rank), base = self + SM0;
  const uint32_t FULL = self + SP, EMPT = FULL + 32, RES = FULL + 64, NOG = FULL + 72;
  const int tid = threadIdx.x, lane = tid & 31, wv = __shfl_sync(0xffffffffu, tid >> 5, 0), wg = wv >> 2;
  const int kq = h & 3, nt = (h >> 2) & 3, mb = TAIL_MB0 + 3 * (h >> 4) + rank;
  auto a_off = [](uint32_t st) { return (0x98685800u >> (8 * st) & 255) * 1024; };
  auto b_off = [](uint32_t st) { return (0xA8783010u >> (8 * st) & 255) * 1024; };
  static_assert(VX2 - SM0 == 80 * 1024 && VX - SM0 == 200 * 1024, "stage layout");
  auto load_b = [&](int kb) {
    const uint32_t sb = base + b_off(kb & 3), full = FULL + 8 * (kb & 3);
    mbar_expect_tx(full, 49152);
    tma_load_2d_mc(sb + rank * 8192, &P.tb, nt * 256 + ((rank + kq) & 3) * 64, (kq * 16 + kb) * 64, full, 7);
    if (kb % 3 == rank) tma_load_2d_mc(sb + 3 * 8192, &P.tb, nt * 256 + ((3 + kq) & 3) * 64, (kq * 16 + kb) * 64, full, 7);
  };
  auto load_a = [&](int kb) { tma_load_2d(base + a_off(kb & 3), &P.ta, (kq * 16 + kb) * 64, mb * 128, FULL + 8 * (kb & 3)); };
  TL(0);
  TL2(128, 10); TL2(160, 11);
  if (wv == 0) {
    if (elect_one()) {
      prefetch_tmap(&P.tb); prefetch_tmap(&P.ta);
      if (isv) mbar_spin(self + B_VM, (cfg::NSEG - 1) & 1);
      for (int i = 0; i < 4; i++) { mbar_init(FULL + 8 * i, 1); mbar_init(EMPT + 8 * i, 24); }
      mbar_init(RES, 1);
      fence_barrier_init();
      mbar_arrive_cluster(self + B_W, rank == 0 ? 1 : 0);
      mbar_arrive_cluster(self + B_W, rank == 2 ? 1 : 2);
      mbar_spin(self + B_W, 1);
#pragma unroll 1
      for (int kb = 0; kb < 4; kb++) load_b(kb);
      TL2(0, 12);
      wait_count(&g_oflag[mb], 32);
      asm volatile("fence.proxy.async.global;" ::: "memory");
      TL2(0, 13);
#pragma unroll 1
      for (int kb = 0; kb < 4; kb++) load_a(kb);
      TL2(0, 14);
    }
  }
  if (wv == 1) {
    if (lane == 0) {
      prefetch_tmap(&P.tx); prefetch_tmap(&P.tg); prefetch_tmap(&P.tout);
      uint32_t gc;
      asm volatile("ld.acquire.gpu.global.u32 %0, [%1];" : "=r"(gc) : "l"(&g_cnt[3][mb]) : "memory");
      const bool ng = gc < GATE_CNT && ld_strong4(&g_next) == 0;
      sts32(NOG, ng ? 1 : gc < GATE_CNT ? 2 : 0);
      if (ng) g_tfix[blockIdx.x] = 1;
      asm volatile("cp.async.bulk.prefetch.tensor.2d.L2.global [%0, {%1, %2}];" ::"l"(&P.tx), "r"(nt * 256 + kq * 64), "r"(mb * 128) : "memory");
    }
  } else if (wv == 2 || wv == 3) {
#pragma unroll 2
    for (int i = tid - 64; i < 3072; i += 64) st_pub128(&g_tpart[blockIdx.x][0][0][0] + i, EMPTY);
  }
  float acc[128];
  __syncthreads();
  KT_START(7);
  const uint32_t gate = lds32(NOG);
  const bool nog = gate == 1;
  if (gate) TL(15); else TL(15);
#pragma unroll 1
  for (int kb = 0; kb < 16; kb++) {
    const uint32_t st = kb & 3, sa = base + a_off(st) + wg * 8192, sb = base + b_off(st);
    mbar_spin(FULL + 8 * st, (kb >> 2) & 1);
    if (kb == 0) TL(2);
    if (kb == 4) TL(3);
    if (kb == 10) TL(4);
    wg_fence();
#pragma unroll
    for (int k = 0; k < 4; k++) {
      wgmma_ss_n256_tb(acc, make_desc(sa + k * 32, 16, 1024), make_desc(sb + k * 2048, 8192, 1024), (kb | k) != 0);
      if (k == 0) {
        wg_commit();
        wg_wait<1>();
        if (kb > 0 && kb <= 13 && lane < 3) mbar_arrive_cluster(EMPT + 8 * ((kb - 1) & 3), lane);
        wg_fence();
      }
    }
    wg_commit();
    if (kb >= 2 && kb < 15 && wv == ((kb & 1) << 2)) {
      if (elect_one()) {
        mbar_spin(EMPT + 8 * ((kb - 2) & 3), ((kb - 2) >> 2) & 1);
        if (kb < 14) {
          load_b(kb + 2);
          load_a(kb + 2);
        } else if (nog) {
          mbar_arrive(RES);
        } else {
          if (gate) wait_count(&g_cnt[3][mb], GATE_CNT);
          asm volatile("fence.proxy.async.global;" ::: "memory");
          mbar_expect_tx(RES, 32768);
          tma_load_2d(base, &P.tx, nt * 256 + kq * 64, mb * 128, RES);
          tma_load_2d(base + 16384, &P.tg, nt * 256 + kq * 64, mb * 128, RES);
        }
      }
      __syncwarp();
    }
  }
  wg_wait<0>();
  TL(5);
#pragma unroll
  for (int j = 1; j < 4; j++) {
    uint4* dst = &g_tpart[((h & ~3) + ((j + kq) & 3)) * 3 + rank][j - 1][0][tid];
#pragma unroll
    for (int i = 0; i < 4; i++) {
      const float* a = &acc[32 * j + 8 * i];
      asm volatile("st.relaxed.gpu.global.v4.u32 [%0], {%1,%2,%3,%4};" ::"l"(dst + i * 256), "r"(pack_bf16(a[0], a[1])),
                   "r"(pack_bf16(a[2], a[3])), "r"(pack_bf16(a[4], a[5])), "r"(pack_bf16(a[6], a[7])) : "memory");
    }
  }
  TL(6);
#pragma unroll 1
  for (int j = 0, tries = 0; j < 3 && tries < POLL_TRIES; tries++) {
    uint4 pt[4];
#pragma unroll
    for (int i = 0; i < 4; i++) pt[i] = ld_strong16(&g_tpart[blockIdx.x][j][i][tid]);
    if (!__all_sync(0xffffffffu, max(max(umax4(pt[0]), umax4(pt[1])), max(umax4(pt[2]), umax4(pt[3]))) != EMPTY)) continue;
#pragma unroll
    for (int i = 0; i < 16; i++) { acc[2 * i] += bf_lo((&pt[0].x)[i]); acc[2 * i + 1] += bf_hi((&pt[0].x)[i]); }
    j++;
  }
  mbar_spin(RES, 0);
  TL(7);
  const uint32_t xa = base + (wv * 16 + ((lane >> 3) & 1) * 8 + (lane & 7)) * 128 + (((lane >> 4) ^ (lane & 7)) << 4);
#pragma unroll
  for (int i = 0; i < 4; i++) {
    uint32_t x[4], g[4], o[4];
    ldsm4(x, xa ^ (i << 5));
    ldsm4(g, (xa ^ (i << 5)) + 16384);
#pragma unroll
    for (int k = 0; k < 4; k++) {
      const uint32_t sv = pack_bf16(acc[8 * i + 2 * k], acc[8 * i + 2 * k + 1]);
      o[k] = nog ? sv : add_bf16x2(x[k], mul_bf16x2(sv, g[k]));
    }
    stsm4(xa ^ (i << 5), o[0], o[1], o[2], o[3]);
  }
  TL(8);
  fence_proxy_async_smem();
  __syncwarp();
  if (elect_one()) {
    tma_store_2d(&P.tout, base + wv * 2048, nt * 256 + kq * 64, mb * 128 + wv * 16);
    tma_store_commit();
    tma_store_wait_read();
  }
  TL(9);
  KT_END(7);
}

__global__ void __launch_bounds__(256, 1) f_kernel(const __grid_constant__ FParams P) {
  using namespace fk;
  extern __shared__ __align__(1024) uint8_t smem_f[];
  uint32_t crank, rank, hw;
  asm("mov.u32 %0, %%cluster_ctarank;" : "=r"(crank));
  const int h = blockIdx.x / 3;
  if (smem_u32(smem_f) != mapa(0, crank) + SM0) return;
  PROF2(0);
  KT_START(1);
  KT_START(0);
  {
    const uint32_t self = mapa(0, crank);
    SMAP;
    const int tid = threadIdx.x, lane = tid & 31, wv = __shfl_sync(0xffffffffu, tid >> 5, 0);
    PRO(0);
    if (wv == 0) {
      uint32_t sm;
      asm("mov.u32 %0, %%smid;" : "=r"(sm));
      sts32(PROBE + 96, sm >> 1);
      asm volatile("fence.release.sync_restrict::shared::cta.cluster;" ::: "memory");
    }
    asm volatile("barrier.cluster.arrive.relaxed.aligned;" ::: "memory");
    if (wv == 7) {
      if (blockIdx.x == 2) {
#pragma unroll
        for (int i = 0; i < 3; i++) { (&g_cnt[0][0])[32 * i + lane] = 0; g_tfix[32 * i + lane] = 0; }
        if (lane < 16) g_oflag[lane] = 0;
        if (lane == 0) { g_next = 0; g_lnok[0] = 0; }
        __threadfence();
        __syncwarp();
      }
      pdl_launch_dependents();
    }
    const int row0 = blockIdx.x * 8 + wv;
    const bool third = row0 + 1536 < cfg::S;
    uint32_t cur[1][16], raw[2][16];
    load_row16(cur[0], P.x + (size_t)row0 * cfg::D, lane);
    load_row16(raw[0], P.x + (size_t)(row0 + 768) * cfg::D, lane);
    load_row16(raw[1], P.x + (size_t)(row0 + (third ? 1536 : 0)) * cfg::D, lane);
    {
      uint32_t tpc;
      asm volatile("barrier.cluster.wait.aligned;" ::: "memory");
      asm volatile("ld.shared::cluster.u32 %0, [%1];" : "=r"(tpc) : "r"(mapa(PROBE + 96, lane % 3)) : "memory");
      const uint32_t t0 = __shfl_sync(0xffffffffu, tpc, 0), t1 = __shfl_sync(0xffffffffu, tpc, 1), t2 = __shfl_sync(0xffffffffu, tpc, 2);
      hw = t1 == t2 ? 0x09 : t0 == t2 ? 0x18 : 0x24;
      rank = (hw & 3) == crank ? 0 : ((hw >> 2) & 3) == crank ? 1 : 2;
    }
    const bool isv = rank == 2;
    const CUtensorMap* m0 = isv ? &P.wv : &P.wq;
    const CUtensorMap* m1 = isv ? &P.wv : &P.wk;
    const int col0 = h * 128 + (isv ? 0 : 64 * rank), col1 = h * 128 + (isv ? 64 : 64 * rank);
    if (wv == 0) {
      if (elect_one()) {
        for (int i = 0; i < 2; i++) mbar_init(B_XN + 8 * i, 1);
        mbar_init(B_H1, 4);
        mbar_init(B_SM, isv ? 1 : 6);
        mbar_init(B_VM, isv ? 8 : 1);
        mbar_init(B_VX, 1);
        mbar_init(B_ST, 1);
        mbar_init(B_PF, 2);
        for (int i = 0; i < 6; i++) mbar_init(B_PB + 8 * i, 1);
        mbar_init(B_W, 2);
        mbar_init(B_WO, 1);
        fence_barrier_init();
        mbar_expect_tx(B_SM, isv ? 2 * SP_SRC : SP_SRC);
        if (isv) mbar_expect_tx(B_ST, 7168);
        else { mbar_expect_tx(B_VM, 2048); mbar_expect_tx(B_VX, 8192); }
      }
    }
    const int j = 2 * h + rank;
    if (lane == 0) {
      const uint2 b = probe_pair(P.xch + (isv ? H1_BYTES + wv * 8192 + h * 128 : j * 32768 + (wv & 3) * 8192 + (wv >> 2) * 128),
                                 isv ? EMPTY : 0, PROBE + 64, P.nprobe);
      sts64(PROBE + wv * 8, b.x, b.y);
    }
    PROF2(3);
    PRO(1);
    __syncwarp();
    if (wv == 1) {
      const uint32_t off = (blockIdx.x * 32 + lane) * 688;
      if (off < cfg::D * cfg::D * 2) l2_prefetch(reinterpret_cast<const char*>(P.w1) + off, min(688u, cfg::D * cfg::D * 2 - off));
    }
    if (wv == 0) {
      asm volatile("{\n.reg .pred p;\nsetp.eq.u32 p, %0, %1;\n@p st.shared.u32 [%2], %0;\n}" ::"r"(raw[1][15]), "r"(cur[0][0] ^ raw[0][15]), "r"(PROBE + 64) : "memory");
      if (elect_one()) {
#pragma unroll 1
        for (int n = 0; n < 2 * PRE_G; n++) {
          const int i = n >> 1, g = n & 1, row = (isv ? Chunks<true>::rf(g, i) : Chunks<false>::rf(g, i)) * 64;
          if (!g) mbar_expect_tx(B_PB + 8 * i, 32768);
          tma_load_2d(SM0 + n * 16384, m0, col0, row, B_PB + 8 * i);
          tma_load_2d(SM0 + n * 16384 + 8192, m1, col1, row, B_PB + 8 * i);
        }
      }
    }
    __syncthreads();
    PRO(2);
    asm volatile("barrier.cluster.arrive.relaxed.aligned;" ::: "memory");
    PRO(3);
    if (wv == 2) { sts32(self + ONES + lane * 4, 0x3F803F80u); fence_proxy_async_smem(); }
    uint32_t pb[2], pc[2];
    lds64(pb, PROBE + (lane & 7) * 8);
    lds64(pc, PROBE + ((lane & 7) ^ 4) * 8);
    const uint32_t mask = __ballot_sync(0xffffffffu, isv ? pb[1] < pb[0] : min(pb[1], pc[1]) < min(pb[0], pc[0])) & (isv ? 255 : 15);
    if (!isv) {
#pragma unroll
      for (int i = 0; i < 4; i++) st_pub128(P.xch + j * 32768 + i * 8192 + ((mask >> i) & 1) * 4096 + tid * 16, 0);
      if (wv < 4) st_pub64(P.xch + H1_BYTES + (wv >> 1) * 32768 + (j >> 4) * 8192 + (wv & 1) * 4096 + (j & 15) * 256 + lane * 8, EMPTY, EMPTY);
    }
#pragma unroll 1
    for (int it = 0; it < (third ? 6 : 4); it++) {
      ln_regs<1>(cur);
      store_row16(cur[0], ((it & 1) ? P.xn2 : P.xn_ptr) + (size_t)(row0 + (it >> 1) * 768) * cfg::D, lane);
      if (it == 0) PRO(4);
      if (it & 1) {
#pragma unroll
        for (int i = 0; i < 16; i++) { cur[0][i] = raw[0][i]; raw[0][i] = raw[1][i]; }
      }
    }
    PRO(5);
    __syncthreads();
    PRO(6);
    if (tid == 64) {
      __threadfence();
      PRO(7);
      st_pub32(&g_mask[3 * h + rank], 0x100 | mask);
    }
    KT_END(0);
    __syncwarp();
  }
  const int wg = __shfl_sync(0xffffffffu, threadIdx.x >> 7, 0);
  if (rank == 2) { if (wg == 0) f_main<true, 0>(P, h, 2, hw); else f_main<true, 1>(P, h, 2, hw); }
  else { if (wg == 0) f_main<false, 0>(P, h, rank, hw); else f_main<false, 1>(P, h, rank, hw); }
  PROF2(5);
  KT_END(1);
  __syncwarp();
  f_tail(P, h, crank, rank == 2);
}

#define GCL 1
#define G_PF 3
#define G_PFM 2
#define G_LATE 0
namespace gk {
enum { T_B1 = 0, T_B2 = 1, T_B3 = 2, T_B4 = 3, T_O = 4, T_LN = 5, T_END = 7 };
constexpr int NST = 3, STAGE = 49152, MAXITEMS = 512, NEW = 3;
constexpr uint32_t OUTB = NST * STAGE, BARS = OUTB + 65536;
constexpr uint32_t B_FULL = BARS, B_EMPTY = BARS + 32, B_ITEM = BARS + 64, B_FILL = BARS + 128, B_FREE = BARS + 160, B_LN = BARS + 176, ITEMS = BARS + 192;
constexpr int SMEM = BARS + 256;
static_assert(GATE_CNT == 4 * NEW && T_B4 == 3, "gate counter");
}
struct GParams {
  CUtensorMap a[5], b[5];
  bf16* c[5];
  const bf16* r[5];
  bf16* x1n;
  int nitems, lnpos;
  uint16_t items[gk::MAXITEMS];
};
#define ILOG(i)

__device__ __forceinline__ void tma_load_3d_mc(uint32_t dst, const CUtensorMap* map, int x, int y, int z, uint32_t bar) {
  asm volatile("cp.async.bulk.tensor.3d.shared::cluster.global.mbarrier::complete_tx::bytes.multicast::cluster "
               "[%0], [%1, {%3, %4, %5}], [%2], %6;"
               ::"r"(dst), "l"(map), "r"(bar), "r"(x), "r"(y), "r"(z), "h"((uint16_t)3) : "memory");
}
__device__ __forceinline__ float tanh_approx(float x) { float y; asm("tanh.approx.f32 %0, %1;" : "=f"(y) : "f"(x)); return y; }
__global__ void __launch_bounds__(384, 1) g_kernel(const __grid_constant__ GParams P) {
  using namespace gk;
  extern __shared__ __align__(1024) uint8_t smem_g[];
  const uint32_t base = smem_u32(smem_g);
  const int tid = threadIdx.x, warp = __shfl_sync(0xffffffffu, tid >> 5, 0), lane = tid & 31;
  const int rank = blockIdx.x % GCL;
  KT_START(2);
  if (tid == 0) {
    for (int s = 0; s < NST; s++) { mbar_init(base + B_FULL + 8 * s, 1); mbar_init(base + B_EMPTY + 8 * s, 8 * GCL); }
    for (int s = 0; s < 8; s++) mbar_init(base + B_ITEM + 8 * s, 1);
    for (int s = 0; s < 2; s++) { mbar_init(base + B_FILL + 8 * s, 4); mbar_init(base + B_FREE + 8 * s, NEW); }
    mbar_init(base + B_LN, 1);
    fence_barrier_init();
  }
  __syncthreads();
  if (GCL > 1) cluster_sync();
  auto release = [&](uint32_t st) {
    if (GCL > 1) { if (lane < GCL) mbar_arrive_cluster(base + B_EMPTY + 8 * st, lane); }
    else if (lane == 0) mbar_arrive(base + B_EMPTY + 8 * st);
  };
  auto get_item = [&](int q) {
    mbar_wait(base + B_ITEM + 8 * (q & 7), (q >> 3) & 1);
    return lds32(base + ITEMS + 4 * (q & 7));
  };

  if (warp == 8) {
    if (lane < 10) prefetch_tmap(&P.a[0] + lane);
    if (lane == 0) {
      uint32_t st = 0, ph = 1;
#pragma unroll 1
      for (int q = 0;; q++) {
        if (GCL > 1) mbar_expect_tx(base + B_ITEM + 8 * (q & 7), 4);
        if (rank == 0) {
          const unsigned idx = atomicAdd(&g_next, 1), ln = idx - P.lnpos;
          const uint32_t v = (idx < (unsigned)P.nitems ? P.items[idx] : T_END) | (ln < 64 / GCL ? (ln + 1) << 16 : 0);
          if (GCL > 1) {
#pragma unroll
            for (int r = 0; r < GCL; r++) st_async32(mapa(base + ITEMS + 4 * (q & 7), r), v, mapa(base + B_ITEM + 8 * (q & 7), r));
          } else {
            sts32(base + ITEMS + 4 * (q & 7), v);
            mbar_arrive(base + B_ITEM + 8 * (q & 7));
          }
        }
        const uint32_t item = get_item(q);
        const int type = item & 7, mb = ((item >> 3) & 15) + rank, nt = (item >> 7) & 15;
        ILOG(1);
        if (q == 0) { __threadfence(); sts32(base + ITEMS + 32, ld_strong4(&g_oflag[14]) >= 32); }
        if (type == T_END) break;
        if (type == T_B2) {
          wait_count(&g_cnt[T_B1][max(mb - 1, 0)], 4 * NEW); wait_count(&g_cnt[T_B1][mb], 4 * NEW); wait_count(&g_cnt[T_B1][min(mb + 1, 15)], 4 * NEW);
        } else if (type == T_B3) wait_count(&g_cnt[T_LN][mb], 32);
        else if (type == T_B4) wait_count(&g_cnt[T_B3][mb], 14 * NEW);
        else if (type == T_O) wait_count(&g_oflag[mb], 32);
        asm volatile("fence.proxy.async.global;" ::: "memory");
        ILOG(2);
        const CUtensorMap *ma = &P.a[type], *mbm = &P.b[type];
        const int nkb = type == T_B4 ? cfg::F / 64 : type == T_O ? cfg::HD / 64 : cfg::D / 64;
#pragma unroll 1
        for (int kb = 0; kb < nkb; kb++) {
          mbar_wait(base + B_EMPTY + 8 * st, ph);
          const uint32_t sa = base + st * STAGE, full = base + B_FULL + 8 * st;
          mbar_expect_tx(full, STAGE);
          int arow = mb * 128;
          if (type == T_B2) { const int qd = kb >> 2; arow += (qd == 0) ? -1 : (qd == 1) ? 1 : (qd == 2) ? -2 : 2; }
          if (GCL > 1) tma_load_3d_mc(sa + 16384 + rank * 16384, mbm, 0, kb * 64, nt * 4 + rank * 2, full);
          else tma_load_3d(sa + 16384, mbm, 0, kb * 64, nt * 4, full);
          if (q == 0 && kb == 0) { mbar_wait(base + B_LN, 0); asm volatile("fence.proxy.async.global;" ::: "memory"); }
          tma_load_2d(sa, ma, kb * 64, arow, full);
          if (G_PF && type >= T_B4 && kb + G_PF < nkb) {
            if (G_PFM & 1) asm volatile("cp.async.bulk.prefetch.tensor.3d.L2.global [%0, {0, %1, %2}];" ::"l"(mbm), "r"((kb + G_PF) * 64), "r"(nt * 4 + rank * 2) : "memory");
            if (G_PFM & 2) asm volatile("cp.async.bulk.prefetch.tensor.2d.L2.global [%0, {%1, %2}];" ::"l"(ma), "r"((kb + G_PF) * 64), "r"(mb * 128) : "memory");
          }
          if (++st == NST) { st = 0; ph ^= 1; }
        }
      }
    }
  } else {
    const int wg = warp >> 2, ew = warp > 8 ? warp - 9 : warp + NEW;
    const uint32_t outa = base + OUTB + (warp * 16 + ((lane >> 3) & 1) * 8 + (lane & 7)) * 512 + (((lane >> 4) ^ (lane & 7)) << 4);
    uint32_t st = 0, ph = 0;
    float acc[128];
    auto kill_acc = [&]() {
#pragma unroll
      for (int i = 0; i < 128; i++) acc[i] = 0.f;
    };
    if (warp == 9) {
#pragma unroll 1
      for (int tries = 0; tries < POLL_TRIES; tries++) {
        uint4 v;
        asm volatile("ld.acquire.gpu.global.v4.u32 {%0,%1,%2,%3}, [%4];" : "=r"(v.x), "=r"(v.y), "=r"(v.z), "=r"(v.w)
                     : "l"(lane < 24 ? &g_mask[4 * lane] : &g_lnok[0]) : "memory");
        const uint32_t ok = __ballot_sync(0xffffffffu, v.x & v.y & v.z & v.w & 0x100);
        if ((ok & 0xFFFFFF) == 0xFFFFFF || (ok >> 24)) break;
        __nanosleep(200);
      }
      if (lane == 0) mbar_arrive(base + B_LN);
    }
    uint32_t next = get_item(0);
#pragma unroll 1
    for (int q = 0;; q++) {
      const uint32_t item = next;
      const int type = item & 7, mb = ((item >> 3) & 15) + rank, nt = (item >> 7) & 15;
      if (type == T_END) break;
      if (warp < 8) {
      if (item >> 16) {
        const int ln = (item >> 16) - 1, lb = (ln >> 2) * GCL + rank;
        const size_t row = (size_t)(lb * 128 + (ln & 3) * 32 + warp * 4) * cfg::D;
        wait_count(&g_cnt[T_B2][lb], 4 * NEW);
        uint32_t cur[2][16], nxt[2][16];
#pragma unroll
        for (int r = 0; r < 2; r++) {
          load_row16(cur[r], P.c[T_B2] + row + r * cfg::D, lane);
          load_row16(nxt[r], P.c[T_B2] + row + (r + 2) * cfg::D, lane);
        }
#pragma unroll 1
        for (int r2 = 0; r2 < 4; r2 += 2) {
          ln_regs<2>(cur);
#pragma unroll
          for (int r = 0; r < 2; r++) {
            store_row16(cur[r], P.x1n + row + (r2 + r) * cfg::D, lane);
#pragma unroll
            for (int i = 0; i < 16; i++) cur[r][i] = nxt[r][i];
          }
        }
        __syncwarp();
        if (lane == 0) asm volatile("red.release.gpu.global.add.u32 [%0], 1;" ::"l"(&g_cnt[T_LN][lb]) : "memory");
        __syncwarp();
        if (tid == 0) ILOG(6);
        kill_acc();
      }
      const int nkb = type == T_B4 ? cfg::F / 64 : type == T_O ? cfg::HD / 64 : cfg::D / 64;
      uint32_t prev = 0;
      mbar_wait(base + B_FULL + 8 * st, ph);
#pragma unroll 1
      for (int kb = 0; kb < nkb; kb++) {
        mbar_spin(base + B_FULL + 8 * st, ph);
        if (kb == 0 && tid == 0) ILOG(3);
        const uint64_t da = make_desc(base + wg * 8192, 16, 1024) + st * (STAGE >> 4), db = make_desc(base + 16384, 8192, 1024) + st * (STAGE >> 4);
        wg_fence();
#pragma unroll
        for (int k = 0; k < 4; k++) {
          wgmma_ss_n256_tb(acc, da + k * 2, db + k * 128, (kb | k) != 0);
          if (k == 0) {
            wg_commit();
            wg_wait<1>();
            if (kb > 0) release(prev);
            wg_fence();
          }
        }
        wg_commit();
        prev = st;
        if (++st == NST) { st = 0; ph ^= 1; }
      }
      next = get_item(q + 1);
      if (q > 0) mbar_wait(base + B_FREE + 8 * wg, (q - 1) & 1);
      wg_wait<0>();
      if (tid == 0) ILOG(4);
      release(prev);
#pragma unroll
      for (int j = 0; j < 16; j++)
        stsm4((outa ^ ((j & 3) << 5)) + (j >> 2) * 128, pack_bf16(acc[8 * j], acc[8 * j + 1]), pack_bf16(acc[8 * j + 2], acc[8 * j + 3]),
              pack_bf16(acc[8 * j + 4], acc[8 * j + 5]), pack_bf16(acc[8 * j + 6], acc[8 * j + 7]));
      __syncwarp();
      if (lane == 0) mbar_arrive(base + B_FILL + 8 * wg);
      if (tid == 0) ILOG(5);
      if ((next & 7) != T_END) continue;
      }
      if (type == T_O) wait_count(&g_cnt[T_B4][mb], 4 * NEW);
      const int ldc = type == T_B3 ? cfg::F : cfg::D;
      bf16* cp = P.c[type] + (size_t)mb * 128 * ldc + nt * 256 + lane * 8;
      const size_t roff = (size_t)mb * 128 * cfg::D + nt * 256 + lane * 8;
      const bf16 *rp = P.r[type] + roff, *gp = P.c[T_B4] + roff;
      const bool gelu = type == T_B1 || type == T_B3;
      uint32_t yn[4][4];
      uint4 rn[4], gn[4];
#pragma unroll
      for (int i = 0; i < 4; i++) rn[i] = gn[i] = make_uint4(0, 0, 0, 0);
      auto fetch_res = [&](int grp) {
#pragma unroll
        for (int i = 0; i < 4; i++) {
          rn[i] = __ldcg(reinterpret_cast<const uint4*>(rp + (grp * 4 + i) * cfg::D));
          if (type == T_O) gn[i] = __ldcg(reinterpret_cast<const uint4*>(gp + (grp * 4 + i) * cfg::D));
        }
      };
      auto fetch_y = [&](int grp) {
        const uint32_t a = base + OUTB + grp * 2048 + ((lane ^ ((grp & 1) << 2)) << 4);
#pragma unroll
        for (int i = 0; i < 4; i++) lds128(yn[i], (a ^ (i << 4)) + i * 512);
      };
      auto store_y = [&](int grp, const uint32_t (&y)[4][4]) {
        char* p = reinterpret_cast<char*>(cp) + (uint32_t)(grp * 8 * ldc);
#pragma unroll
        for (int i = 0; i < 4; i++) *reinterpret_cast<uint4*>(p + (uint32_t)(i * 2 * ldc)) = make_uint4(y[i][0], y[i][1], y[i][2], y[i][3]);
      };
      if (type == T_B4) wait_count(&g_cnt[T_B2][mb], 4 * NEW);
      if (type >= T_B4 && warp > 8) for (int r = tid - 288; r < 128; r += 96) l2_prefetch(rp - lane * 8 + r * cfg::D, 512);
      if (!gelu) fetch_res(ew);
      mbar_wait(base + B_FILL, q & 1);
      fetch_y(ew);
      next = get_item(q + 1);
      mbar_wait(base + B_FILL + 8, q & 1);
      const int stride = (next & 7) == T_END ? NEW + 8 : NEW;
      if (gelu) {
#pragma unroll 1
        for (int grp = ew; grp < 32; grp += stride) {
          uint32_t y[4][4];
#pragma unroll
          for (int i = 0; i < 16; i++) y[i >> 2][i & 3] = mul_bf16x2(yn[i >> 2][i & 3], 0x3F003F00u);
          const int nx = grp + stride;
          if (nx >= 16 && grp < 16 && lane == 0 && warp > 8) mbar_arrive(base + B_FREE);
          if (!G_LATE) fetch_y(min(nx, 31));
#pragma unroll
          for (int i = 0; i < 16; i++) {
            uint32_t& v = y[i >> 2][i & 3];
            const float h0 = bf_lo(v), h1 = bf_hi(v);
            const float t0 = tanh_approx(h0 * fmaf(h0 * h0, 0.285419265090401f, 1.5957691216057308f));
            const float t1 = tanh_approx(h1 * fmaf(h1 * h1, 0.285419265090401f, 1.5957691216057308f));
            v = pack_bf16(fmaf(h0, t0, h0), fmaf(h1, t1, h1));
          }
          if (G_LATE) fetch_y(min(nx, 31));
          store_y(grp, y);
        }
      } else {
#pragma unroll 1
        for (int grp = ew; grp < 32; grp += stride) {
          uint32_t y[4][4];
          if (type == T_O) {
#pragma unroll
            for (int i = 0; i < 16; i++) yn[i >> 2][i & 3] = mul_bf16x2(yn[i >> 2][i & 3], (&gn[i >> 2].x)[i & 3]);
          }
#pragma unroll
          for (int i = 0; i < 16; i++) y[i >> 2][i & 3] = add_bf16x2(yn[i >> 2][i & 3], (&rn[i >> 2].x)[i & 3]);
          const int nx = grp + stride;
          if (nx >= 16 && grp < 16 && lane == 0 && warp > 8) mbar_arrive(base + B_FREE);
          fetch_res(min(nx, 31));
          fetch_y(min(nx, 31));
          if (type == T_B4) {
#pragma unroll
            for (int i = 0; i < 16; i++) {
              uint32_t& v = y[i >> 2][i & 3];
              const float h0 = 0.5f * bf_lo(v), h1 = 0.5f * bf_hi(v);
              v = pack_bf16(fmaf(h0, tanh_approx(h0), h0), fmaf(h1, tanh_approx(h1), h1));
            }
          }
          store_y(grp, y);
        }
      }
      __syncwarp();
      if (lane == 0 && warp > 8) mbar_arrive(base + B_FREE + 8);
      if (stride != NEW) named_bar_sync(2, 352);
      if (type != T_O && lane == 0 && warp > 8) asm volatile("red.release.gpu.global.add.u32 [%0], 1;" ::"l"(&g_cnt[type][mb]) : "memory");
      __syncwarp();
      if (tid == 288) ILOG(7);
      kill_acc();
    }
    KT_END(2);
  }
  __syncwarp();
  if (warp >= 8) {
   named_bar_sync(1, 128);
   const bool late = lds32(base + ITEMS + 32);
   if (late) pdl_wait();
#pragma unroll 1
   for (int c = blockIdx.x; late && c < 96; c += gridDim.x) {
     if (__ldcg(&g_tfix[c]) == 0) continue;
     const int hh = c / 3, mb = TAIL_MB0 + 3 * (hh >> 4) + c % 3;
     wait_count(&g_cnt[T_B4][mb], GATE_CNT);
#pragma unroll 1
     for (int i = tid - 256; i < 1024; i += 128) {
       const size_t off = (size_t)(mb * 128 + (i >> 3)) * cfg::D + (hh & 15) * 64 + (i & 7) * 8;
       const uint4 sv = __ldcg(reinterpret_cast<const uint4*>(P.c[T_O] + off)), gv = __ldcg(reinterpret_cast<const uint4*>(P.c[T_B4] + off)),
                   xv = __ldcg(reinterpret_cast<const uint4*>(P.r[T_O] + off));
       *reinterpret_cast<uint4*>(P.c[T_O] + off) = make_uint4(add_bf16x2(xv.x, mul_bf16x2(sv.x, gv.x)), add_bf16x2(xv.y, mul_bf16x2(sv.y, gv.y)),
                                                              add_bf16x2(xv.z, mul_bf16x2(sv.z, gv.z)), add_bf16x2(xv.w, mul_bf16x2(sv.w, gv.w)));
     }
   }
  }
  if (GCL > 1) cluster_sync();
}

__device__ bf16 g_xn[cfg::S * cfg::D];
__device__ bf16 g_xn2[cfg::S * cfg::D];
__device__ bf16 g_h[cfg::S * cfg::D];
__device__ bf16 g_x1[cfg::S * cfg::D];
__device__ bf16 g_x1n[cfg::S * cfg::D];
__device__ bf16 g_u[cfg::S * cfg::F];
__device__ bf16 g_g[cfg::S * cfg::D];
__device__ bf16 g_o[cfg::S * cfg::HD];

typedef CUresult (*PFN_encodeTiled)(CUtensorMap*, CUtensorMapDataType, cuuint32_t, void*, const cuuint64_t*,
                                    const cuuint64_t*, const cuuint32_t*, const cuuint32_t*, CUtensorMapInterleave,
                                    CUtensorMapSwizzle, CUtensorMapL2promotion, CUtensorMapFloatOOBfill);

static PFN_encodeTiled get_encoder() {
  static PFN_encodeTiled fn = nullptr;
  if (!fn) {
    void* p = nullptr;
    cudaDriverEntryPointQueryResult st;
    cudaGetDriverEntryPoint("cuTensorMapEncodeTiled", &p, cudaEnableDefault, &st);
    fn = (PFN_encodeTiled)p;
  }
  return fn;
}
static CUtensorMap make_map(const void* ptr, int rows, int cols, int box_rows, int box_cols, int swizzle_bytes) {
  CUtensorMap m;
  cuuint64_t dims[2] = {(cuuint64_t)cols, (cuuint64_t)rows};
  cuuint64_t strides[1] = {(cuuint64_t)cols * 2};
  cuuint32_t box[2] = {(cuuint32_t)box_cols, (cuuint32_t)box_rows};
  cuuint32_t estr[2] = {1, 1};
  CUtensorMapSwizzle sw = swizzle_bytes == 128 ? CU_TENSOR_MAP_SWIZZLE_128B
                        : swizzle_bytes == 64 ? CU_TENSOR_MAP_SWIZZLE_64B
                        : swizzle_bytes == 32 ? CU_TENSOR_MAP_SWIZZLE_32B : CU_TENSOR_MAP_SWIZZLE_NONE;
  get_encoder()(&m, CU_TENSOR_MAP_DATA_TYPE_BFLOAT16, 2, const_cast<void*>(ptr), dims, strides, box, estr,
                CU_TENSOR_MAP_INTERLEAVE_NONE, sw, CU_TENSOR_MAP_L2_PROMOTION_L2_128B, CU_TENSOR_MAP_FLOAT_OOB_FILL_NONE);
  return m;
}
static CUtensorMap make_map3(const void* ptr, int rows, int cols, int box_rows, int nblk) {
  CUtensorMap m;
  cuuint64_t dims[3] = {64, (cuuint64_t)rows, (cuuint64_t)(cols / 64)};
  cuuint64_t strides[2] = {(cuuint64_t)cols * 2, 128};
  cuuint32_t box[3] = {64, (cuuint32_t)box_rows, (cuuint32_t)nblk};
  cuuint32_t estr[3] = {1, 1, 1};
  get_encoder()(&m, CU_TENSOR_MAP_DATA_TYPE_BFLOAT16, 3, const_cast<void*>(ptr), dims, strides, box, estr,
                CU_TENSOR_MAP_INTERLEAVE_NONE, CU_TENSOR_MAP_SWIZZLE_128B, CU_TENSOR_MAP_L2_PROMOTION_L2_128B,
                CU_TENSOR_MAP_FLOAT_OOB_FILL_NONE);
  return m;
}
template <class T> static T* sym(T& s) { void* p = nullptr; cudaGetSymbolAddress(&p, s); return (T*)p; }
#define SYM(name) ((bf16*)[] { void* p = nullptr; cudaGetSymbolAddress(&p, name); return p; }())

#define G_CTAS 36
#define B4_FIRST (GCL == 1 ? 9 : 16)
#define O_FIRST 2
#define LN_POS 63
static int build_items(uint16_t* it) {
  using namespace gk;
  int n = 0;
  auto add = [&](int type, int nrows, int ncols, int row0 = 0) {
    for (int mb = row0; mb < nrows; mb += GCL) for (int nt = 0; nt < ncols; nt++) it[n++] = (uint16_t)(type | mb << 3 | nt << 7);
  };
  add(T_B1, 16, 4); add(T_B2, 16, 4); add(T_B3, 16, 14);
  add(T_B4, B4_FIRST, 4); add(T_O, O_FIRST, 4); add(T_B4, 16, 4, B4_FIRST); add(T_O, TAIL_MB0, 4, O_FIRST);
  return n;
}

extern "C" void kernel_launch(void* const* d_in, const int* in_sizes, int n_in, void* d_out, int out_size) {
  using namespace cfg;
  const bf16* x = (const bf16*)d_in[0];
  const bf16* mem0 = (const bf16*)d_in[1];
  const bf16* Wq = (const bf16*)d_in[2];
  const bf16* Wk = (const bf16*)d_in[3];
  const bf16* Wv = (const bf16*)d_in[4];
  const bf16* Wo = (const bf16*)d_in[5];
  const bf16* w1 = (const bf16*)d_in[8];
  const bf16* w2 = (const bf16*)d_in[9];
  const bf16* w3 = (const bf16*)d_in[10];
  const bf16* w4 = (const bf16*)d_in[11];
  bf16* out = (bf16*)d_out;
  cudaStream_t st = cudaStreamPerThread;

  bf16 *xn = SYM(g_xn), *xn2 = SYM(g_xn2), *hb = SYM(g_h), *x1 = SYM(g_x1), *x1n = SYM(g_x1n), *u = SYM(g_u),
       *g = SYM(g_g), *o = SYM(g_o);

  {
    cudaFuncSetAttribute(f_kernel, cudaFuncAttributeMaxDynamicSharedMemorySize, fk::SMEM);
    FParams P;
    P.wq = make_map(Wq, D, HD, 64, 64, 128); P.wk = make_map(Wk, D, HD, 64, 64, 128); P.wv = make_map(Wv, D, HD, 64, 64, 128);
    P.wo = make_map(Wo, HD, D, 128, 64, 128); P.wo16 = make_map(Wo, HD, D, 128, 16, 32); P.xn = make_map3(xn, S, D, 32, 4); P.xn12 = make_map3(xn, S, D, 32, 12); P.o = make_map3(o, S, HD, 32, 2);
    P.ta = make_map(o, S, HD, 128, 64, 128); P.tb = make_map(Wo, HD, D, 64, 64, 128); P.tx = make_map(x, S, D, 128, 64, 128);
    P.tg = make_map(g, S, D, 128, 64, 128); P.tout = make_map(out, S, D, 16, 64, 128);
    P.mem0 = mem0;
    P.nprobe = PROBE_N;
    P.dxn = make_desc(fk::XN, 16, 1024);
    P.x = x; P.w1 = w1; P.xn_ptr = xn; P.xn2 = xn2;
    P.xch = (char*)(((uintptr_t)SYM(g_xch) + 8191) & ~(uintptr_t)8191);
    cudaLaunchConfig_t cfg = {};
    cfg.gridDim = dim3(96); cfg.blockDim = dim3(256); cfg.dynamicSmemBytes = fk::SMEM; cfg.stream = st;
    cudaLaunchAttribute at[2];
    at[0].id = cudaLaunchAttributeClusterDimension;
    at[0].val.clusterDim.x = 3; at[0].val.clusterDim.y = 1; at[0].val.clusterDim.z = 1;
    cfg.attrs = at; cfg.numAttrs = 1;
    cudaLaunchKernelEx(&cfg, f_kernel, P);
  }
  {
    cudaFuncSetAttribute(g_kernel, cudaFuncAttributeMaxDynamicSharedMemorySize, gk::SMEM);
    GParams G;
    const bf16* as[5] = {xn2, hb, x1n, u, o};
    const bf16* bs[5] = {w1, w2, w3, w4, Wo};
    bf16* cs[5] = {hb, x1, u, g, out};
    const bf16* rs[5] = {xn, xn, xn, x1, x};
    const int ks[5] = {D, D, D, F, HD}, ns[5] = {D, D, F, D, D};
    for (int i = 0; i < 5; i++) {
      G.a[i] = make_map(as[i], S, ks[i], 128, 64, 128);
      G.b[i] = make_map3(bs[i], ks[i], ns[i], 64, 4 / GCL);
      G.c[i] = cs[i];
      G.r[i] = rs[i];
    }
    G.x1n = x1n;
    G.nitems = build_items(G.items);
    G.lnpos = LN_POS * 2 / GCL;
    cudaLaunchConfig_t cfg = {};
    cfg.gridDim = dim3(G_CTAS); cfg.blockDim = dim3(384); cfg.dynamicSmemBytes = gk::SMEM; cfg.stream = st;
    cudaLaunchAttribute at[2];
    at[0].id = cudaLaunchAttributeClusterDimension;
    at[0].val.clusterDim.x = GCL; at[0].val.clusterDim.y = 1; at[0].val.clusterDim.z = 1;
    at[1].id = cudaLaunchAttributeProgrammaticStreamSerialization;
    at[1].val.programmaticStreamSerializationAllowed = 1;
    cfg.attrs = at;
    cfg.numAttrs = 2;
    cudaLaunchKernelEx(&cfg, g_kernel, G);
  }
}
```

```cpp
#include <cuda_runtime.h>
#include <cuda_bf16.h>
#include <cuda.h>
#include <stdint.h>

typedef __nv_bfloat16 bf16;

namespace cfg {
constexpr int S = 2048;
constexpr int D = 1024;
constexpr int H = 32;
constexpr int DH = 128;
constexpr int HD = H * DH;
constexpr int M = 8;
constexpr int SEG = 32;
constexpr int NSEG = S / SEG;
constexpr int F = 3584;
}

__device__ __forceinline__ uint32_t smem_u32(const void* p) { return (uint32_t)__cvta_generic_to_shared(p); }

__device__ __forceinline__ void mbar_init(uint32_t bar, uint32_t count) {
  asm volatile("mbarrier.init.shared::cta.b64 [%0], %1;" ::"r"(bar), "r"(count) : "memory");
}
__device__ __forceinline__ void mbar_expect_tx(uint32_t bar, uint32_t bytes) {
  asm volatile("mbarrier.arrive.expect_tx.shared::cta.b64 _, [%0], %1;" ::"r"(bar), "r"(bytes) : "memory");
}
__device__ __forceinline__ void mbar_arrive(uint32_t bar) {
  asm volatile("mbarrier.arrive.shared::cta.b64 _, [%0];" ::"r"(bar) : "memory");
}
__device__ __forceinline__ bool mbar_try(uint32_t bar, uint32_t parity) {
  uint32_t done;
  asm volatile("{\n.reg .pred p;\nmbarrier.try_wait.parity.shared::cta.b64 p, [%1], %2, 20000;\nselp.u32 %0, 1, 0, p;\n}"
               : "=r"(done) : "r"(bar), "r"(parity) : "memory");
  return done != 0;
}
__device__ __forceinline__ bool mbar_try_nohint(uint32_t bar, uint32_t parity) {
  uint32_t done;
  asm volatile("{\n.reg .pred p;\nmbarrier.try_wait.parity.shared::cta.b64 p, [%1], %2;\nselp.u32 %0, 1, 0, p;\n}"
               : "=r"(done) : "r"(bar), "r"(parity) : "memory");
  return done != 0;
}
constexpr int MBAR_TRIES = 4096;
constexpr int POLL_TRIES = 1 << 16;
__device__ __forceinline__ void mbar_wait(uint32_t bar, uint32_t parity) {
#pragma unroll 1
  for (int n = 0; n < MBAR_TRIES; n++)
    if (mbar_try(bar, parity)) break;
}
__device__ __forceinline__ void mbar_wait_fast(uint32_t bar, uint32_t parity) {
#pragma unroll 1
  for (int n = 0; n < (POLL_TRIES << 4); n++)
    if (mbar_try_nohint(bar, parity)) break;
}
__device__ __forceinline__ void fence_barrier_init() { asm volatile("fence.mbarrier_init.release.cluster;" ::: "memory"); }
__device__ __forceinline__ void fence_proxy_async_smem() { asm volatile("fence.proxy.async.shared::cta;" ::: "memory"); }

__device__ __forceinline__ void tma_load_2d(uint32_t dst, const CUtensorMap* map, int x, int y, uint32_t bar) {
  asm volatile("cp.async.bulk.tensor.2d.shared::cluster.global.mbarrier::complete_tx::bytes [%0], [%1, {%3, %4}], [%2];"
               ::"r"(dst), "l"(map), "r"(bar), "r"(x), "r"(y) : "memory");
}
__device__ __forceinline__ void tma_load_3d(uint32_t dst, const CUtensorMap* map, int x, int y, int z, uint32_t bar) {
  asm volatile("cp.async.bulk.tensor.3d.shared::cluster.global.mbarrier::complete_tx::bytes [%0], [%1, {%3, %4, %5}], [%2];"
               ::"r"(dst), "l"(map), "r"(bar), "r"(x), "r"(y), "r"(z) : "memory");
}
__device__ __forceinline__ void tma_store_2d(const CUtensorMap* map, uint32_t src, int x, int y) {
  asm volatile("cp.async.bulk.tensor.2d.global.shared::cta.bulk_group [%0, {%2, %3}], [%1];"
               ::"l"(map), "r"(src), "r"(x), "r"(y) : "memory");
}
__device__ __forceinline__ void tma_store_commit() { asm volatile("cp.async.bulk.commit_group;" ::: "memory"); }
__device__ __forceinline__ void tma_store_wait_all() { asm volatile("cp.async.bulk.wait_group 0;" ::: "memory"); }
__device__ __forceinline__ void tma_store_wait_read() { asm volatile("cp.async.bulk.wait_group.read 0;" ::: "memory"); }
__device__ __forceinline__ void prefetch_tmap(const CUtensorMap* map) {
  asm volatile("prefetch.tensormap [%0];" ::"l"(map) : "memory");
}

__device__ __forceinline__ void wg_fence() { asm volatile("wgmma.fence.sync.aligned;" ::: "memory"); }
__device__ __forceinline__ void wg_commit() { asm volatile("wgmma.commit_group.sync.aligned;" ::: "memory"); }
template <int N> __device__ __forceinline__ void wg_wait() { asm volatile("wgmma.wait_group.sync.aligned %0;" ::"n"(N) : "memory"); }

#define named_bar_sync(id, n) asm volatile("bar.sync %0, %1;" ::"n"(id), "n"(n) : "memory")
#define named_bar_arrive(id, n) asm volatile("bar.arrive %0, %1;" ::"n"(id), "n"(n) : "memory")

__host__ __device__ __forceinline__ uint64_t make_desc(uint32_t addr, uint32_t lbo, uint32_t sbo) {
  return (uint64_t)((addr & 0x3FFFF) >> 4) | ((uint64_t)(lbo >> 4) << 16) | ((uint64_t)(sbo >> 4) << 32) | (1ull << 62);
}

__device__ __forceinline__ uint64_t make_desc0(uint32_t addr, uint32_t lbo, uint32_t sbo) {
  return (uint64_t)((addr & 0x3FFFF) >> 4) | ((uint64_t)(lbo >> 4) << 16) | ((uint64_t)(sbo >> 4) << 32);
}

__device__ __forceinline__ uint32_t pack_bf16(float lo, float hi) {
  uint32_t r;
  asm("cvt.rn.bf16x2.f32 %0, %1, %2;" : "=r"(r) : "f"(hi), "f"(lo));
  return r;
}
__device__ __forceinline__ float bf_lo(uint32_t v) { return __uint_as_float(v << 16); }
__device__ __forceinline__ float bf_hi(uint32_t v) { return __uint_as_float(v & 0xFFFF0000u); }
__device__ __forceinline__ float rbf(float v) { return __bfloat162float(__float2bfloat16_rn(v)); }

__device__ __forceinline__ void pdl_launch_dependents() { asm volatile("griddepcontrol.launch_dependents;" ::: "memory"); }
__device__ __forceinline__ void pdl_wait() { asm volatile("griddepcontrol.wait;" ::: "memory"); }

__device__ __forceinline__ float ex2_approx(float x) { float y; asm("ex2.approx.ftz.f32 %0, %1;" : "=f"(y) : "f"(x)); return y; }
__device__ __forceinline__ float rcp_approx(float x) { float y; asm("rcp.approx.ftz.f32 %0, %1;" : "=f"(y) : "f"(x)); return y; }

__device__ __forceinline__ void mul_sigmoid4(float (&v)[4], const float (&t)[4]) {
#pragma unroll
  for (int i = 0; i < 4; i += 2) {
    const float a = 1.0f + ex2_approx(fminf(t[i], 60.0f)), b = 1.0f + ex2_approx(fminf(t[i + 1], 60.0f));
    const float r = rcp_approx(a * b);
    v[i] *= b * r;
    v[i + 1] *= a * r;
  }
}
__device__ __forceinline__ void gelu4(float (&v)[4]) {
  float t[4];
#pragma unroll
  for (int i = 0; i < 4; i++) t[i] = v[i] * fmaf(v[i] * v[i], -0.10294324f, -2.30220819f);
  mul_sigmoid4(v, t);
}
__device__ __forceinline__ void silu4(float (&v)[4]) {
  float t[4];
#pragma unroll
  for (int i = 0; i < 4; i++) t[i] = v[i] * -1.4426950408889634f;
  mul_sigmoid4(v, t);
}

#define KT_START(id)
#define KT_END(id)

__device__ __forceinline__ void wgmma_ss_n256_tb(float (&d)[128], uint64_t da, uint64_t db, int scale_d) {
  asm volatile("{\n.reg .pred p;\nsetp.ne.b32 p, %130, 0;\n"
    "wgmma.mma_async.sync.aligned.m64n256k16.f32.bf16.bf16 "
    "{%0, %1, %2, %3, %4, %5, %6, %7, %8, %9, %10, %11, %12, %13, %14, %15, "
    "%16, %17, %18, %19, %20, %21, %22, %23, %24, %25, %26, %27, %28, %29, %30, %31, "
    "%32, %33, %34, %35, %36, %37, %38, %39, %40, %41, %42, %43, %44, %45, %46, %47, "
    "%48, %49, %50, %51, %52, %53, %54, %55, %56, %57, %58, %59, %60, %61, %62, %63, "
    "%64, %65, %66, %67, %68, %69, %70, %71, %72, %73, %74, %75, %76, %77, %78, %79, "
    "%80, %81, %82, %83, %84, %85, %86, %87, %88, %89, %90, %91, %92, %93, %94, %95, "
    "%96, %97, %98, %99, %100, %101, %102, %103, %104, %105, %106, %107, %108, %109, %110, %111, "
    "%112, %113, %114, %115, %116, %117, %118, %119, %120, %121, %122, %123, %124, %125, %126, %127}, "
    "%128, %129, p, 1, 1, 0, 1;\n}\n"
    : "+f"(d[0]), "+f"(d[1]), "+f"(d[2]), "+f"(d[3]), "+f"(d[4]), "+f"(d[5]), "+f"(d[6]), "+f"(d[7]),
      "+f"(d[8]), "+f"(d[9]), "+f"(d[10]), "+f"(d[11]), "+f"(d[12]), "+f"(d[13]), "+f"(d[14]), "+f"(d[15]),
      "+f"(d[16]), "+f"(d[17]), "+f"(d[18]), "+f"(d[19]), "+f"(d[20]), "+f"(d[21]), "+f"(d[22]), "+f"(d[23]),
      "+f"(d[24]), "+f"(d[25]), "+f"(d[26]), "+f"(d[27]), "+f"(d[28]), "+f"(d[29]), "+f"(d[30]), "+f"(d[31]),
      "+f"(d[32]), "+f"(d[33]), "+f"(d[34]), "+f"(d[35]), "+f"(d[36]), "+f"(d[37]), "+f"(d[38]), "+f"(d[39]),
      "+f"(d[40]), "+f"(d[41]), "+f"(d[42]), "+f"(d[43]), "+f"(d[44]), "+f"(d[45]), "+f"(d[46]), "+f"(d[47]),
      "+f"(d[48]), "+f"(d[49]), "+f"(d[50]), "+f"(d[51]), "+f"(d[52]), "+f"(d[53]), "+f"(d[54]), "+f"(d[55]),
      "+f"(d[56]), "+f"(d[57]), "+f"(d[58]), "+f"(d[59]), "+f"(d[60]), "+f"(d[61]), "+f"(d[62]), "+f"(d[63]),
      "+f"(d[64]), "+f"(d[65]), "+f"(d[66]), "+f"(d[67]), "+f"(d[68]), "+f"(d[69]), "+f"(d[70]), "+f"(d[71]),
      "+f"(d[72]), "+f"(d[73]), "+f"(d[74]), "+f"(d[75]), "+f"(d[76]), "+f"(d[77]), "+f"(d[78]), "+f"(d[79]),
      "+f"(d[80]), "+f"(d[81]), "+f"(d[82]), "+f"(d[83]), "+f"(d[84]), "+f"(d[85]), "+f"(d[86]), "+f"(d[87]),
      "+f"(d[88]), "+f"(d[89]), "+f"(d[90]), "+f"(d[91]), "+f"(d[92]), "+f"(d[93]), "+f"(d[94]), "+f"(d[95]),
      "+f"(d[96]), "+f"(d[97]), "+f"(d[98]), "+f"(d[99]), "+f"(d[100]), "+f"(d[101]), "+f"(d[102]), "+f"(d[103]),
      "+f"(d[104]), "+f"(d[105]), "+f"(d[106]), "+f"(d[107]), "+f"(d[108]), "+f"(d[109]), "+f"(d[110]), "+f"(d[111]),
      "+f"(d[112]), "+f"(d[113]), "+f"(d[114]), "+f"(d[115]), "+f"(d[116]), "+f"(d[117]), "+f"(d[118]), "+f"(d[119]),
      "+f"(d[120]), "+f"(d[121]), "+f"(d[122]), "+f"(d[123]), "+f"(d[124]), "+f"(d[125]), "+f"(d[126]), "+f"(d[127])
    : "l"(da), "l"(db), "r"(scale_d));
}
__device__ __forceinline__ void wgmma_rs_n32(float (&d)[16], const uint32_t* a, uint64_t db, int scale_d) {
  asm volatile("{\n.reg .pred p;\nsetp.ne.b32 p, %21, 0;\n"
    "wgmma.mma_async.sync.aligned.m64n32k16.f32.bf16.bf16 "
    "{%0, %1, %2, %3, %4, %5, %6, %7, %8, %9, %10, %11, %12, %13, %14, %15}, "
    "{%16, %17, %18, %19}, %20, p, 1, 1, 0;\n}\n"
    : "+f"(d[0]), "+f"(d[1]), "+f"(d[2]), "+f"(d[3]), "+f"(d[4]), "+f"(d[5]), "+f"(d[6]), "+f"(d[7]),
      "+f"(d[8]), "+f"(d[9]), "+f"(d[10]), "+f"(d[11]), "+f"(d[12]), "+f"(d[13]), "+f"(d[14]), "+f"(d[15])
    : "r"(a[0]), "r"(a[1]), "r"(a[2]), "r"(a[3]), "l"(db), "r"(scale_d));
}
__device__ __forceinline__ void wgmma_ss_n32_ta(float (&d)[16], uint64_t da, uint64_t db, int scale_d) {
  asm volatile("{\n.reg .pred p;\nsetp.ne.b32 p, %18, 0;\n"
    "wgmma.mma_async.sync.aligned.m64n32k16.f32.bf16.bf16 "
    "{%0, %1, %2, %3, %4, %5, %6, %7, %8, %9, %10, %11, %12, %13, %14, %15}, "
    "%16, %17, p, 1, 1, 1, 0;\n}\n"
    : "+f"(d[0]), "+f"(d[1]), "+f"(d[2]), "+f"(d[3]), "+f"(d[4]), "+f"(d[5]), "+f"(d[6]), "+f"(d[7]),
      "+f"(d[8]), "+f"(d[9]), "+f"(d[10]), "+f"(d[11]), "+f"(d[12]), "+f"(d[13]), "+f"(d[14]), "+f"(d[15])
    : "l"(da), "l"(db), "r"(scale_d));
}
__device__ __forceinline__ void wgmma_ss_n8_ta(float (&d)[4], uint64_t da, uint64_t db, int scale_d) {
  asm volatile("{\n.reg .pred p;\nsetp.ne.b32 p, %6, 0;\n"
    "wgmma.mma_async.sync.aligned.m64n8k16.f32.bf16.bf16 {%0, %1, %2, %3}, %4, %5, p, 1, 1, 1, 0;\n}\n"
    : "+f"(d[0]), "+f"(d[1]), "+f"(d[2]), "+f"(d[3]) : "l"(da), "l"(db), "r"(scale_d));
}
__device__ __forceinline__ void wgmma_ss_n48_tt(float (&d)[24], uint64_t da, uint64_t db, int scale_d) {
  asm volatile("{\n.reg .pred p;\nsetp.ne.b32 p, %26, 0;\n"
    "wgmma.mma_async.sync.aligned.m64n48k16.f32.bf16.bf16 "
    "{%0, %1, %2, %3, %4, %5, %6, %7, %8, %9, %10, %11, %12, %13, %14, %15, %16, %17, %18, %19, %20, %21, %22, %23}, "
    "%24, %25, p, 1, 1, 1, 1;\n}\n"
    : "+f"(d[0]), "+f"(d[1]), "+f"(d[2]), "+f"(d[3]), "+f"(d[4]), "+f"(d[5]), "+f"(d[6]), "+f"(d[7]), "+f"(d[8]), "+f"(d[9]), "+f"(d[10]), "+f"(d[11]), "+f"(d[12]), "+f"(d[13]), "+f"(d[14]), "+f"(d[15]), "+f"(d[16]), "+f"(d[17]), "+f"(d[18]), "+f"(d[19]), "+f"(d[20]), "+f"(d[21]), "+f"(d[22]), "+f"(d[23])
    : "l"(da), "l"(db), "r"(scale_d));
}
__device__ __forceinline__ void wgmma_ss_n32(float (&d)[16], uint64_t da, uint64_t db, int scale_d) {
  asm volatile("{\n.reg .pred p;\nsetp.ne.b32 p, %18, 0;\n"
    "wgmma.mma_async.sync.aligned.m64n32k16.f32.bf16.bf16 "
    "{%0, %1, %2, %3, %4, %5, %6, %7, %8, %9, %10, %11, %12, %13, %14, %15}, "
    "%16, %17, p, 1, 1, 0, 0;\n}\n"
    : "+f"(d[0]), "+f"(d[1]), "+f"(d[2]), "+f"(d[3]), "+f"(d[4]), "+f"(d[5]), "+f"(d[6]), "+f"(d[7]),
      "+f"(d[8]), "+f"(d[9]), "+f"(d[10]), "+f"(d[11]), "+f"(d[12]), "+f"(d[13]), "+f"(d[14]), "+f"(d[15])
    : "l"(da), "l"(db), "r"(scale_d));
}

__device__ __forceinline__ void tma_load_2d_mc(uint32_t dst, const CUtensorMap* map, int x, int y, uint32_t bar, uint16_t mask) {
  asm volatile("cp.async.bulk.tensor.2d.shared::cluster.global.mbarrier::complete_tx::bytes.multicast::cluster "
               "[%0], [%1, {%3, %4}], [%2], %5;"
               ::"r"(dst), "l"(map), "r"(bar), "r"(x), "r"(y), "h"(mask) : "memory");
}
__device__ __forceinline__ void mbar_arrive_cluster(uint32_t bar, uint32_t cta) {
  asm volatile("{\n.reg .b32 r;\nmapa.shared::cluster.u32 r, %0, %1;\nmbarrier.arrive.shared::cluster.b64 _, [r];\n}"
               ::"r"(bar), "r"(cta) : "memory");
}
__device__ __forceinline__ void cluster_sync() {
  asm volatile("barrier.cluster.arrive.release.aligned;\nbarrier.cluster.wait.acquire.aligned;" ::: "memory");
}
__device__ __forceinline__ void wait_count(const unsigned* p, unsigned need) {
#pragma unroll 1
  for (int tries = 0; tries < (1 << 18); tries++) {
    unsigned v;
    asm volatile("ld.acquire.gpu.global.u32 %0, [%1];" : "=r"(v) : "l"(p) : "memory");
    if (v >= need) break;
    __nanosleep(64);
  }
}
__device__ __forceinline__ uint32_t sub_bf16x2(uint32_t a, uint32_t b) {
  uint32_t d;
  asm("sub.rn.bf16x2 %0, %1, %2;" : "=r"(d) : "r"(a), "r"(b));
  return d;
}
__device__ __forceinline__ uint32_t add_bf16x2(uint32_t a, uint32_t b) {
  uint32_t d;
  asm("add.rn.bf16x2 %0, %1, %2;" : "=r"(d) : "r"(a), "r"(b));
  return d;
}
__device__ __forceinline__ uint32_t mul_bf16x2(uint32_t a, uint32_t b) {
  uint32_t d;
  asm("mul.rn.bf16x2 %0, %1, %2;" : "=r"(d) : "r"(a), "r"(b));
  return d;
}

template <int NR>
__device__ __forceinline__ void ln_regs(uint32_t (&raw)[NR][16]) {
  float m[NR], q[NR];
#pragma unroll
  for (int r = 0; r < NR; r++) {
    float s0 = 0.f, s1 = 0.f;
#pragma unroll
    for (int i = 0; i < 16; i++) { s0 += bf_lo(raw[r][i]); s1 += bf_hi(raw[r][i]); }
    m[r] = s0 + s1;
  }
#pragma unroll
  for (int o = 16; o > 0; o >>= 1)
#pragma unroll
    for (int r = 0; r < NR; r++) m[r] += __shfl_xor_sync(0xffffffffu, m[r], o);
#pragma unroll
  for (int r = 0; r < NR; r++) {
    m[r] *= 1.0f / 1024.0f;
    float s0 = 0.f, s1 = 0.f;
#pragma unroll
    for (int i = 0; i < 16; i++) {
      const float d0 = bf_lo(raw[r][i]) - m[r], d1 = bf_hi(raw[r][i]) - m[r];
      s0 = fmaf(d0, d0, s0); s1 = fmaf(d1, d1, s1);
    }
    q[r] = s0 + s1;
  }
#pragma unroll
  for (int o = 16; o > 0; o >>= 1)
#pragma unroll
    for (int r = 0; r < NR; r++) q[r] += __shfl_xor_sync(0xffffffffu, q[r], o);
#pragma unroll
  for (int r = 0; r < NR; r++) {
    const uint32_t mb = pack_bf16(m[r], m[r]);
    float sq;
    asm("sqrt.approx.f32 %0, %1;" : "=f"(sq) : "f"(rbf(rbf(q[r] * (1.0f / 1024.0f)) + 1e-5f)));
    const float inv = rcp_approx(rbf(sq));
#pragma unroll
    for (int i = 0; i < 16; i++) {
      const uint32_t d = sub_bf16x2(raw[r][i], mb);
      raw[r][i] = pack_bf16(bf_lo(d) * inv, bf_hi(d) * inv);
    }
  }
}
__device__ __forceinline__ void load_row16(uint32_t (&raw)[16], const bf16* src, int lane) {
#pragma unroll
  for (int j = 0; j < 4; j++) {
    const uint4 u = __ldcg(reinterpret_cast<const uint4*>(src + j * 256 + lane * 8));
    raw[4 * j] = u.x; raw[4 * j + 1] = u.y; raw[4 * j + 2] = u.z; raw[4 * j + 3] = u.w;
  }
}
__device__ __forceinline__ void store_row16(const uint32_t (&raw)[16], bf16* dst, int lane) {
#pragma unroll
  for (int j = 0; j < 4; j++)
    *reinterpret_cast<uint4*>(dst + j * 256 + lane * 8) = make_uint4(raw[4 * j], raw[4 * j + 1], raw[4 * j + 2], raw[4 * j + 3]);
}

namespace fk {
constexpr uint32_t SM0 = 1024;
constexpr uint32_t WO = SM0, WS = WO + 90112, XN = WS + 65536, VX = XN + 49152, QK = VX + 8192, PT = QK + 8192,
                   SP = PT + 4096, VM = SP + 2560, OB = VM + 2048, BAR = OB + 2048;
constexpr uint32_t MEMB = XN + 16384, RED = XN + 32768, VX2 = WO + 81920;
constexpr int SMEM = 232448;
static_assert(BAR + 512 == SM0 + SMEM, "shared memory layout");
constexpr uint32_t B_XN = BAR, B_H2 = BAR + 64, B_H1 = BAR + 120, ONES = BAR + 384, B_PF = BAR + 16, B_WO = BAR + 24, B_SM = BAR + 32, B_VM = BAR + 40, B_VX = BAR + 48, B_ST = BAR + 56, B_PB = BAR + 64, B_W = BAR + 112,
                   MASKS = BAR + 128, PROBE = BAR + 256;
constexpr int NB_M0 = 1, NB_M1 = 2, NB_C = 3, NB_O = 4, NB_ST = 5, NB_DU = 6, NB_CF = 7, NB_W1 = 8, NB_XE = 9, NB_HD = 10, NB_MX = 11, NB_O0 = 12;
#define D_H1 550
#define D_H2 1900
#define D_ST 200
#define SMQ 0x1E
#define SMV 0x1E
#define PRE_G 4
#define PRE_A 1
#define LN_DRY 1
#define MASK_AT 4
#define WO_AT 5
#define NS0 4
#define NS0V 4
#define NTA0 2
#define NTA1 1
#define PF0A 3
#define PF0 10
#define PF1V 10
#define PF1 11
#define REFILL_EARLY 1
#define GATE_MX 0
#define GATE_Q 0
#define PF1Q 4
#define PACEQ 0x60
#define PACEV 0
#define PADD 1
#define D_H2V 2000
#define H2_ATV 1
#define VM_BULK 0
#define CF_AT 0
#define H2_AT 0
#define NPRE0 1
#define PROBE_N 4
#define SPACK 1
constexpr uint32_t SPW = SPACK ? 4 : 8, SP_SRC = 160 * SPW;
constexpr int H1_BYTES = 64 * 32768, H2_BYTES = 8 * 8192;
}

#define PROF(wg, i)
#define PROF2(i)
#define RETRY(i)
#define GTSYNC(i)
#define PRO(i)
#define TL(i)
#define TL2(t, i)

__device__ uint4 g_xch[(fk::H1_BYTES + fk::H2_BYTES + 8192) / 16];
__device__ __align__(16) unsigned g_mask[128];
__device__ unsigned g_cnt[8][16];
__device__ unsigned g_next;
constexpr int TAIL_MB0 = 10, GATE_CNT = 12;
__device__ __align__(16) unsigned g_tfix[96], g_lnok[4];
__device__ uint4 g_tpart[96][3][4][256];
__device__ unsigned g_oflag[16];

#define LD_POLL "ld.global.L1::no_allocate"
__device__ __forceinline__ uint4 ld_poll16(const void* p) {
  uint4 v;
  asm volatile(LD_POLL ".v4.u32 {%0,%1,%2,%3}, [%4];" : "=r"(v.x), "=r"(v.y), "=r"(v.z), "=r"(v.w) : "l"(p) : "memory");
  return v;
}
__device__ __forceinline__ uint2 ld_poll8(const void* p) {
  uint2 v;
  asm volatile(LD_POLL ".v2.u32 {%0,%1}, [%2];" : "=r"(v.x), "=r"(v.y) : "l"(p) : "memory");
  return v;
}
__device__ __forceinline__ uint4 ld_strong16(const void* p) {
  uint4 v;
  asm volatile("ld.relaxed.gpu.global.v4.u32 {%0,%1,%2,%3}, [%4];" : "=r"(v.x), "=r"(v.y), "=r"(v.z), "=r"(v.w) : "l"(p) : "memory");
  return v;
}
__device__ __forceinline__ uint2 ld_strong8(const void* p) {
  uint2 v;
  asm volatile("ld.relaxed.gpu.global.v2.u32 {%0,%1}, [%2];" : "=r"(v.x), "=r"(v.y) : "l"(p) : "memory");
  return v;
}
__device__ __forceinline__ void st_pub32(void* p, uint32_t v) { asm volatile("st.relaxed.gpu.global.u32 [%0], %1;" ::"l"(p), "r"(v) : "memory"); }
__device__ __forceinline__ void st_pub16(void* p, uint32_t v) {
  asm volatile("st.relaxed.gpu.global.u16 [%0], %1;" ::"l"(p), "h"((uint16_t)v) : "memory");
}
__device__ __forceinline__ uint32_t ld_strong4(const void* p) {
  uint32_t v;
  asm volatile("ld.relaxed.gpu.global.u32 %0, [%1];" : "=r"(v) : "l"(p) : "memory");
  return v;
}
__device__ __forceinline__ void st_pub64(void* p, uint32_t a, uint32_t b) {
  asm volatile("st.relaxed.gpu.global.v2.u32 [%0], {%1,%2};" ::"l"(p), "r"(a), "r"(b) : "memory");
}
__device__ __forceinline__ void st_pub128(void* p, uint32_t a) {
  asm volatile("st.relaxed.gpu.global.v4.u32 [%0], {%1,%1,%1,%1};" ::"l"(p), "r"(a) : "memory");
}
constexpr uint32_t EMPTY = 0xFFFFFFFFu;
__device__ __forceinline__ uint32_t umax4(const uint4& v) { return max(max(v.x, v.y), max(v.z, v.w)); }
__device__ __forceinline__ void sts128(uint32_t a, uint32_t x, uint32_t y, uint32_t z, uint32_t w) {
  asm volatile("st.shared.v4.u32 [%0], {%1,%2,%3,%4};" ::"r"(a), "r"(x), "r"(y), "r"(z), "r"(w) : "memory");
}
__device__ __forceinline__ void sts64(uint32_t a, uint32_t x, uint32_t y) {
  asm volatile("st.shared.v2.u32 [%0], {%1,%2};" ::"r"(a), "r"(x), "r"(y) : "memory");
}
__device__ __forceinline__ void sts32(uint32_t a, uint32_t x) { asm volatile("st.shared.u32 [%0], %1;" ::"r"(a), "r"(x) : "memory"); }
__device__ __forceinline__ void sts128f(uint32_t a, float x, float y, float z, float w) {
  asm volatile("st.shared.v4.f32 [%0], {%1,%2,%3,%4};" ::"r"(a), "f"(x), "f"(y), "f"(z), "f"(w) : "memory");
}
__device__ __forceinline__ void sts64f(uint32_t a, float x, float y) {
  asm volatile("st.shared.v2.f32 [%0], {%1,%2};" ::"r"(a), "f"(x), "f"(y) : "memory");
}
__device__ __forceinline__ float4 lds128f(uint32_t a) {
  float4 v;
  asm volatile("ld.shared.v4.f32 {%0,%1,%2,%3}, [%4];" : "=f"(v.x), "=f"(v.y), "=f"(v.z), "=f"(v.w) : "r"(a) : "memory");
  return v;
}
__device__ __forceinline__ float2 lds64f(uint32_t a) {
  float2 v;
  asm volatile("ld.shared.v2.f32 {%0,%1}, [%2];" : "=f"(v.x), "=f"(v.y) : "r"(a) : "memory");
  return v;
}
__device__ __forceinline__ float2 lds64f_if(uint32_t a, bool on, float other) {
  float2 v = make_float2(other, other);
  asm volatile("{\n.reg .pred p;\nsetp.ne.u32 p, %3, 0;\n@p ld.shared.v2.f32 {%0,%1}, [%2];\n}" : "+f"(v.x), "+f"(v.y) : "r"(a), "r"((uint32_t)on) : "memory");
  return v;
}
__device__ __forceinline__ void lds128(uint32_t* r, uint32_t a) {
  asm volatile("ld.shared.v4.u32 {%0,%1,%2,%3}, [%4];" : "=r"(r[0]), "=r"(r[1]), "=r"(r[2]), "=r"(r[3]) : "r"(a) : "memory");
}
__device__ __forceinline__ void lds64(uint32_t* r, uint32_t a) {
  asm volatile("ld.shared.v2.u32 {%0,%1}, [%2];" : "=r"(r[0]), "=r"(r[1]) : "r"(a) : "memory");
}
__device__ __forceinline__ uint32_t lds32(uint32_t a) {
  uint32_t v;
  asm volatile("ld.shared.u32 %0, [%1];" : "=r"(v) : "r"(a) : "memory");
  return v;
}
__device__ __forceinline__ void ldsm4(uint32_t* r, uint32_t a) {
  asm volatile("ldmatrix.sync.aligned.m8n8.x4.shared.b16 {%0,%1,%2,%3}, [%4];"
               : "=r"(r[0]), "=r"(r[1]), "=r"(r[2]), "=r"(r[3]) : "r"(a) : "memory");
}
__device__ __forceinline__ void ldsm4t(uint32_t* r, uint32_t a) {
  asm volatile("ldmatrix.sync.aligned.m8n8.x4.trans.shared.b16 {%0,%1,%2,%3}, [%4];"
               : "=r"(r[0]), "=r"(r[1]), "=r"(r[2]), "=r"(r[3]) : "r"(a) : "memory");
}
__device__ __forceinline__ void stsm4(uint32_t a, uint32_t r0, uint32_t r1, uint32_t r2, uint32_t r3) {
  asm volatile("stmatrix.sync.aligned.m8n8.x4.shared.b16 [%0], {%1,%2,%3,%4};"
               ::"r"(a), "r"(r0), "r"(r1), "r"(r2), "r"(r3) : "memory");
}
__device__ __forceinline__ void stsm4t(uint32_t a, uint32_t r0, uint32_t r1, uint32_t r2, uint32_t r3) {
  asm volatile("stmatrix.sync.aligned.m8n8.x4.trans.shared.b16 [%0], {%1,%2,%3,%4};"
               ::"r"(a), "r"(r0), "r"(r1), "r"(r2), "r"(r3) : "memory");
}
__device__ __forceinline__ void mma16816(float* d, const uint32_t* a, uint32_t b0, uint32_t b1) {
  asm volatile("mma.sync.aligned.m16n8k16.row.col.f32.bf16.bf16.f32 {%0,%1,%2,%3}, {%4,%5,%6,%7}, {%8,%9}, {%0,%1,%2,%3};"
               : "+f"(d[0]), "+f"(d[1]), "+f"(d[2]), "+f"(d[3])
               : "r"(a[0]), "r"(a[1]), "r"(a[2]), "r"(a[3]), "r"(b0), "r"(b1));
}
__device__ __forceinline__ void mma16816z(float* d, const uint32_t* a, uint32_t b0, uint32_t b1) {
  asm volatile("mma.sync.aligned.m16n8k16.row.col.f32.bf16.bf16.f32 {%0,%1,%2,%3}, {%4,%5,%6,%7}, {%8,%9}, {%10,%10,%10,%10};"
               : "=f"(d[0]), "=f"(d[1]), "=f"(d[2]), "=f"(d[3])
               : "r"(a[0]), "r"(a[1]), "r"(a[2]), "r"(a[3]), "r"(b0), "r"(b1), "f"(0.f));
}
__device__ __forceinline__ void mma1688(float* d, uint32_t a0, uint32_t a1, uint32_t b0) {
  asm volatile("mma.sync.aligned.m16n8k8.row.col.f32.bf16.bf16.f32 {%0,%1,%2,%3}, {%4,%5}, {%6}, {%0,%1,%2,%3};"
               : "+f"(d[0]), "+f"(d[1]), "+f"(d[2]), "+f"(d[3]) : "r"(a0), "r"(a1), "r"(b0));
}
__device__ __forceinline__ uint32_t movtrans(uint32_t a) {
  uint32_t d;
  asm volatile("movmatrix.sync.aligned.m8n8.trans.b16 %0, %1;" : "=r"(d) : "r"(a));
  return d;
}
__device__ __forceinline__ uint32_t mapa(uint32_t a, uint32_t rank) {
  uint32_t d;
  asm("mapa.shared::cluster.u32 %0, %1, %2;" : "=r"(d) : "r"(a), "r"(rank));
  return d;
}
__device__ __forceinline__ void st_async64(uint32_t a, uint32_t x, uint32_t y, uint32_t bar) {
  asm volatile("st.async.weak.shared::cluster.mbarrier::complete_tx::bytes.v2.b32 [%0], {%1,%2}, [%3];"
               ::"r"(a), "r"(x), "r"(y), "r"(bar) : "memory");
}
__device__ __forceinline__ void st_async64f(uint32_t a, float x, float y, uint32_t bar) {
  st_async64(a, __float_as_uint(x), __float_as_uint(y), bar);
}
__device__ __forceinline__ void bulk_s2s(uint32_t dst, uint32_t src, uint32_t bytes, uint32_t bar) {
  asm volatile("cp.async.bulk.shared::cluster.shared::cta.mbarrier::complete_tx::bytes [%0], [%1], %2, [%3];"
               ::"r"(dst), "r"(src), "r"(bytes), "r"(bar) : "memory");
}
__device__ __forceinline__ void tma_store_3d(const CUtensorMap* map, uint32_t src, int x, int y, int z) {
  asm volatile("cp.async.bulk.tensor.3d.global.shared::cta.bulk_group [%0, {%2, %3, %4}], [%1];"
               ::"l"(map), "r"(src), "r"(x), "r"(y), "r"(z) : "memory");
}
__device__ __forceinline__ void mbar_spin(uint32_t bar, uint32_t parity) {
  asm volatile("{\n.reg .pred p;\n.reg .b32 n;\nmov.u32 n, 0x100000;\nMW_L:\n"
               "mbarrier.try_wait.parity.shared::cta.b64 p, [%0], %1;\n@p bra.uni MW_D;\n"
               "add.s32 n, n, -1;\nsetp.ne.u32 p, n, 0;\n@p bra.uni MW_L;\nMW_D:\n}" ::"r"(bar), "r"(parity) : "memory");
}
__device__ __forceinline__ bool mbar_test(uint32_t bar, uint32_t parity) {
  uint32_t done;
  asm volatile("{\n.reg .pred p;\nmbarrier.test_wait.parity.shared::cta.b64 p, [%1], %2;\nselp.u32 %0, 1, 0, p;\n}"
               : "=r"(done) : "r"(bar), "r"(parity) : "memory");
  return done != 0;
}
__device__ __forceinline__ void mbar_arrive_remote(uint32_t bar) {
  asm volatile("mbarrier.arrive.shared::cluster.b64 _, [%0];" ::"r"(bar) : "memory");
}
__device__ __forceinline__ bool elect_one() {
  uint32_t r;
  asm volatile("{\n.reg .pred p;\nelect.sync _|p, 0xffffffff;\nselp.u32 %0, 1, 0, p;\n}" : "=r"(r));
  return r != 0;
}
__device__ __forceinline__ void st_async32(uint32_t a, uint32_t x, uint32_t bar) {
  asm volatile("st.async.weak.shared::cluster.mbarrier::complete_tx::bytes.b32 [%0], %1, [%2];" ::"r"(a), "r"(x), "r"(bar) : "memory");
}
#define named_bar_and(id, n, in, out) \
  asm volatile("{\n.reg .pred p, q;\nsetp.ne.u32 p, %1, 0;\nbar.red.and.pred q, %2, %3, p;\nselp.u32 %0, 1, 0, q;\n}" \
               : "=r"(out) : "r"(in), "n"(id), "n"(n) : "memory")
__device__ __forceinline__ void bulk_g2s(uint32_t dst, const void* src, uint32_t bytes, uint32_t bar) {
  asm volatile("cp.async.bulk.shared::cluster.global.mbarrier::complete_tx::bytes [%0], [%1], %2, [%3];"
               ::"r"(dst), "l"(src), "r"(bytes), "r"(bar) : "memory");
}
__device__ __forceinline__ void l2_prefetch(const void* p, uint32_t bytes) {
  asm volatile("cp.async.bulk.prefetch.L2.global [%0], %1;" ::"l"(p), "r"(bytes) : "memory");
}

__device__ __forceinline__ uint32_t clk32() { uint32_t c; asm volatile("mov.u32 %0, %%clock;" : "=r"(c)::"memory"); return c; }
__device__ __forceinline__ void spin_until(uint32_t t) { while ((int32_t)(clk32() - t) < 0) {} }
#define PIN(x) asm volatile("" : "+r"(x))
#define OPQ                                                                                     \
  int tid_o = tid;                                                                              \
  asm volatile("" : "+r"(tid_o));                                                               \
  const int lane = tid_o & 31, w = (tid_o >> 5) & 3, t7 = tid_o & 127, lg = lane >> 2,          \
            lq = lane & 3, mi = lane >> 3, mr = lane & 7;                                       \
  (void)w; (void)t7; (void)lg; (void)lq; (void)mi; (void)mr; (void)lane

#define SMAP                                                                                                          \
  const uint32_t SM0 = self + fk::SM0, WO = self + fk::WO, WS = self + fk::WS, XN = self + fk::XN, VX = self + fk::VX, \
                 QK = self + fk::QK, PT = self + fk::PT, SP = self + fk::SP, VM = self + fk::VM, OB = self + fk::OB,   \
                 RED = self + fk::RED, VX2 = self + fk::VX2, MEMB = self + fk::MEMB, B_XN = self + fk::B_XN, B_SM = self + fk::B_SM,       \
                 B_VM = self + fk::B_VM, B_VX = self + fk::B_VX, B_ST = self + fk::B_ST, B_PB = self + fk::B_PB,       \
                 B_W = self + fk::B_W, B_H2 = self + fk::B_H2, B_H1 = self + fk::B_H1, B_PF = self + fk::B_PF, B_WO = self + fk::B_WO, MASKS = self + fk::MASKS, PROBE = self + fk::PROBE;                             \
  (void)SM0; (void)WO; (void)WS; (void)XN; (void)VX; (void)QK; (void)PT; (void)SP; (void)VM; (void)OB; (void)RED; (void)VX2; \
  (void)MEMB; (void)B_XN; (void)B_SM; (void)B_VM; (void)B_VX; (void)B_ST; (void)B_PB; (void)B_W; (void)MASKS; (void)PROBE; (void)B_H2; (void)B_H1; (void)B_PF; (void)B_WO

struct FParams {
  CUtensorMap wq, wk, wv, wo, wo16, xn, xn12, o;
  CUtensorMap ta, tb, tx, tg, tout;
  const bf16 *mem0, *x;
  bf16* xn_ptr;
  uint64_t dxn;
  int nprobe;
  char* xch;
};

__device__ __forceinline__ uint2 probe_pair(char* p, uint32_t val, uint32_t dummy, int n) {
  uint2 best = make_uint2(0x7FFFFFFF, 0x7FFFFFFF);
  st_pub128(p, val); st_pub128(p + 16, val); st_pub128(p + 4096, val); st_pub128(p + 4112, val);
#pragma unroll 1
  for (int r = 0; r < n; r++) {
    uint32_t v;
    const uint32_t c0 = clk32();
    asm volatile("atom.relaxed.gpu.global.exch.b32 %0, [%1], %2;" : "=r"(v) : "l"(p + (r & 1) * 4096), "r"(val) : "memory");
    asm volatile("{\n.reg .pred p;\nsetp.eq.u32 p, %0, 0x12345678;\n@p st.shared.u32 [%1], %0;\n}" ::"r"(v), "r"(dummy) : "memory");
    const uint32_t d = clk32() - c0;
    if (r & 1) best.y = min(best.y, d); else best.x = min(best.x, d);
  }
  return best;
}

typedef uint32_t WRegs[6][2][4][4];

constexpr uint32_t nth_chunks(uint32_t mask) {
  uint32_t t = 0;
  for (int c = 0, n = 0; c < 10; c++) if ((mask >> c) & 1) t |= c << (4 * n++);
  return t;
}
constexpr uint64_t chunk_pos(uint32_t mask) {
  uint64_t t = 0;
  for (int c = 0, a = 0, b = 0; c < 10; c++) t |= (uint64_t)(((mask >> c) & 1) ? a++ : b++) << (4 * c);
  return t;
}
template <bool ISV> struct Chunks {
  static constexpr uint32_t MASK = ISV ? SMV : SMQ, SMT = nth_chunks(MASK), RFT = nth_chunks(~MASK & 1023);
  static_assert(!(MASK & 1), "the first chunk initialises the accumulators");
  static __device__ __forceinline__ constexpr int rf(int wg, int i) { return wg ? 10 + i : (RFT >> (4 * i)) & 15; }
  static __device__ __forceinline__ constexpr int sm(int i) { return (SMT >> (4 * i)) & 15; }
  static constexpr uint64_t IDX = chunk_pos(MASK);
  static __device__ __forceinline__ constexpr int idx(int c) { return (IDX >> (4 * c)) & 15; }
};

template <bool ISV, int WG> struct ProjCfg {
  static constexpr int N0 = ISV ? NS0V : NS0, NS = WG ? 8 - N0 : N0, P0 = WG ? N0 : 0, NTA = WG ? NTA1 : NTA0;
};
__device__ __forceinline__ void load_pair(uint32_t (&t)[4][4], uint32_t wsa, int pp) {
#pragma unroll
  for (int f = 0; f < 4; f++) ldsm4t(t[f], wsa + ((pp >> 1) * 2 + (f & 1)) * 8192 + ((pp & 1) * 2 + (f >> 1)) * 2048);
}
template <bool ISV, int WG>
__device__ __forceinline__ void proj_mem(const WRegs& wr, uint32_t (&ta)[ProjCfg<ISV, WG>::NTA][4][4], uint32_t wsa, uint32_t mba,
                                         float (&a0)[4], float (&a1)[4]) {
  constexpr int NS = ProjCfg<ISV, WG>::NS, P0 = ProjCfg<ISV, WG>::P0, NTA = ProjCfg<ISV, WG>::NTA, NP = 12 + NS;
  float acc[4][4];
  auto spos = [](int j) { return j < NTA ? j : j + (j - NTA + 1) * 12 / (NS - NTA > 0 ? NS - NTA : 1); };
  auto which = [&](int p) { int r = -1; for (int j = 0; j < NS; j++) if (spos(j) == p) r = j; return r; };
  auto nsm_before = [&](int p) { int n = 0; for (int j = 0; j < NS; j++) if (spos(j) < p) n++; return n; };
#pragma unroll
  for (int p = 0; p < NP; p++) {
    const int j = which(p), r = j >= 0 ? 0 : p - nsm_before(p);
    uint32_t bp[4], tl[4][4];
    ldsm4(bp, mba + (j >= 0 ? Chunks<ISV>::sm((P0 + (j >= 0 ? j : 0)) >> 1) * 1024 + ((P0 + j) & 1) * 512 : Chunks<ISV>::rf(WG, r >> 1) * 1024 + (r & 1) * 512));
    if (j >= NTA) load_pair(tl, wsa, P0 + j);
#pragma unroll
    for (int u = 0; u < 2; u++)
#pragma unroll
      for (int T = 0; T < 2; T++) {
        const uint32_t* a = j >= NTA ? tl[u * 2 + T] : j >= 0 ? ta[j >= 0 ? j % NTA : 0][u * 2 + T] : wr[r >> 1][T][(r & 1) * 2 + u];
        if (p == 0) mma16816z(acc[u * 2 + T], a, bp[2 * u], bp[2 * u + 1]);
        else mma16816(acc[u * 2 + T], a, bp[2 * u], bp[2 * u + 1]);
      }
  }
#pragma unroll
  for (int i = 0; i < 4; i++) { a0[i] = acc[0][i] + acc[2][i]; a1[i] = acc[1][i] + acc[3][i]; }
}
template <bool ISV, int WG, int J0, int J1>
__device__ __forceinline__ void proj_mem_prefetch(uint32_t (&ta)[ProjCfg<ISV, WG>::NTA][4][4], uint32_t wsa) {
#pragma unroll
  for (int j = J0; j < J1; j++) load_pair(ta[j], wsa, ProjCfg<ISV, WG>::P0 + j);
}

template <bool ISV, int WG>
__device__ __forceinline__ void proj_finish(const float (&a0)[4], const float (&a1)[4], uint32_t peer0, uint32_t peer1, uint32_t self, int tid, int warp,
                                            uint32_t (&vmo)[4]) {
  using namespace fk;
  SMAP;
  OPQ;
  if (!ISV) {
    stsm4(PT + mr * 16 + ((mi >> 1) ? WG * 1024 + w * 256 + (mi & 1) * 128 : 2048 + w * 512 + (mi & 1) * 256 + WG * 128),
          pack_bf16(a0[0], a0[1]), pack_bf16(a0[2], a0[3]), pack_bf16(a1[0], a1[1]), pack_bf16(a1[2], a1[3]));
    named_bar_sync(NB_C, 256);
  } else {
    if (WG == 0) sts128f(RED + t7 * 16, a1[0], a1[1], a1[2], a1[3]);
    else sts128f(RED + 2048 + t7 * 16, a0[0], a0[1], a0[2], a0[3]);
    if (WG == 1) { lds64(vmo, VM + t7 * 8); lds64(vmo + 2, VM + 1024 + t7 * 8); }
    named_bar_sync(NB_C, 256);
    const float4 p = lds128f(RED + (1 - WG) * 2048 + t7 * 16);
    const float* k = WG == 0 ? a0 : a1;
    const uint32_t v0 = pack_bf16(k[0] + p.x, k[1] + p.y), v1 = pack_bf16(k[2] + p.z, k[3] + p.w);
    const uint32_t off = VM + WG * 1024 + t7 * 8;
    if (VM_BULK) {
      sts64(off, v0, v1);
      fence_proxy_async_smem();
      __syncwarp();
      const uint32_t a = VM + WG * 1024 + warp * 256;
      if (elect_one()) {
        bulk_s2s(peer0 + a, a, 256, peer0 + B_VM);
        bulk_s2s(peer1 + a, a, 256, peer1 + B_VM);
        mbar_arrive(B_VM);
      }
    } else {
      st_async64(peer0 + off, v0, v1, peer0 + B_VM);
      st_async64(peer1 + off, v0, v1, peer1 + B_VM);
      sts64(off, v0, v1);
      __syncwarp();
      if (lane == 0) mbar_arrive(B_VM);
    }
  }
}

__device__ __forceinline__ void send_scores(float s0, float s1, uint32_t off, uint32_t peer0, uint32_t peer1, uint32_t bar, int lane) {
  if (SPACK) {
    const uint32_t v = pack_bf16(s0, s1);
    st_async32(peer0 + off, v, peer0 + bar);
    st_async32(peer1 + off, v, peer1 + bar);
    sts32(off, v);
  } else {
    st_async64f(peer0 + off, s0, s1, peer0 + bar);
    st_async64f(peer1 + off, s0, s1, peer1 + bar);
    sts64f(off, s0, s1);
  }
  __syncwarp();
  if (lane == 0) mbar_arrive(bar);
}

template <int MODE>
__device__ __forceinline__ void wo_load(uint32_t* r, int f, uint32_t woa, uint32_t wob, bool third) {
  constexpr int NT = MODE ? 3 : 2;
  if (MODE >= 2 && f % 3 == 2)
    asm volatile("{\n.reg .pred p;\nsetp.ne.u32 p, %5, 0;\nmov.b32 %0, 0;\nmov.b32 %1, 0;\nmov.b32 %2, 0;\nmov.b32 %3, 0;\n"
                 "@p ldmatrix.sync.aligned.m8n8.x4.trans.shared.b16 {%0,%1,%2,%3}, [%4];\n}"
                 : "=r"(r[0]), "=r"(r[1]), "=r"(r[2]), "=r"(r[3]) : "r"(wob + (f / 3) * 512), "r"((uint32_t)third) : "memory");
  else ldsm4t(r, woa + (f % NT) * 32768 + (f / NT) * 2048);
}
template <int MODE, int PF>
__device__ __forceinline__ void wo_phase(uint32_t (&wf)[PF][4], uint32_t woa, uint32_t wob, bool third, uint32_t oba, char* h1p,
                                         uint32_t sel, uint32_t tag) {
  constexpr int NT = MODE ? 3 : 2;
  float c[NT][4];
  uint32_t of[2][4];
  ldsm4t(of[0], oba);
#pragma unroll
  for (int k = 0; k < 8; k++) {
    if ((k & 1) == 0 && k + 2 < 8) ldsm4t(of[((k >> 1) + 1) & 1], oba + ((k >> 1) + 1) * 512);
#pragma unroll
    for (int i = 0; i < NT; i++) {
      const int f = k * NT + i;
      const uint32_t b0 = of[(k >> 1) & 1][2 * (k & 1)], b1 = of[(k >> 1) & 1][2 * (k & 1) + 1];
      if (k == 0) mma16816z(c[i], wf[f % PF], b0, b1); else mma16816(c[i], wf[f % PF], b0, b1);
      if (f + PF < 8 * NT) wo_load<MODE>(wf[f % PF], f + PF, woa, wob, third);
    }
  }
#pragma unroll
  for (int i = 0; i < NT; i++) {
    char* p = h1p + i * (8 * 32768) + ((sel >> (2 * i)) & 3) * 2048;
    const uint32_t tm = (sel >> 10) & 1;
    if (MODE < 2 || i < 2 || third) {
      st_pub32(p, (pack_bf16(c[i][0], c[i][1]) & ~tm) | (tag & tm));
      st_pub32(p + 1024, (pack_bf16(c[i][2], c[i][3]) & ~tm) | (tag & tm));
    }
  }
}
template <int MODE, int F0, int F1, int PF>
__device__ __forceinline__ void wo_prefetch(uint32_t (&wf)[PF][4], uint32_t woa, uint32_t wob, bool third) {
#pragma unroll
  for (int f = F0; f < F1; f++) wo_load<MODE>(wf[f], f, woa, wob, third);
}

template <bool ISV> __device__ __forceinline__ uint32_t tok_addr(uint32_t base, int tid) {
  OPQ;
  return ISV ? base + w * 2048 + (mi & 1) * 1024 + (mi >> 1) * 128 + mr * 16 : base + (mi >> 1) * 1024 + w * 256 + (mi & 1) * 128 + mr * 16;
}
template <bool ISV> __device__ __forceinline__ constexpr uint32_t tok_off(int T, int i) { return ISV ? T * 512 + i * 256 : T * 4096 + i * 2048; }
template <bool ISV, int T, bool ADD>
__device__ __forceinline__ void tok_store(const float (&x)[16], uint32_t a, const uint32_t (&p)[2][4]) {
#pragma unroll
  for (int i = 0; i < 2; i++) {
    uint32_t r[4];
#pragma unroll
    for (int k = 0; k < 4; k++)
      r[k] = !ADD ? pack_bf16(x[8 * i + 2 * k], x[8 * i + 2 * k + 1])
           : PADD ? add_bf16x2(pack_bf16(x[8 * i + 2 * k], x[8 * i + 2 * k + 1]), p[i][k])
                  : pack_bf16(x[8 * i + 2 * k] + bf_lo(p[i][k]), x[8 * i + 2 * k + 1] + bf_hi(p[i][k]));
    stsm4(a + tok_off<ISV>(T, i), r[0], r[1], r[2], r[3]);
  }
}

__device__ __forceinline__ void load_xn(const FParams& P, int seg, uint32_t self) {
  SMAP;
  mbar_expect_tx(B_XN, 49152);
  tma_load_3d(XN, &P.xn12, 0, seg * 32, 0, B_XN);
}

#define DESC_ADD(d, n) asm volatile("add.s64 %0, %0, %1;" : "+l"(d) : "n"(n))

template <bool ISV>
__device__ __forceinline__ void f_wg0(const FParams& P, const WRegs& wr, const int h, const int rank, const uint32_t hw, int tid) {
  using namespace fk;
  const uint32_t self = mapa(0, (hw >> (2 * rank)) & 3), peer0 = mapa(0, (hw >> (ISV ? 0 : 2 * (rank ^ 1))) & 3) - self,
                 peer1 = mapa(0, (hw >> (ISV ? 2 : 4)) & 3) - self;
  SMAP;
  const int tile0 = rank * 22;
  const uint32_t usel = __shfl_sync(0xffffffffu, tid, 0);
  const int warp = __shfl_sync(0xffffffffu, threadIdx.x >> 5, 0);
  constexpr int WMODE = ISV ? 0 : 2;
  const bool three = warp < 2;
  uint32_t h2ph = 1;
  tid ^= 0x5500;
#pragma unroll 1
  for (int s = -1;;) {
    uint32_t ta[ProjCfg<ISV, 0>::NTA][4][4], wsa, mba;
    const char* src = P.xch + H1_BYTES + ((s & 1) * 4 + warp) * 8192 + ((usel >> (16 + (s & 1))) & 1) * 4096;
    {
      const uint32_t ph = (s + 1) & 1;
      float x0[16], x1[16];
      uint32_t t_pub = 0;
      wg_fence();
      static_assert(Chunks<ISV>::MASK == 0x1E, "chunks 1 .. 4 are in shared memory");
      uint64_t db = P.dxn;
      auto rs_chunk = [&](int ci, bool pace) {
#pragma unroll
        for (int u = 0; u < 4; u++) {
          wgmma_rs_n32(x0, wr[ci][0][u], db, (ci | u) != 0);
          wgmma_rs_n32(x1, wr[ci][1][u], db, (ci | u) != 0);
          if (u < 3) DESC_ADD(db, 2); else DESC_ADD(db, 250);
          if (pace) { wg_commit(); wg_wait<2>(); wg_fence(); }
        }
      };
      rs_chunk(0, false);
      t_pub = clk32() - 60;
      PROF(0, 8); PROF(0, 1);
#pragma unroll
      for (int c = 1; c <= 4; c++) {
#pragma unroll
        for (int u = 0; u < 4; u++) {
          const uint64_t dx = make_desc(fk::XN + c * 4096 + u * 32, 16, 1024);
          wgmma_ss_n32_ta(x0, make_desc(fk::WS + (c - 1) * 16384 + u * 2048, 8192, 1024), dx, 1);
          wgmma_ss_n32_ta(x1, make_desc(fk::WS + (c - 1) * 16384 + 8192 + u * 2048, 8192, 1024), dx, 1);
          if (c == 4 && u == 1) { wg_commit(); wg_wait<1>(); named_bar_arrive(NB_XE, 160); wg_fence(); }
        }
        if (c == 3) wg_commit();
      }
      DESC_ADD(db, 1024);
#pragma unroll
      for (int c = 5; c < 10; c++) {
        if (c == 9) named_bar_arrive(NB_ST, 256);
        rs_chunk(c - 4, ((ISV ? PACEV : PACEQ) >> c) & 1);
      }
      wg_commit();
      wg_wait<0>();
      PROF(0, 10);
      const uint32_t tb = ISV ? (ph ? VX2 : VX) : QK;
      auto h2_issue = [&]() {
        spin_until(t_pub + (ISV ? D_H2V : D_H2));
        PROF(0, 13);
        if (elect_one()) { mbar_expect_tx(B_H2 + 8 * warp, 4096); bulk_g2s(MEMB + warp * 4096, src, 4096, B_H2 + 8 * warp); }
      };
      named_bar_sync(NB_CF, ISV ? 160 : 256);
      if ((ISV ? H2_ATV : H2_AT) == 0) h2_issue();
      const uint32_t none[2][4] = {}, tka = tok_addr<ISV>(tb, tid);
      tok_store<ISV, 0, false>(x0, tka, none);
      if ((ISV ? H2_ATV : H2_AT) == 1) h2_issue();
      tok_store<ISV, 1, false>(x1, tka, none);
      if ((ISV ? H2_ATV : H2_AT) == 2) h2_issue();
      named_bar_arrive(NB_DU, 256);
    }
    {
      OPQ;
      wsa = WS + ((mi >> 1) * 8 + mr) * 128 + (((2 * w + (mi & 1)) ^ mr) << 4);
      mba = MEMB + lane * 16;
      PIN(wsa); PIN(mba);
      {
        const uint32_t chk = MEMB + w * 4096 + lane * 32 + lg * 4, bar = B_H2 + 8 * warp;
        PROF(0, 11);
        proj_mem_prefetch<ISV, 0, 0, NPRE0>(ta, wsa);
#pragma unroll 1
        for (int tries = 0; tries < POLL_TRIES; tries++) {
          mbar_spin(bar, h2ph);
          h2ph ^= 1;
          const uint32_t mx = max(max(lds32(chk), lds32(chk + 1024)), max(lds32(chk + 2048), lds32(chk + 3072)));
          if (__all_sync(0xffffffffu, mx != EMPTY)) break;
          RETRY(1);
          if (elect_one()) { mbar_expect_tx(bar, 4096); bulk_g2s(MEMB + warp * 4096, src, 4096, bar); }
        }
      }
      PROF(0, 12);
      named_bar_arrive(NB_M1, 256);
      proj_mem_prefetch<ISV, 0, NPRE0, NTA0>(ta, wsa);
      named_bar_sync(NB_M0, 128);
    }
    s++;
    tid ^= 0x5500;
    {
      float a0[4], a1[4];
      proj_mem<ISV, 0>(wr, ta, wsa, mba, a0, a1);
      PROF(0, 2);
      uint32_t unused[4];
      proj_finish<ISV, 0>(a0, a1, peer0, peer1, self, tid, warp, unused);
      PROF(0, 3);
      if (s + 1 == cfg::NSEG) break;
      uint32_t wf[PF0][4], woa, wob;
      bool xn_ok;
      {
        OPQ;
        if (!ISV) {
          uint32_t qf[4][4], kf[2][4];
          const uint32_t qa = PT + 2048 + lane * 16, ka = QK + 4096 + w * 1024 + lane * 16;
          ldsm4t(qf[0], qa); ldsm4t(kf[0], ka); ldsm4t(qf[1], qa + 512);
          ldsm4t(qf[2], qa + 1024); ldsm4t(kf[1], ka + 512); ldsm4t(qf[3], qa + 1536);
          float c0[4], c1[4];
          mma16816z(c0, qf[0], kf[0][0], kf[0][1]);
          mma16816z(c1, qf[1], kf[0][2], kf[0][3]);
          mma16816(c0, qf[2], kf[1][0], kf[1][1]);
          mma16816(c1, qf[3], kf[1][2], kf[1][3]);
          const float s0 = (c0[0] + c0[2]) + (c1[0] + c1[2]), s1 = (c0[1] + c0[3]) + (c1[1] + c1[3]);
          send_scores(s0, s1, SP + rank * SP_SRC + t7 * SPW, peer0, peer1, B_SM, lane);
        }
        PROF(0, 4);
        woa = WO + 16384 + ((mi >> 1) * 8 + mr) * 128 + (((2 * w + (mi & 1)) ^ mr) << 4);
        wob = WO + 81920 + w * 4096 + ((mi >> 1) * 8 + mr) * 32 + (((mi & 1) ^ (mr >> 2)) << 4);
        uint32_t vf[2][2][4], vm[2][2];
        if (s == 0) mbar_spin(B_WO, 0);
        if (!ISV) mbar_spin(B_VX, s & 1);
        PROF(0, 14);
#pragma unroll
        for (int T = 0; T < 2; T++)
#pragma unroll
          for (int kk = 0; kk < 2; kk++) ldsm4(vf[T][kk], ((ISV && (s & 1)) ? VX2 : VX) + w * 2048 + (mi & 1) * 1024 + (mi >> 1) * 128 + mr * 16 + T * 512 + kk * 256);
        wo_prefetch<WMODE, 0, PF0A>(wf, woa, wob, three);
        uint32_t spa = SP + lane * SPW, vma = VM + t7 * 8, oa = OB + (mi >> 1) * 1024 + w * 256 + (mi & 1) * 128 + mr * 16;
        PIN(spa); PIN(vma); PIN(oa);
        mbar_spin(B_SM, s & 1);
        PROF(0, 5);
        float sc[10];
#pragma unroll
        for (int j = 0; j < 5; j++) {
          if (SPACK) {
            const uint32_t x = lds32(spa + j * 128), y = lds32(spa + SP_SRC + j * 128);
            sc[2 * j] = bf_lo(x) + bf_lo(y); sc[2 * j + 1] = bf_hi(x) + bf_hi(y);
          } else {
            const float2 x = lds64f(spa + j * 256), y = lds64f(spa + SP_SRC + j * 256);
            sc[2 * j] = x.x + y.x; sc[2 * j + 1] = x.y + y.y;
          }
        }
        const bool vm_ok = mbar_test(B_VM, s & 1);
        lds64(vm[0], vma); lds64(vm[1], vma + 1024);
        float m = fmaxf(fmaxf(fmaxf(sc[0], sc[1]), fmaxf(sc[2], sc[3])), fmaxf(fmaxf(sc[4], sc[5]), fmaxf(sc[6], sc[7])));
        m = fmaxf(m, fmaxf(sc[8], sc[9]));
        const float cs = 0.08838834764831845f * 1.4426950408889634f;
        uint32_t pb[5];
        m = fmaxf(m, __shfl_xor_sync(0xffffffffu, m, 1));
        m = fmaxf(m, __shfl_xor_sync(0xffffffffu, m, 2));
        if (ISV ? GATE_MX : GATE_Q) named_bar_arrive(NB_MX, 256);
        const float mc = -m * cs;
#pragma unroll
        for (int j = 0; j < 5; j++) pb[j] = pack_bf16(ex2_approx(fmaf(sc[2 * j], cs, mc)), ex2_approx(fmaf(sc[2 * j + 1], cs, mc)));
        PROF(0, 15);
        if (!vm_ok) { mbar_spin(B_VM, s & 1); lds64(vm[0], vma); lds64(vm[1], vma + 1024); }
        PROF(0, 6);
        float o0[4], o1[4], rs[4];
        const uint32_t ones[4] = {0x3F803F80u, 0x3F803F80u, 0x3F803F80u, 0x3F803F80u};
        mma16816z(rs, ones, pb[0], pb[1]);
        mma16816z(o0, vf[0][0], pb[0], pb[1]);
        mma16816z(o1, vf[1][0], pb[0], pb[1]);
        mma16816(rs, ones, pb[2], pb[3]);
        mma16816(o0, vf[0][1], pb[2], pb[3]);
        mma16816(o1, vf[1][1], pb[2], pb[3]);
        mma1688(rs, ones[0], ones[0], pb[4]);
        mma1688(o0, vm[0][0], vm[0][1], pb[4]);
        mma1688(o1, vm[1][0], vm[1][1], pb[4]);
        const float i0 = rcp_approx(rs[0]), i1 = rcp_approx(rs[1]);
        stsm4(oa, pack_bf16(o0[0] * i0, o0[1] * i1), pack_bf16(o0[2] * i0, o0[3] * i1),
              pack_bf16(o1[0] * i0, o1[1] * i1), pack_bf16(o1[2] * i0, o1[3] * i1));
      }
      {
        OPQ;
        named_bar_arrive(NB_O, 256);
        wo_prefetch<WMODE, PF0A, PF0>(wf, woa, wob, three);
        xn_ok = mbar_test(B_XN, (s + 1) & 1);
        char* h1p = P.xch + (tile0 + 4 + w) * 32768 + (h >> 3) * 8192 + (h & 7) * 128 + (((2 * lq + (lg & 1)) ^ (h & 7)) << 4) + (lg >> 1) * 4;
        uint32_t oba = OB + lane * 16;
        PIN(oba);
        PROF(0, 7);
        named_bar_sync(NB_O0, 128);
        const uint32_t tag = ((s >> 1) & 1) ^ 1;
        wo_phase<WMODE>(wf, woa, wob, three, oba, h1p, tid >> 8, tag);
        PROF(0, 9);
        if (!xn_ok) mbar_spin(B_XN, (s + 1) & 1);
        named_bar_sync(NB_HD, 256);
      }
    }
  }
}

template <bool ISV>
__device__ __forceinline__ void f_wg1(const FParams& P, const WRegs& wr, const int h, const int rank, const uint32_t hw, int tid) {
  using namespace fk;
  const uint32_t self = mapa(0, (hw >> (2 * rank)) & 3), peer0 = mapa(0, (hw >> (ISV ? 0 : 2 * (rank ^ 1))) & 3) - self,
                 peer1 = mapa(0, (hw >> (ISV ? 2 : 4)) & 3) - self;
  SMAP;
  const int tile0 = rank * 22;
  const uint32_t usel = __shfl_sync(0xffffffffu, tid, 0);
  const int warp = __shfl_sync(0xffffffffu, (threadIdx.x >> 5) & 3, 0);
  constexpr int WMODE = 1;
  uint32_t h1ph = 0;
  auto o_done = [&](int mb) {
    tma_store_wait_all();
    asm volatile("fence.proxy.async.global;" ::: "memory");
    asm volatile("red.relaxed.gpu.global.add.u32 [%0], 1;" ::"l"(&g_oflag[mb]) : "memory");
  };
  uint32_t vmo[4] = {0, 0, 0, 0};
  if (ISV) {
    OPQ;
    sts32(PT + (t7 >> 2) * 128 + ((5 ^ lg) << 4) + lq * 4, 0);
    sts32(PT + (t7 >> 2) * 128 + ((6 ^ lg) << 4) + lq * 4, 0);
  }
  tid ^= 0x5500;
#pragma unroll 1
  for (int s = -1;;) {
    uint32_t ta[ProjCfg<ISV, 1>::NTA][4][4], wsa, mba;
    if (s + 1 < cfg::NSEG) mbar_spin(B_XN, (s + 1) & 1);
    const uint32_t t_pub = clk32();
    auto refill = [&]() {
      if (warp == 3) {
        named_bar_sync(NB_XE, 160);
        if (elect_one()) {
          mbar_expect_tx(B_XN + 8, 16384);
          tma_load_3d(XN, &P.xn, 0, (s + 1) * 32, 12, B_XN + 8);
        }
      }
    };
    auto arm = [&]() {
      if ((tid & 255) == 160) {
        if (s == 1) st_pub32(&g_mask[3 * h + rank], 0);
        if (s + 2 < cfg::NSEG) { mbar_expect_tx(B_SM, ISV ? 2 * SP_SRC : SP_SRC); if (!ISV) mbar_expect_tx(B_VX, 8192); }
        if (!ISV && s + 1 < cfg::NSEG) mbar_expect_tx(B_VM, 2048);
        if (ISV && s >= 1 && s < cfg::NSEG) mbar_expect_tx(B_ST, 7168);
      }
      if (ISV && s < cfg::NSEG && (tid & 254) == 192) mbar_arrive_remote(((tid & 1) ? peer1 : peer0) + B_ST);
      __syncwarp();
    };
    if (ISV) {
      if (s >= 0) arm();
      if (s >= 1) {
        OPQ;
        if (warp == 0 && (s & 3) == 1 && s > 1) { if (elect_one()) o_done((s - 2) >> 2); }
        const uint32_t vb = (s & 1) ? VX : VX2;
        float x0[16], x1[16];
        wg_fence();
        wgmma_rs_n32(x0, vmo, make_desc(fk::PT + 64, 16, 1024), 0);
        wgmma_rs_n32(x1, vmo, make_desc(fk::PT + 96, 16, 1024), 0);
#pragma unroll
        for (int kk = 0; kk < 2; kk++) {
          wgmma_ss_n32(x0, make_desc0(vb + kk * 256, 128, 1024), make_desc(fk::PT + kk * 32, 16, 1024), 1);
          wgmma_ss_n32(x1, make_desc0(vb + 512 + kk * 256, 128, 1024), make_desc(fk::PT + kk * 32, 16, 1024), 1);
        }
        wg_commit();
        wg_wait<0>();
        named_bar_sync(NB_W1, 128);
        PROF(1, 4);
        const uint32_t stg = vb + (8 * (mi >> 1) + mr) * 128 + (((2 * w + (mi & 1)) ^ mr) << 4);
#pragma unroll
        for (int T = 0; T < 2; T++) {
          const float* x = T ? x1 : x0;
#pragma unroll
          for (int jj = 0; jj < 4; jj += 2)
            stsm4t(stg + T * 4096 + jj * 1024, pack_bf16(x[4 * jj], x[4 * jj + 1]), pack_bf16(x[4 * jj + 2], x[4 * jj + 3]),
                   pack_bf16(x[4 * jj + 4], x[4 * jj + 5]), pack_bf16(x[4 * jj + 6], x[4 * jj + 7]));
        }
        fence_proxy_async_smem();
        named_bar_sync(NB_W1, 128);
        PROF(1, 10);
        if (warp == 0) {
          if (elect_one()) {
            tma_store_3d(&P.o, vb, 0, (s - 1) * 32, 2 * h);
            tma_store_commit();
          }
          __syncwarp();
        }
        if (s == cfg::NSEG) break;
      }
      if (s + 1 < cfg::NSEG) refill();
      PROF(1, 11);
    } else if (s < 0) {
      named_bar_arrive(NB_CF, 256);
      refill();
    } else {
      float x[24];
      wg_fence();
#pragma unroll
      for (int k = 0; k < 4; k++) wgmma_ss_n48_tt(x, make_desc0(fk::QK + k * 256, 128, 1024), make_desc0(fk::QK + 4096 + k * 256, 128, 1024), k != 0);
      wg_commit();
      arm();
      auto send_tok = [&]() {
        if (warp < 2) {
          OPQ;
          const uint32_t d0 = peer1 + QK + rank * 3584 + lane * 8 + w * 1280, d1 = d0 + 512 + w * 512, bar = peer1 + B_ST;
          mbar_spin(B_ST, s & 1);
          const float NEG = -500000000.0f / 0.08838834764831845f;
          const bool m0 = 2 * lq > lg, m1 = 2 * lq + 1 > lg;
          st_async64f(d0, x[16] + x[20], x[17] + x[21], bar);
          st_async64f(d1, x[18] + x[22], x[19] + x[23], bar);
          st_async64f(d1 + 256, x[2], x[3], bar);
          if (warp == 0) {
            st_async64f(d0 + 256, m0 ? NEG : x[0], m1 ? NEG : x[1], bar);
            st_async64f(d1 + 512, m0 ? NEG : x[6], m1 ? NEG : x[7], bar);
          } else {
            st_async64f(d0 + 256, x[0], x[1], bar);
            st_async64f(d1 + 512, x[6], x[7], bar);
            st_async64f(d0 + 512, x[4], x[5], bar);
            st_async64f(d0 + 768, m0 ? NEG : x[8], m1 ? NEG : x[9], bar);
            st_async64f(d1 + 768, x[10], x[11], bar);
            st_async64f(d1 + 1024, m0 ? NEG : x[14], m1 ? NEG : x[15], bar);
          }
        }
        PROF(1, 4);
      };
      const bool fin = s + 1 == cfg::NSEG;
      OPQ;
      const int j = 2 * h + rank;
      const char* src = P.xch + j * 32768 + warp * 8192 + (((usel >> 14) & 2) + (s & 1)) * 2048;
      char* dst = P.xch + H1_BYTES + (j >> 4) * 8192 + (lq >> 1) * 4096 + (j & 15) * 256 + (lq & 1) * 128 + (2 * w + (lg & 1)) * 16 + (lg >> 1) * 4;
      const uint32_t chk = VX + mi * 2048 + mr * 128 + (w ^ (mr >> 1)) * 32 + ((lane & 1) + 2 * mi) * 4;
      const uint32_t tmask = (s >> 1) & 1;
      if (!fin) {
        spin_until(t_pub + D_H1);
        if (elect_one()) { mbar_expect_tx(B_H1, 2048); bulk_g2s(VX + warp * 2048, src, 2048, B_H1); }
      }
      __syncwarp();
      wg_wait<0>();
      PROF(1, 6);
      send_tok();
      if (fin) { mbar_spin(B_VM, s & 1); break; }
      named_bar_arrive(NB_CF, 256);
      if (REFILL_EARLY) refill();
#pragma unroll 1
      for (int tries = 0; tries < POLL_TRIES; tries++) {
        float d0[4], d1[4], d2[4], d3[4];
        mbar_spin(B_H1, h1ph);
        h1ph ^= 1;
        PROF(1, 10);
        const uint32_t t0 = lds32(chk), t1 = lds32(chk + 1024);
        wg_fence();
        const uint64_t ones = (uint64_t)(fk::ONES >> 4);
        wgmma_ss_n8_ta(d0, make_desc(fk::VX, 8192, 2048), ones, 0);
        wgmma_ss_n8_ta(d1, make_desc(fk::VX + 1024, 8192, 2048), ones, 0);
        wgmma_ss_n8_ta(d2, make_desc(fk::VX + 4096, 8192, 2048), ones, 0);
        wgmma_ss_n8_ta(d3, make_desc(fk::VX + 5120, 8192, 2048), ones, 0);
        wg_commit();
        uint32_t tt;
        asm volatile("lop3.b32 %0, %1, %2, %3, 0x42;" : "=r"(tt) : "r"(t0), "r"(t1), "r"(tmask) : "memory");
        uint32_t ok;
        named_bar_and(NB_W1, 128, tt & 1, ok);
        if (!ok) { if (elect_one()) { mbar_expect_tx(B_H1, 2048); bulk_g2s(VX + warp * 2048, src, 2048, B_H1); } }
        wg_wait<0>();
        if (ok) {
          st_pub32(dst + (s & 1) * 32768, (lq & 1) ? pack_bf16(d1[0] + d3[0], d1[2] + d3[2]) : pack_bf16(d0[0] + d2[0], d0[2] + d2[2]));
          PROF(1, 12);
          st_pub32(dst + ((s & 1) ^ 1) * 32768, EMPTY);
          break;
        }
        RETRY(0);
      }
      named_bar_sync(NB_W1, 128);
      if ((tid & 255) == 192) mbar_arrive_remote(peer1 + B_PF);
      __syncwarp();
      if (!REFILL_EARLY) refill();
      PROF(1, 11);
    }
    if (!ISV || s + 1 < cfg::NSEG) {
      const uint32_t ph = (s + 1) & 1;
      float x0[16], x1[16];
      uint64_t db = P.dxn + 10 * 256;
      named_bar_sync(NB_ST, 256);
      wg_fence();
#pragma unroll
      for (int c = 0; c < 6; c++) {
        if (c == 2) { mbar_spin(B_XN + 8, ph); wg_fence(); }
        if (ISV && c == CF_AT) {
          if (warp == 0) {
            if (elect_one()) tma_store_wait_read();
            __syncwarp();
            named_bar_arrive(NB_CF, 160);
          }
          wg_fence();
        }
#pragma unroll
        for (int u = 0; u < 4; u++) {
          wgmma_rs_n32(x0, wr[c][0][u], db, (c | u) != 0);
          wgmma_rs_n32(x1, wr[c][1][u], db, (c | u) != 0);
          if (u < 3) DESC_ADD(db, 2); else if (c == 1) DESC_ADD(db, 250 - 12 * 256); else DESC_ADD(db, 250);
        }
      }
      wg_commit();
      OPQ;
      const uint32_t tb = ISV ? (ph ? VX2 : VX) : QK, tka = tok_addr<ISV>(tb, tid);
      uint32_t p0[2][4], p1[2][4];
      named_bar_sync(NB_DU, 256);
      ldsm4(p1[0], tka + tok_off<ISV>(1, 0)); ldsm4(p1[1], tka + tok_off<ISV>(1, 1));
      ldsm4(p0[0], tka + tok_off<ISV>(0, 0)); ldsm4(p0[1], tka + tok_off<ISV>(0, 1));
      if (ISV && s >= 0) mbar_spin(B_PF, s & 1);
      wg_wait<0>();
      PROF(1, 13);
      tok_store<ISV, 1, true>(x1, tka, p1);
      tok_store<ISV, 0, true>(x0, tka, p0);
      if (ISV && s + 2 < cfg::NSEG) {
        fence_proxy_async_smem();
        __syncwarp();
        if (elect_one()) {
          bulk_s2s(peer0 + VX + warp * 2048, tb + warp * 2048, 2048, peer0 + B_VX);
          bulk_s2s(peer1 + VX + warp * 2048, tb + warp * 2048, 2048, peer1 + B_VX);
        }
      }
      wsa = WS + ((mi >> 1) * 8 + mr) * 128 + (((2 * w + (mi & 1)) ^ mr) << 4);
      mba = MEMB + lane * 16;
      PIN(wsa); PIN(mba);
      proj_mem_prefetch<ISV, 1, 0, NTA1>(ta, wsa);
      PROF(1, 14);
      named_bar_sync(NB_M1, 256);
      s++;
      PROF(1, 1);
      float a0[4], a1[4];
      proj_mem<ISV, 1>(wr, ta, wsa, mba, a0, a1);
      PROF(1, 2);
      proj_finish<ISV, 1>(a0, a1, peer0, peer1, self, tid, warp, vmo);
      PROF(1, 3);
    } else {
      OPQ;
      mbar_spin(B_VM, s & 1);
      lds64(vmo, VM + t7 * 8); lds64(vmo + 2, VM + 1024 + t7 * 8);
      s++;
    }
    tid ^= 0x5500;
    const bool last = s + 1 >= cfg::NSEG;
    constexpr int PFW = ISV ? PF1V : PF1;
    uint32_t wf[PFW][4], woa;
    if (ISV) {
      OPQ;
      woa = WO + ((mi >> 1) * 8 + mr) * 128 + (((2 * w + (mi & 1)) ^ mr) << 4);
      if (s >= 1) {
        const uint32_t sa = QK + ((w * (w + 3)) >> 1) * 256 + lane * 8;
        mbar_spin(B_ST, (s - 1) & 1);
        float sc[10];
        {
          const float NEG = -1000000000.0f / 0.08838834764831845f;
          float2 x[5], y[5];
#pragma unroll
          for (int b = 0; b < 5; b++) {
            x[b] = b < 2 ? lds64f(sa + b * 256) : lds64f_if(sa + b * 256, b <= w + 1, NEG);
            y[b] = b < 2 ? lds64f(sa + 3584 + b * 256) : lds64f_if(sa + 3584 + b * 256, b <= w + 1, 0.f);
          }
#pragma unroll
          for (int b = 0; b < 5; b++) { sc[2 * b] = x[b].x + y[b].x; sc[2 * b + 1] = x[b].y + y[b].y; }
        }
        float m = fmaxf(fmaxf(fmaxf(sc[0], sc[1]), fmaxf(sc[2], sc[3])), fmaxf(fmaxf(sc[4], sc[5]), fmaxf(sc[6], sc[7])));
        m = fmaxf(m, fmaxf(sc[8], sc[9]));
        m = fmaxf(m, __shfl_xor_sync(0xffffffffu, m, 1));
        m = fmaxf(m, __shfl_xor_sync(0xffffffffu, m, 2));
        const float cs = 0.08838834764831845f * 1.4426950408889634f;
#pragma unroll
        for (int i = 0; i < 10; i++) sc[i] = ex2_approx((sc[i] - m) * cs);
        float sum = ((sc[0] + sc[1]) + (sc[2] + sc[3])) + ((sc[4] + sc[5]) + (sc[6] + sc[7])) + (sc[8] + sc[9]);
        sum += __shfl_xor_sync(0xffffffffu, sum, 1);
        sum += __shfl_xor_sync(0xffffffffu, sum, 2);
        const float inv = rcp_approx(sum);
        const uint32_t pa = PT + (w * 8 + mr) * 128, pm = pack_bf16(sc[0] * inv, sc[1] * inv);
        stsm4(pa + ((mi ^ mr) << 4), pack_bf16(sc[2] * inv, sc[3] * inv), pack_bf16(sc[4] * inv, sc[5] * inv),
              pack_bf16(sc[6] * inv, sc[7] * inv), pack_bf16(sc[8] * inv, sc[9] * inv));
        asm volatile("stmatrix.sync.aligned.m8n8.x2.shared.b16 [%0], {%1,%1};" ::"r"(pa + ((((mi & 1) ? 7 : 4) ^ mr) << 4)), "r"(pm) : "memory");
      }
      if (warp == 3 && !last) {
        mbar_spin(B_VM, s & 1);
        if (elect_one()) load_xn(P, s + 1, self);
      }
      PROF(1, 5);
    } else {
      if (warp == 0) {
        OPQ;
        uint32_t kf[4][4], qf[4][4];
        float c0[4], c1[4], d0[4], d1[4];
        const uint32_t ka = PT + (mi >> 1) * 1024 + (mi & 1) * 128 + mr * 16;
#pragma unroll
        for (int k = 0; k < 4; k++) { ldsm4t(qf[k], PT + 2048 + k * 512 + lane * 16); ldsm4t(kf[k], ka + k * 256); }
        mma16816z(c0, qf[0], kf[0][0], kf[0][1]); mma16816z(c1, qf[0], kf[0][2], kf[0][3]);
        mma16816z(d0, qf[1], kf[1][0], kf[1][1]); mma16816z(d1, qf[1], kf[1][2], kf[1][3]);
        mma16816(c0, qf[2], kf[2][0], kf[2][1]); mma16816(c1, qf[2], kf[2][2], kf[2][3]);
        mma16816(d0, qf[3], kf[3][0], kf[3][1]); mma16816(d1, qf[3], kf[3][2], kf[3][3]);
        const float s0 = ((c0[0] + c0[2]) + (c1[0] + c1[2])) + ((d0[0] + d0[2]) + (d1[0] + d1[2]));
        const float s1 = ((c0[1] + c0[3]) + (c1[1] + c1[3])) + ((d0[1] + d0[3]) + (d1[1] + d1[3]));
        if (!last) send_scores(s0, s1, SP + rank * SP_SRC + (128 + lane) * SPW, peer0, peer1, B_SM, lane);
        PROF(1, 5);
      } else {
        const uint32_t t_c = clk32() + lds32(B_XN) * 0;
        if (warp == 3 && !last) { if (elect_one()) load_xn(P, s + 1, self); }
        spin_until(t_c + D_ST);
      }
      OPQ;
      woa = WO + ((mi >> 1) * 8 + mr) * 128 + (((2 * w + (mi & 1)) ^ mr) << 4);
    }
    if (!last) {
      OPQ;
      uint32_t oba = OB + lane * 16;
      if (s == 0) mbar_spin(B_WO, 0);
      if (!ISV) wo_prefetch<WMODE, 0, PF1Q>(wf, woa, 0, true);
      if (ISV ? GATE_MX : GATE_Q) named_bar_sync(NB_MX, 256);
      wo_prefetch<WMODE, ISV ? 0 : PF1Q, PFW>(wf, woa, 0, true);
      char* h1p = P.xch + (tile0 + w) * 32768 + (h >> 3) * 8192 + (h & 7) * 128 + (((2 * lq + (lg & 1)) ^ (h & 7)) << 4) + (lg >> 1) * 4;
      fence_proxy_async_smem();
      PROF(1, 7);
      named_bar_sync(NB_O, 256);
      PROF(1, 8);
      wo_phase<WMODE>(wf, woa, 0, true, oba, h1p, tid >> 8, ((s >> 1) & 1) ^ 1);
      PROF(1, 9);
      named_bar_sync(NB_HD, 256);
    } else {
      fence_proxy_async_smem();
      named_bar_sync(NB_W1, 128);
    }
  }
  if (ISV && warp == 0) { if (elect_one()) o_done(15); }
}

template <bool ISV, int WG>
__device__ __forceinline__ void f_main(const FParams& P, const int h, const int rank, const uint32_t hw) {
  using namespace fk;
  const uint32_t self = mapa(0, (hw >> (2 * rank)) & 3);
  SMAP;
  const int tid = __shfl_sync(0xffffffffu, threadIdx.x, threadIdx.x & 31);
  const int tile0 = rank * 22, ntile = ISV ? 20 : 22;
  const CUtensorMap* m0 = ISV ? &P.wv : &P.wq;
  const CUtensorMap* m1 = ISV ? &P.wv : &P.wk;
  const int col0 = h * 128 + (ISV ? 0 : 64 * rank), col1 = h * 128 + (ISV ? 64 : 64 * rank);
  WRegs wr;
  uint32_t sel = 0;
  {
    OPQ;
    const uint32_t a = SM0 + WG * 16384 + ((mi >> 1) * 8 + mr) * 128 + (((2 * w + (mi & 1)) ^ mr) << 4);
    uint2 mi0 = make_uint2(0, 0);
    if (!ISV && WG == 1) mi0 = *reinterpret_cast<const uint2*>(P.mem0 + ((lane >> 1) & 7) * cfg::D + (2 * h + rank) * 16 + (lane >> 4) * 8 + (lane & 1) * 4);
#pragma unroll
    for (int i = 0; i < 6; i++) {
      if (i == MASK_AT && WG == 1 && w == 1) {
        uint4 v;
#pragma unroll 1
        for (int tries = 0; tries < POLL_TRIES; tries++) {
          asm volatile("ld.acquire.gpu.global.v4.u32 {%0,%1,%2,%3}, [%4];" : "=r"(v.x), "=r"(v.y), "=r"(v.z), "=r"(v.w)
                       : "l"(&g_mask[4 * min(lane, 23)]) : "memory");
          if (__all_sync(0xffffffffu, v.x & v.y & v.z & v.w & 0x100)) break;
          __nanosleep(100);
        }
        sts128(OB + lane * 16, v.x, v.y, v.z, v.w);
      }
      mbar_wait(B_PB + 8 * i, 0);
      PRO(8 + i);
#pragma unroll
      for (int T = 0; T < 2; T++)
#pragma unroll
        for (int u = 0; u < 4; u++) ldsm4t(wr[i][T][u], a + i * 32768 + T * 8192 + u * 2048);
      named_bar_sync(NB_C, 256);
      if (WG == 1 && w == (i & 3)) {
        if (elect_one()) {
          if (i <= 2 && i + PRE_G < 6) {
#pragma unroll 1
            for (int n = 2 * (i + PRE_G); n < (i == 2 ? 12 : 2 * (i + PRE_G) + 2); n++) {
              const int ii = n >> 1, row = Chunks<ISV>::rf(n & 1, ii) * 64;
              if (!(n & 1)) mbar_expect_tx(B_PB + 8 * ii, 32768);
              tma_load_2d(SM0 + n * 16384, m0, col0, row, B_PB + 8 * ii);
              tma_load_2d(SM0 + n * 16384 + 8192, m1, col1, row, B_PB + 8 * ii);
            }
          }
          if (i == 3 || i == 4) {
            const int p0 = i == 3 ? 0 : 5, p1 = i == 3 ? 5 : 8;
            mbar_expect_tx(B_W, (p1 - p0) * 8192);
#pragma unroll 1
            for (int p = p0; p < p1; p++) tma_load_2d(WS + p * 8192, (p & 1) ? m1 : m0, (p & 1) ? col1 : col0, Chunks<ISV>::sm(p >> 1) * 64, B_W);
          }
          if (i == 5) {
            asm volatile("fence.proxy.async.global;" ::: "memory");
            load_xn(P, 0, self);
          }
          if (i == WO_AT) {
            mbar_expect_tx(B_WO, ntile * 4096);
#pragma unroll 1
            for (int t = 0; t < 5; t++) tma_load_2d(WO + t * 16384, &P.wo, tile0 * 16 + t * 64, h * 128, B_WO);
            if (!ISV) {
              tma_load_2d(WO + 81920, &P.wo16, tile0 * 16 + 320, h * 128, B_WO);
              tma_load_2d(WO + 86016, &P.wo16, tile0 * 16 + 336, h * 128, B_WO);
            }
          }
        }
      }
    }
    PROF2(1);
    if (!ISV && WG == 1 && w < 2) st_pub64(P.xch + H1_BYTES + 32768 + (h >> 3) * 8192 + w * 4096 + ((2 * h + rank) & 15) * 256 + lane * 8, mi0.x, mi0.y);
    if (blockIdx.x == 2 && tid == 160) { __threadfence(); st_pub128(g_lnok, 0x100); }
#pragma unroll
    for (int i = 0; i < 3; i++) {
      const int t = min(tile0 + 8 * i + w + (WG ? 0 : 4), 63);
      sel |= ((lds32(OB + ((t >> 1) * 3 + (t & 1)) * 4) >> (h >> 3)) & 1) << (2 * i + 1);
    }
    const uint32_t own = lds32(OB + (3 * h + rank) * 4) >> w, m2 = lds32(OB + (3 * h + 2) * 4) >> w;
    sel |= (own & 1) << 7 | (m2 & 1) << 8 | (m2 & 16) << 5;
    sel |= (((((lg ^ h) & 1) << 2) | (lg >> 1)) == (h & 1) + 2 * (h >> 3)) << 10;
  }
  asm volatile("barrier.cluster.wait.aligned;" ::: "memory");
  PRO(14);
  mbar_wait(B_W, 0);
  mbar_wait(B_XN, 0);
  PRO(15);
  PROF2(4);
  GTSYNC(0);
  PROF2(2);
  KT_END(8);
  if (WG == 0) f_wg0<ISV>(P, wr, h, rank, hw, tid | sel << 8); else f_wg1<ISV>(P, wr, h, rank, hw, tid | sel << 8);
}

__device__ __forceinline__ void f_tail(const FParams& P, const int h, const uint32_t rank, const bool isv) {
  using namespace fk;
  const uint32_t self = mapa(0, rank), base = self + SM0;
  const uint32_t FULL = self + SP, EMPT = FULL + 32, RES = FULL + 64, NOG = FULL + 72;
  const int tid = threadIdx.x, lane = tid & 31, wv = __shfl_sync(0xffffffffu, tid >> 5, 0), wg = wv >> 2;
  const int kq = h & 3, nt = (h >> 2) & 3, mb = TAIL_MB0 + 3 * (h >> 4) + rank;
  auto a_off = [](uint32_t st) { return (0x98685800u >> (8 * st) & 255) * 1024; };
  auto b_off = [](uint32_t st) { return (0xA8783010u >> (8 * st) & 255) * 1024; };
  static_assert(VX2 - SM0 == 80 * 1024 && VX - SM0 == 200 * 1024, "stage layout");
  auto load_b = [&](int kb) {
    const uint32_t sb = base + b_off(kb & 3), full = FULL + 8 * (kb & 3);
    mbar_expect_tx(full, 49152);
    tma_load_2d_mc(sb + rank * 8192, &P.tb, nt * 256 + ((rank + kq) & 3) * 64, (kq * 16 + kb) * 64, full, 7);
    if (kb % 3 == rank) tma_load_2d_mc(sb + 3 * 8192, &P.tb, nt * 256 + ((3 + kq) & 3) * 64, (kq * 16 + kb) * 64, full, 7);
  };
  auto load_a = [&](int kb) { tma_load_2d(base + a_off(kb & 3), &P.ta, (kq * 16 + kb) * 64, mb * 128, FULL + 8 * (kb & 3)); };
  TL(0);
  TL2(128, 10); TL2(160, 11);
  if (wv == 0) {
    if (elect_one()) {
      prefetch_tmap(&P.tb); prefetch_tmap(&P.ta);
      if (isv) mbar_spin(self + B_VM, (cfg::NSEG - 1) & 1);
      for (int i = 0; i < 4; i++) { mbar_init(FULL + 8 * i, 1); mbar_init(EMPT + 8 * i, 24); }
      mbar_init(RES, 1);
      fence_barrier_init();
      mbar_arrive_cluster(self + B_W, rank == 0 ? 1 : 0);
      mbar_arrive_cluster(self + B_W, rank == 2 ? 1 : 2);
      mbar_spin(self + B_W, 1);
#pragma unroll 1
      for (int kb = 0; kb < 4; kb++) load_b(kb);
      TL2(0, 12);
      wait_count(&g_oflag[mb], 32);
      asm volatile("fence.proxy.async.global;" ::: "memory");
      TL2(0, 13);
#pragma unroll 1
      for (int kb = 0; kb < 4; kb++) load_a(kb);
      TL2(0, 14);
    }
  }
  if (wv == 1) {
    if (lane == 0) {
      prefetch_tmap(&P.tx); prefetch_tmap(&P.tg); prefetch_tmap(&P.tout);
      uint32_t gc;
      asm volatile("ld.acquire.gpu.global.u32 %0, [%1];" : "=r"(gc) : "l"(&g_cnt[3][mb]) : "memory");
      const bool ng = gc < GATE_CNT && ld_strong4(&g_next) == 0;
      sts32(NOG, ng ? 1 : gc < GATE_CNT ? 2 : 0);
      if (ng) g_tfix[blockIdx.x] = 1;
      asm volatile("cp.async.bulk.prefetch.tensor.2d.L2.global [%0, {%1, %2}];" ::"l"(&P.tx), "r"(nt * 256 + kq * 64), "r"(mb * 128) : "memory");
    }
  } else if (wv == 2 || wv == 3) {
#pragma unroll 2
    for (int i = tid - 64; i < 3072; i += 64) st_pub128(&g_tpart[blockIdx.x][0][0][0] + i, EMPTY);
  }
  float acc[128];
  __syncthreads();
  KT_START(7);
  const uint32_t gate = lds32(NOG);
  const bool nog = gate == 1;
  if (gate) TL(15); else TL(15);
#pragma unroll 1
  for (int kb = 0; kb < 16; kb++) {
    const uint32_t st = kb & 3, sa = base + a_off(st) + wg * 8192, sb = base + b_off(st);
    mbar_spin(FULL + 8 * st, (kb >> 2) & 1);
    if (kb == 0) TL(2);
    if (kb == 4) TL(3);
    if (kb == 10) TL(4);
    wg_fence();
#pragma unroll
    for (int k = 0; k < 4; k++) {
      wgmma_ss_n256_tb(acc, make_desc(sa + k * 32, 16, 1024), make_desc(sb + k * 2048, 8192, 1024), (kb | k) != 0);
      if (k == 0) {
        wg_commit();
        wg_wait<1>();
        if (kb > 0 && kb <= 13 && lane < 3) mbar_arrive_cluster(EMPT + 8 * ((kb - 1) & 3), lane);
        wg_fence();
      }
    }
    wg_commit();
    if (kb >= 2 && kb < 15 && wv == ((kb & 1) << 2)) {
      if (elect_one()) {
        mbar_spin(EMPT + 8 * ((kb - 2) & 3), ((kb - 2) >> 2) & 1);
        if (kb < 14) {
          load_b(kb + 2);
          load_a(kb + 2);
        } else if (nog) {
          mbar_arrive(RES);
        } else {
          if (gate) wait_count(&g_cnt[3][mb], GATE_CNT);
          asm volatile("fence.proxy.async.global;" ::: "memory");
          mbar_expect_tx(RES, 32768);
          tma_load_2d(base, &P.tx, nt * 256 + kq * 64, mb * 128, RES);
          tma_load_2d(base + 16384, &P.tg, nt * 256 + kq * 64, mb * 128, RES);
        }
      }
      __syncwarp();
    }
  }
  wg_wait<0>();
  TL(5);
#pragma unroll
  for (int j = 1; j < 4; j++) {
    uint4* dst = &g_tpart[((h & ~3) + ((j + kq) & 3)) * 3 + rank][j - 1][0][tid];
#pragma unroll
    for (int i = 0; i < 4; i++) {
      const float* a = &acc[32 * j + 8 * i];
      asm volatile("st.relaxed.gpu.global.v4.u32 [%0], {%1,%2,%3,%4};" ::"l"(dst + i * 256), "r"(pack_bf16(a[0], a[1])),
                   "r"(pack_bf16(a[2], a[3])), "r"(pack_bf16(a[4], a[5])), "r"(pack_bf16(a[6], a[7])) : "memory");
    }
  }
  TL(6);
#pragma unroll 1
  for (int j = 0, tries = 0; j < 3 && tries < POLL_TRIES; tries++) {
    uint4 pt[4];
#pragma unroll
    for (int i = 0; i < 4; i++) pt[i] = ld_strong16(&g_tpart[blockIdx.x][j][i][tid]);
    if (!__all_sync(0xffffffffu, max(max(umax4(pt[0]), umax4(pt[1])), max(umax4(pt[2]), umax4(pt[3]))) != EMPTY)) continue;
#pragma unroll
    for (int i = 0; i < 16; i++) { acc[2 * i] += bf_lo((&pt[0].x)[i]); acc[2 * i + 1] += bf_hi((&pt[0].x)[i]); }
    j++;
  }
  mbar_spin(RES, 0);
  TL(7);
  const uint32_t xa = base + (wv * 16 + ((lane >> 3) & 1) * 8 + (lane & 7)) * 128 + (((lane >> 4) ^ (lane & 7)) << 4);
#pragma unroll
  for (int i = 0; i < 4; i++) {
    uint32_t x[4], g[4], o[4];
    ldsm4(x, xa ^ (i << 5));
    ldsm4(g, (xa ^ (i << 5)) + 16384);
#pragma unroll
    for (int k = 0; k < 4; k++) {
      const uint32_t sv = pack_bf16(acc[8 * i + 2 * k], acc[8 * i + 2 * k + 1]);
      o[k] = nog ? sv : add_bf16x2(x[k], mul_bf16x2(sv, g[k]));
    }
    stsm4(xa ^ (i << 5), o[0], o[1], o[2], o[3]);
  }
  TL(8);
  fence_proxy_async_smem();
  __syncwarp();
  if (elect_one()) {
    tma_store_2d(&P.tout, base + wv * 2048, nt * 256 + kq * 64, mb * 128 + wv * 16);
    tma_store_commit();
    tma_store_wait_read();
  }
  TL(9);
  KT_END(7);
}

__global__ void __launch_bounds__(256, 1) f_kernel(const __grid_constant__ FParams P) {
  using namespace fk;
  extern __shared__ __align__(1024) uint8_t smem_f[];
  uint32_t crank, rank, hw;
  asm("mov.u32 %0, %%cluster_ctarank;" : "=r"(crank));
  const int h = blockIdx.x / 3;
  if (smem_u32(smem_f) != mapa(0, crank) + SM0) return;
  PROF2(0);
  KT_START(1);
  KT_START(0);
  {
    const uint32_t self = mapa(0, crank);
    SMAP;
    const int tid = threadIdx.x, lane = tid & 31, wv = __shfl_sync(0xffffffffu, tid >> 5, 0);
    PRO(0);
    if (wv == 0) {
      uint32_t sm;
      asm("mov.u32 %0, %%smid;" : "=r"(sm));
      sts32(PROBE + 96, sm >> 1);
      asm volatile("fence.release.sync_restrict::shared::cta.cluster;" ::: "memory");
    }
    asm volatile("barrier.cluster.arrive.relaxed.aligned;" ::: "memory");
    if (wv == 7) {
      if (blockIdx.x == 2) {
#pragma unroll
        for (int i = 0; i < 4; i++) { (&g_cnt[0][0])[32 * i + lane] = 0; if (i < 3) g_tfix[32 * i + lane] = 0; }
        if (lane < 16) g_oflag[lane] = 0;
        if (lane == 0) { g_next = 0; g_lnok[0] = 0; }
        __threadfence();
        __syncwarp();
      }
      pdl_launch_dependents();
    }
    const int row0 = blockIdx.x * 8 + wv;
    const bool third = row0 + 1536 < cfg::S;
    uint32_t cur[1][16] = {}, raw[3][16];
    load_row16(raw[0], P.x + (size_t)row0 * cfg::D, lane);
    load_row16(raw[1], P.x + (size_t)(row0 + 768) * cfg::D, lane);
    load_row16(raw[2], P.x + (size_t)(row0 + (third ? 1536 : 0)) * cfg::D, lane);
    {
      uint32_t tpc;
      asm volatile("barrier.cluster.wait.aligned;" ::: "memory");
      asm volatile("ld.shared::cluster.u32 %0, [%1];" : "=r"(tpc) : "r"(mapa(PROBE + 96, lane % 3)) : "memory");
      const uint32_t t0 = __shfl_sync(0xffffffffu, tpc, 0), t1 = __shfl_sync(0xffffffffu, tpc, 1), t2 = __shfl_sync(0xffffffffu, tpc, 2);
      hw = t1 == t2 ? 0x09 : t0 == t2 ? 0x18 : 0x24;
      rank = (hw & 3) == crank ? 0 : ((hw >> 2) & 3) == crank ? 1 : 2;
    }
    const bool isv = rank == 2;
    const CUtensorMap* m0 = isv ? &P.wv : &P.wq;
    const CUtensorMap* m1 = isv ? &P.wv : &P.wk;
    const int col0 = h * 128 + (isv ? 0 : 64 * rank), col1 = h * 128 + (isv ? 64 : 64 * rank);
    auto req_weights = [&](int n0, int n1) {
#pragma unroll 1
        for (int n = n0; n < n1; n++) {
          const int i = n >> 1, g = n & 1, row = (isv ? Chunks<true>::rf(g, i) : Chunks<false>::rf(g, i)) * 64;
          if (!g) mbar_expect_tx(B_PB + 8 * i, 32768);
          tma_load_2d(SM0 + n * 16384, m0, col0, row, B_PB + 8 * i);
          tma_load_2d(SM0 + n * 16384 + 8192, m1, col1, row, B_PB + 8 * i);
        }
    };
    if (wv == 0) {
      if (elect_one()) {
        for (int i = 0; i < 2; i++) mbar_init(B_XN + 8 * i, 1);
        mbar_init(B_H1, 4);
        mbar_init(B_SM, isv ? 1 : 6);
        mbar_init(B_VM, isv ? 8 : 1);
        mbar_init(B_VX, 1);
        mbar_init(B_ST, 1);
        mbar_init(B_PF, 2);
        for (int i = 0; i < 6; i++) mbar_init(B_PB + 8 * i, 1);
        mbar_init(B_W, 2);
        mbar_init(B_WO, 1);
        fence_barrier_init();
        if (PRE_A) req_weights(0, 2 * PRE_A);
        mbar_expect_tx(B_SM, isv ? 2 * SP_SRC : SP_SRC);
        if (isv) mbar_expect_tx(B_ST, 7168);
        else { mbar_expect_tx(B_VM, 2048); mbar_expect_tx(B_VX, 8192); }
      }
    }
    const int j = 2 * h + rank;
    const bool dry = LN_DRY && !isv && wv == 6;
    if (dry) sts64(PROBE + wv * 8, 0x7FFFFFFF, 0x7FFFFFFF);
    if (lane == 0 && !dry) {
      const uint2 b = probe_pair(P.xch + (isv ? H1_BYTES + wv * 8192 + h * 128 : j * 32768 + (wv & 3) * 8192 + (wv >> 2) * 128),
                                 isv ? EMPTY : 0, PROBE + 64, P.nprobe);
      sts64(PROBE + wv * 8, b.x, b.y);
    }
    uint32_t mask = 0;
#pragma unroll 1
    for (int it = -1; it < (third ? 3 : 2); it++) {
      if (it >= 0 || dry) {
        ln_regs<1>(cur);
        if (it >= 0) store_row16(cur[0], P.xn_ptr + (size_t)(row0 + it * 768) * cfg::D, lane);
      }
      if (it == 0) PRO(4);
      if (it < 0) {
    PROF2(3);
    PRO(1);
    __syncwarp();
    if (wv == 0) {
      asm volatile("{\n.reg .pred p;\nsetp.eq.u32 p, %0, %1;\n@p st.shared.u32 [%2], %0;\n}" ::"r"(raw[2][15]), "r"(raw[0][0] ^ raw[1][15]), "r"(PROBE + 64) : "memory");
      if (elect_one()) {
        req_weights(2 * PRE_A, 2 * PRE_G);
      }
    }
    __syncthreads();
    PRO(2);
    asm volatile("barrier.cluster.arrive.relaxed.aligned;" ::: "memory");
    PRO(3);
    if (wv == 2) sts32(self + ONES + lane * 4, 0x3F803F80u);
    uint32_t pb[2], pc[2];
    lds64(pb, PROBE + (lane & 7) * 8);
    lds64(pc, PROBE + ((lane & 7) ^ 4) * 8);
    mask = __ballot_sync(0xffffffffu, isv ? pb[1] < pb[0] : min(pb[1], pc[1]) < min(pb[0], pc[0])) & (isv ? 255 : 15);
    if (!isv) {
#pragma unroll
      for (int i = 0; i < 4; i++) st_pub128(P.xch + j * 32768 + i * 8192 + ((mask >> i) & 1) * 4096 + tid * 16, 0);
      if (wv < 4) st_pub64(P.xch + H1_BYTES + (wv >> 1) * 32768 + (j >> 4) * 8192 + (wv & 1) * 4096 + (j & 15) * 256 + lane * 8, EMPTY, EMPTY);
    }
      }
#pragma unroll
      for (int i = 0; i < 16; i++) { cur[0][i] = raw[0][i]; raw[0][i] = raw[1][i]; raw[1][i] = raw[2][i]; }
    }
    PRO(5);
    __syncthreads();
    PRO(6);
    if (tid == 64) {
      __threadfence();
      PRO(7);
      st_pub32(&g_mask[3 * h + rank], 0x100 | mask);
    }
    KT_END(0);
    __syncwarp();
  }
  const int wg = __shfl_sync(0xffffffffu, threadIdx.x >> 7, 0);
  if (rank == 2) { if (wg == 0) f_main<true, 0>(P, h, 2, hw); else f_main<true, 1>(P, h, 2, hw); }
  else { if (wg == 0) f_main<false, 0>(P, h, rank, hw); else f_main<false, 1>(P, h, rank, hw); }
  PROF2(5);
  KT_END(1);
  __syncwarp();
  f_tail(P, h, crank, rank == 2);
}

#define GCL 1
#define G_PF 3
#define G_PFM 2
#define G_LATE 0
namespace gk {
enum { T_B1 = 0, T_B2 = 1, T_B3 = 2, T_B4 = 3, T_O = 4, T_LN = 5, T_LN0 = 6, T_END = 7 };
constexpr int NST = 3, STAGE = 49152, MAXITEMS = 512, NEW = 3;
constexpr uint32_t OUTB = NST * STAGE, BARS = OUTB + 65536;
constexpr uint32_t B_FULL = BARS, B_EMPTY = BARS + 32, B_ITEM = BARS + 64, B_FILL = BARS + 128, B_FREE = BARS + 160, B_LN = BARS + 176, ITEMS = BARS + 192;
constexpr int SMEM = BARS + 256;
static_assert(GATE_CNT == 4 * NEW && T_B4 == 3, "gate counter");
}
struct GParams {
  CUtensorMap a[5], b[5];
  bf16* c[5];
  const bf16* r[5];
  bf16 *x1n, *xn2;
  const bf16* w1;
  int nitems, lnpos;
  uint16_t items[gk::MAXITEMS];
};
#define ILOG(i)

__device__ __forceinline__ void tma_load_3d_mc(uint32_t dst, const CUtensorMap* map, int x, int y, int z, uint32_t bar) {
  asm volatile("cp.async.bulk.tensor.3d.shared::cluster.global.mbarrier::complete_tx::bytes.multicast::cluster "
               "[%0], [%1, {%3, %4, %5}], [%2], %6;"
               ::"r"(dst), "l"(map), "r"(bar), "r"(x), "r"(y), "r"(z), "h"((uint16_t)3) : "memory");
}
__device__ __forceinline__ float tanh_approx(float x) { float y; asm("tanh.approx.f32 %0, %1;" : "=f"(y) : "f"(x)); return y; }
__global__ void __launch_bounds__(384, 1) g_kernel(const __grid_constant__ GParams P) {
  using namespace gk;
  extern __shared__ __align__(1024) uint8_t smem_g[];
  const uint32_t base = smem_u32(smem_g);
  const int tid = threadIdx.x, warp = __shfl_sync(0xffffffffu, tid >> 5, 0), lane = tid & 31;
  const int rank = blockIdx.x % GCL;
  KT_START(2);
  if (tid == 0) {
    for (int s = 0; s < NST; s++) { mbar_init(base + B_FULL + 8 * s, 1); mbar_init(base + B_EMPTY + 8 * s, 8 * GCL); }
    for (int s = 0; s < 8; s++) mbar_init(base + B_ITEM + 8 * s, 1);
    for (int s = 0; s < 2; s++) { mbar_init(base + B_FILL + 8 * s, 4); mbar_init(base + B_FREE + 8 * s, NEW); }
    mbar_init(base + B_LN, 1);
    fence_barrier_init();
  }
  __syncthreads();
  if (GCL > 1) cluster_sync();
  auto release = [&](uint32_t st) {
    if (GCL > 1) { if (lane < GCL) mbar_arrive_cluster(base + B_EMPTY + 8 * st, lane); }
    else if (lane == 0) mbar_arrive(base + B_EMPTY + 8 * st);
  };
  auto get_item = [&](int q) {
    mbar_wait(base + B_ITEM + 8 * (q & 7), (q >> 3) & 1);
    return lds32(base + ITEMS + 4 * (q & 7));
  };

  if (warp == 8) {
    if (lane < 10) prefetch_tmap(&P.a[0] + lane);
    for (int r = blockIdx.x * 32 + lane; r < cfg::D; r += gridDim.x * 32) l2_prefetch(P.w1 + r * cfg::D, 2048);
    if (lane == 0) {
      uint32_t st = 0, ph = 1;
#pragma unroll 1
      for (int q = 0;; q++) {
        if (GCL > 1) mbar_expect_tx(base + B_ITEM + 8 * (q & 7), 4);
        if (rank == 0) {
          const unsigned idx = atomicAdd(&g_next, 1), ln = idx - P.lnpos;
          const uint32_t v = (idx < (unsigned)P.nitems ? P.items[idx] : T_END) | (ln < 64 / GCL ? (ln + 1) << 16 : idx < 32 / GCL ? (idx + 129) << 16 : 0);
          if (GCL > 1) {
#pragma unroll
            for (int r = 0; r < GCL; r++) st_async32(mapa(base + ITEMS + 4 * (q & 7), r), v, mapa(base + B_ITEM + 8 * (q & 7), r));
          } else {
            sts32(base + ITEMS + 4 * (q & 7), v);
            mbar_arrive(base + B_ITEM + 8 * (q & 7));
          }
        }
        const uint32_t item = get_item(q);
        const int type = item & 7, mb = ((item >> 3) & 15) + rank, nt = (item >> 7) & 15;
        ILOG(1);
        if (q == 0) { __threadfence(); sts32(base + ITEMS + 32, ld_strong4(&g_oflag[14]) >= 32); }
        if (type == T_END) break;
        if (type == T_B2) {
          wait_count(&g_cnt[T_B1][max(mb - 1, 0)], 4 * NEW); wait_count(&g_cnt[T_B1][mb], 4 * NEW); wait_count(&g_cnt[T_B1][min(mb + 1, 15)], 4 * NEW);
        } else if (type == T_B3) wait_count(&g_cnt[T_LN][mb], 32);
        else if (type == T_B4) wait_count(&g_cnt[T_B3][mb], 14 * NEW);
        else if (type == T_O) wait_count(&g_oflag[mb], 32);
        asm volatile("fence.proxy.async.global;" ::: "memory");
        ILOG(2);
        const CUtensorMap *ma = &P.a[type], *mbm = &P.b[type];
        const int nkb = type == T_B4 ? cfg::F / 64 : type == T_O ? cfg::HD / 64 : cfg::D / 64;
#pragma unroll 1
        for (int kb = 0; kb < nkb; kb++) {
          mbar_wait(base + B_EMPTY + 8 * st, ph);
          const uint32_t sa = base + st * STAGE, full = base + B_FULL + 8 * st;
          mbar_expect_tx(full, STAGE);
          int arow = mb * 128;
          if (type == T_B2) { const int qd = kb >> 2; arow += (qd == 0) ? -1 : (qd == 1) ? 1 : (qd == 2) ? -2 : 2; }
          if (GCL > 1) tma_load_3d_mc(sa + 16384 + rank * 16384, mbm, 0, kb * 64, nt * 4 + rank * 2, full);
          else tma_load_3d(sa + 16384, mbm, 0, kb * 64, nt * 4, full);
          if (type == T_B1 && kb == 0) { wait_count(&g_cnt[T_LN0][mb], 32); asm volatile("fence.proxy.async.global;" ::: "memory"); }
          tma_load_2d(sa, ma, kb * 64, arow, full);
          if (G_PF && type >= T_B4 && kb + G_PF < nkb) {
            if (G_PFM & 1) asm volatile("cp.async.bulk.prefetch.tensor.3d.L2.global [%0, {0, %1, %2}];" ::"l"(mbm), "r"((kb + G_PF) * 64), "r"(nt * 4 + rank * 2) : "memory");
            if (G_PFM & 2) asm volatile("cp.async.bulk.prefetch.tensor.2d.L2.global [%0, {%1, %2}];" ::"l"(ma), "r"((kb + G_PF) * 64), "r"(mb * 128) : "memory");
          }
          if (++st == NST) { st = 0; ph ^= 1; }
        }
      }
    }
  } else {
    const int wg = warp >> 2, ew = warp > 8 ? warp - 9 : warp + NEW;
    const uint32_t outa = base + OUTB + (warp * 16 + ((lane >> 3) & 1) * 8 + (lane & 7)) * 512 + (((lane >> 4) ^ (lane & 7)) << 4);
    uint32_t st = 0, ph = 0;
    float acc[128];
    auto kill_acc = [&]() {
#pragma unroll
      for (int i = 0; i < 128; i++) acc[i] = 0.f;
    };
    if (warp == 9) {
#pragma unroll 1
      for (int tries = 0; tries < POLL_TRIES; tries++) {
        uint4 v;
        asm volatile("ld.acquire.gpu.global.v4.u32 {%0,%1,%2,%3}, [%4];" : "=r"(v.x), "=r"(v.y), "=r"(v.z), "=r"(v.w)
                     : "l"(lane < 24 ? &g_mask[4 * lane] : &g_lnok[0]) : "memory");
        const uint32_t ok = __ballot_sync(0xffffffffu, v.x & v.y & v.z & v.w & 0x100);
        if ((ok & 0xFFFFFF) == 0xFFFFFF || (ok >> 24)) break;
        __nanosleep(200);
      }
      if (lane == 0) mbar_arrive(base + B_LN);
    }
    uint32_t next = get_item(0);
#pragma unroll 1
    for (int q = 0;; q++) {
      const uint32_t item = next;
      const int type = item & 7, mb = ((item >> 3) & 15) + rank, nt = (item >> 7) & 15;
      if (type == T_END) break;
      if (warp < 8) {
      if (item >> 16) {
        const bool first = item >> 23;
#pragma unroll 1
        for (int ln = ((item >> 16) & 127) - 1; ln < 64 / GCL; ln += first ? 32 / GCL : 64) {
          const int lb = (ln >> 2) * GCL + rank;
          const size_t row = (size_t)(lb * 128 + (ln & 3) * 32 + warp * 4) * cfg::D;
          const bf16* src = (first ? P.r[T_O] : P.c[T_B2]) + row;
          bf16* dst = (first ? P.xn2 : P.x1n) + row;
          if (!first) wait_count(&g_cnt[T_B2][lb], 4 * NEW);
          uint32_t cur[2][16], nxt[2][16];
#pragma unroll
          for (int r = 0; r < 2; r++) {
            load_row16(cur[r], src + r * cfg::D, lane);
            load_row16(nxt[r], src + (r + 2) * cfg::D, lane);
          }
#pragma unroll 1
          for (int it = first ? 0 : 1; it < 4; it += first ? 1 : 2) {
            ln_regs<2>(cur);
            if (it & 1) {
#pragma unroll
              for (int r = 0; r < 2; r++) {
                store_row16(cur[r], dst + (it - 1 + r) * cfg::D, lane);
#pragma unroll
                for (int i = 0; i < 16; i++) cur[r][i] = nxt[r][i];
              }
            }
          }
          __syncwarp();
          if (lane == 0) asm volatile("red.release.gpu.global.add.u32 [%0], 1;" ::"l"(&g_cnt[first ? T_LN0 : T_LN][lb]) : "memory");
          __syncwarp();
        }
        if (tid == 0) ILOG(6);
        kill_acc();
      }
      const int nkb = type == T_B4 ? cfg::F / 64 : type == T_O ? cfg::HD / 64 : cfg::D / 64;
      uint32_t prev = 0;
      mbar_wait(base + B_FULL + 8 * st, ph);
#pragma unroll 1
      for (int kb = 0; kb < nkb; kb++) {
        mbar_spin(base + B_FULL + 8 * st, ph);
        if (kb == 0 && tid == 0) ILOG(3);
        const uint64_t da = make_desc(base + wg * 8192, 16, 1024) + st * (STAGE >> 4), db = make_desc(base + 16384, 8192, 1024) + st * (STAGE >> 4);
        wg_fence();
#pragma unroll
        for (int k = 0; k < 4; k++) {
          wgmma_ss_n256_tb(acc, da + k * 2, db + k * 128, (kb | k) != 0);
          if (k == 0) {
            wg_commit();
            wg_wait<1>();
            if (kb > 0) release(prev);
            wg_fence();
          }
        }
        wg_commit();
        prev = st;
        if (++st == NST) { st = 0; ph ^= 1; }
      }
      next = get_item(q + 1);
      if (q > 0) mbar_wait(base + B_FREE + 8 * wg, (q - 1) & 1);
      wg_wait<0>();
      if (tid == 0) ILOG(4);
      release(prev);
#pragma unroll
      for (int j = 0; j < 16; j++)
        stsm4((outa ^ ((j & 3) << 5)) + (j >> 2) * 128, pack_bf16(acc[8 * j], acc[8 * j + 1]), pack_bf16(acc[8 * j + 2], acc[8 * j + 3]),
              pack_bf16(acc[8 * j + 4], acc[8 * j + 5]), pack_bf16(acc[8 * j + 6], acc[8 * j + 7]));
      __syncwarp();
      if (lane == 0) mbar_arrive(base + B_FILL + 8 * wg);
      if (tid == 0) ILOG(5);
      if ((next & 7) != T_END) continue;
      }
      if (type == T_O) wait_count(&g_cnt[T_B4][mb], 4 * NEW);
      const int ldc = type == T_B3 ? cfg::F : cfg::D;
      bf16* cp = P.c[type] + (size_t)mb * 128 * ldc + nt * 256 + lane * 8;
      const size_t roff = (size_t)mb * 128 * cfg::D + nt * 256 + lane * 8;
      const bf16 *rp = P.r[type] + roff, *gp = P.c[T_B4] + roff;
      const bool gelu = type == T_B1 || type == T_B3;
      uint32_t yn[4][4];
      uint4 rn[4], gn[4];
#pragma unroll
      for (int i = 0; i < 4; i++) rn[i] = gn[i] = make_uint4(0, 0, 0, 0);
      auto fetch_res = [&](int grp) {
#pragma unroll
        for (int i = 0; i < 4; i++) {
          rn[i] = __ldcg(reinterpret_cast<const uint4*>(rp + (grp * 4 + i) * cfg::D));
          if (type == T_O) gn[i] = __ldcg(reinterpret_cast<const uint4*>(gp + (grp * 4 + i) * cfg::D));
        }
      };
      auto fetch_y = [&](int grp) {
        const uint32_t a = base + OUTB + grp * 2048 + ((lane ^ ((grp & 1) << 2)) << 4);
#pragma unroll
        for (int i = 0; i < 4; i++) lds128(yn[i], (a ^ (i << 4)) + i * 512);
      };
      auto store_y = [&](int grp, const uint32_t (&y)[4][4]) {
        char* p = reinterpret_cast<char*>(cp) + (uint32_t)(grp * 8 * ldc);
#pragma unroll
        for (int i = 0; i < 4; i++) *reinterpret_cast<uint4*>(p + (uint32_t)(i * 2 * ldc)) = make_uint4(y[i][0], y[i][1], y[i][2], y[i][3]);
      };
      if (type == T_B2) mbar_wait(base + B_LN, 0);
      if (type == T_B4) wait_count(&g_cnt[T_B2][mb], 4 * NEW);
      if (type >= T_B4 && warp > 8) for (int r = tid - 288; r < 128; r += 96) l2_prefetch(rp - lane * 8 + r * cfg::D, 512);
      if (!gelu) fetch_res(ew);
      mbar_wait(base + B_FILL, q & 1);
      fetch_y(ew);
      next = get_item(q + 1);
      mbar_wait(base + B_FILL + 8, q & 1);
      const int stride = (next & 7) == T_END ? NEW + 8 : NEW;
      if (gelu) {
#pragma unroll 1
        for (int grp = ew; grp < 32; grp += stride) {
          uint32_t y[4][4];
#pragma unroll
          for (int i = 0; i < 16; i++) y[i >> 2][i & 3] = mul_bf16x2(yn[i >> 2][i & 3], 0x3F003F00u);
          const int nx = grp + stride;
          if (nx >= 16 && grp < 16 && lane == 0 && warp > 8) mbar_arrive(base + B_FREE);
          if (!G_LATE) fetch_y(min(nx, 31));
#pragma unroll
          for (int i = 0; i < 16; i++) {
            uint32_t& v = y[i >> 2][i & 3];
            const float h0 = bf_lo(v), h1 = bf_hi(v);
            const float t0 = tanh_approx(h0 * fmaf(h0 * h0, 0.285419265090401f, 1.5957691216057308f));
            const float t1 = tanh_approx(h1 * fmaf(h1 * h1, 0.285419265090401f, 1.5957691216057308f));
            v = pack_bf16(fmaf(h0, t0, h0), fmaf(h1, t1, h1));
          }
          if (G_LATE) fetch_y(min(nx, 31));
          store_y(grp, y);
        }
      } else {
#pragma unroll 1
        for (int grp = ew; grp < 32; grp += stride) {
          uint32_t y[4][4];
          if (type == T_O) {
#pragma unroll
            for (int i = 0; i < 16; i++) yn[i >> 2][i & 3] = mul_bf16x2(yn[i >> 2][i & 3], (&gn[i >> 2].x)[i & 3]);
          }
#pragma unroll
          for (int i = 0; i < 16; i++) y[i >> 2][i & 3] = add_bf16x2(yn[i >> 2][i & 3], (&rn[i >> 2].x)[i & 3]);
          const int nx = grp + stride;
          if (nx >= 16 && grp < 16 && lane == 0 && warp > 8) mbar_arrive(base + B_FREE);
          fetch_res(min(nx, 31));
          fetch_y(min(nx, 31));
          if (type == T_B4) {
#pragma unroll
            for (int i = 0; i < 16; i++) {
              uint32_t& v = y[i >> 2][i & 3];
              const float h0 = 0.5f * bf_lo(v), h1 = 0.5f * bf_hi(v);
              v = pack_bf16(fmaf(h0, tanh_approx(h0), h0), fmaf(h1, tanh_approx(h1), h1));
            }
          }
          store_y(grp, y);
        }
      }
      __syncwarp();
      if (lane == 0 && warp > 8) mbar_arrive(base + B_FREE + 8);
      if (stride != NEW) named_bar_sync(2, 352);
      if (type != T_O && lane == 0 && warp > 8) asm volatile("red.release.gpu.global.add.u32 [%0], 1;" ::"l"(&g_cnt[type][mb]) : "memory");
      __syncwarp();
      if (tid == 288) ILOG(7);
      kill_acc();
    }
    KT_END(2);
  }
  __syncwarp();
  if (warp >= 8) {
   named_bar_sync(1, 128);
   const bool late = lds32(base + ITEMS + 32);
   if (late) pdl_wait();
#pragma unroll 1
   for (int c = blockIdx.x; late && c < 96; c += gridDim.x) {
     if (__ldcg(&g_tfix[c]) == 0) continue;
     const int hh = c / 3, mb = TAIL_MB0 + 3 * (hh >> 4) + c % 3;
     wait_count(&g_cnt[T_B4][mb], GATE_CNT);
#pragma unroll 1
     for (int i = tid - 256; i < 1024; i += 128) {
       const size_t off = (size_t)(mb * 128 + (i >> 3)) * cfg::D + (hh & 15) * 64 + (i & 7) * 8;
       const uint4 sv = __ldcg(reinterpret_cast<const uint4*>(P.c[T_O] + off)), gv = __ldcg(reinterpret_cast<const uint4*>(P.c[T_B4] + off)),
                   xv = __ldcg(reinterpret_cast<const uint4*>(P.r[T_O] + off));
       *reinterpret_cast<uint4*>(P.c[T_O] + off) = make_uint4(add_bf16x2(xv.x, mul_bf16x2(sv.x, gv.x)), add_bf16x2(xv.y, mul_bf16x2(sv.y, gv.y)),
                                                              add_bf16x2(xv.z, mul_bf16x2(sv.z, gv.z)), add_bf16x2(xv.w, mul_bf16x2(sv.w, gv.w)));
     }
   }
  }
  if (GCL > 1) cluster_sync();
}

__device__ bf16 g_xn[cfg::S * cfg::D];
__device__ bf16 g_xn2[cfg::S * cfg::D];
__device__ bf16 g_h[cfg::S * cfg::D];
__device__ bf16 g_x1[cfg::S * cfg::D];
__device__ bf16 g_x1n[cfg::S * cfg::D];
__device__ bf16 g_u[cfg::S * cfg::F];
__device__ bf16 g_g[cfg::S * cfg::D];
__device__ bf16 g_o[cfg::S * cfg::HD];

typedef CUresult (*PFN_encodeTiled)(CUtensorMap*, CUtensorMapDataType, cuuint32_t, void*, const cuuint64_t*,
                                    const cuuint64_t*, const cuuint32_t*, const cuuint32_t*, CUtensorMapInterleave,
                                    CUtensorMapSwizzle, CUtensorMapL2promotion, CUtensorMapFloatOOBfill);

static PFN_encodeTiled get_encoder() {
  static PFN_encodeTiled fn = nullptr;
  if (!fn) {
    void* p = nullptr;
    cudaDriverEntryPointQueryResult st;
    cudaGetDriverEntryPoint("cuTensorMapEncodeTiled", &p, cudaEnableDefault, &st);
    fn = (PFN_encodeTiled)p;
  }
  return fn;
}
static CUtensorMap make_map(const void* ptr, int rows, int cols, int box_rows, int box_cols, int swizzle_bytes) {
  CUtensorMap m;
  cuuint64_t dims[2] = {(cuuint64_t)cols, (cuuint64_t)rows};
  cuuint64_t strides[1] = {(cuuint64_t)cols * 2};
  cuuint32_t box[2] = {(cuuint32_t)box_cols, (cuuint32_t)box_rows};
  cuuint32_t estr[2] = {1, 1};
  CUtensorMapSwizzle sw = swizzle_bytes == 128 ? CU_TENSOR_MAP_SWIZZLE_128B
                        : swizzle_bytes == 64 ? CU_TENSOR_MAP_SWIZZLE_64B
                        : swizzle_bytes == 32 ? CU_TENSOR_MAP_SWIZZLE_32B : CU_TENSOR_MAP_SWIZZLE_NONE;
  get_encoder()(&m, CU_TENSOR_MAP_DATA_TYPE_BFLOAT16, 2, const_cast<void*>(ptr), dims, strides, box, estr,
                CU_TENSOR_MAP_INTERLEAVE_NONE, sw, CU_TENSOR_MAP_L2_PROMOTION_L2_128B, CU_TENSOR_MAP_FLOAT_OOB_FILL_NONE);
  return m;
}
static CUtensorMap make_map3(const void* ptr, int rows, int cols, int box_rows, int nblk) {
  CUtensorMap m;
  cuuint64_t dims[3] = {64, (cuuint64_t)rows, (cuuint64_t)(cols / 64)};
  cuuint64_t strides[2] = {(cuuint64_t)cols * 2, 128};
  cuuint32_t box[3] = {64, (cuuint32_t)box_rows, (cuuint32_t)nblk};
  cuuint32_t estr[3] = {1, 1, 1};
  get_encoder()(&m, CU_TENSOR_MAP_DATA_TYPE_BFLOAT16, 3, const_cast<void*>(ptr), dims, strides, box, estr,
                CU_TENSOR_MAP_INTERLEAVE_NONE, CU_TENSOR_MAP_SWIZZLE_128B, CU_TENSOR_MAP_L2_PROMOTION_L2_128B,
                CU_TENSOR_MAP_FLOAT_OOB_FILL_NONE);
  return m;
}
template <class T> static T* sym(T& s) { void* p = nullptr; cudaGetSymbolAddress(&p, s); return (T*)p; }
#define SYM(name) ((bf16*)[] { void* p = nullptr; cudaGetSymbolAddress(&p, name); return p; }())

#define G_CTAS 36
#define B4_FIRST (GCL == 1 ? 9 : 16)
#define O_FIRST 2
#define LN_POS 63
static int build_items(uint16_t* it) {
  using namespace gk;
  int n = 0;
  auto add = [&](int type, int nrows, int ncols, int row0 = 0) {
    for (int mb = row0; mb < nrows; mb += GCL) for (int nt = 0; nt < ncols; nt++) it[n++] = (uint16_t)(type | mb << 3 | nt << 7);
  };
  add(T_B1, 16, 4); add(T_B2, 16, 4); add(T_B3, 16, 14);
  add(T_B4, B4_FIRST, 4); add(T_O, O_FIRST, 4); add(T_B4, 16, 4, B4_FIRST); add(T_O, TAIL_MB0, 4, O_FIRST);
  return n;
}

extern "C" void kernel_launch(void* const* d_in, const int* in_sizes, int n_in, void* d_out, int out_size) {
  using namespace cfg;
  const bf16* x = (const bf16*)d_in[0];
  const bf16* mem0 = (const bf16*)d_in[1];
  const bf16* Wq = (const bf16*)d_in[2];
  const bf16* Wk = (const bf16*)d_in[3];
  const bf16* Wv = (const bf16*)d_in[4];
  const bf16* Wo = (const bf16*)d_in[5];
  const bf16* w1 = (const bf16*)d_in[8];
  const bf16* w2 = (const bf16*)d_in[9];
  const bf16* w3 = (const bf16*)d_in[10];
  const bf16* w4 = (const bf16*)d_in[11];
  bf16* out = (bf16*)d_out;
  cudaStream_t st = cudaStreamPerThread;

  bf16 *xn = SYM(g_xn), *xn2 = SYM(g_xn2), *hb = SYM(g_h), *x1 = SYM(g_x1), *x1n = SYM(g_x1n), *u = SYM(g_u),
       *g = SYM(g_g), *o = SYM(g_o);

  {
    cudaFuncSetAttribute(f_kernel, cudaFuncAttributeMaxDynamicSharedMemorySize, fk::SMEM);
    FParams P;
    P.wq = make_map(Wq, D, HD, 64, 64, 128); P.wk = make_map(Wk, D, HD, 64, 64, 128); P.wv = make_map(Wv, D, HD, 64, 64, 128);
    P.wo = make_map(Wo, HD, D, 128, 64, 128); P.wo16 = make_map(Wo, HD, D, 128, 16, 32); P.xn = make_map3(xn, S, D, 32, 4); P.xn12 = make_map3(xn, S, D, 32, 12); P.o = make_map3(o, S, HD, 32, 2);
    P.ta = make_map(o, S, HD, 128, 64, 128); P.tb = make_map(Wo, HD, D, 64, 64, 128); P.tx = make_map(x, S, D, 128, 64, 128);
    P.tg = make_map(g, S, D, 128, 64, 128); P.tout = make_map(out, S, D, 16, 64, 128);
    P.mem0 = mem0;
    P.nprobe = PROBE_N;
    P.dxn = make_desc(fk::XN, 16, 1024);
    P.x = x; P.xn_ptr = xn;
    P.xch = (char*)(((uintptr_t)SYM(g_xch) + 8191) & ~(uintptr_t)8191);
    cudaLaunchConfig_t cfg = {};
    cfg.gridDim = dim3(96); cfg.blockDim = dim3(256); cfg.dynamicSmemBytes = fk::SMEM; cfg.stream = st;
    cudaLaunchAttribute at[2];
    at[0].id = cudaLaunchAttributeClusterDimension;
    at[0].val.clusterDim.x = 3; at[0].val.clusterDim.y = 1; at[0].val.clusterDim.z = 1;
    cfg.attrs = at; cfg.numAttrs = 1;
    cudaLaunchKernelEx(&cfg, f_kernel, P);
  }
  {
    cudaFuncSetAttribute(g_kernel, cudaFuncAttributeMaxDynamicSharedMemorySize, gk::SMEM);
    GParams G;
    const bf16* as[5] = {xn2, hb, x1n, u, o};
    const bf16* bs[5] = {w1, w2, w3, w4, Wo};
    bf16* cs[5] = {hb, x1, u, g, out};
    const bf16* rs[5] = {xn, xn, xn, x1, x};
    const int ks[5] = {D, D, D, F, HD}, ns[5] = {D, D, F, D, D};
    for (int i = 0; i < 5; i++) {
      G.a[i] = make_map(as[i], S, ks[i], 128, 64, 128);
      G.b[i] = make_map3(bs[i], ks[i], ns[i], 64, 4 / GCL);
      G.c[i] = cs[i];
      G.r[i] = rs[i];
    }
    G.x1n = x1n; G.xn2 = xn2; G.w1 = w1;
    G.nitems = build_items(G.items);
    G.lnpos = LN_POS * 2 / GCL;
    cudaLaunchConfig_t cfg = {};
    cfg.gridDim = dim3(G_CTAS); cfg.blockDim = dim3(384); cfg.dynamicSmemBytes = gk::SMEM; cfg.stream = st;
    cudaLaunchAttribute at[2];
    at[0].id = cudaLaunchAttributeClusterDimension;
    at[0].val.clusterDim.x = GCL; at[0].val.clusterDim.y = 1; at[0].val.clusterDim.z = 1;
    at[1].id = cudaLaunchAttributeProgrammaticStreamSerialization;
    at[1].val.programmaticStreamSerializationAllowed = 1;
    cfg.attrs = at;
    cfg.numAttrs = 2;
    cudaLaunchKernelEx(&cfg, g_kernel, G);
  }
}
```

```cpp
#include <cuda_runtime.h>
#include <cuda_bf16.h>
#include <cuda.h>
#include <stdint.h>

typedef __nv_bfloat16 bf16;

namespace cfg {
constexpr int S = 2048;
constexpr int D = 1024;
constexpr int H = 32;
constexpr int DH = 128;
constexpr int HD = H * DH;
constexpr int M = 8;
constexpr int SEG = 32;
constexpr int NSEG = S / SEG;
constexpr int F = 3584;
}

__device__ __forceinline__ uint32_t smem_u32(const void* p) { return (uint32_t)__cvta_generic_to_shared(p); }

__device__ __forceinline__ void mbar_init(uint32_t bar, uint32_t count) {
  asm volatile("mbarrier.init.shared::cta.b64 [%0], %1;" ::"r"(bar), "r"(count) : "memory");
}
__device__ __forceinline__ void mbar_expect_tx(uint32_t bar, uint32_t bytes) {
  asm volatile("mbarrier.arrive.expect_tx.shared::cta.b64 _, [%0], %1;" ::"r"(bar), "r"(bytes) : "memory");
}
__device__ __forceinline__ void mbar_arrive(uint32_t bar) {
  asm volatile("mbarrier.arrive.shared::cta.b64 _, [%0];" ::"r"(bar) : "memory");
}
__device__ __forceinline__ bool mbar_try(uint32_t bar, uint32_t parity) {
  uint32_t done;
  asm volatile("{\n.reg .pred p;\nmbarrier.try_wait.parity.shared::cta.b64 p, [%1], %2, 20000;\nselp.u32 %0, 1, 0, p;\n}"
               : "=r"(done) : "r"(bar), "r"(parity) : "memory");
  return done != 0;
}
__device__ __forceinline__ bool mbar_try_nohint(uint32_t bar, uint32_t parity) {
  uint32_t done;
  asm volatile("{\n.reg .pred p;\nmbarrier.try_wait.parity.shared::cta.b64 p, [%1], %2;\nselp.u32 %0, 1, 0, p;\n}"
               : "=r"(done) : "r"(bar), "r"(parity) : "memory");
  return done != 0;
}
constexpr int MBAR_TRIES = 4096;
constexpr int POLL_TRIES = 1 << 16;
__device__ __forceinline__ void mbar_wait(uint32_t bar, uint32_t parity) {
#pragma unroll 1
  for (int n = 0; n < MBAR_TRIES; n++)
    if (mbar_try(bar, parity)) break;
}
__device__ __forceinline__ void mbar_wait_fast(uint32_t bar, uint32_t parity) {
#pragma unroll 1
  for (int n = 0; n < (POLL_TRIES << 4); n++)
    if (mbar_try_nohint(bar, parity)) break;
}
__device__ __forceinline__ void fence_barrier_init() { asm volatile("fence.mbarrier_init.release.cluster;" ::: "memory"); }
__device__ __forceinline__ void fence_proxy_async_smem() { asm volatile("fence.proxy.async.shared::cta;" ::: "memory"); }

__device__ __forceinline__ void tma_load_2d(uint32_t dst, const CUtensorMap* map, int x, int y, uint32_t bar) {
  asm volatile("cp.async.bulk.tensor.2d.shared::cluster.global.mbarrier::complete_tx::bytes [%0], [%1, {%3, %4}], [%2];"
               ::"r"(dst), "l"(map), "r"(bar), "r"(x), "r"(y) : "memory");
}
__device__ __forceinline__ void tma_load_3d(uint32_t dst, const CUtensorMap* map, int x, int y, int z, uint32_t bar) {
  asm volatile("cp.async.bulk.tensor.3d.shared::cluster.global.mbarrier::complete_tx::bytes [%0], [%1, {%3, %4, %5}], [%2];"
               ::"r"(dst), "l"(map), "r"(bar), "r"(x), "r"(y), "r"(z) : "memory");
}
__device__ __forceinline__ void tma_store_2d(const CUtensorMap* map, uint32_t src, int x, int y) {
  asm volatile("cp.async.bulk.tensor.2d.global.shared::cta.bulk_group [%0, {%2, %3}], [%1];"
               ::"l"(map), "r"(src), "r"(x), "r"(y) : "memory");
}
__device__ __forceinline__ void tma_store_commit() { asm volatile("cp.async.bulk.commit_group;" ::: "memory"); }
__device__ __forceinline__ void tma_store_wait_all() { asm volatile("cp.async.bulk.wait_group 0;" ::: "memory"); }
__device__ __forceinline__ void tma_store_wait_read() { asm volatile("cp.async.bulk.wait_group.read 0;" ::: "memory"); }
__device__ __forceinline__ void prefetch_tmap(const CUtensorMap* map) {
  asm volatile("prefetch.tensormap [%0];" ::"l"(map) : "memory");
}

__device__ __forceinline__ void wg_fence() { asm volatile("wgmma.fence.sync.aligned;" ::: "memory"); }
__device__ __forceinline__ void wg_commit() { asm volatile("wgmma.commit_group.sync.aligned;" ::: "memory"); }
template <int N> __device__ __forceinline__ void wg_wait() { asm volatile("wgmma.wait_group.sync.aligned %0;" ::"n"(N) : "memory"); }

#define named_bar_sync(id, n) asm volatile("bar.sync %0, %1;" ::"n"(id), "n"(n) : "memory")
#define named_bar_arrive(id, n) asm volatile("bar.arrive %0, %1;" ::"n"(id), "n"(n) : "memory")

__host__ __device__ __forceinline__ uint64_t make_desc(uint32_t addr, uint32_t lbo, uint32_t sbo) {
  return (uint64_t)((addr & 0x3FFFF) >> 4) | ((uint64_t)(lbo >> 4) << 16) | ((uint64_t)(sbo >> 4) << 32) | (1ull << 62);
}

__device__ __forceinline__ uint64_t make_desc0(uint32_t addr, uint32_t lbo, uint32_t sbo) {
  return (uint64_t)((addr & 0x3FFFF) >> 4) | ((uint64_t)(lbo >> 4) << 16) | ((uint64_t)(sbo >> 4) << 32);
}

__device__ __forceinline__ uint32_t pack_bf16(float lo, float hi) {
  uint32_t r;
  asm("cvt.rn.bf16x2.f32 %0, %1, %2;" : "=r"(r) : "f"(hi), "f"(lo));
  return r;
}
__device__ __forceinline__ float bf_lo(uint32_t v) { return __uint_as_float(v << 16); }
__device__ __forceinline__ float bf_hi(uint32_t v) { return __uint_as_float(v & 0xFFFF0000u); }
__device__ __forceinline__ float rbf(float v) { return __bfloat162float(__float2bfloat16_rn(v)); }

__device__ __forceinline__ void pdl_launch_dependents() { asm volatile("griddepcontrol.launch_dependents;" ::: "memory"); }
__device__ __forceinline__ void pdl_wait() { asm volatile("griddepcontrol.wait;" ::: "memory"); }

__device__ __forceinline__ float ex2_approx(float x) { float y; asm("ex2.approx.ftz.f32 %0, %1;" : "=f"(y) : "f"(x)); return y; }
__device__ __forceinline__ float rcp_approx(float x) { float y; asm("rcp.approx.ftz.f32 %0, %1;" : "=f"(y) : "f"(x)); return y; }

__device__ __forceinline__ void mul_sigmoid4(float (&v)[4], const float (&t)[4]) {
#pragma unroll
  for (int i = 0; i < 4; i += 2) {
    const float a = 1.0f + ex2_approx(fminf(t[i], 60.0f)), b = 1.0f + ex2_approx(fminf(t[i + 1], 60.0f));
    const float r = rcp_approx(a * b);
    v[i] *= b * r;
    v[i + 1] *= a * r;
  }
}
__device__ __forceinline__ void gelu4(float (&v)[4]) {
  float t[4];
#pragma unroll
  for (int i = 0; i < 4; i++) t[i] = v[i] * fmaf(v[i] * v[i], -0.10294324f, -2.30220819f);
  mul_sigmoid4(v, t);
}
__device__ __forceinline__ void silu4(float (&v)[4]) {
  float t[4];
#pragma unroll
  for (int i = 0; i < 4; i++) t[i] = v[i] * -1.4426950408889634f;
  mul_sigmoid4(v, t);
}

#define KT_START(id)
#define KT_END(id)

__device__ __forceinline__ void wgmma_ss_n256_tb(float (&d)[128], uint64_t da, uint64_t db, int scale_d) {
  asm volatile("{\n.reg .pred p;\nsetp.ne.b32 p, %130, 0;\n"
    "wgmma.mma_async.sync.aligned.m64n256k16.f32.bf16.bf16 "
    "{%0, %1, %2, %3, %4, %5, %6, %7, %8, %9, %10, %11, %12, %13, %14, %15, "
    "%16, %17, %18, %19, %20, %21, %22, %23, %24, %25, %26, %27, %28, %29, %30, %31, "
    "%32, %33, %34, %35, %36, %37, %38, %39, %40, %41, %42, %43, %44, %45, %46, %47, "
    "%48, %49, %50, %51, %52, %53, %54, %55, %56, %57, %58, %59, %60, %61, %62, %63, "
    "%64, %65, %66, %67, %68, %69, %70, %71, %72, %73, %74, %75, %76, %77, %78, %79, "
    "%80, %81, %82, %83, %84, %85, %86, %87, %88, %89, %90, %91, %92, %93, %94, %95, "
    "%96, %97, %98, %99, %100, %101, %102, %103, %104, %105, %106, %107, %108, %109, %110, %111, "
    "%112, %113, %114, %115, %116, %117, %118, %119, %120, %121, %122, %123, %124, %125, %126, %127}, "
    "%128, %129, p, 1, 1, 0, 1;\n}\n"
    : "+f"(d[0]), "+f"(d[1]), "+f"(d[2]), "+f"(d[3]), "+f"(d[4]), "+f"(d[5]), "+f"(d[6]), "+f"(d[7]),
      "+f"(d[8]), "+f"(d[9]), "+f"(d[10]), "+f"(d[11]), "+f"(d[12]), "+f"(d[13]), "+f"(d[14]), "+f"(d[15]),
      "+f"(d[16]), "+f"(d[17]), "+f"(d[18]), "+f"(d[19]), "+f"(d[20]), "+f"(d[21]), "+f"(d[22]), "+f"(d[23]),
      "+f"(d[24]), "+f"(d[25]), "+f"(d[26]), "+f"(d[27]), "+f"(d[28]), "+f"(d[29]), "+f"(d[30]), "+f"(d[31]),
      "+f"(d[32]), "+f"(d[33]), "+f"(d[34]), "+f"(d[35]), "+f"(d[36]), "+f"(d[37]), "+f"(d[38]), "+f"(d[39]),
      "+f"(d[40]), "+f"(d[41]), "+f"(d[42]), "+f"(d[43]), "+f"(d[44]), "+f"(d[45]), "+f"(d[46]), "+f"(d[47]),
      "+f"(d[48]), "+f"(d[49]), "+f"(d[50]), "+f"(d[51]), "+f"(d[52]), "+f"(d[53]), "+f"(d[54]), "+f"(d[55]),
      "+f"(d[56]), "+f"(d[57]), "+f"(d[58]), "+f"(d[59]), "+f"(d[60]), "+f"(d[61]), "+f"(d[62]), "+f"(d[63]),
      "+f"(d[64]), "+f"(d[65]), "+f"(d[66]), "+f"(d[67]), "+f"(d[68]), "+f"(d[69]), "+f"(d[70]), "+f"(d[71]),
      "+f"(d[72]), "+f"(d[73]), "+f"(d[74]), "+f"(d[75]), "+f"(d[76]), "+f"(d[77]), "+f"(d[78]), "+f"(d[79]),
      "+f"(d[80]), "+f"(d[81]), "+f"(d[82]), "+f"(d[83]), "+f"(d[84]), "+f"(d[85]), "+f"(d[86]), "+f"(d[87]),
      "+f"(d[88]), "+f"(d[89]), "+f"(d[90]), "+f"(d[91]), "+f"(d[92]), "+f"(d[93]), "+f"(d[94]), "+f"(d[95]),
      "+f"(d[96]), "+f"(d[97]), "+f"(d[98]), "+f"(d[99]), "+f"(d[100]), "+f"(d[101]), "+f"(d[102]), "+f"(d[103]),
      "+f"(d[104]), "+f"(d[105]), "+f"(d[106]), "+f"(d[107]), "+f"(d[108]), "+f"(d[109]), "+f"(d[110]), "+f"(d[111]),
      "+f"(d[112]), "+f"(d[113]), "+f"(d[114]), "+f"(d[115]), "+f"(d[116]), "+f"(d[117]), "+f"(d[118]), "+f"(d[119]),
      "+f"(d[120]), "+f"(d[121]), "+f"(d[122]), "+f"(d[123]), "+f"(d[124]), "+f"(d[125]), "+f"(d[126]), "+f"(d[127])
    : "l"(da), "l"(db), "r"(scale_d));
}
__device__ __forceinline__ void wgmma_rs_n32(float (&d)[16], const uint32_t* a, uint64_t db, int scale_d) {
  asm volatile("{\n.reg .pred p;\nsetp.ne.b32 p, %21, 0;\n"
    "wgmma.mma_async.sync.aligned.m64n32k16.f32.bf16.bf16 "
    "{%0, %1, %2, %3, %4, %5, %6, %7, %8, %9, %10, %11, %12, %13, %14, %15}, "
    "{%16, %17, %18, %19}, %20, p, 1, 1, 0;\n}\n"
    : "+f"(d[0]), "+f"(d[1]), "+f"(d[2]), "+f"(d[3]), "+f"(d[4]), "+f"(d[5]), "+f"(d[6]), "+f"(d[7]),
      "+f"(d[8]), "+f"(d[9]), "+f"(d[10]), "+f"(d[11]), "+f"(d[12]), "+f"(d[13]), "+f"(d[14]), "+f"(d[15])
    : "r"(a[0]), "r"(a[1]), "r"(a[2]), "r"(a[3]), "l"(db), "r"(scale_d));
}
__device__ __forceinline__ void wgmma_ss_n32_ta(float (&d)[16], uint64_t da, uint64_t db, int scale_d) {
  asm volatile("{\n.reg .pred p;\nsetp.ne.b32 p, %18, 0;\n"
    "wgmma.mma_async.sync.aligned.m64n32k16.f32.bf16.bf16 "
    "{%0, %1, %2, %3, %4, %5, %6, %7, %8, %9, %10, %11, %12, %13, %14, %15}, "
    "%16, %17, p, 1, 1, 1, 0;\n}\n"
    : "+f"(d[0]), "+f"(d[1]), "+f"(d[2]), "+f"(d[3]), "+f"(d[4]), "+f"(d[5]), "+f"(d[6]), "+f"(d[7]),
      "+f"(d[8]), "+f"(d[9]), "+f"(d[10]), "+f"(d[11]), "+f"(d[12]), "+f"(d[13]), "+f"(d[14]), "+f"(d[15])
    : "l"(da), "l"(db), "r"(scale_d));
}
__device__ __forceinline__ void wgmma_ss_n8_ta(float (&d)[4], uint64_t da, uint64_t db, int scale_d) {
  asm volatile("{\n.reg .pred p;\nsetp.ne.b32 p, %6, 0;\n"
    "wgmma.mma_async.sync.aligned.m64n8k16.f32.bf16.bf16 {%0, %1, %2, %3}, %4, %5, p, 1, 1, 1, 0;\n}\n"
    : "+f"(d[0]), "+f"(d[1]), "+f"(d[2]), "+f"(d[3]) : "l"(da), "l"(db), "r"(scale_d));
}
__device__ __forceinline__ void wgmma_ss_n48_tt(float (&d)[24], uint64_t da, uint64_t db, int scale_d) {
  asm volatile("{\n.reg .pred p;\nsetp.ne.b32 p, %26, 0;\n"
    "wgmma.mma_async.sync.aligned.m64n48k16.f32.bf16.bf16 "
    "{%0, %1, %2, %3, %4, %5, %6, %7, %8, %9, %10, %11, %12, %13, %14, %15, %16, %17, %18, %19, %20, %21, %22, %23}, "
    "%24, %25, p, 1, 1, 1, 1;\n}\n"
    : "+f"(d[0]), "+f"(d[1]), "+f"(d[2]), "+f"(d[3]), "+f"(d[4]), "+f"(d[5]), "+f"(d[6]), "+f"(d[7]), "+f"(d[8]), "+f"(d[9]), "+f"(d[10]), "+f"(d[11]), "+f"(d[12]), "+f"(d[13]), "+f"(d[14]), "+f"(d[15]), "+f"(d[16]), "+f"(d[17]), "+f"(d[18]), "+f"(d[19]), "+f"(d[20]), "+f"(d[21]), "+f"(d[22]), "+f"(d[23])
    : "l"(da), "l"(db), "r"(scale_d));
}
__device__ __forceinline__ void wgmma_ss_n32(float (&d)[16], uint64_t da, uint64_t db, int scale_d) {
  asm volatile("{\n.reg .pred p;\nsetp.ne.b32 p, %18, 0;\n"
    "wgmma.mma_async.sync.aligned.m64n32k16.f32.bf16.bf16 "
    "{%0, %1, %2, %3, %4, %5, %6, %7, %8, %9, %10, %11, %12, %13, %14, %15}, "
    "%16, %17, p, 1, 1, 0, 0;\n}\n"
    : "+f"(d[0]), "+f"(d[1]), "+f"(d[2]), "+f"(d[3]), "+f"(d[4]), "+f"(d[5]), "+f"(d[6]), "+f"(d[7]),
      "+f"(d[8]), "+f"(d[9]), "+f"(d[10]), "+f"(d[11]), "+f"(d[12]), "+f"(d[13]), "+f"(d[14]), "+f"(d[15])
    : "l"(da), "l"(db), "r"(scale_d));
}

__device__ __forceinline__ void tma_load_2d_mc(uint32_t dst, const CUtensorMap* map, int x, int y, uint32_t bar, uint16_t mask) {
  asm volatile("cp.async.bulk.tensor.2d.shared::cluster.global.mbarrier::complete_tx::bytes.multicast::cluster "
               "[%0], [%1, {%3, %4}], [%2], %5;"
               ::"r"(dst), "l"(map), "r"(bar), "r"(x), "r"(y), "h"(mask) : "memory");
}
__device__ __forceinline__ void mbar_arrive_cluster(uint32_t bar, uint32_t cta) {
  asm volatile("{\n.reg .b32 r;\nmapa.shared::cluster.u32 r, %0, %1;\nmbarrier.arrive.shared::cluster.b64 _, [r];\n}"
               ::"r"(bar), "r"(cta) : "memory");
}
__device__ __forceinline__ void cluster_sync() {
  asm volatile("barrier.cluster.arrive.release.aligned;\nbarrier.cluster.wait.acquire.aligned;" ::: "memory");
}
__device__ __forceinline__ void wait_count(const unsigned* p, unsigned need) {
#pragma unroll 1
  for (int tries = 0; tries < (1 << 18); tries++) {
    unsigned v;
    asm volatile("ld.acquire.gpu.global.u32 %0, [%1];" : "=r"(v) : "l"(p) : "memory");
    if (v >= need) break;
    __nanosleep(64);
  }
}
__device__ __forceinline__ uint32_t sub_bf16x2(uint32_t a, uint32_t b) {
  uint32_t d;
  asm("sub.rn.bf16x2 %0, %1, %2;" : "=r"(d) : "r"(a), "r"(b));
  return d;
}
__device__ __forceinline__ uint32_t add_bf16x2(uint32_t a, uint32_t b) {
  uint32_t d;
  asm("add.rn.bf16x2 %0, %1, %2;" : "=r"(d) : "r"(a), "r"(b));
  return d;
}
__device__ __forceinline__ uint32_t mul_bf16x2(uint32_t a, uint32_t b) {
  uint32_t d;
  asm("mul.rn.bf16x2 %0, %1, %2;" : "=r"(d) : "r"(a), "r"(b));
  return d;
}

template <int NR>
__device__ __forceinline__ void ln_regs(uint32_t (&raw)[NR][16]) {
  float m[NR], q[NR];
#pragma unroll
  for (int r = 0; r < NR; r++) {
    float s0 = 0.f, s1 = 0.f;
#pragma unroll
    for (int i = 0; i < 16; i++) { s0 += bf_lo(raw[r][i]); s1 += bf_hi(raw[r][i]); }
    m[r] = s0 + s1;
  }
#pragma unroll
  for (int o = 16; o > 0; o >>= 1)
#pragma unroll
    for (int r = 0; r < NR; r++) m[r] += __shfl_xor_sync(0xffffffffu, m[r], o);
#pragma unroll
  for (int r = 0; r < NR; r++) {
    m[r] *= 1.0f / 1024.0f;
    float s0 = 0.f, s1 = 0.f;
#pragma unroll
    for (int i = 0; i < 16; i++) {
      const float d0 = bf_lo(raw[r][i]) - m[r], d1 = bf_hi(raw[r][i]) - m[r];
      s0 = fmaf(d0, d0, s0); s1 = fmaf(d1, d1, s1);
    }
    q[r] = s0 + s1;
  }
#pragma unroll
  for (int o = 16; o > 0; o >>= 1)
#pragma unroll
    for (int r = 0; r < NR; r++) q[r] += __shfl_xor_sync(0xffffffffu, q[r], o);
#pragma unroll
  for (int r = 0; r < NR; r++) {
    const uint32_t mb = pack_bf16(m[r], m[r]);
    float sq;
    asm("sqrt.approx.f32 %0, %1;" : "=f"(sq) : "f"(rbf(rbf(q[r] * (1.0f / 1024.0f)) + 1e-5f)));
    const float inv = rcp_approx(rbf(sq));
#pragma unroll
    for (int i = 0; i < 16; i++) {
      const uint32_t d = sub_bf16x2(raw[r][i], mb);
      raw[r][i] = pack_bf16(bf_lo(d) * inv, bf_hi(d) * inv);
    }
  }
}
__device__ __forceinline__ void load_row16(uint32_t (&raw)[16], const bf16* src, int lane) {
#pragma unroll
  for (int j = 0; j < 4; j++) {
    const uint4 u = __ldcg(reinterpret_cast<const uint4*>(src + j * 256 + lane * 8));
    raw[4 * j] = u.x; raw[4 * j + 1] = u.y; raw[4 * j + 2] = u.z; raw[4 * j + 3] = u.w;
  }
}
__device__ __forceinline__ void store_row16(const uint32_t (&raw)[16], bf16* dst, int lane) {
#pragma unroll
  for (int j = 0; j < 4; j++)
    *reinterpret_cast<uint4*>(dst + j * 256 + lane * 8) = make_uint4(raw[4 * j], raw[4 * j + 1], raw[4 * j + 2], raw[4 * j + 3]);
}

namespace fk {
constexpr uint32_t SM0 = 1024;
constexpr uint32_t WO = SM0, WS = WO + 90112, XN = WS + 65536, VX = XN + 49152, QK = VX + 8192, PT = QK + 8192,
                   SP = PT + 4096, VM = SP + 2560, OB = VM + 2048, BAR = OB + 2048;
constexpr uint32_t MEMB = XN + 16384, RED = XN + 32768, VX2 = WO + 81920;
constexpr int SMEM = 232448;
static_assert(BAR + 512 == SM0 + SMEM, "shared memory layout");
constexpr uint32_t B_XN = BAR, B_H2 = BAR + 64, B_H1 = BAR + 120, ONES = BAR + 384, B_PF = BAR + 16, B_WO = BAR + 24, B_SM = BAR + 32, B_VM = BAR + 40, B_VX = BAR + 48, B_ST = BAR + 56, B_PB = BAR + 64, B_W = BAR + 112,
                   MASKS = BAR + 128, PROBE = BAR + 256;
constexpr int NB_M0 = 1, NB_M1 = 2, NB_C = 3, NB_O = 4, NB_ST = 5, NB_DU = 6, NB_CF = 7, NB_W1 = 8, NB_XE = 9, NB_HD = 10, NB_MX = 11, NB_O0 = 12;
#define D_H1 550
#define D_H2 1900
#define D_ST 200
#define SMQ 0x1E
#define SMV 0x1E
#define PRE_G 4
#define PRE_A 1
#define LN_DRY 1
#define MASK_AT 4
#define WO_AT 5
#define NS0 4
#define NS0V 4
#define NTA0 2
#define NTA1 1
#define PF0A 3
#define PF0 10
#define PF1V 10
#define PF1 11
#define REFILL_EARLY 1
#define GATE_MX 0
#define GATE_Q 0
#define PF1Q 4
#define PACEQ 0x60
#define PACEV 0
#define PADD 1
#define D_H2V 2200
#define D_H2L 1700
#define H2_ATV 1
#define VM_BULK 0
#define CF_AT 0
#define H2_AT 0
#define NPRE0 1
#define PROBE_N 4
#define SPACK 1
constexpr uint32_t SPW = SPACK ? 4 : 8, SP_SRC = 160 * SPW;
constexpr int H1_BYTES = 64 * 32768, H2_BYTES = 8 * 8192;
}

#define PROF(wg, i)
#define PROF2(i)
#define RETRY(i)
#define GTSYNC(i)
#define PRO(i)
#define TL(i)
#define TL2(t, i)

__device__ uint4 g_xch[(fk::H1_BYTES + fk::H2_BYTES + 8192) / 16];
__device__ __align__(16) unsigned g_mask[128];
__device__ unsigned g_cnt[8][16];
__device__ unsigned g_next;
constexpr int TAIL_MB0 = 10, GATE_CNT = 12;
__device__ __align__(16) unsigned g_tfix[96], g_lnok[4];
__device__ uint4 g_tpart[96][3][4][256];
__device__ unsigned g_oflag[16];

#define LD_POLL "ld.global.L1::no_allocate"
__device__ __forceinline__ uint4 ld_poll16(const void* p) {
  uint4 v;
  asm volatile(LD_POLL ".v4.u32 {%0,%1,%2,%3}, [%4];" : "=r"(v.x), "=r"(v.y), "=r"(v.z), "=r"(v.w) : "l"(p) : "memory");
  return v;
}
__device__ __forceinline__ uint2 ld_poll8(const void* p) {
  uint2 v;
  asm volatile(LD_POLL ".v2.u32 {%0,%1}, [%2];" : "=r"(v.x), "=r"(v.y) : "l"(p) : "memory");
  return v;
}
__device__ __forceinline__ uint4 ld_strong16(const void* p) {
  uint4 v;
  asm volatile("ld.relaxed.gpu.global.v4.u32 {%0,%1,%2,%3}, [%4];" : "=r"(v.x), "=r"(v.y), "=r"(v.z), "=r"(v.w) : "l"(p) : "memory");
  return v;
}
__device__ __forceinline__ uint2 ld_strong8(const void* p) {
  uint2 v;
  asm volatile("ld.relaxed.gpu.global.v2.u32 {%0,%1}, [%2];" : "=r"(v.x), "=r"(v.y) : "l"(p) : "memory");
  return v;
}
__device__ __forceinline__ void st_pub32(void* p, uint32_t v) { asm volatile("st.relaxed.gpu.global.u32 [%0], %1;" ::"l"(p), "r"(v) : "memory"); }
__device__ __forceinline__ void st_pub16(void* p, uint32_t v) {
  asm volatile("st.relaxed.gpu.global.u16 [%0], %1;" ::"l"(p), "h"((uint16_t)v) : "memory");
}
__device__ __forceinline__ uint32_t ld_strong4(const void* p) {
  uint32_t v;
  asm volatile("ld.relaxed.gpu.global.u32 %0, [%1];" : "=r"(v) : "l"(p) : "memory");
  return v;
}
__device__ __forceinline__ void st_pub64(void* p, uint32_t a, uint32_t b) {
  asm volatile("st.relaxed.gpu.global.v2.u32 [%0], {%1,%2};" ::"l"(p), "r"(a), "r"(b) : "memory");
}
__device__ __forceinline__ void st_pub128(void* p, uint32_t a) {
  asm volatile("st.relaxed.gpu.global.v4.u32 [%0], {%1,%1,%1,%1};" ::"l"(p), "r"(a) : "memory");
}
constexpr uint32_t EMPTY = 0xFFFFFFFFu;
__device__ __forceinline__ uint32_t umax4(const uint4& v) { return max(max(v.x, v.y), max(v.z, v.w)); }
__device__ __forceinline__ void sts128(uint32_t a, uint32_t x, uint32_t y, uint32_t z, uint32_t w) {
  asm volatile("st.shared.v4.u32 [%0], {%1,%2,%3,%4};" ::"r"(a), "r"(x), "r"(y), "r"(z), "r"(w) : "memory");
}
__device__ __forceinline__ void sts64(uint32_t a, uint32_t x, uint32_t y) {
  asm volatile("st.shared.v2.u32 [%0], {%1,%2};" ::"r"(a), "r"(x), "r"(y) : "memory");
}
__device__ __forceinline__ void sts32(uint32_t a, uint32_t x) { asm volatile("st.shared.u32 [%0], %1;" ::"r"(a), "r"(x) : "memory"); }
__device__ __forceinline__ void sts128f(uint32_t a, float x, float y, float z, float w) {
  asm volatile("st.shared.v4.f32 [%0], {%1,%2,%3,%4};" ::"r"(a), "f"(x), "f"(y), "f"(z), "f"(w) : "memory");
}
__device__ __forceinline__ void sts64f(uint32_t a, float x, float y) {
  asm volatile("st.shared.v2.f32 [%0], {%1,%2};" ::"r"(a), "f"(x), "f"(y) : "memory");
}
__device__ __forceinline__ float4 lds128f(uint32_t a) {
  float4 v;
  asm volatile("ld.shared.v4.f32 {%0,%1,%2,%3}, [%4];" : "=f"(v.x), "=f"(v.y), "=f"(v.z), "=f"(v.w) : "r"(a) : "memory");
  return v;
}
__device__ __forceinline__ float2 lds64f(uint32_t a) {
  float2 v;
  asm volatile("ld.shared.v2.f32 {%0,%1}, [%2];" : "=f"(v.x), "=f"(v.y) : "r"(a) : "memory");
  return v;
}
__device__ __forceinline__ float2 lds64f_if(uint32_t a, bool on, float other) {
  float2 v = make_float2(other, other);
  asm volatile("{\n.reg .pred p;\nsetp.ne.u32 p, %3, 0;\n@p ld.shared.v2.f32 {%0,%1}, [%2];\n}" : "+f"(v.x), "+f"(v.y) : "r"(a), "r"((uint32_t)on) : "memory");
  return v;
}
__device__ __forceinline__ void lds128(uint32_t* r, uint32_t a) {
  asm volatile("ld.shared.v4.u32 {%0,%1,%2,%3}, [%4];" : "=r"(r[0]), "=r"(r[1]), "=r"(r[2]), "=r"(r[3]) : "r"(a) : "memory");
}
__device__ __forceinline__ void lds64(uint32_t* r, uint32_t a) {
  asm volatile("ld.shared.v2.u32 {%0,%1}, [%2];" : "=r"(r[0]), "=r"(r[1]) : "r"(a) : "memory");
}
__device__ __forceinline__ uint32_t lds32(uint32_t a) {
  uint32_t v;
  asm volatile("ld.shared.u32 %0, [%1];" : "=r"(v) : "r"(a) : "memory");
  return v;
}
__device__ __forceinline__ void ldsm4(uint32_t* r, uint32_t a) {
  asm volatile("ldmatrix.sync.aligned.m8n8.x4.shared.b16 {%0,%1,%2,%3}, [%4];"
               : "=r"(r[0]), "=r"(r[1]), "=r"(r[2]), "=r"(r[3]) : "r"(a) : "memory");
}
__device__ __forceinline__ void ldsm4t(uint32_t* r, uint32_t a) {
  asm volatile("ldmatrix.sync.aligned.m8n8.x4.trans.shared.b16 {%0,%1,%2,%3}, [%4];"
               : "=r"(r[0]), "=r"(r[1]), "=r"(r[2]), "=r"(r[3]) : "r"(a) : "memory");
}
__device__ __forceinline__ void stsm4(uint32_t a, uint32_t r0, uint32_t r1, uint32_t r2, uint32_t r3) {
  asm volatile("stmatrix.sync.aligned.m8n8.x4.shared.b16 [%0], {%1,%2,%3,%4};"
               ::"r"(a), "r"(r0), "r"(r1), "r"(r2), "r"(r3) : "memory");
}
__device__ __forceinline__ void stsm4t(uint32_t a, uint32_t r0, uint32_t r1, uint32_t r2, uint32_t r3) {
  asm volatile("stmatrix.sync.aligned.m8n8.x4.trans.shared.b16 [%0], {%1,%2,%3,%4};"
               ::"r"(a), "r"(r0), "r"(r1), "r"(r2), "r"(r3) : "memory");
}
__device__ __forceinline__ void mma16816(float* d, const uint32_t* a, uint32_t b0, uint32_t b1) {
  asm volatile("mma.sync.aligned.m16n8k16.row.col.f32.bf16.bf16.f32 {%0,%1,%2,%3}, {%4,%5,%6,%7}, {%8,%9}, {%0,%1,%2,%3};"
               : "+f"(d[0]), "+f"(d[1]), "+f"(d[2]), "+f"(d[3])
               : "r"(a[0]), "r"(a[1]), "r"(a[2]), "r"(a[3]), "r"(b0), "r"(b1));
}
__device__ __forceinline__ void mma16816z(float* d, const uint32_t* a, uint32_t b0, uint32_t b1) {
  asm volatile("mma.sync.aligned.m16n8k16.row.col.f32.bf16.bf16.f32 {%0,%1,%2,%3}, {%4,%5,%6,%7}, {%8,%9}, {%10,%10,%10,%10};"
               : "=f"(d[0]), "=f"(d[1]), "=f"(d[2]), "=f"(d[3])
               : "r"(a[0]), "r"(a[1]), "r"(a[2]), "r"(a[3]), "r"(b0), "r"(b1), "f"(0.f));
}
__device__ __forceinline__ void mma1688(float* d, uint32_t a0, uint32_t a1, uint32_t b0) {
  asm volatile("mma.sync.aligned.m16n8k8.row.col.f32.bf16.bf16.f32 {%0,%1,%2,%3}, {%4,%5}, {%6}, {%0,%1,%2,%3};"
               : "+f"(d[0]), "+f"(d[1]), "+f"(d[2]), "+f"(d[3]) : "r"(a0), "r"(a1), "r"(b0));
}
__device__ __forceinline__ uint32_t movtrans(uint32_t a) {
  uint32_t d;
  asm volatile("movmatrix.sync.aligned.m8n8.trans.b16 %0, %1;" : "=r"(d) : "r"(a));
  return d;
}
__device__ __forceinline__ uint32_t mapa(uint32_t a, uint32_t rank) {
  uint32_t d;
  asm("mapa.shared::cluster.u32 %0, %1, %2;" : "=r"(d) : "r"(a), "r"(rank));
  return d;
}
__device__ __forceinline__ void st_async64(uint32_t a, uint32_t x, uint32_t y, uint32_t bar) {
  asm volatile("st.async.weak.shared::cluster.mbarrier::complete_tx::bytes.v2.b32 [%0], {%1,%2}, [%3];"
               ::"r"(a), "r"(x), "r"(y), "r"(bar) : "memory");
}
__device__ __forceinline__ void st_async64f(uint32_t a, float x, float y, uint32_t bar) {
  st_async64(a, __float_as_uint(x), __float_as_uint(y), bar);
}
__device__ __forceinline__ void bulk_s2s(uint32_t dst, uint32_t src, uint32_t bytes, uint32_t bar) {
  asm volatile("cp.async.bulk.shared::cluster.shared::cta.mbarrier::complete_tx::bytes [%0], [%1], %2, [%3];"
               ::"r"(dst), "r"(src), "r"(bytes), "r"(bar) : "memory");
}
__device__ __forceinline__ void tma_store_3d(const CUtensorMap* map, uint32_t src, int x, int y, int z) {
  asm volatile("cp.async.bulk.tensor.3d.global.shared::cta.bulk_group [%0, {%2, %3, %4}], [%1];"
               ::"l"(map), "r"(src), "r"(x), "r"(y), "r"(z) : "memory");
}
__device__ __forceinline__ void mbar_spin(uint32_t bar, uint32_t parity) {
  asm volatile("{\n.reg .pred p;\n.reg .b32 n;\nmov.u32 n, 0x100000;\nMW_L:\n"
               "mbarrier.try_wait.parity.shared::cta.b64 p, [%0], %1;\n@p bra.uni MW_D;\n"
               "add.s32 n, n, -1;\nsetp.ne.u32 p, n, 0;\n@p bra.uni MW_L;\nMW_D:\n}" ::"r"(bar), "r"(parity) : "memory");
}
__device__ __forceinline__ bool mbar_test(uint32_t bar, uint32_t parity) {
  uint32_t done;
  asm volatile("{\n.reg .pred p;\nmbarrier.test_wait.parity.shared::cta.b64 p, [%1], %2;\nselp.u32 %0, 1, 0, p;\n}"
               : "=r"(done) : "r"(bar), "r"(parity) : "memory");
  return done != 0;
}
__device__ __forceinline__ void mbar_arrive_remote(uint32_t bar) {
  asm volatile("mbarrier.arrive.shared::cluster.b64 _, [%0];" ::"r"(bar) : "memory");
}
__device__ __forceinline__ bool elect_one() {
  uint32_t r;
  asm volatile("{\n.reg .pred p;\nelect.sync _|p, 0xffffffff;\nselp.u32 %0, 1, 0, p;\n}" : "=r"(r));
  return r != 0;
}
__device__ __forceinline__ void st_async32(uint32_t a, uint32_t x, uint32_t bar) {
  asm volatile("st.async.weak.shared::cluster.mbarrier::complete_tx::bytes.b32 [%0], %1, [%2];" ::"r"(a), "r"(x), "r"(bar) : "memory");
}
#define named_bar_and(id, n, in, out) \
  asm volatile("{\n.reg .pred p, q;\nsetp.ne.u32 p, %1, 0;\nbar.red.and.pred q, %2, %3, p;\nselp.u32 %0, 1, 0, q;\n}" \
               : "=r"(out) : "r"(in), "n"(id), "n"(n) : "memory")
__device__ __forceinline__ void bulk_g2s(uint32_t dst, const void* src, uint32_t bytes, uint32_t bar) {
  asm volatile("cp.async.bulk.shared::cluster.global.mbarrier::complete_tx::bytes [%0], [%1], %2, [%3];"
               ::"r"(dst), "l"(src), "r"(bytes), "r"(bar) : "memory");
}
__device__ __forceinline__ void l2_prefetch(const void* p, uint32_t bytes) {
  asm volatile("cp.async.bulk.prefetch.L2.global [%0], %1;" ::"l"(p), "r"(bytes) : "memory");
}

__device__ __forceinline__ uint32_t clk32() { uint32_t c; asm volatile("mov.u32 %0, %%clock;" : "=r"(c)::"memory"); return c; }
__device__ __forceinline__ void spin_until(uint32_t t) { while ((int32_t)(clk32() - t) < 0) {} }
#define PIN(x) asm volatile("" : "+r"(x))
#define OPQ                                                                                     \
  int tid_o = tid;                                                                              \
  asm volatile("" : "+r"(tid_o));                                                               \
  const int lane = tid_o & 31, w = (tid_o >> 5) & 3, t7 = tid_o & 127, lg = lane >> 2,          \
            lq = lane & 3, mi = lane >> 3, mr = lane & 7;                                       \
  (void)w; (void)t7; (void)lg; (void)lq; (void)mi; (void)mr; (void)lane

#define SMAP                                                                                                          \
  const uint32_t SM0 = self + fk::SM0, WO = self + fk::WO, WS = self + fk::WS, XN = self + fk::XN, VX = self + fk::VX, \
                 QK = self + fk::QK, PT = self + fk::PT, SP = self + fk::SP, VM = self + fk::VM, OB = self + fk::OB,   \
                 RED = self + fk::RED, VX2 = self + fk::VX2, MEMB = self + fk::MEMB, B_XN = self + fk::B_XN, B_SM = self + fk::B_SM,       \
                 B_VM = self + fk::B_VM, B_VX = self + fk::B_VX, B_ST = self + fk::B_ST, B_PB = self + fk::B_PB,       \
                 B_W = self + fk::B_W, B_H2 = self + fk::B_H2, B_H1 = self + fk::B_H1, B_PF = self + fk::B_PF, B_WO = self + fk::B_WO, MASKS = self + fk::MASKS, PROBE = self + fk::PROBE;                             \
  (void)SM0; (void)WO; (void)WS; (void)XN; (void)VX; (void)QK; (void)PT; (void)SP; (void)VM; (void)OB; (void)RED; (void)VX2; \
  (void)MEMB; (void)B_XN; (void)B_SM; (void)B_VM; (void)B_VX; (void)B_ST; (void)B_PB; (void)B_W; (void)MASKS; (void)PROBE; (void)B_H2; (void)B_H1; (void)B_PF; (void)B_WO

struct FParams {
  CUtensorMap wq, wk, wv, wo, wo16, xn, xn12, o;
  CUtensorMap ta, tb, tx, tg, tout;
  const bf16 *mem0, *x;
  bf16* xn_ptr;
  uint64_t dxn;
  int nprobe;
  char* xch;
};

__device__ __forceinline__ uint2 probe_pair(char* p, uint32_t val, uint32_t dummy, int n) {
  uint2 best = make_uint2(0x7FFFFFFF, 0x7FFFFFFF);
  st_pub128(p, val); st_pub128(p + 16, val); st_pub128(p + 4096, val); st_pub128(p + 4112, val);
#pragma unroll 1
  for (int r = 0; r < n; r++) {
    uint32_t v;
    const uint32_t c0 = clk32();
    asm volatile("atom.relaxed.gpu.global.exch.b32 %0, [%1], %2;" : "=r"(v) : "l"(p + (r & 1) * 4096), "r"(val) : "memory");
    asm volatile("{\n.reg .pred p;\nsetp.eq.u32 p, %0, 0x12345678;\n@p st.shared.u32 [%1], %0;\n}" ::"r"(v), "r"(dummy) : "memory");
    const uint32_t d = clk32() - c0;
    if (r & 1) best.y = min(best.y, d); else best.x = min(best.x, d);
  }
  return best;
}

typedef uint32_t WRegs[6][2][4][4];

constexpr uint32_t nth_chunks(uint32_t mask) {
  uint32_t t = 0;
  for (int c = 0, n = 0; c < 10; c++) if ((mask >> c) & 1) t |= c << (4 * n++);
  return t;
}
constexpr uint64_t chunk_pos(uint32_t mask) {
  uint64_t t = 0;
  for (int c = 0, a = 0, b = 0; c < 10; c++) t |= (uint64_t)(((mask >> c) & 1) ? a++ : b++) << (4 * c);
  return t;
}
template <bool ISV> struct Chunks {
  static constexpr uint32_t MASK = ISV ? SMV : SMQ, SMT = nth_chunks(MASK), RFT = nth_chunks(~MASK & 1023);
  static_assert(!(MASK & 1), "the first chunk initialises the accumulators");
  static __device__ __forceinline__ constexpr int rf(int wg, int i) { return wg ? 10 + i : (RFT >> (4 * i)) & 15; }
  static __device__ __forceinline__ constexpr int sm(int i) { return (SMT >> (4 * i)) & 15; }
  static constexpr uint64_t IDX = chunk_pos(MASK);
  static __device__ __forceinline__ constexpr int idx(int c) { return (IDX >> (4 * c)) & 15; }
};

template <bool ISV, int WG> struct ProjCfg {
  static constexpr int N0 = ISV ? NS0V : NS0, NS = WG ? 8 - N0 : N0, P0 = WG ? N0 : 0, NTA = WG ? NTA1 : NTA0;
};
__device__ __forceinline__ void load_pair(uint32_t (&t)[4][4], uint32_t wsa, int pp) {
#pragma unroll
  for (int f = 0; f < 4; f++) ldsm4t(t[f], wsa + ((pp >> 1) * 2 + (f & 1)) * 8192 + ((pp & 1) * 2 + (f >> 1)) * 2048);
}
template <bool ISV, int WG>
__device__ __forceinline__ void proj_mem(const WRegs& wr, uint32_t (&ta)[ProjCfg<ISV, WG>::NTA][4][4], uint32_t wsa, uint32_t mba,
                                         float (&a0)[4], float (&a1)[4]) {
  constexpr int NS = ProjCfg<ISV, WG>::NS, P0 = ProjCfg<ISV, WG>::P0, NTA = ProjCfg<ISV, WG>::NTA, NP = 12 + NS;
  float acc[4][4];
  auto spos = [](int j) { return j < NTA ? j : j + (j - NTA + 1) * 12 / (NS - NTA > 0 ? NS - NTA : 1); };
  auto which = [&](int p) { int r = -1; for (int j = 0; j < NS; j++) if (spos(j) == p) r = j; return r; };
  auto nsm_before = [&](int p) { int n = 0; for (int j = 0; j < NS; j++) if (spos(j) < p) n++; return n; };
#pragma unroll
  for (int p = 0; p < NP; p++) {
    const int j = which(p), r = j >= 0 ? 0 : p - nsm_before(p);
    uint32_t bp[4], tl[4][4];
    ldsm4(bp, mba + (j >= 0 ? Chunks<ISV>::sm((P0 + (j >= 0 ? j : 0)) >> 1) * 1024 + ((P0 + j) & 1) * 512 : Chunks<ISV>::rf(WG, r >> 1) * 1024 + (r & 1) * 512));
    if (j >= NTA) load_pair(tl, wsa, P0 + j);
#pragma unroll
    for (int u = 0; u < 2; u++)
#pragma unroll
      for (int T = 0; T < 2; T++) {
        const uint32_t* a = j >= NTA ? tl[u * 2 + T] : j >= 0 ? ta[j >= 0 ? j % NTA : 0][u * 2 + T] : wr[r >> 1][T][(r & 1) * 2 + u];
        if (p == 0) mma16816z(acc[u * 2 + T], a, bp[2 * u], bp[2 * u + 1]);
        else mma16816(acc[u * 2 + T], a, bp[2 * u], bp[2 * u + 1]);
      }
  }
#pragma unroll
  for (int i = 0; i < 4; i++) { a0[i] = acc[0][i] + acc[2][i]; a1[i] = acc[1][i] + acc[3][i]; }
}
template <bool ISV, int WG, int J0, int J1>
__device__ __forceinline__ void proj_mem_prefetch(uint32_t (&ta)[ProjCfg<ISV, WG>::NTA][4][4], uint32_t wsa) {
#pragma unroll
  for (int j = J0; j < J1; j++) load_pair(ta[j], wsa, ProjCfg<ISV, WG>::P0 + j);
}

template <bool ISV, int WG>
__device__ __forceinline__ void proj_finish(const float (&a0)[4], const float (&a1)[4], uint32_t peer0, uint32_t peer1, uint32_t self, int tid, int warp,
                                            uint32_t (&vmo)[4]) {
  using namespace fk;
  SMAP;
  OPQ;
  if (!ISV) {
    stsm4(PT + mr * 16 + ((mi >> 1) ? WG * 1024 + w * 256 + (mi & 1) * 128 : 2048 + w * 512 + (mi & 1) * 256 + WG * 128),
          pack_bf16(a0[0], a0[1]), pack_bf16(a0[2], a0[3]), pack_bf16(a1[0], a1[1]), pack_bf16(a1[2], a1[3]));
    named_bar_sync(NB_C, 256);
  } else {
    if (WG == 0) sts128f(RED + t7 * 16, a1[0], a1[1], a1[2], a1[3]);
    else sts128f(RED + 2048 + t7 * 16, a0[0], a0[1], a0[2], a0[3]);
    if (WG == 1) { lds64(vmo, VM + t7 * 8); lds64(vmo + 2, VM + 1024 + t7 * 8); }
    named_bar_sync(NB_C, 256);
    const float4 p = lds128f(RED + (1 - WG) * 2048 + t7 * 16);
    const float* k = WG == 0 ? a0 : a1;
    const uint32_t v0 = pack_bf16(k[0] + p.x, k[1] + p.y), v1 = pack_bf16(k[2] + p.z, k[3] + p.w);
    const uint32_t off = VM + WG * 1024 + t7 * 8;
    if (VM_BULK) {
      sts64(off, v0, v1);
      fence_proxy_async_smem();
      __syncwarp();
      const uint32_t a = VM + WG * 1024 + warp * 256;
      if (elect_one()) {
        bulk_s2s(peer0 + a, a, 256, peer0 + B_VM);
        bulk_s2s(peer1 + a, a, 256, peer1 + B_VM);
        mbar_arrive(B_VM);
      }
    } else {
      st_async64(peer0 + off, v0, v1, peer0 + B_VM);
      st_async64(peer1 + off, v0, v1, peer1 + B_VM);
      sts64(off, v0, v1);
      __syncwarp();
      if (lane == 0) mbar_arrive(B_VM);
    }
  }
}

__device__ __forceinline__ void send_scores(float s0, float s1, uint32_t off, uint32_t peer0, uint32_t peer1, uint32_t bar, int lane) {
  if (SPACK) {
    const uint32_t v = pack_bf16(s0, s1);
    st_async32(peer0 + off, v, peer0 + bar);
    st_async32(peer1 + off, v, peer1 + bar);
    sts32(off, v);
  } else {
    st_async64f(peer0 + off, s0, s1, peer0 + bar);
    st_async64f(peer1 + off, s0, s1, peer1 + bar);
    sts64f(off, s0, s1);
  }
  __syncwarp();
  if (lane == 0) mbar_arrive(bar);
}

template <int MODE>
__device__ __forceinline__ void wo_load(uint32_t* r, int f, uint32_t woa, uint32_t wob, bool third) {
  constexpr int NT = MODE ? 3 : 2;
  if (MODE >= 2 && f % 3 == 2)
    asm volatile("{\n.reg .pred p;\nsetp.ne.u32 p, %5, 0;\nmov.b32 %0, 0;\nmov.b32 %1, 0;\nmov.b32 %2, 0;\nmov.b32 %3, 0;\n"
                 "@p ldmatrix.sync.aligned.m8n8.x4.trans.shared.b16 {%0,%1,%2,%3}, [%4];\n}"
                 : "=r"(r[0]), "=r"(r[1]), "=r"(r[2]), "=r"(r[3]) : "r"(wob + (f / 3) * 512), "r"((uint32_t)third) : "memory");
  else ldsm4t(r, woa + (f % NT) * 32768 + (f / NT) * 2048);
}
template <int MODE, int PF>
__device__ __forceinline__ void wo_phase(uint32_t (&wf)[PF][4], uint32_t woa, uint32_t wob, bool third, uint32_t oba, char* h1p,
                                         uint32_t sel, uint32_t tag) {
  constexpr int NT = MODE ? 3 : 2;
  float c[NT][4];
  uint32_t of[2][4];
  ldsm4t(of[0], oba);
#pragma unroll
  for (int k = 0; k < 8; k++) {
    if ((k & 1) == 0 && k + 2 < 8) ldsm4t(of[((k >> 1) + 1) & 1], oba + ((k >> 1) + 1) * 512);
#pragma unroll
    for (int i = 0; i < NT; i++) {
      const int f = k * NT + i;
      const uint32_t b0 = of[(k >> 1) & 1][2 * (k & 1)], b1 = of[(k >> 1) & 1][2 * (k & 1) + 1];
      if (k == 0) mma16816z(c[i], wf[f % PF], b0, b1); else mma16816(c[i], wf[f % PF], b0, b1);
      if (f + PF < 8 * NT) wo_load<MODE>(wf[f % PF], f + PF, woa, wob, third);
    }
  }
#pragma unroll
  for (int i = 0; i < NT; i++) {
    char* p = h1p + i * (8 * 32768) + ((sel >> (2 * i)) & 3) * 2048;
    const uint32_t tm = (sel >> 10) & 1;
    if (MODE < 2 || i < 2 || third) {
      st_pub32(p, (pack_bf16(c[i][0], c[i][1]) & ~tm) | (tag & tm));
      st_pub32(p + 1024, (pack_bf16(c[i][2], c[i][3]) & ~tm) | (tag & tm));
    }
  }
}
template <int MODE, int F0, int F1, int PF>
__device__ __forceinline__ void wo_prefetch(uint32_t (&wf)[PF][4], uint32_t woa, uint32_t wob, bool third) {
#pragma unroll
  for (int f = F0; f < F1; f++) wo_load<MODE>(wf[f], f, woa, wob, third);
}

template <bool ISV> __device__ __forceinline__ uint32_t tok_addr(uint32_t base, int tid) {
  OPQ;
  return ISV ? base + w * 2048 + (mi & 1) * 1024 + (mi >> 1) * 128 + mr * 16 : base + (mi >> 1) * 1024 + w * 256 + (mi & 1) * 128 + mr * 16;
}
template <bool ISV> __device__ __forceinline__ constexpr uint32_t tok_off(int T, int i) { return ISV ? T * 512 + i * 256 : T * 4096 + i * 2048; }
template <bool ISV, int T, bool ADD>
__device__ __forceinline__ void tok_store(const float (&x)[16], uint32_t a, const uint32_t (&p)[2][4]) {
#pragma unroll
  for (int i = 0; i < 2; i++) {
    uint32_t r[4];
#pragma unroll
    for (int k = 0; k < 4; k++)
      r[k] = !ADD ? pack_bf16(x[8 * i + 2 * k], x[8 * i + 2 * k + 1])
           : PADD ? add_bf16x2(pack_bf16(x[8 * i + 2 * k], x[8 * i + 2 * k + 1]), p[i][k])
                  : pack_bf16(x[8 * i + 2 * k] + bf_lo(p[i][k]), x[8 * i + 2 * k + 1] + bf_hi(p[i][k]));
    stsm4(a + tok_off<ISV>(T, i), r[0], r[1], r[2], r[3]);
  }
}

__device__ __forceinline__ void load_xn(const FParams& P, int seg, uint32_t self) {
  SMAP;
  mbar_expect_tx(B_XN, 49152);
  tma_load_3d(XN, &P.xn12, 0, seg * 32, 0, B_XN);
}

#define DESC_ADD(d, n) asm volatile("add.s64 %0, %0, %1;" : "+l"(d) : "n"(n))

template <bool ISV>
__device__ __forceinline__ void f_wg0(const FParams& P, const WRegs& wr, const int h, const int rank, const uint32_t hw, int tid) {
  using namespace fk;
  const uint32_t self = mapa(0, (hw >> (2 * rank)) & 3), peer0 = mapa(0, (hw >> (ISV ? 0 : 2 * (rank ^ 1))) & 3) - self,
                 peer1 = mapa(0, (hw >> (ISV ? 2 : 4)) & 3) - self;
  SMAP;
  const int tile0 = rank * 22;
  const uint32_t usel = __shfl_sync(0xffffffffu, tid, 0);
  const int warp = __shfl_sync(0xffffffffu, threadIdx.x >> 5, 0);
  constexpr int WMODE = ISV ? 0 : 2;
  const bool three = warp < 2;
  uint32_t d_h2 = D_H2V, h2ph = 1;
  tid ^= 0x5500;
#pragma unroll 1
  for (int s = -1;;) {
    uint32_t ta[ProjCfg<ISV, 0>::NTA][4][4], wsa, mba;
    const char* src = P.xch + H1_BYTES + ((s & 1) * 4 + warp) * 8192 + ((usel >> (16 + (s & 1))) & 1) * 4096;
    {
      const uint32_t ph = (s + 1) & 1;
      float x0[16], x1[16];
      uint32_t t_pub = 0;
      wg_fence();
      static_assert(Chunks<ISV>::MASK == 0x1E, "chunks 1 .. 4 are in shared memory");
      uint64_t db = P.dxn;
      auto rs_chunk = [&](int ci, bool pace) {
#pragma unroll
        for (int u = 0; u < 4; u++) {
          wgmma_rs_n32(x0, wr[ci][0][u], db, (ci | u) != 0);
          wgmma_rs_n32(x1, wr[ci][1][u], db, (ci | u) != 0);
          if (u < 3) DESC_ADD(db, 2); else DESC_ADD(db, 250);
          if (pace) { wg_commit(); wg_wait<2>(); wg_fence(); }
        }
      };
      rs_chunk(0, false);
      t_pub = clk32() - 60;
      PROF(0, 8); PROF(0, 1);
#pragma unroll
      for (int c = 1; c <= 4; c++) {
#pragma unroll
        for (int u = 0; u < 4; u++) {
          const uint64_t dx = make_desc(fk::XN + c * 4096 + u * 32, 16, 1024);
          wgmma_ss_n32_ta(x0, make_desc(fk::WS + (c - 1) * 16384 + u * 2048, 8192, 1024), dx, 1);
          wgmma_ss_n32_ta(x1, make_desc(fk::WS + (c - 1) * 16384 + 8192 + u * 2048, 8192, 1024), dx, 1);
          if (c == 4 && u == 1) { wg_commit(); wg_wait<1>(); named_bar_arrive(NB_XE, 160); wg_fence(); }
        }
        if (c == 3) wg_commit();
      }
      DESC_ADD(db, 1024);
#pragma unroll
      for (int c = 5; c < 10; c++) {
        if (c == 9) named_bar_arrive(NB_ST, 256);
        rs_chunk(c - 4, ((ISV ? PACEV : PACEQ) >> c) & 1);
      }
      wg_commit();
      wg_wait<0>();
      PROF(0, 10);
      const uint32_t tb = ISV ? (ph ? VX2 : VX) : QK;
      auto h2_issue = [&]() {
        spin_until(t_pub + (ISV ? d_h2 : D_H2));
        PROF(0, 13);
        if (elect_one()) { mbar_expect_tx(B_H2 + 8 * warp, 4096); bulk_g2s(MEMB + warp * 4096, src, 4096, B_H2 + 8 * warp); }
      };
      named_bar_sync(NB_CF, ISV ? 160 : 256);
      if ((ISV ? H2_ATV : H2_AT) == 0) h2_issue();
      const uint32_t none[2][4] = {}, tka = tok_addr<ISV>(tb, tid);
      tok_store<ISV, 0, false>(x0, tka, none);
      if ((ISV ? H2_ATV : H2_AT) == 1) h2_issue();
      tok_store<ISV, 1, false>(x1, tka, none);
      if ((ISV ? H2_ATV : H2_AT) == 2) h2_issue();
      named_bar_arrive(NB_DU, 256);
    }
    {
      OPQ;
      wsa = WS + ((mi >> 1) * 8 + mr) * 128 + (((2 * w + (mi & 1)) ^ mr) << 4);
      mba = MEMB + lane * 16;
      PIN(wsa); PIN(mba);
      {
        const uint32_t chk = MEMB + w * 4096 + lane * 32 + lg * 4, bar = B_H2 + 8 * warp;
        PROF(0, 11);
        proj_mem_prefetch<ISV, 0, 0, NPRE0>(ta, wsa);
#pragma unroll 1
        for (int tries = 0; tries < POLL_TRIES; tries++) {
          mbar_spin(bar, h2ph);
          h2ph ^= 1;
          const uint32_t mx = max(max(lds32(chk), lds32(chk + 1024)), max(lds32(chk + 2048), lds32(chk + 3072)));
          if (__all_sync(0xffffffffu, mx != EMPTY)) break;
          RETRY(1);
          if (elect_one()) { mbar_expect_tx(bar, 4096); bulk_g2s(MEMB + warp * 4096, src, 4096, bar); }
        }
      }
      PROF(0, 12);
      named_bar_arrive(NB_M1, 256);
      proj_mem_prefetch<ISV, 0, NPRE0, NTA0>(ta, wsa);
      named_bar_sync(NB_M0, 128);
    }
    s++;
    tid ^= 0x5500;
    {
      float a0[4], a1[4];
      proj_mem<ISV, 0>(wr, ta, wsa, mba, a0, a1);
      PROF(0, 2);
      uint32_t unused[4];
      proj_finish<ISV, 0>(a0, a1, peer0, peer1, self, tid, warp, unused);
      PROF(0, 3);
      if (s + 1 == cfg::NSEG) break;
      uint32_t wf[PF0][4], woa, wob;
      bool xn_ok;
      {
        OPQ;
        if (!ISV) {
          uint32_t qf[4][4], kf[2][4];
          const uint32_t qa = PT + 2048 + lane * 16, ka = QK + 4096 + w * 1024 + lane * 16;
          ldsm4t(qf[0], qa); ldsm4t(kf[0], ka); ldsm4t(qf[1], qa + 512);
          ldsm4t(qf[2], qa + 1024); ldsm4t(kf[1], ka + 512); ldsm4t(qf[3], qa + 1536);
          float c0[4], c1[4];
          mma16816z(c0, qf[0], kf[0][0], kf[0][1]);
          mma16816z(c1, qf[1], kf[0][2], kf[0][3]);
          mma16816(c0, qf[2], kf[1][0], kf[1][1]);
          mma16816(c1, qf[3], kf[1][2], kf[1][3]);
          const float s0 = (c0[0] + c0[2]) + (c1[0] + c1[2]), s1 = (c0[1] + c0[3]) + (c1[1] + c1[3]);
          send_scores(s0, s1, SP + rank * SP_SRC + t7 * SPW, peer0, peer1, B_SM, lane);
        }
        PROF(0, 4);
        woa = WO + 16384 + ((mi >> 1) * 8 + mr) * 128 + (((2 * w + (mi & 1)) ^ mr) << 4);
        wob = WO + 81920 + w * 4096 + ((mi >> 1) * 8 + mr) * 32 + (((mi & 1) ^ (mr >> 2)) << 4);
        uint32_t vf[2][2][4], vm[2][2];
        if (s == 0) mbar_spin(B_WO, 0);
        if (!ISV) mbar_spin(B_VX, s & 1);
        PROF(0, 14);
#pragma unroll
        for (int T = 0; T < 2; T++)
#pragma unroll
          for (int kk = 0; kk < 2; kk++) ldsm4(vf[T][kk], ((ISV && (s & 1)) ? VX2 : VX) + w * 2048 + (mi & 1) * 1024 + (mi >> 1) * 128 + mr * 16 + T * 512 + kk * 256);
        wo_prefetch<WMODE, 0, PF0A>(wf, woa, wob, three);
        uint32_t spa = SP + lane * SPW, vma = VM + t7 * 8, oa = OB + (mi >> 1) * 1024 + w * 256 + (mi & 1) * 128 + mr * 16;
        PIN(spa); PIN(vma); PIN(oa);
        if (ISV) {
          d_h2 = D_H2L;
          if (!__all_sync(0xffffffffu, mbar_test(B_SM, s & 1))) { d_h2 = D_H2V; mbar_spin(B_SM, s & 1); }
        } else {
          mbar_spin(B_SM, s & 1);
        }
        PROF(0, 5);
        float sc[10];
#pragma unroll
        for (int j = 0; j < 5; j++) {
          if (SPACK) {
            const uint32_t x = lds32(spa + j * 128), y = lds32(spa + SP_SRC + j * 128);
            sc[2 * j] = bf_lo(x) + bf_lo(y); sc[2 * j + 1] = bf_hi(x) + bf_hi(y);
          } else {
            const float2 x = lds64f(spa + j * 256), y = lds64f(spa + SP_SRC + j * 256);
            sc[2 * j] = x.x + y.x; sc[2 * j + 1] = x.y + y.y;
          }
        }
        const bool vm_ok = mbar_test(B_VM, s & 1);
        lds64(vm[0], vma); lds64(vm[1], vma + 1024);
        float m = fmaxf(fmaxf(fmaxf(sc[0], sc[1]), fmaxf(sc[2], sc[3])), fmaxf(fmaxf(sc[4], sc[5]), fmaxf(sc[6], sc[7])));
        m = fmaxf(m, fmaxf(sc[8], sc[9]));
        const float cs = 0.08838834764831845f * 1.4426950408889634f;
        uint32_t pb[5];
        m = fmaxf(m, __shfl_xor_sync(0xffffffffu, m, 1));
        m = fmaxf(m, __shfl_xor_sync(0xffffffffu, m, 2));
        if (ISV ? GATE_MX : GATE_Q) named_bar_arrive(NB_MX, 256);
        const float mc = -m * cs;
#pragma unroll
        for (int j = 0; j < 5; j++) pb[j] = pack_bf16(ex2_approx(fmaf(sc[2 * j], cs, mc)), ex2_approx(fmaf(sc[2 * j + 1], cs, mc)));
        PROF(0, 15);
        if (!vm_ok) { mbar_spin(B_VM, s & 1); lds64(vm[0], vma); lds64(vm[1], vma + 1024); }
        PROF(0, 6);
        float o0[4], o1[4], rs[4];
        const uint32_t ones[4] = {0x3F803F80u, 0x3F803F80u, 0x3F803F80u, 0x3F803F80u};
        mma16816z(rs, ones, pb[0], pb[1]);
        mma16816z(o0, vf[0][0], pb[0], pb[1]);
        mma16816z(o1, vf[1][0], pb[0], pb[1]);
        mma16816(rs, ones, pb[2], pb[3]);
        mma16816(o0, vf[0][1], pb[2], pb[3]);
        mma16816(o1, vf[1][1], pb[2], pb[3]);
        mma1688(rs, ones[0], ones[0], pb[4]);
        mma1688(o0, vm[0][0], vm[0][1], pb[4]);
        mma1688(o1, vm[1][0], vm[1][1], pb[4]);
        const float i0 = rcp_approx(rs[0]), i1 = rcp_approx(rs[1]);
        stsm4(oa, pack_bf16(o0[0] * i0, o0[1] * i1), pack_bf16(o0[2] * i0, o0[3] * i1),
              pack_bf16(o1[0] * i0, o1[1] * i1), pack_bf16(o1[2] * i0, o1[3] * i1));
      }
      {
        OPQ;
        named_bar_arrive(NB_O, 256);
        wo_prefetch<WMODE, PF0A, PF0>(wf, woa, wob, three);
        xn_ok = mbar_test(B_XN, (s + 1) & 1);
        char* h1p = P.xch + (tile0 + 4 + w) * 32768 + (h >> 3) * 8192 + (h & 7) * 128 + (((2 * lq + (lg & 1)) ^ (h & 7)) << 4) + (lg >> 1) * 4;
        uint32_t oba = OB + lane * 16;
        PIN(oba);
        PROF(0, 7);
        named_bar_sync(NB_O0, 128);
        const uint32_t tag = ((s >> 1) & 1) ^ 1;
        wo_phase<WMODE>(wf, woa, wob, three, oba, h1p, tid >> 8, tag);
        PROF(0, 9);
        if (!xn_ok) mbar_spin(B_XN, (s + 1) & 1);
        named_bar_sync(NB_HD, 256);
      }
    }
  }
}

template <bool ISV>
__device__ __forceinline__ void f_wg1(const FParams& P, const WRegs& wr, const int h, const int rank, const uint32_t hw, int tid) {
  using namespace fk;
  const uint32_t self = mapa(0, (hw >> (2 * rank)) & 3), peer0 = mapa(0, (hw >> (ISV ? 0 : 2 * (rank ^ 1))) & 3) - self,
                 peer1 = mapa(0, (hw >> (ISV ? 2 : 4)) & 3) - self;
  SMAP;
  const int tile0 = rank * 22;
  const uint32_t usel = __shfl_sync(0xffffffffu, tid, 0);
  const int warp = __shfl_sync(0xffffffffu, (threadIdx.x >> 5) & 3, 0);
  constexpr int WMODE = 1;
  uint32_t h1ph = 0;
  auto o_done = [&](int mb) {
    tma_store_wait_all();
    asm volatile("fence.proxy.async.global;" ::: "memory");
    asm volatile("red.relaxed.gpu.global.add.u32 [%0], 1;" ::"l"(&g_oflag[mb]) : "memory");
  };
  uint32_t vmo[4] = {0, 0, 0, 0};
  if (ISV) {
    OPQ;
    sts32(PT + (t7 >> 2) * 128 + ((5 ^ lg) << 4) + lq * 4, 0);
    sts32(PT + (t7 >> 2) * 128 + ((6 ^ lg) << 4) + lq * 4, 0);
  }
  tid ^= 0x5500;
#pragma unroll 1
  for (int s = -1;;) {
    uint32_t ta[ProjCfg<ISV, 1>::NTA][4][4], wsa, mba;
    if (s + 1 < cfg::NSEG) mbar_spin(B_XN, (s + 1) & 1);
    const uint32_t t_pub = clk32();
    auto refill = [&]() {
      if (warp == 3) {
        named_bar_sync(NB_XE, 160);
        if (elect_one()) {
          mbar_expect_tx(B_XN + 8, 16384);
          tma_load_3d(XN, &P.xn, 0, (s + 1) * 32, 12, B_XN + 8);
        }
      }
    };
    auto arm = [&]() {
      if ((tid & 255) == 160) {
        if (s == 1) st_pub32(&g_mask[3 * h + rank], 0);
        if (s + 2 < cfg::NSEG) { mbar_expect_tx(B_SM, ISV ? 2 * SP_SRC : SP_SRC); if (!ISV) mbar_expect_tx(B_VX, 8192); }
        if (!ISV && s + 1 < cfg::NSEG) mbar_expect_tx(B_VM, 2048);
        if (ISV && s >= 1 && s < cfg::NSEG) mbar_expect_tx(B_ST, 7168);
      }
      if (ISV && s < cfg::NSEG && (tid & 254) == 192) mbar_arrive_remote(((tid & 1) ? peer1 : peer0) + B_ST);
      __syncwarp();
    };
    if (ISV) {
      if (s >= 0) arm();
      if (s >= 1) {
        OPQ;
        if (warp == 0 && (s & 3) == 1 && s > 1) { if (elect_one()) o_done((s - 2) >> 2); }
        const uint32_t vb = (s & 1) ? VX : VX2;
        float x0[16], x1[16];
        wg_fence();
        wgmma_rs_n32(x0, vmo, make_desc(fk::PT + 64, 16, 1024), 0);
        wgmma_rs_n32(x1, vmo, make_desc(fk::PT + 96, 16, 1024), 0);
#pragma unroll
        for (int kk = 0; kk < 2; kk++) {
          wgmma_ss_n32(x0, make_desc0(vb + kk * 256, 128, 1024), make_desc(fk::PT + kk * 32, 16, 1024), 1);
          wgmma_ss_n32(x1, make_desc0(vb + 512 + kk * 256, 128, 1024), make_desc(fk::PT + kk * 32, 16, 1024), 1);
        }
        wg_commit();
        wg_wait<0>();
        named_bar_sync(NB_W1, 128);
        PROF(1, 4);
        const uint32_t stg = vb + (8 * (mi >> 1) + mr) * 128 + (((2 * w + (mi & 1)) ^ mr) << 4);
#pragma unroll
        for (int T = 0; T < 2; T++) {
          const float* x = T ? x1 : x0;
#pragma unroll
          for (int jj = 0; jj < 4; jj += 2)
            stsm4t(stg + T * 4096 + jj * 1024, pack_bf16(x[4 * jj], x[4 * jj + 1]), pack_bf16(x[4 * jj + 2], x[4 * jj + 3]),
                   pack_bf16(x[4 * jj + 4], x[4 * jj + 5]), pack_bf16(x[4 * jj + 6], x[4 * jj + 7]));
        }
        fence_proxy_async_smem();
        named_bar_sync(NB_W1, 128);
        PROF(1, 10);
        if (warp == 0) {
          if (elect_one()) {
            tma_store_3d(&P.o, vb, 0, (s - 1) * 32, 2 * h);
            tma_store_commit();
          }
          __syncwarp();
        }
        if (s == cfg::NSEG) break;
      }
      if (s + 1 < cfg::NSEG) refill();
      PROF(1, 11);
    } else if (s < 0) {
      named_bar_arrive(NB_CF, 256);
      refill();
    } else {
      float x[24];
      wg_fence();
#pragma unroll
      for (int k = 0; k < 4; k++) wgmma_ss_n48_tt(x, make_desc0(fk::QK + k * 256, 128, 1024), make_desc0(fk::QK + 4096 + k * 256, 128, 1024), k != 0);
      wg_commit();
      arm();
      auto send_tok = [&]() {
        if (warp < 2) {
          OPQ;
          const uint32_t d0 = peer1 + QK + rank * 3584 + lane * 8 + w * 1280, d1 = d0 + 512 + w * 512, bar = peer1 + B_ST;
          mbar_spin(B_ST, s & 1);
          const float NEG = -500000000.0f / 0.08838834764831845f;
          const bool m0 = 2 * lq > lg, m1 = 2 * lq + 1 > lg;
          st_async64f(d0, x[16] + x[20], x[17] + x[21], bar);
          st_async64f(d1, x[18] + x[22], x[19] + x[23], bar);
          st_async64f(d1 + 256, x[2], x[3], bar);
          if (warp == 0) {
            st_async64f(d0 + 256, m0 ? NEG : x[0], m1 ? NEG : x[1], bar);
            st_async64f(d1 + 512, m0 ? NEG : x[6], m1 ? NEG : x[7], bar);
          } else {
            st_async64f(d0 + 256, x[0], x[1], bar);
            st_async64f(d1 + 512, x[6], x[7], bar);
            st_async64f(d0 + 512, x[4], x[5], bar);
            st_async64f(d0 + 768, m0 ? NEG : x[8], m1 ? NEG : x[9], bar);
            st_async64f(d1 + 768, x[10], x[11], bar);
            st_async64f(d1 + 1024, m0 ? NEG : x[14], m1 ? NEG : x[15], bar);
          }
        }
        PROF(1, 4);
      };
      const bool fin = s + 1 == cfg::NSEG;
      OPQ;
      const int j = 2 * h + rank;
      const char* src = P.xch + j * 32768 + warp * 8192 + (((usel >> 14) & 2) + (s & 1)) * 2048;
      char* dst = P.xch + H1_BYTES + (j >> 4) * 8192 + (lq >> 1) * 4096 + (j & 15) * 256 + (lq & 1) * 128 + (2 * w + (lg & 1)) * 16 + (lg >> 1) * 4;
      const uint32_t chk = VX + mi * 2048 + mr * 128 + (w ^ (mr >> 1)) * 32 + ((lane & 1) + 2 * mi) * 4;
      const uint32_t tmask = (s >> 1) & 1;
      if (!fin) {
        spin_until(t_pub + D_H1);
        if (elect_one()) { mbar_expect_tx(B_H1, 2048); bulk_g2s(VX + warp * 2048, src, 2048, B_H1); }
      }
      __syncwarp();
      wg_wait<0>();
      PROF(1, 6);
      send_tok();
      if (fin) { mbar_spin(B_VM, s & 1); break; }
      named_bar_arrive(NB_CF, 256);
      if (REFILL_EARLY) refill();
#pragma unroll 1
      for (int tries = 0; tries < POLL_TRIES; tries++) {
        float d0[4], d1[4], d2[4], d3[4];
        mbar_spin(B_H1, h1ph);
        h1ph ^= 1;
        PROF(1, 10);
        const uint32_t t0 = lds32(chk), t1 = lds32(chk + 1024);
        wg_fence();
        const uint64_t ones = (uint64_t)(fk::ONES >> 4);
        wgmma_ss_n8_ta(d0, make_desc(fk::VX, 8192, 2048), ones, 0);
        wgmma_ss_n8_ta(d1, make_desc(fk::VX + 1024, 8192, 2048), ones, 0);
        wgmma_ss_n8_ta(d2, make_desc(fk::VX + 4096, 8192, 2048), ones, 0);
        wgmma_ss_n8_ta(d3, make_desc(fk::VX + 5120, 8192, 2048), ones, 0);
        wg_commit();
        uint32_t tt;
        asm volatile("lop3.b32 %0, %1, %2, %3, 0x42;" : "=r"(tt) : "r"(t0), "r"(t1), "r"(tmask) : "memory");
        uint32_t ok;
        named_bar_and(NB_W1, 128, tt & 1, ok);
        if (!ok) { if (elect_one()) { mbar_expect_tx(B_H1, 2048); bulk_g2s(VX + warp * 2048, src, 2048, B_H1); } }
        wg_wait<0>();
        if (ok) {
          st_pub32(dst + (s & 1) * 32768, (lq & 1) ? pack_bf16(d1[0] + d3[0], d1[2] + d3[2]) : pack_bf16(d0[0] + d2[0], d0[2] + d2[2]));
          PROF(1, 12);
          st_pub32(dst + ((s & 1) ^ 1) * 32768, EMPTY);
          break;
        }
        RETRY(0);
      }
      named_bar_sync(NB_W1, 128);
      if ((tid & 255) == 192) mbar_arrive_remote(peer1 + B_PF);
      __syncwarp();
      if (!REFILL_EARLY) refill();
      PROF(1, 11);
    }
    if (!ISV || s + 1 < cfg::NSEG) {
      const uint32_t ph = (s + 1) & 1;
      float x0[16], x1[16];
      uint64_t db = P.dxn + 10 * 256;
      named_bar_sync(NB_ST, 256);
      wg_fence();
#pragma unroll
      for (int c = 0; c < 6; c++) {
        if (c == 2) { PROF(1, 0); mbar_spin(B_XN + 8, ph); PROF(1, 15); wg_fence(); }
        if (ISV && c == CF_AT) {
          if (warp == 0) {
            if (elect_one()) tma_store_wait_read();
            __syncwarp();
            named_bar_arrive(NB_CF, 160);
          }
          wg_fence();
        }
#pragma unroll
        for (int u = 0; u < 4; u++) {
          wgmma_rs_n32(x0, wr[c][0][u], db, (c | u) != 0);
          wgmma_rs_n32(x1, wr[c][1][u], db, (c | u) != 0);
          if (u < 3) DESC_ADD(db, 2); else if (c == 1) DESC_ADD(db, 250 - 12 * 256); else DESC_ADD(db, 250);
        }
      }
      wg_commit();
      OPQ;
      const uint32_t tb = ISV ? (ph ? VX2 : VX) : QK, tka = tok_addr<ISV>(tb, tid);
      uint32_t p0[2][4], p1[2][4];
      named_bar_sync(NB_DU, 256);
      ldsm4(p1[0], tka + tok_off<ISV>(1, 0)); ldsm4(p1[1], tka + tok_off<ISV>(1, 1));
      ldsm4(p0[0], tka + tok_off<ISV>(0, 0)); ldsm4(p0[1], tka + tok_off<ISV>(0, 1));
      if (ISV && s >= 0) mbar_spin(B_PF, s & 1);
      wg_wait<0>();
      PROF(1, 13);
      tok_store<ISV, 1, true>(x1, tka, p1);
      tok_store<ISV, 0, true>(x0, tka, p0);
      if (ISV && s + 2 < cfg::NSEG) {
        fence_proxy_async_smem();
        __syncwarp();
        if (elect_one()) {
          bulk_s2s(peer0 + VX + warp * 2048, tb + warp * 2048, 2048, peer0 + B_VX);
          bulk_s2s(peer1 + VX + warp * 2048, tb + warp * 2048, 2048, peer1 + B_VX);
        }
      }
      wsa = WS + ((mi >> 1) * 8 + mr) * 128 + (((2 * w + (mi & 1)) ^ mr) << 4);
      mba = MEMB + lane * 16;
      PIN(wsa); PIN(mba);
      proj_mem_prefetch<ISV, 1, 0, NTA1>(ta, wsa);
      PROF(1, 14);
      named_bar_sync(NB_M1, 256);
      s++;
      PROF(1, 1);
      float a0[4], a1[4];
      proj_mem<ISV, 1>(wr, ta, wsa, mba, a0, a1);
      PROF(1, 2);
      proj_finish<ISV, 1>(a0, a1, peer0, peer1, self, tid, warp, vmo);
      PROF(1, 3);
    } else {
      OPQ;
      mbar_spin(B_VM, s & 1);
      lds64(vmo, VM + t7 * 8); lds64(vmo + 2, VM + 1024 + t7 * 8);
      s++;
    }
    tid ^= 0x5500;
    const bool last = s + 1 >= cfg::NSEG;
    constexpr int PFW = ISV ? PF1V : PF1;
    uint32_t wf[PFW][4], woa;
    if (ISV) {
      OPQ;
      woa = WO + ((mi >> 1) * 8 + mr) * 128 + (((2 * w + (mi & 1)) ^ mr) << 4);
      if (s >= 1) {
        const uint32_t sa = QK + ((w * (w + 3)) >> 1) * 256 + lane * 8;
        mbar_spin(B_ST, (s - 1) & 1);
        float sc[10];
        {
          const float NEG = -1000000000.0f / 0.08838834764831845f;
          float2 x[5], y[5];
#pragma unroll
          for (int b = 0; b < 5; b++) {
            x[b] = b < 2 ? lds64f(sa + b * 256) : lds64f_if(sa + b * 256, b <= w + 1, NEG);
            y[b] = b < 2 ? lds64f(sa + 3584 + b * 256) : lds64f_if(sa + 3584 + b * 256, b <= w + 1, 0.f);
          }
#pragma unroll
          for (int b = 0; b < 5; b++) { sc[2 * b] = x[b].x + y[b].x; sc[2 * b + 1] = x[b].y + y[b].y; }
        }
        float m = fmaxf(fmaxf(fmaxf(sc[0], sc[1]), fmaxf(sc[2], sc[3])), fmaxf(fmaxf(sc[4], sc[5]), fmaxf(sc[6], sc[7])));
        m = fmaxf(m, fmaxf(sc[8], sc[9]));
        m = fmaxf(m, __shfl_xor_sync(0xffffffffu, m, 1));
        m = fmaxf(m, __shfl_xor_sync(0xffffffffu, m, 2));
        const float cs = 0.08838834764831845f * 1.4426950408889634f;
#pragma unroll
        for (int i = 0; i < 10; i++) sc[i] = ex2_approx((sc[i] - m) * cs);
        float sum = ((sc[0] + sc[1]) + (sc[2] + sc[3])) + ((sc[4] + sc[5]) + (sc[6] + sc[7])) + (sc[8] + sc[9]);
        sum += __shfl_xor_sync(0xffffffffu, sum, 1);
        sum += __shfl_xor_sync(0xffffffffu, sum, 2);
        const float inv = rcp_approx(sum);
        const uint32_t pa = PT + (w * 8 + mr) * 128, pm = pack_bf16(sc[0] * inv, sc[1] * inv);
        stsm4(pa + ((mi ^ mr) << 4), pack_bf16(sc[2] * inv, sc[3] * inv), pack_bf16(sc[4] * inv, sc[5] * inv),
              pack_bf16(sc[6] * inv, sc[7] * inv), pack_bf16(sc[8] * inv, sc[9] * inv));
        asm volatile("stmatrix.sync.aligned.m8n8.x2.shared.b16 [%0], {%1,%1};" ::"r"(pa + ((((mi & 1) ? 7 : 4) ^ mr) << 4)), "r"(pm) : "memory");
      }
      if (warp == 3 && !last) {
        mbar_spin(B_VM, s & 1);
        if (elect_one()) load_xn(P, s + 1, self);
      }
      PROF(1, 5);
    } else {
      if (warp == 0) {
        OPQ;
        uint32_t kf[4][4], qf[4][4];
        float c0[4], c1[4], d0[4], d1[4];
        const uint32_t ka = PT + (mi >> 1) * 1024 + (mi & 1) * 128 + mr * 16;
#pragma unroll
        for (int k = 0; k < 4; k++) { ldsm4t(qf[k], PT + 2048 + k * 512 + lane * 16); ldsm4t(kf[k], ka + k * 256); }
        mma16816z(c0, qf[0], kf[0][0], kf[0][1]); mma16816z(c1, qf[0], kf[0][2], kf[0][3]);
        mma16816z(d0, qf[1], kf[1][0], kf[1][1]); mma16816z(d1, qf[1], kf[1][2], kf[1][3]);
        mma16816(c0, qf[2], kf[2][0], kf[2][1]); mma16816(c1, qf[2], kf[2][2], kf[2][3]);
        mma16816(d0, qf[3], kf[3][0], kf[3][1]); mma16816(d1, qf[3], kf[3][2], kf[3][3]);
        const float s0 = ((c0[0] + c0[2]) + (c1[0] + c1[2])) + ((d0[0] + d0[2]) + (d1[0] + d1[2]));
        const float s1 = ((c0[1] + c0[3]) + (c1[1] + c1[3])) + ((d0[1] + d0[3]) + (d1[1] + d1[3]));
        if (!last) send_scores(s0, s1, SP + rank * SP_SRC + (128 + lane) * SPW, peer0, peer1, B_SM, lane);
        PROF(1, 5);
      } else {
        const uint32_t t_c = clk32() + lds32(B_XN) * 0;
        if (warp == 3 && !last) { if (elect_one()) load_xn(P, s + 1, self); }
        spin_until(t_c + D_ST);
      }
      OPQ;
      woa = WO + ((mi >> 1) * 8 + mr) * 128 + (((2 * w + (mi & 1)) ^ mr) << 4);
    }
    if (!last) {
      OPQ;
      uint32_t oba = OB + lane * 16;
      if (s == 0) mbar_spin(B_WO, 0);
      if (!ISV) wo_prefetch<WMODE, 0, PF1Q>(wf, woa, 0, true);
      if (ISV ? GATE_MX : GATE_Q) named_bar_sync(NB_MX, 256);
      wo_prefetch<WMODE, ISV ? 0 : PF1Q, PFW>(wf, woa, 0, true);
      char* h1p = P.xch + (tile0 + w) * 32768 + (h >> 3) * 8192 + (h & 7) * 128 + (((2 * lq + (lg & 1)) ^ (h & 7)) << 4) + (lg >> 1) * 4;
      fence_proxy_async_smem();
      PROF(1, 7);
      named_bar_sync(NB_O, 256);
      PROF(1, 8);
      wo_phase<WMODE>(wf, woa, 0, true, oba, h1p, tid >> 8, ((s >> 1) & 1) ^ 1);
      PROF(1, 9);
      named_bar_sync(NB_HD, 256);
    } else {
      fence_proxy_async_smem();
      named_bar_sync(NB_W1, 128);
    }
  }
  if (ISV && warp == 0) { if (elect_one()) o_done(15); }
}

template <bool ISV, int WG>
__device__ __forceinline__ void f_main(const FParams& P, const int h, const int rank, const uint32_t hw) {
  using namespace fk;
  const uint32_t self = mapa(0, (hw >> (2 * rank)) & 3);
  SMAP;
  const int tid = __shfl_sync(0xffffffffu, threadIdx.x, threadIdx.x & 31);
  const int tile0 = rank * 22, ntile = ISV ? 20 : 22;
  const CUtensorMap* m0 = ISV ? &P.wv : &P.wq;
  const CUtensorMap* m1 = ISV ? &P.wv : &P.wk;
  const int col0 = h * 128 + (ISV ? 0 : 64 * rank), col1 = h * 128 + (ISV ? 64 : 64 * rank);
  WRegs wr;
  uint32_t sel = 0;
  {
    OPQ;
    const uint32_t a = SM0 + WG * 16384 + ((mi >> 1) * 8 + mr) * 128 + (((2 * w + (mi & 1)) ^ mr) << 4);
    uint2 mi0 = make_uint2(0, 0);
    if (!ISV && WG == 1) mi0 = *reinterpret_cast<const uint2*>(P.mem0 + ((lane >> 1) & 7) * cfg::D + (2 * h + rank) * 16 + (lane >> 4) * 8 + (lane & 1) * 4);
#pragma unroll
    for (int i = 0; i < 6; i++) {
      if (i == MASK_AT && WG == 1 && w == 1) {
        uint4 v;
#pragma unroll 1
        for (int tries = 0; tries < POLL_TRIES; tries++) {
          asm volatile("ld.acquire.gpu.global.v4.u32 {%0,%1,%2,%3}, [%4];" : "=r"(v.x), "=r"(v.y), "=r"(v.z), "=r"(v.w)
                       : "l"(&g_mask[4 * min(lane, 23)]) : "memory");
          if (__all_sync(0xffffffffu, v.x & v.y & v.z & v.w & 0x100)) break;
          __nanosleep(100);
        }
        sts128(OB + lane * 16, v.x, v.y, v.z, v.w);
      }
      mbar_wait(B_PB + 8 * i, 0);
      PRO(8 + i);
#pragma unroll
      for (int T = 0; T < 2; T++)
#pragma unroll
        for (int u = 0; u < 4; u++) ldsm4t(wr[i][T][u], a + i * 32768 + T * 8192 + u * 2048);
      named_bar_sync(NB_C, 256);
      if (WG == 1 && w == (i & 3)) {
        if (elect_one()) {
          if (i <= 2 && i + PRE_G < 6) {
#pragma unroll 1
            for (int n = 2 * (i + PRE_G); n < (i == 2 ? 12 : 2 * (i + PRE_G) + 2); n++) {
              const int ii = n >> 1, row = Chunks<ISV>::rf(n & 1, ii) * 64;
              if (!(n & 1)) mbar_expect_tx(B_PB + 8 * ii, 32768);
              tma_load_2d(SM0 + n * 16384, m0, col0, row, B_PB + 8 * ii);
              tma_load_2d(SM0 + n * 16384 + 8192, m1, col1, row, B_PB + 8 * ii);
            }
          }
          if (i == 3 || i == 4) {
            const int p0 = i == 3 ? 0 : 5, p1 = i == 3 ? 5 : 8;
            mbar_expect_tx(B_W, (p1 - p0) * 8192);
#pragma unroll 1
            for (int p = p0; p < p1; p++) tma_load_2d(WS + p * 8192, (p & 1) ? m1 : m0, (p & 1) ? col1 : col0, Chunks<ISV>::sm(p >> 1) * 64, B_W);
          }
          if (i == 5) {
            asm volatile("fence.proxy.async.global;" ::: "memory");
            load_xn(P, 0, self);
          }
          if (i == WO_AT) {
            mbar_expect_tx(B_WO, ntile * 4096);
#pragma unroll 1
            for (int t = 0; t < 5; t++) tma_load_2d(WO + t * 16384, &P.wo, tile0 * 16 + t * 64, h * 128, B_WO);
            if (!ISV) {
              tma_load_2d(WO + 81920, &P.wo16, tile0 * 16 + 320, h * 128, B_WO);
              tma_load_2d(WO + 86016, &P.wo16, tile0 * 16 + 336, h * 128, B_WO);
            }
          }
        }
      }
    }
    PROF2(1);
    if (!ISV && WG == 1 && w < 2) st_pub64(P.xch + H1_BYTES + 32768 + (h >> 3) * 8192 + w * 4096 + ((2 * h + rank) & 15) * 256 + lane * 8, mi0.x, mi0.y);
    if (blockIdx.x == 2 && tid == 160) { __threadfence(); st_pub128(g_lnok, 0x100); }
#pragma unroll
    for (int i = 0; i < 3; i++) {
      const int t = min(tile0 + 8 * i + w + (WG ? 0 : 4), 63);
      sel |= ((lds32(OB + ((t >> 1) * 3 + (t & 1)) * 4) >> (h >> 3)) & 1) << (2 * i + 1);
    }
    const uint32_t own = lds32(OB + (3 * h + rank) * 4) >> w, m2 = lds32(OB + (3 * h + 2) * 4) >> w;
    sel |= (own & 1) << 7 | (m2 & 1) << 8 | (m2 & 16) << 5;
    sel |= (((((lg ^ h) & 1) << 2) | (lg >> 1)) == (h & 1) + 2 * (h >> 3)) << 10;
  }
  asm volatile("barrier.cluster.wait.aligned;" ::: "memory");
  PRO(14);
  mbar_wait(B_W, 0);
  mbar_wait(B_XN, 0);
  PRO(15);
  PROF2(4);
  GTSYNC(0);
  PROF2(2);
  KT_END(8);
  if (WG == 0) f_wg0<ISV>(P, wr, h, rank, hw, tid | sel << 8); else f_wg1<ISV>(P, wr, h, rank, hw, tid | sel << 8);
}

__device__ __forceinline__ void f_tail(const FParams& P, const int h, const uint32_t rank, const bool isv) {
  using namespace fk;
  const uint32_t self = mapa(0, rank), base = self + SM0;
  const uint32_t FULL = self + SP, EMPT = FULL + 32, RES = FULL + 64, NOG = FULL + 72;
  const int tid = threadIdx.x, lane = tid & 31, wv = __shfl_sync(0xffffffffu, tid >> 5, 0), wg = wv >> 2;
  const int kq = h & 3, nt = (h >> 2) & 3, mb = TAIL_MB0 + 3 * (h >> 4) + rank;
  auto a_off = [](uint32_t st) { return (0x98685800u >> (8 * st) & 255) * 1024; };
  auto b_off = [](uint32_t st) { return (0xA8783010u >> (8 * st) & 255) * 1024; };
  static_assert(VX2 - SM0 == 80 * 1024 && VX - SM0 == 200 * 1024, "stage layout");
  auto load_b = [&](int kb) {
    const uint32_t sb = base + b_off(kb & 3), full = FULL + 8 * (kb & 3);
    mbar_expect_tx(full, 49152);
    tma_load_2d_mc(sb + rank * 8192, &P.tb, nt * 256 + ((rank + kq) & 3) * 64, (kq * 16 + kb) * 64, full, 7);
    if (kb % 3 == rank) tma_load_2d_mc(sb + 3 * 8192, &P.tb, nt * 256 + ((3 + kq) & 3) * 64, (kq * 16 + kb) * 64, full, 7);
  };
  auto load_a = [&](int kb) { tma_load_2d(base + a_off(kb & 3), &P.ta, (kq * 16 + kb) * 64, mb * 128, FULL + 8 * (kb & 3)); };
  TL(0);
  TL2(128, 10); TL2(160, 11);
  if (wv == 0) {
    if (elect_one()) {
      prefetch_tmap(&P.tb); prefetch_tmap(&P.ta);
      if (isv) mbar_spin(self + B_VM, (cfg::NSEG - 1) & 1);
      for (int i = 0; i < 4; i++) { mbar_init(FULL + 8 * i, 1); mbar_init(EMPT + 8 * i, 24); }
      mbar_init(RES, 1);
      fence_barrier_init();
      mbar_arrive_cluster(self + B_W, rank == 0 ? 1 : 0);
      mbar_arrive_cluster(self + B_W, rank == 2 ? 1 : 2);
      mbar_spin(self + B_W, 1);
#pragma unroll 1
      for (int kb = 0; kb < 4; kb++) load_b(kb);
      TL2(0, 12);
      wait_count(&g_oflag[mb], 32);
      asm volatile("fence.proxy.async.global;" ::: "memory");
      TL2(0, 13);
#pragma unroll 1
      for (int kb = 0; kb < 4; kb++) load_a(kb);
      TL2(0, 14);
    }
  }
  if (wv == 1) {
    if (lane == 0) {
      prefetch_tmap(&P.tx); prefetch_tmap(&P.tg); prefetch_tmap(&P.tout);
      uint32_t gc;
      asm volatile("ld.acquire.gpu.global.u32 %0, [%1];" : "=r"(gc) : "l"(&g_cnt[3][mb]) : "memory");
      const bool ng = gc < GATE_CNT && ld_strong4(&g_next) == 0;
      sts32(NOG, ng ? 1 : gc < GATE_CNT ? 2 : 0);
      if (ng) g_tfix[blockIdx.x] = 1;
      asm volatile("cp.async.bulk.prefetch.tensor.2d.L2.global [%0, {%1, %2}];" ::"l"(&P.tx), "r"(nt * 256 + kq * 64), "r"(mb * 128) : "memory");
    }
  } else if (wv == 2 || wv == 3) {
#pragma unroll 2
    for (int i = tid - 64; i < 3072; i += 64) st_pub128(&g_tpart[blockIdx.x][0][0][0] + i, EMPTY);
  }
  float acc[128];
  __syncthreads();
  KT_START(7);
  const uint32_t gate = lds32(NOG);
  const bool nog = gate == 1;
  if (gate) TL(15); else TL(15);
#pragma unroll 1
  for (int kb = 0; kb < 16; kb++) {
    const uint32_t st = kb & 3, sa = base + a_off(st) + wg * 8192, sb = base + b_off(st);
    mbar_spin(FULL + 8 * st, (kb >> 2) & 1);
    if (kb == 0) TL(2);
    if (kb == 4) TL(3);
    if (kb == 10) TL(4);
    wg_fence();
#pragma unroll
    for (int k = 0; k < 4; k++) {
      wgmma_ss_n256_tb(acc, make_desc(sa + k * 32, 16, 1024), make_desc(sb + k * 2048, 8192, 1024), (kb | k) != 0);
      if (k == 0) {
        wg_commit();
        wg_wait<1>();
        if (kb > 0 && kb <= 13 && lane < 3) mbar_arrive_cluster(EMPT + 8 * ((kb - 1) & 3), lane);
        wg_fence();
      }
    }
    wg_commit();
    if (kb >= 2 && kb < 15 && wv == ((kb & 1) << 2)) {
      if (elect_one()) {
        mbar_spin(EMPT + 8 * ((kb - 2) & 3), ((kb - 2) >> 2) & 1);
        if (kb < 14) {
          load_b(kb + 2);
          load_a(kb + 2);
        } else if (nog) {
          mbar_arrive(RES);
        } else {
          if (gate) wait_count(&g_cnt[3][mb], GATE_CNT);
          asm volatile("fence.proxy.async.global;" ::: "memory");
          mbar_expect_tx(RES, 32768);
          tma_load_2d(base, &P.tx, nt * 256 + kq * 64, mb * 128, RES);
          tma_load_2d(base + 16384, &P.tg, nt * 256 + kq * 64, mb * 128, RES);
        }
      }
      __syncwarp();
    }
  }
  wg_wait<0>();
  TL(5);
#pragma unroll
  for (int j = 1; j < 4; j++) {
    uint4* dst = &g_tpart[((h & ~3) + ((j + kq) & 3)) * 3 + rank][j - 1][0][tid];
#pragma unroll
    for (int i = 0; i < 4; i++) {
      const float* a = &acc[32 * j + 8 * i];
      asm volatile("st.relaxed.gpu.global.v4.u32 [%0], {%1,%2,%3,%4};" ::"l"(dst + i * 256), "r"(pack_bf16(a[0], a[1])),
                   "r"(pack_bf16(a[2], a[3])), "r"(pack_bf16(a[4], a[5])), "r"(pack_bf16(a[6], a[7])) : "memory");
    }
  }
  TL(6);
#pragma unroll 1
  for (int j = 0, tries = 0; j < 3 && tries < POLL_TRIES; tries++) {
    uint4 pt[4];
#pragma unroll
    for (int i = 0; i < 4; i++) pt[i] = ld_strong16(&g_tpart[blockIdx.x][j][i][tid]);
    if (!__all_sync(0xffffffffu, max(max(umax4(pt[0]), umax4(pt[1])), max(umax4(pt[2]), umax4(pt[3]))) != EMPTY)) continue;
#pragma unroll
    for (int i = 0; i < 16; i++) { acc[2 * i] += bf_lo((&pt[0].x)[i]); acc[2 * i + 1] += bf_hi((&pt[0].x)[i]); }
    j++;
  }
  mbar_spin(RES, 0);
  TL(7);
  const uint32_t xa = base + (wv * 16 + ((lane >> 3) & 1) * 8 + (lane & 7)) * 128 + (((lane >> 4) ^ (lane & 7)) << 4);
#pragma unroll
  for (int i = 0; i < 4; i++) {
    uint32_t x[4], g[4], o[4];
    ldsm4(x, xa ^ (i << 5));
    ldsm4(g, (xa ^ (i << 5)) + 16384);
#pragma unroll
    for (int k = 0; k < 4; k++) {
      const uint32_t sv = pack_bf16(acc[8 * i + 2 * k], acc[8 * i + 2 * k + 1]);
      o[k] = nog ? sv : add_bf16x2(x[k], mul_bf16x2(sv, g[k]));
    }
    stsm4(xa ^ (i << 5), o[0], o[1], o[2], o[3]);
  }
  TL(8);
  fence_proxy_async_smem();
  __syncwarp();
  if (elect_one()) {
    tma_store_2d(&P.tout, base + wv * 2048, nt * 256 + kq * 64, mb * 128 + wv * 16);
    tma_store_commit();
    tma_store_wait_read();
  }
  TL(9);
  KT_END(7);
}

__global__ void __launch_bounds__(256, 1) f_kernel(const __grid_constant__ FParams P) {
  using namespace fk;
  extern __shared__ __align__(1024) uint8_t smem_f[];
  uint32_t crank, rank, hw;
  asm("mov.u32 %0, %%cluster_ctarank;" : "=r"(crank));
  const int h = blockIdx.x / 3;
  if (smem_u32(smem_f) != mapa(0, crank) + SM0) return;
  PROF2(0);
  KT_START(1);
  KT_START(0);
  {
    const uint32_t self = mapa(0, crank);
    SMAP;
    const int tid = threadIdx.x, lane = tid & 31, wv = __shfl_sync(0xffffffffu, tid >> 5, 0);
    PRO(0);
    if (wv == 0) {
      uint32_t sm;
      asm("mov.u32 %0, %%smid;" : "=r"(sm));
      sts32(PROBE + 96, sm >> 1);
      asm volatile("fence.release.sync_restrict::shared::cta.cluster;" ::: "memory");
    }
    asm volatile("barrier.cluster.arrive.relaxed.aligned;" ::: "memory");
    if (wv == 7) {
      if (blockIdx.x == 2) {
#pragma unroll
        for (int i = 0; i < 4; i++) { (&g_cnt[0][0])[32 * i + lane] = 0; if (i < 3) g_tfix[32 * i + lane] = 0; }
        if (lane < 16) g_oflag[lane] = 0;
        if (lane == 0) { g_next = 0; g_lnok[0] = 0; }
        __threadfence();
        __syncwarp();
      }
      pdl_launch_dependents();
    }
    const int row0 = blockIdx.x * 8 + wv;
    const bool third = row0 + 1536 < cfg::S;
    uint32_t cur[1][16] = {}, raw[3][16];
    load_row16(raw[0], P.x + (size_t)row0 * cfg::D, lane);
    load_row16(raw[1], P.x + (size_t)(row0 + 768) * cfg::D, lane);
    load_row16(raw[2], P.x + (size_t)(row0 + (third ? 1536 : 0)) * cfg::D, lane);
    {
      uint32_t tpc;
      asm volatile("barrier.cluster.wait.aligned;" ::: "memory");
      asm volatile("ld.shared::cluster.u32 %0, [%1];" : "=r"(tpc) : "r"(mapa(PROBE + 96, lane % 3)) : "memory");
      const uint32_t t0 = __shfl_sync(0xffffffffu, tpc, 0), t1 = __shfl_sync(0xffffffffu, tpc, 1), t2 = __shfl_sync(0xffffffffu, tpc, 2);
      hw = t1 == t2 ? 0x09 : t0 == t2 ? 0x18 : 0x24;
      rank = (hw & 3) == crank ? 0 : ((hw >> 2) & 3) == crank ? 1 : 2;
    }
    const bool isv = rank == 2;
    const CUtensorMap* m0 = isv ? &P.wv : &P.wq;
    const CUtensorMap* m1 = isv ? &P.wv : &P.wk;
    const int col0 = h * 128 + (isv ? 0 : 64 * rank), col1 = h * 128 + (isv ? 64 : 64 * rank);
    auto req_weights = [&](int n0, int n1) {
#pragma unroll 1
        for (int n = n0; n < n1; n++) {
          const int i = n >> 1, g = n & 1, row = (isv ? Chunks<true>::rf(g, i) : Chunks<false>::rf(g, i)) * 64;
          if (!g) mbar_expect_tx(B_PB + 8 * i, 32768);
          tma_load_2d(SM0 + n * 16384, m0, col0, row, B_PB + 8 * i);
          tma_load_2d(SM0 + n * 16384 + 8192, m1, col1, row, B_PB + 8 * i);
        }
    };
    if (wv == 0) {
      if (elect_one()) {
        for (int i = 0; i < 2; i++) mbar_init(B_XN + 8 * i, 1);
        mbar_init(B_H1, 4);
        mbar_init(B_SM, isv ? 1 : 6);
        mbar_init(B_VM, isv ? 8 : 1);
        mbar_init(B_VX, 1);
        mbar_init(B_ST, 1);
        mbar_init(B_PF, 2);
        for (int i = 0; i < 6; i++) mbar_init(B_PB + 8 * i, 1);
        mbar_init(B_W, 2);
        mbar_init(B_WO, 1);
        fence_barrier_init();
        if (PRE_A) req_weights(0, 2 * PRE_A);
        mbar_expect_tx(B_SM, isv ? 2 * SP_SRC : SP_SRC);
        if (isv) mbar_expect_tx(B_ST, 7168);
        else { mbar_expect_tx(B_VM, 2048); mbar_expect_tx(B_VX, 8192); }
      }
    }
    const int j = 2 * h + rank;
    const bool dry = LN_DRY && !isv && wv == 6;
    if (dry) sts64(PROBE + wv * 8, 0x7FFFFFFF, 0x7FFFFFFF);
    if (lane == 0 && !dry) {
      const uint2 b = probe_pair(P.xch + (isv ? H1_BYTES + wv * 8192 + h * 128 : j * 32768 + (wv & 3) * 8192 + (wv >> 2) * 128),
                                 isv ? EMPTY : 0, PROBE + 64, P.nprobe);
      sts64(PROBE + wv * 8, b.x, b.y);
    }
    uint32_t mask = 0;
#pragma unroll 1
    for (int it = -1; it < (third ? 3 : 2); it++) {
      if (it >= 0 || dry) {
        ln_regs<1>(cur);
        if (it >= 0) store_row16(cur[0], P.xn_ptr + (size_t)(row0 + it * 768) * cfg::D, lane);
      }
      if (it == 0) PRO(4);
      if (it < 0) {
    PROF2(3);
    PRO(1);
    __syncwarp();
    if (wv == 0) {
      asm volatile("{\n.reg .pred p;\nsetp.eq.u32 p, %0, %1;\n@p st.shared.u32 [%2], %0;\n}" ::"r"(raw[2][15]), "r"(raw[0][0] ^ raw[1][15]), "r"(PROBE + 64) : "memory");
      if (elect_one()) {
        req_weights(2 * PRE_A, 2 * PRE_G);
      }
    }
    __syncthreads();
    PRO(2);
    asm volatile("barrier.cluster.arrive.relaxed.aligned;" ::: "memory");
    PRO(3);
    if (wv == 2) sts32(self + ONES + lane * 4, 0x3F803F80u);
    uint32_t pb[2], pc[2];
    lds64(pb, PROBE + (lane & 7) * 8);
    lds64(pc, PROBE + ((lane & 7) ^ 4) * 8);
    mask = __ballot_sync(0xffffffffu, isv ? pb[1] < pb[0] : min(pb[1], pc[1]) < min(pb[0], pc[0])) & (isv ? 255 : 15);
    if (!isv) {
#pragma unroll
      for (int i = 0; i < 4; i++) st_pub128(P.xch + j * 32768 + i * 8192 + ((mask >> i) & 1) * 4096 + tid * 16, 0);
      if (wv < 4) st_pub64(P.xch + H1_BYTES + (wv >> 1) * 32768 + (j >> 4) * 8192 + (wv & 1) * 4096 + (j & 15) * 256 + lane * 8, EMPTY, EMPTY);
    }
      }
#pragma unroll
      for (int i = 0; i < 16; i++) { cur[0][i] = raw[0][i]; raw[0][i] = raw[1][i]; raw[1][i] = raw[2][i]; }
    }
    PRO(5);
    __syncthreads();
    PRO(6);
    if (tid == 64) {
      __threadfence();
      PRO(7);
      st_pub32(&g_mask[3 * h + rank], 0x100 | mask);
    }
    KT_END(0);
    __syncwarp();
  }
  const int wg = __shfl_sync(0xffffffffu, threadIdx.x >> 7, 0);
  if (rank == 2) { if (wg == 0) f_main<true, 0>(P, h, 2, hw); else f_main<true, 1>(P, h, 2, hw); }
  else { if (wg == 0) f_main<false, 0>(P, h, rank, hw); else f_main<false, 1>(P, h, rank, hw); }
  PROF2(5);
  KT_END(1);
  __syncwarp();
  f_tail(P, h, crank, rank == 2);
}

#define GCL 1
#define G_PF 3
#define G_PFM 2
#define G_LATE 0
namespace gk {
enum { T_B1 = 0, T_B2 = 1, T_B3 = 2, T_B4 = 3, T_O = 4, T_LN = 5, T_LN0 = 6, T_END = 7 };
constexpr int NST = 3, STAGE = 49152, MAXITEMS = 512, NEW = 3;
constexpr uint32_t OUTB = NST * STAGE, BARS = OUTB + 65536;
constexpr uint32_t B_FULL = BARS, B_EMPTY = BARS + 32, B_ITEM = BARS + 64, B_FILL = BARS + 128, B_FREE = BARS + 160, B_LN = BARS + 176, ITEMS = BARS + 192;
constexpr int SMEM = BARS + 256;
static_assert(GATE_CNT == 4 * NEW && T_B4 == 3, "gate counter");
}
struct GParams {
  CUtensorMap a[5], b[5];
  bf16* c[5];
  const bf16* r[5];
  bf16 *x1n, *xn2;
  const bf16* w1;
  int nitems, lnpos;
  uint16_t items[gk::MAXITEMS];
};
#define ILOG(i)

__device__ __forceinline__ void tma_load_3d_mc(uint32_t dst, const CUtensorMap* map, int x, int y, int z, uint32_t bar) {
  asm volatile("cp.async.bulk.tensor.3d.shared::cluster.global.mbarrier::complete_tx::bytes.multicast::cluster "
               "[%0], [%1, {%3, %4, %5}], [%2], %6;"
               ::"r"(dst), "l"(map), "r"(bar), "r"(x), "r"(y), "r"(z), "h"((uint16_t)3) : "memory");
}
__device__ __forceinline__ float tanh_approx(float x) { float y; asm("tanh.approx.f32 %0, %1;" : "=f"(y) : "f"(x)); return y; }
__global__ void __launch_bounds__(384, 1) g_kernel(const __grid_constant__ GParams P) {
  using namespace gk;
  extern __shared__ __align__(1024) uint8_t smem_g[];
  const uint32_t base = smem_u32(smem_g);
  const int tid = threadIdx.x, warp = __shfl_sync(0xffffffffu, tid >> 5, 0), lane = tid & 31;
  const int rank = blockIdx.x % GCL;
  KT_START(2);
  if (tid == 0) {
    for (int s = 0; s < NST; s++) { mbar_init(base + B_FULL + 8 * s, 1); mbar_init(base + B_EMPTY + 8 * s, 8 * GCL); }
    for (int s = 0; s < 8; s++) mbar_init(base + B_ITEM + 8 * s, 1);
    for (int s = 0; s < 2; s++) { mbar_init(base + B_FILL + 8 * s, 4); mbar_init(base + B_FREE + 8 * s, NEW); }
    mbar_init(base + B_LN, 1);
    fence_barrier_init();
  }
  __syncthreads();
  if (GCL > 1) cluster_sync();
  auto release = [&](uint32_t st) {
    if (GCL > 1) { if (lane < GCL) mbar_arrive_cluster(base + B_EMPTY + 8 * st, lane); }
    else if (lane == 0) mbar_arrive(base + B_EMPTY + 8 * st);
  };
  auto get_item = [&](int q) {
    mbar_wait(base + B_ITEM + 8 * (q & 7), (q >> 3) & 1);
    return lds32(base + ITEMS + 4 * (q & 7));
  };

  if (warp == 8) {
    if (lane < 10) prefetch_tmap(&P.a[0] + lane);
    for (int r = blockIdx.x * 32 + lane; r < cfg::D; r += gridDim.x * 32) l2_prefetch(P.w1 + r * cfg::D, 2048);
    if (lane == 0) {
      uint32_t st = 0, ph = 1;
#pragma unroll 1
      for (int q = 0;; q++) {
        if (GCL > 1) mbar_expect_tx(base + B_ITEM + 8 * (q & 7), 4);
        if (rank == 0) {
          const unsigned idx = atomicAdd(&g_next, 1), ln = idx - P.lnpos;
          const uint32_t v = (idx < (unsigned)P.nitems ? P.items[idx] : T_END) | (ln < 64 / GCL ? (ln + 1) << 16 : idx < 32 / GCL ? (idx + 129) << 16 : 0);
          if (GCL > 1) {
#pragma unroll
            for (int r = 0; r < GCL; r++) st_async32(mapa(base + ITEMS + 4 * (q & 7), r), v, mapa(base + B_ITEM + 8 * (q & 7), r));
          } else {
            sts32(base + ITEMS + 4 * (q & 7), v);
            mbar_arrive(base + B_ITEM + 8 * (q & 7));
          }
        }
        const uint32_t item = get_item(q);
        const int type = item & 7, mb = ((item >> 3) & 15) + rank, nt = (item >> 7) & 15;
        ILOG(1);
        if (q == 0) { __threadfence(); sts32(base + ITEMS + 32, ld_strong4(&g_oflag[14]) >= 32); }
        if (type == T_END) break;
        if (type == T_B2) {
          wait_count(&g_cnt[T_B1][max(mb - 1, 0)], 4 * NEW); wait_count(&g_cnt[T_B1][mb], 4 * NEW); wait_count(&g_cnt[T_B1][min(mb + 1, 15)], 4 * NEW);
        } else if (type == T_B3) wait_count(&g_cnt[T_LN][mb], 32);
        else if (type == T_B4) wait_count(&g_cnt[T_B3][mb], 14 * NEW);
        else if (type == T_O) wait_count(&g_oflag[mb], 32);
        asm volatile("fence.proxy.async.global;" ::: "memory");
        ILOG(2);
        const CUtensorMap *ma = &P.a[type], *mbm = &P.b[type];
        const int nkb = type == T_B4 ? cfg::F / 64 : type == T_O ? cfg::HD / 64 : cfg::D / 64;
#pragma unroll 1
        for (int kb = 0; kb < nkb; kb++) {
          mbar_wait(base + B_EMPTY + 8 * st, ph);
          const uint32_t sa = base + st * STAGE, full = base + B_FULL + 8 * st;
          mbar_expect_tx(full, STAGE);
          int arow = mb * 128;
          if (type == T_B2) { const int qd = kb >> 2; arow += (qd == 0) ? -1 : (qd == 1) ? 1 : (qd == 2) ? -2 : 2; }
          if (GCL > 1) tma_load_3d_mc(sa + 16384 + rank * 16384, mbm, 0, kb * 64, nt * 4 + rank * 2, full);
          else tma_load_3d(sa + 16384, mbm, 0, kb * 64, nt * 4, full);
          if (type == T_B1 && kb == 0) { wait_count(&g_cnt[T_LN0][mb], 32); asm volatile("fence.proxy.async.global;" ::: "memory"); }
          tma_load_2d(sa, ma, kb * 64, arow, full);
          if (G_PF && type >= T_B4 && kb + G_PF < nkb) {
            if (G_PFM & 1) asm volatile("cp.async.bulk.prefetch.tensor.3d.L2.global [%0, {0, %1, %2}];" ::"l"(mbm), "r"((kb + G_PF) * 64), "r"(nt * 4 + rank * 2) : "memory");
            if (G_PFM & 2) asm volatile("cp.async.bulk.prefetch.tensor.2d.L2.global [%0, {%1, %2}];" ::"l"(ma), "r"((kb + G_PF) * 64), "r"(mb * 128) : "memory");
          }
          if (++st == NST) { st = 0; ph ^= 1; }
        }
      }
    }
  } else {
    const int wg = warp >> 2, ew = warp > 8 ? warp - 9 : warp + NEW;
    const uint32_t outa = base + OUTB + (warp * 16 + ((lane >> 3) & 1) * 8 + (lane & 7)) * 512 + (((lane >> 4) ^ (lane & 7)) << 4);
    uint32_t st = 0, ph = 0;
    float acc[128];
    auto kill_acc = [&]() {
#pragma unroll
      for (int i = 0; i < 128; i++) acc[i] = 0.f;
    };
    if (warp == 9) {
#pragma unroll 1
      for (int tries = 0; tries < POLL_TRIES; tries++) {
        uint4 v;
        asm volatile("ld.acquire.gpu.global.v4.u32 {%0,%1,%2,%3}, [%4];" : "=r"(v.x), "=r"(v.y), "=r"(v.z), "=r"(v.w)
                     : "l"(lane < 24 ? &g_mask[4 * lane] : &g_lnok[0]) : "memory");
        const uint32_t ok = __ballot_sync(0xffffffffu, v.x & v.y & v.z & v.w & 0x100);
        if ((ok & 0xFFFFFF) == 0xFFFFFF || (ok >> 24)) break;
        __nanosleep(200);
      }
      if (lane == 0) mbar_arrive(base + B_LN);
    }
    uint32_t next = get_item(0);
#pragma unroll 1
    for (int q = 0;; q++) {
      const uint32_t item = next;
      const int type = item & 7, mb = ((item >> 3) & 15) + rank, nt = (item >> 7) & 15;
      if (type == T_END) break;
      if (warp < 8) {
      if (item >> 16) {
        const bool first = item >> 23;
#pragma unroll 1
        for (int ln = ((item >> 16) & 127) - 1; ln < 64 / GCL; ln += first ? 32 / GCL : 64) {
          const int lb = (ln >> 2) * GCL + rank;
          const size_t row = (size_t)(lb * 128 + (ln & 3) * 32 + warp * 4) * cfg::D;
          const bf16* src = (first ? P.r[T_O] : P.c[T_B2]) + row;
          bf16* dst = (first ? P.xn2 : P.x1n) + row;
          if (!first) wait_count(&g_cnt[T_B2][lb], 4 * NEW);
          uint32_t cur[2][16], nxt[2][16];
#pragma unroll
          for (int r = 0; r < 2; r++) {
            load_row16(cur[r], src + r * cfg::D, lane);
            load_row16(nxt[r], src + (r + 2) * cfg::D, lane);
          }
#pragma unroll 1
          for (int it = first ? 0 : 1; it < 4; it += first ? 1 : 2) {
            ln_regs<2>(cur);
            if (it & 1) {
#pragma unroll
              for (int r = 0; r < 2; r++) {
                store_row16(cur[r], dst + (it - 1 + r) * cfg::D, lane);
#pragma unroll
                for (int i = 0; i < 16; i++) cur[r][i] = nxt[r][i];
              }
            }
          }
          __syncwarp();
          if (lane == 0) asm volatile("red.release.gpu.global.add.u32 [%0], 1;" ::"l"(&g_cnt[first ? T_LN0 : T_LN][lb]) : "memory");
          __syncwarp();
        }
        if (tid == 0) ILOG(6);
        kill_acc();
      }
      const int nkb = type == T_B4 ? cfg::F / 64 : type == T_O ? cfg::HD / 64 : cfg::D / 64;
      uint32_t prev = 0;
      mbar_wait(base + B_FULL + 8 * st, ph);
#pragma unroll 1
      for (int kb = 0; kb < nkb; kb++) {
        mbar_spin(base + B_FULL + 8 * st, ph);
        if (kb == 0 && tid == 0) ILOG(3);
        const uint64_t da = make_desc(base + wg * 8192, 16, 1024) + st * (STAGE >> 4), db = make_desc(base + 16384, 8192, 1024) + st * (STAGE >> 4);
        wg_fence();
#pragma unroll
        for (int k = 0; k < 4; k++) {
          wgmma_ss_n256_tb(acc, da + k * 2, db + k * 128, (kb | k) != 0);
          if (k == 0) {
            wg_commit();
            wg_wait<1>();
            if (kb > 0) release(prev);
            wg_fence();
          }
        }
        wg_commit();
        prev = st;
        if (++st == NST) { st = 0; ph ^= 1; }
      }
      next = get_item(q + 1);
      if (q > 0) mbar_wait(base + B_FREE + 8 * wg, (q - 1) & 1);
      wg_wait<0>();
      if (tid == 0) ILOG(4);
      release(prev);
#pragma unroll
      for (int j = 0; j < 16; j++)
        stsm4((outa ^ ((j & 3) << 5)) + (j >> 2) * 128, pack_bf16(acc[8 * j], acc[8 * j + 1]), pack_bf16(acc[8 * j + 2], acc[8 * j + 3]),
              pack_bf16(acc[8 * j + 4], acc[8 * j + 5]), pack_bf16(acc[8 * j + 6], acc[8 * j + 7]));
      __syncwarp();
      if (lane == 0) mbar_arrive(base + B_FILL + 8 * wg);
      if (tid == 0) ILOG(5);
      if ((next & 7) != T_END) continue;
      }
      if (type == T_O) wait_count(&g_cnt[T_B4][mb], 4 * NEW);
      const int ldc = type == T_B3 ? cfg::F : cfg::D;
      bf16* cp = P.c[type] + (size_t)mb * 128 * ldc + nt * 256 + lane * 8;
      const size_t roff = (size_t)mb * 128 * cfg::D + nt * 256 + lane * 8;
      const bf16 *rp = P.r[type] + roff, *gp = P.c[T_B4] + roff;
      const bool gelu = type == T_B1 || type == T_B3;
      uint32_t yn[4][4];
      uint4 rn[4], gn[4];
#pragma unroll
      for (int i = 0; i < 4; i++) rn[i] = gn[i] = make_uint4(0, 0, 0, 0);
      auto fetch_res = [&](int grp) {
#pragma unroll
        for (int i = 0; i < 4; i++) {
          rn[i] = __ldcg(reinterpret_cast<const uint4*>(rp + (grp * 4 + i) * cfg::D));
          if (type == T_O) gn[i] = __ldcg(reinterpret_cast<const uint4*>(gp + (grp * 4 + i) * cfg::D));
        }
      };
      auto fetch_y = [&](int grp) {
        const uint32_t a = base + OUTB + grp * 2048 + ((lane ^ ((grp & 1) << 2)) << 4);
#pragma unroll
        for (int i = 0; i < 4; i++) lds128(yn[i], (a ^ (i << 4)) + i * 512);
      };
      auto store_y = [&](int grp, const uint32_t (&y)[4][4]) {
        char* p = reinterpret_cast<char*>(cp) + (uint32_t)(grp * 8 * ldc);
#pragma unroll
        for (int i = 0; i < 4; i++) *reinterpret_cast<uint4*>(p + (uint32_t)(i * 2 * ldc)) = make_uint4(y[i][0], y[i][1], y[i][2], y[i][3]);
      };
      if (type == T_B2) mbar_wait(base + B_LN, 0);
      if (type == T_B4) wait_count(&g_cnt[T_B2][mb], 4 * NEW);
      if (type >= T_B4 && warp > 8) for (int r = tid - 288; r < 128; r += 96) l2_prefetch(rp - lane * 8 + r * cfg::D, 512);
      if (!gelu) fetch_res(ew);
      mbar_wait(base + B_FILL, q & 1);
      fetch_y(ew);
      next = get_item(q + 1);
      mbar_wait(base + B_FILL + 8, q & 1);
      const int stride = (next & 7) == T_END ? NEW + 8 : NEW;
      if (gelu) {
#pragma unroll 1
        for (int grp = ew; grp < 32; grp += stride) {
          uint32_t y[4][4];
#pragma unroll
          for (int i = 0; i < 16; i++) y[i >> 2][i & 3] = mul_bf16x2(yn[i >> 2][i & 3], 0x3F003F00u);
          const int nx = grp + stride;
          if (nx >= 16 && grp < 16 && lane == 0 && warp > 8) mbar_arrive(base + B_FREE);
          if (!G_LATE) fetch_y(min(nx, 31));
#pragma unroll
          for (int i = 0; i < 16; i++) {
            uint32_t& v = y[i >> 2][i & 3];
            const float h0 = bf_lo(v), h1 = bf_hi(v);
            const float t0 = tanh_approx(h0 * fmaf(h0 * h0, 0.285419265090401f, 1.5957691216057308f));
            const float t1 = tanh_approx(h1 * fmaf(h1 * h1, 0.285419265090401f, 1.5957691216057308f));
            v = pack_bf16(fmaf(h0, t0, h0), fmaf(h1, t1, h1));
          }
          if (G_LATE) fetch_y(min(nx, 31));
          store_y(grp, y);
        }
      } else {
#pragma unroll 1
        for (int grp = ew; grp < 32; grp += stride) {
          uint32_t y[4][4];
          if (type == T_O) {
#pragma unroll
            for (int i = 0; i < 16; i++) yn[i >> 2][i & 3] = mul_bf16x2(yn[i >> 2][i & 3], (&gn[i >> 2].x)[i & 3]);
          }
#pragma unroll
          for (int i = 0; i < 16; i++) y[i >> 2][i & 3] = add_bf16x2(yn[i >> 2][i & 3], (&rn[i >> 2].x)[i & 3]);
          const int nx = grp + stride;
          if (nx >= 16 && grp < 16 && lane == 0 && warp > 8) mbar_arrive(base + B_FREE);
          fetch_res(min(nx, 31));
          fetch_y(min(nx, 31));
          if (type == T_B4) {
#pragma unroll
            for (int i = 0; i < 16; i++) {
              uint32_t& v = y[i >> 2][i & 3];
              const float h0 = 0.5f * bf_lo(v), h1 = 0.5f * bf_hi(v);
              v = pack_bf16(fmaf(h0, tanh_approx(h0), h0), fmaf(h1, tanh_approx(h1), h1));
            }
          }
          store_y(grp, y);
        }
      }
      __syncwarp();
      if (lane == 0 && warp > 8) mbar_arrive(base + B_FREE + 8);
      if (stride != NEW) named_bar_sync(2, 352);
      if (type != T_O && lane == 0 && warp > 8) asm volatile("red.release.gpu.global.add.u32 [%0], 1;" ::"l"(&g_cnt[type][mb]) : "memory");
      __syncwarp();
      if (tid == 288) ILOG(7);
      kill_acc();
    }
    KT_END(2);
  }
  __syncwarp();
  if (warp >= 8) {
   named_bar_sync(1, 128);
   const bool late = lds32(base + ITEMS + 32);
   if (late) pdl_wait();
#pragma unroll 1
   for (int c = blockIdx.x; late && c < 96; c += gridDim.x) {
     if (__ldcg(&g_tfix[c]) == 0) continue;
     const int hh = c / 3, mb = TAIL_MB0 + 3 * (hh >> 4) + c % 3;
     wait_count(&g_cnt[T_B4][mb], GATE_CNT);
#pragma unroll 1
     for (int i = tid - 256; i < 1024; i += 128) {
       const size_t off = (size_t)(mb * 128 + (i >> 3)) * cfg::D + (hh & 15) * 64 + (i & 7) * 8;
       const uint4 sv = __ldcg(reinterpret_cast<const uint4*>(P.c[T_O] + off)), gv = __ldcg(reinterpret_cast<const uint4*>(P.c[T_B4] + off)),
                   xv = __ldcg(reinterpret_cast<const uint4*>(P.r[T_O] + off));
       *reinterpret_cast<uint4*>(P.c[T_O] + off) = make_uint4(add_bf16x2(xv.x, mul_bf16x2(sv.x, gv.x)), add_bf16x2(xv.y, mul_bf16x2(sv.y, gv.y)),
                                                              add_bf16x2(xv.z, mul_bf16x2(sv.z, gv.z)), add_bf16x2(xv.w, mul_bf16x2(sv.w, gv.w)));
     }
   }
  }
  if (GCL > 1) cluster_sync();
}

__device__ bf16 g_xn[cfg::S * cfg::D];
__device__ bf16 g_xn2[cfg::S * cfg::D];
__device__ bf16 g_h[cfg::S * cfg::D];
__device__ bf16 g_x1[cfg::S * cfg::D];
__device__ bf16 g_x1n[cfg::S * cfg::D];
__device__ bf16 g_u[cfg::S * cfg::F];
__device__ bf16 g_g[cfg::S * cfg::D];
__device__ bf16 g_o[cfg::S * cfg::HD];

typedef CUresult (*PFN_encodeTiled)(CUtensorMap*, CUtensorMapDataType, cuuint32_t, void*, const cuuint64_t*,
                                    const cuuint64_t*, const cuuint32_t*, const cuuint32_t*, CUtensorMapInterleave,
                                    CUtensorMapSwizzle, CUtensorMapL2promotion, CUtensorMapFloatOOBfill);

static PFN_encodeTiled get_encoder() {
  static PFN_encodeTiled fn = nullptr;
  if (!fn) {
    void* p = nullptr;
    cudaDriverEntryPointQueryResult st;
    cudaGetDriverEntryPoint("cuTensorMapEncodeTiled", &p, cudaEnableDefault, &st);
    fn = (PFN_encodeTiled)p;
  }
  return fn;
}
static CUtensorMap make_map(const void* ptr, int rows, int cols, int box_rows, int box_cols, int swizzle_bytes) {
  CUtensorMap m;
  cuuint64_t dims[2] = {(cuuint64_t)cols, (cuuint64_t)rows};
  cuuint64_t strides[1] = {(cuuint64_t)cols * 2};
  cuuint32_t box[2] = {(cuuint32_t)box_cols, (cuuint32_t)box_rows};
  cuuint32_t estr[2] = {1, 1};
  CUtensorMapSwizzle sw = swizzle_bytes == 128 ? CU_TENSOR_MAP_SWIZZLE_128B
                        : swizzle_bytes == 64 ? CU_TENSOR_MAP_SWIZZLE_64B
                        : swizzle_bytes == 32 ? CU_TENSOR_MAP_SWIZZLE_32B : CU_TENSOR_MAP_SWIZZLE_NONE;
  get_encoder()(&m, CU_TENSOR_MAP_DATA_TYPE_BFLOAT16, 2, const_cast<void*>(ptr), dims, strides, box, estr,
                CU_TENSOR_MAP_INTERLEAVE_NONE, sw, CU_TENSOR_MAP_L2_PROMOTION_L2_128B, CU_TENSOR_MAP_FLOAT_OOB_FILL_NONE);
  return m;
}
static CUtensorMap make_map3(const void* ptr, int rows, int cols, int box_rows, int nblk) {
  CUtensorMap m;
  cuuint64_t dims[3] = {64, (cuuint64_t)rows, (cuuint64_t)(cols / 64)};
  cuuint64_t strides[2] = {(cuuint64_t)cols * 2, 128};
  cuuint32_t box[3] = {64, (cuuint32_t)box_rows, (cuuint32_t)nblk};
  cuuint32_t estr[3] = {1, 1, 1};
  get_encoder()(&m, CU_TENSOR_MAP_DATA_TYPE_BFLOAT16, 3, const_cast<void*>(ptr), dims, strides, box, estr,
                CU_TENSOR_MAP_INTERLEAVE_NONE, CU_TENSOR_MAP_SWIZZLE_128B, CU_TENSOR_MAP_L2_PROMOTION_L2_128B,
                CU_TENSOR_MAP_FLOAT_OOB_FILL_NONE);
  return m;
}
template <class T> static T* sym(T& s) { void* p = nullptr; cudaGetSymbolAddress(&p, s); return (T*)p; }
#define SYM(name) ((bf16*)[] { void* p = nullptr; cudaGetSymbolAddress(&p, name); return p; }())

#define G_CTAS 36
#define B4_FIRST (GCL == 1 ? 9 : 16)
#define O_FIRST 2
#define LN_POS 63
static int build_items(uint16_t* it) {
  using namespace gk;
  int n = 0;
  auto add = [&](int type, int nrows, int ncols, int row0 = 0) {
    for (int mb = row0; mb < nrows; mb += GCL) for (int nt = 0; nt < ncols; nt++) it[n++] = (uint16_t)(type | mb << 3 | nt << 7);
  };
  add(T_B1, 16, 4); add(T_B2, 16, 4); add(T_B3, 16, 14);
  add(T_B4, B4_FIRST, 4); add(T_O, O_FIRST, 4); add(T_B4, 16, 4, B4_FIRST); add(T_O, TAIL_MB0, 4, O_FIRST);
  return n;
}

extern "C" void kernel_launch(void* const* d_in, const int* in_sizes, int n_in, void* d_out, int out_size) {
  using namespace cfg;
  const bf16* x = (const bf16*)d_in[0];
  const bf16* mem0 = (const bf16*)d_in[1];
  const bf16* Wq = (const bf16*)d_in[2];
  const bf16* Wk = (const bf16*)d_in[3];
  const bf16* Wv = (const bf16*)d_in[4];
  const bf16* Wo = (const bf16*)d_in[5];
  const bf16* w1 = (const bf16*)d_in[8];
  const bf16* w2 = (const bf16*)d_in[9];
  const bf16* w3 = (const bf16*)d_in[10];
  const bf16* w4 = (const bf16*)d_in[11];
  bf16* out = (bf16*)d_out;
  cudaStream_t st = cudaStreamPerThread;

  bf16 *xn = SYM(g_xn), *xn2 = SYM(g_xn2), *hb = SYM(g_h), *x1 = SYM(g_x1), *x1n = SYM(g_x1n), *u = SYM(g_u),
       *g = SYM(g_g), *o = SYM(g_o);

  {
    cudaFuncSetAttribute(f_kernel, cudaFuncAttributeMaxDynamicSharedMemorySize, fk::SMEM);
    FParams P;
    P.wq = make_map(Wq, D, HD, 64, 64, 128); P.wk = make_map(Wk, D, HD, 64, 64, 128); P.wv = make_map(Wv, D, HD, 64, 64, 128);
    P.wo = make_map(Wo, HD, D, 128, 64, 128); P.wo16 = make_map(Wo, HD, D, 128, 16, 32); P.xn = make_map3(xn, S, D, 32, 4); P.xn12 = make_map3(xn, S, D, 32, 12); P.o = make_map3(o, S, HD, 32, 2);
    P.ta = make_map(o, S, HD, 128, 64, 128); P.tb = make_map(Wo, HD, D, 64, 64, 128); P.tx = make_map(x, S, D, 128, 64, 128);
    P.tg = make_map(g, S, D, 128, 64, 128); P.tout = make_map(out, S, D, 16, 64, 128);
    P.mem0 = mem0;
    P.nprobe = PROBE_N;
    P.dxn = make_desc(fk::XN, 16, 1024);
    P.x = x; P.xn_ptr = xn;
    P.xch = (char*)(((uintptr_t)SYM(g_xch) + 8191) & ~(uintptr_t)8191);
    cudaLaunchConfig_t cfg = {};
    cfg.gridDim = dim3(96); cfg.blockDim = dim3(256); cfg.dynamicSmemBytes = fk::SMEM; cfg.stream = st;
    cudaLaunchAttribute at[2];
    at[0].id = cudaLaunchAttributeClusterDimension;
    at[0].val.clusterDim.x = 3; at[0].val.clusterDim.y = 1; at[0].val.clusterDim.z = 1;
    cfg.attrs = at; cfg.numAttrs = 1;
    cudaLaunchKernelEx(&cfg, f_kernel, P);
  }
  {
    cudaFuncSetAttribute(g_kernel, cudaFuncAttributeMaxDynamicSharedMemorySize, gk::SMEM);
    GParams G;
    const bf16* as[5] = {xn2, hb, x1n, u, o};
    const bf16* bs[5] = {w1, w2, w3, w4, Wo};
    bf16* cs[5] = {hb, x1, u, g, out};
    const bf16* rs[5] = {xn, xn, xn, x1, x};
    const int ks[5] = {D, D, D, F, HD}, ns[5] = {D, D, F, D, D};
    for (int i = 0; i < 5; i++) {
      G.a[i] = make_map(as[i], S, ks[i], 128, 64, 128);
      G.b[i] = make_map3(bs[i], ks[i], ns[i], 64, 4 / GCL);
      G.c[i] = cs[i];
      G.r[i] = rs[i];
    }
    G.x1n = x1n; G.xn2 = xn2; G.w1 = w1;
    G.nitems = build_items(G.items);
    G.lnpos = LN_POS * 2 / GCL;
    cudaLaunchConfig_t cfg = {};
    cfg.gridDim = dim3(G_CTAS); cfg.blockDim = dim3(384); cfg.dynamicSmemBytes = gk::SMEM; cfg.stream = st;
    cudaLaunchAttribute at[2];
    at[0].id = cudaLaunchAttributeClusterDimension;
    at[0].val.clusterDim.x = GCL; at[0].val.clusterDim.y = 1; at[0].val.clusterDim.z = 1;
    at[1].id = cudaLaunchAttributeProgrammaticStreamSerialization;
    at[1].val.programmaticStreamSerializationAllowed = 1;
    cfg.attrs = at;
    cfg.numAttrs = 2;
    cudaLaunchKernelEx(&cfg, g_kernel, G);
  }
}
```

```cpp
#include <cuda_runtime.h>
#include <cuda_bf16.h>
#include <cuda.h>
#include <stdint.h>

typedef __nv_bfloat16 bf16;

namespace cfg {
constexpr int S = 2048;
constexpr int D = 1024;
constexpr int H = 32;
constexpr int DH = 128;
constexpr int HD = H * DH;
constexpr int M = 8;
constexpr int SEG = 32;
constexpr int NSEG = S / SEG;
constexpr int F = 3584;
}

__device__ __forceinline__ uint32_t smem_u32(const void* p) { return (uint32_t)__cvta_generic_to_shared(p); }

__device__ __forceinline__ void mbar_init(uint32_t bar, uint32_t count) {
  asm volatile("mbarrier.init.shared::cta.b64 [%0], %1;" ::"r"(bar), "r"(count) : "memory");
}
__device__ __forceinline__ void mbar_expect_tx(uint32_t bar, uint32_t bytes) {
  asm volatile("mbarrier.arrive.expect_tx.shared::cta.b64 _, [%0], %1;" ::"r"(bar), "r"(bytes) : "memory");
}
__device__ __forceinline__ void mbar_arrive(uint32_t bar) {
  asm volatile("mbarrier.arrive.shared::cta.b64 _, [%0];" ::"r"(bar) : "memory");
}
__device__ __forceinline__ bool mbar_try(uint32_t bar, uint32_t parity) {
  uint32_t done;
  asm volatile("{\n.reg .pred p;\nmbarrier.try_wait.parity.shared::cta.b64 p, [%1], %2, 20000;\nselp.u32 %0, 1, 0, p;\n}"
               : "=r"(done) : "r"(bar), "r"(parity) : "memory");
  return done != 0;
}
__device__ __forceinline__ bool mbar_try_nohint(uint32_t bar, uint32_t parity) {
  uint32_t done;
  asm volatile("{\n.reg .pred p;\nmbarrier.try_wait.parity.shared::cta.b64 p, [%1], %2;\nselp.u32 %0, 1, 0, p;\n}"
               : "=r"(done) : "r"(bar), "r"(parity) : "memory");
  return done != 0;
}
constexpr int MBAR_TRIES = 4096;
constexpr int POLL_TRIES = 1 << 16;
__device__ __forceinline__ void mbar_wait(uint32_t bar, uint32_t parity) {
#pragma unroll 1
  for (int n = 0; n < MBAR_TRIES; n++)
    if (mbar_try(bar, parity)) break;
}
__device__ __forceinline__ void mbar_wait_fast(uint32_t bar, uint32_t parity) {
#pragma unroll 1
  for (int n = 0; n < (POLL_TRIES << 4); n++)
    if (mbar_try_nohint(bar, parity)) break;
}
__device__ __forceinline__ void fence_barrier_init() { asm volatile("fence.mbarrier_init.release.cluster;" ::: "memory"); }
__device__ __forceinline__ void fence_proxy_async_smem() { asm volatile("fence.proxy.async.shared::cta;" ::: "memory"); }

__device__ __forceinline__ void tma_load_2d(uint32_t dst, const CUtensorMap* map, int x, int y, uint32_t bar) {
  asm volatile("cp.async.bulk.tensor.2d.shared::cluster.global.mbarrier::complete_tx::bytes [%0], [%1, {%3, %4}], [%2];"
               ::"r"(dst), "l"(map), "r"(bar), "r"(x), "r"(y) : "memory");
}
__device__ __forceinline__ void tma_load_3d(uint32_t dst, const CUtensorMap* map, int x, int y, int z, uint32_t bar) {
  asm volatile("cp.async.bulk.tensor.3d.shared::cluster.global.mbarrier::complete_tx::bytes [%0], [%1, {%3, %4, %5}], [%2];"
               ::"r"(dst), "l"(map), "r"(bar), "r"(x), "r"(y), "r"(z) : "memory");
}
__device__ __forceinline__ void tma_store_2d(const CUtensorMap* map, uint32_t src, int x, int y) {
  asm volatile("cp.async.bulk.tensor.2d.global.shared::cta.bulk_group [%0, {%2, %3}], [%1];"
               ::"l"(map), "r"(src), "r"(x), "r"(y) : "memory");
}
__device__ __forceinline__ void tma_store_commit() { asm volatile("cp.async.bulk.commit_group;" ::: "memory"); }
__device__ __forceinline__ void tma_store_wait_all() { asm volatile("cp.async.bulk.wait_group 0;" ::: "memory"); }
__device__ __forceinline__ void tma_store_wait_read() { asm volatile("cp.async.bulk.wait_group.read 0;" ::: "memory"); }
__device__ __forceinline__ void prefetch_tmap(const CUtensorMap* map) {
  asm volatile("prefetch.tensormap [%0];" ::"l"(map) : "memory");
}

__device__ __forceinline__ void wg_fence() { asm volatile("wgmma.fence.sync.aligned;" ::: "memory"); }
__device__ __forceinline__ void wg_commit() { asm volatile("wgmma.commit_group.sync.aligned;" ::: "memory"); }
template <int N> __device__ __forceinline__ void wg_wait() { asm volatile("wgmma.wait_group.sync.aligned %0;" ::"n"(N) : "memory"); }

#define named_bar_sync(id, n) asm volatile("bar.sync %0, %1;" ::"n"(id), "n"(n) : "memory")
#define named_bar_arrive(id, n) asm volatile("bar.arrive %0, %1;" ::"n"(id), "n"(n) : "memory")

__host__ __device__ __forceinline__ uint64_t make_desc(uint32_t addr, uint32_t lbo, uint32_t sbo) {
  return (uint64_t)((addr & 0x3FFFF) >> 4) | ((uint64_t)(lbo >> 4) << 16) | ((uint64_t)(sbo >> 4) << 32) | (1ull << 62);
}

__device__ __forceinline__ uint64_t make_desc0(uint32_t addr, uint32_t lbo, uint32_t sbo) {
  return (uint64_t)((addr & 0x3FFFF) >> 4) | ((uint64_t)(lbo >> 4) << 16) | ((uint64_t)(sbo >> 4) << 32);
}

__device__ __forceinline__ uint32_t pack_bf16(float lo, float hi) {
  uint32_t r;
  asm("cvt.rn.bf16x2.f32 %0, %1, %2;" : "=r"(r) : "f"(hi), "f"(lo));
  return r;
}
__device__ __forceinline__ float bf_lo(uint32_t v) { return __uint_as_float(v << 16); }
__device__ __forceinline__ float bf_hi(uint32_t v) { return __uint_as_float(v & 0xFFFF0000u); }
__device__ __forceinline__ float rbf(float v) { return __bfloat162float(__float2bfloat16_rn(v)); }

__device__ __forceinline__ void pdl_launch_dependents() { asm volatile("griddepcontrol.launch_dependents;" ::: "memory"); }
__device__ __forceinline__ void pdl_wait() { asm volatile("griddepcontrol.wait;" ::: "memory"); }

__device__ __forceinline__ float ex2_approx(float x) { float y; asm("ex2.approx.ftz.f32 %0, %1;" : "=f"(y) : "f"(x)); return y; }
__device__ __forceinline__ float rcp_approx(float x) { float y; asm("rcp.approx.ftz.f32 %0, %1;" : "=f"(y) : "f"(x)); return y; }

__device__ __forceinline__ void mul_sigmoid4(float (&v)[4], const float (&t)[4]) {
#pragma unroll
  for (int i = 0; i < 4; i += 2) {
    const float a = 1.0f + ex2_approx(fminf(t[i], 60.0f)), b = 1.0f + ex2_approx(fminf(t[i + 1], 60.0f));
    const float r = rcp_approx(a * b);
    v[i] *= b * r;
    v[i + 1] *= a * r;
  }
}
__device__ __forceinline__ void gelu4(float (&v)[4]) {
  float t[4];
#pragma unroll
  for (int i = 0; i < 4; i++) t[i] = v[i] * fmaf(v[i] * v[i], -0.10294324f, -2.30220819f);
  mul_sigmoid4(v, t);
}
__device__ __forceinline__ void silu4(float (&v)[4]) {
  float t[4];
#pragma unroll
  for (int i = 0; i < 4; i++) t[i] = v[i] * -1.4426950408889634f;
  mul_sigmoid4(v, t);
}

#define KT_START(id)
#define KT_END(id)

__device__ __forceinline__ void wgmma_ss_n256_tb(float (&d)[128], uint64_t da, uint64_t db, int scale_d) {
  asm volatile("{\n.reg .pred p;\nsetp.ne.b32 p, %130, 0;\n"
    "wgmma.mma_async.sync.aligned.m64n256k16.f32.bf16.bf16 "
    "{%0, %1, %2, %3, %4, %5, %6, %7, %8, %9, %10, %11, %12, %13, %14, %15, "
    "%16, %17, %18, %19, %20, %21, %22, %23, %24, %25, %26, %27, %28, %29, %30, %31, "
    "%32, %33, %34, %35, %36, %37, %38, %39, %40, %41, %42, %43, %44, %45, %46, %47, "
    "%48, %49, %50, %51, %52, %53, %54, %55, %56, %57, %58, %59, %60, %61, %62, %63, "
    "%64, %65, %66, %67, %68, %69, %70, %71, %72, %73, %74, %75, %76, %77, %78, %79, "
    "%80, %81, %82, %83, %84, %85, %86, %87, %88, %89, %90, %91, %92, %93, %94, %95, "
    "%96, %97, %98, %99, %100, %101, %102, %103, %104, %105, %106, %107, %108, %109, %110, %111, "
    "%112, %113, %114, %115, %116, %117, %118, %119, %120, %121, %122, %123, %124, %125, %126, %127}, "
    "%128, %129, p, 1, 1, 0, 1;\n}\n"
    : "+f"(d[0]), "+f"(d[1]), "+f"(d[2]), "+f"(d[3]), "+f"(d[4]), "+f"(d[5]), "+f"(d[6]), "+f"(d[7]),
      "+f"(d[8]), "+f"(d[9]), "+f"(d[10]), "+f"(d[11]), "+f"(d[12]), "+f"(d[13]), "+f"(d[14]), "+f"(d[15]),
      "+f"(d[16]), "+f"(d[17]), "+f"(d[18]), "+f"(d[19]), "+f"(d[20]), "+f"(d[21]), "+f"(d[22]), "+f"(d[23]),
      "+f"(d[24]), "+f"(d[25]), "+f"(d[26]), "+f"(d[27]), "+f"(d[28]), "+f"(d[29]), "+f"(d[30]), "+f"(d[31]),
      "+f"(d[32]), "+f"(d[33]), "+f"(d[34]), "+f"(d[35]), "+f"(d[36]), "+f"(d[37]), "+f"(d[38]), "+f"(d[39]),
      "+f"(d[40]), "+f"(d[41]), "+f"(d[42]), "+f"(d[43]), "+f"(d[44]), "+f"(d[45]), "+f"(d[46]), "+f"(d[47]),
      "+f"(d[48]), "+f"(d[49]), "+f"(d[50]), "+f"(d[51]), "+f"(d[52]), "+f"(d[53]), "+f"(d[54]), "+f"(d[55]),
      "+f"(d[56]), "+f"(d[57]), "+f"(d[58]), "+f"(d[59]), "+f"(d[60]), "+f"(d[61]), "+f"(d[62]), "+f"(d[63]),
      "+f"(d[64]), "+f"(d[65]), "+f"(d[66]), "+f"(d[67]), "+f"(d[68]), "+f"(d[69]), "+f"(d[70]), "+f"(d[71]),
      "+f"(d[72]), "+f"(d[73]), "+f"(d[74]), "+f"(d[75]), "+f"(d[76]), "+f"(d[77]), "+f"(d[78]), "+f"(d[79]),
      "+f"(d[80]), "+f"(d[81]), "+f"(d[82]), "+f"(d[83]), "+f"(d[84]), "+f"(d[85]), "+f"(d[86]), "+f"(d[87]),
      "+f"(d[88]), "+f"(d[89]), "+f"(d[90]), "+f"(d[91]), "+f"(d[92]), "+f"(d[93]), "+f"(d[94]), "+f"(d[95]),
      "+f"(d[96]), "+f"(d[97]), "+f"(d[98]), "+f"(d[99]), "+f"(d[100]), "+f"(d[101]), "+f"(d[102]), "+f"(d[103]),
      "+f"(d[104]), "+f"(d[105]), "+f"(d[106]), "+f"(d[107]), "+f"(d[108]), "+f"(d[109]), "+f"(d[110]), "+f"(d[111]),
      "+f"(d[112]), "+f"(d[113]), "+f"(d[114]), "+f"(d[115]), "+f"(d[116]), "+f"(d[117]), "+f"(d[118]), "+f"(d[119]),
      "+f"(d[120]), "+f"(d[121]), "+f"(d[122]), "+f"(d[123]), "+f"(d[124]), "+f"(d[125]), "+f"(d[126]), "+f"(d[127])
    : "l"(da), "l"(db), "r"(scale_d));
}
__device__ __forceinline__ void wgmma_rs_n32(float (&d)[16], const uint32_t* a, uint64_t db, int scale_d) {
  asm volatile("{\n.reg .pred p;\nsetp.ne.b32 p, %21, 0;\n"
    "wgmma.mma_async.sync.aligned.m64n32k16.f32.bf16.bf16 "
    "{%0, %1, %2, %3, %4, %5, %6, %7, %8, %9, %10, %11, %12, %13, %14, %15}, "
    "{%16, %17, %18, %19}, %20, p, 1, 1, 0;\n}\n"
    : "+f"(d[0]), "+f"(d[1]), "+f"(d[2]), "+f"(d[3]), "+f"(d[4]), "+f"(d[5]), "+f"(d[6]), "+f"(d[7]),
      "+f"(d[8]), "+f"(d[9]), "+f"(d[10]), "+f"(d[11]), "+f"(d[12]), "+f"(d[13]), "+f"(d[14]), "+f"(d[15])
    : "r"(a[0]), "r"(a[1]), "r"(a[2]), "r"(a[3]), "l"(db), "r"(scale_d));
}
__device__ __forceinline__ void wgmma_ss_n32_ta(float (&d)[16], uint64_t da, uint64_t db, int scale_d) {
  asm volatile("{\n.reg .pred p;\nsetp.ne.b32 p, %18, 0;\n"
    "wgmma.mma_async.sync.aligned.m64n32k16.f32.bf16.bf16 "
    "{%0, %1, %2, %3, %4, %5, %6, %7, %8, %9, %10, %11, %12, %13, %14, %15}, "
    "%16, %17, p, 1, 1, 1, 0;\n}\n"
    : "+f"(d[0]), "+f"(d[1]), "+f"(d[2]), "+f"(d[3]), "+f"(d[4]), "+f"(d[5]), "+f"(d[6]), "+f"(d[7]),
      "+f"(d[8]), "+f"(d[9]), "+f"(d[10]), "+f"(d[11]), "+f"(d[12]), "+f"(d[13]), "+f"(d[14]), "+f"(d[15])
    : "l"(da), "l"(db), "r"(scale_d));
}
__device__ __forceinline__ void wgmma_ss_n8_ta(float (&d)[4], uint64_t da, uint64_t db, int scale_d) {
  asm volatile("{\n.reg .pred p;\nsetp.ne.b32 p, %6, 0;\n"
    "wgmma.mma_async.sync.aligned.m64n8k16.f32.bf16.bf16 {%0, %1, %2, %3}, %4, %5, p, 1, 1, 1, 0;\n}\n"
    : "+f"(d[0]), "+f"(d[1]), "+f"(d[2]), "+f"(d[3]) : "l"(da), "l"(db), "r"(scale_d));
}
__device__ __forceinline__ void wgmma_ss_n48_tt(float (&d)[24], uint64_t da, uint64_t db, int scale_d) {
  asm volatile("{\n.reg .pred p;\nsetp.ne.b32 p, %26, 0;\n"
    "wgmma.mma_async.sync.aligned.m64n48k16.f32.bf16.bf16 "
    "{%0, %1, %2, %3, %4, %5, %6, %7, %8, %9, %10, %11, %12, %13, %14, %15, %16, %17, %18, %19, %20, %21, %22, %23}, "
    "%24, %25, p, 1, 1, 1, 1;\n}\n"
    : "+f"(d[0]), "+f"(d[1]), "+f"(d[2]), "+f"(d[3]), "+f"(d[4]), "+f"(d[5]), "+f"(d[6]), "+f"(d[7]), "+f"(d[8]), "+f"(d[9]), "+f"(d[10]), "+f"(d[11]), "+f"(d[12]), "+f"(d[13]), "+f"(d[14]), "+f"(d[15]), "+f"(d[16]), "+f"(d[17]), "+f"(d[18]), "+f"(d[19]), "+f"(d[20]), "+f"(d[21]), "+f"(d[22]), "+f"(d[23])
    : "l"(da), "l"(db), "r"(scale_d));
}
__device__ __forceinline__ void wgmma_ss_n32(float (&d)[16], uint64_t da, uint64_t db, int scale_d) {
  asm volatile("{\n.reg .pred p;\nsetp.ne.b32 p, %18, 0;\n"
    "wgmma.mma_async.sync.aligned.m64n32k16.f32.bf16.bf16 "
    "{%0, %1, %2, %3, %4, %5, %6, %7, %8, %9, %10, %11, %12, %13, %14, %15}, "
    "%16, %17, p, 1, 1, 0, 0;\n}\n"
    : "+f"(d[0]), "+f"(d[1]), "+f"(d[2]), "+f"(d[3]), "+f"(d[4]), "+f"(d[5]), "+f"(d[6]), "+f"(d[7]),
      "+f"(d[8]), "+f"(d[9]), "+f"(d[10]), "+f"(d[11]), "+f"(d[12]), "+f"(d[13]), "+f"(d[14]), "+f"(d[15])
    : "l"(da), "l"(db), "r"(scale_d));
}

__device__ __forceinline__ void tma_load_2d_mc(uint32_t dst, const CUtensorMap* map, int x, int y, uint32_t bar, uint16_t mask) {
  asm volatile("cp.async.bulk.tensor.2d.shared::cluster.global.mbarrier::complete_tx::bytes.multicast::cluster "
               "[%0], [%1, {%3, %4}], [%2], %5;"
               ::"r"(dst), "l"(map), "r"(bar), "r"(x), "r"(y), "h"(mask) : "memory");
}
__device__ __forceinline__ void mbar_arrive_cluster(uint32_t bar, uint32_t cta) {
  asm volatile("{\n.reg .b32 r;\nmapa.shared::cluster.u32 r, %0, %1;\nmbarrier.arrive.shared::cluster.b64 _, [r];\n}"
               ::"r"(bar), "r"(cta) : "memory");
}
__device__ __forceinline__ void cluster_sync() {
  asm volatile("barrier.cluster.arrive.release.aligned;\nbarrier.cluster.wait.acquire.aligned;" ::: "memory");
}
__device__ __forceinline__ void wait_count(const unsigned* p, unsigned need) {
#pragma unroll 1
  for (int tries = 0; tries < (1 << 18); tries++) {
    unsigned v;
    asm volatile("ld.acquire.gpu.global.u32 %0, [%1];" : "=r"(v) : "l"(p) : "memory");
    if (v >= need) break;
    __nanosleep(64);
  }
}
__device__ __forceinline__ uint32_t sub_bf16x2(uint32_t a, uint32_t b) {
  uint32_t d;
  asm("sub.rn.bf16x2 %0, %1, %2;" : "=r"(d) : "r"(a), "r"(b));
  return d;
}
__device__ __forceinline__ uint32_t add_bf16x2(uint32_t a, uint32_t b) {
  uint32_t d;
  asm("add.rn.bf16x2 %0, %1, %2;" : "=r"(d) : "r"(a), "r"(b));
  return d;
}
__device__ __forceinline__ uint32_t mul_bf16x2(uint32_t a, uint32_t b) {
  uint32_t d;
  asm("mul.rn.bf16x2 %0, %1, %2;" : "=r"(d) : "r"(a), "r"(b));
  return d;
}

template <int NR>
__device__ __forceinline__ void ln_regs(uint32_t (&raw)[NR][16]) {
  float m[NR], q[NR];
#pragma unroll
  for (int r = 0; r < NR; r++) {
    float s0 = 0.f, s1 = 0.f;
#pragma unroll
    for (int i = 0; i < 16; i++) { s0 += bf_lo(raw[r][i]); s1 += bf_hi(raw[r][i]); }
    m[r] = s0 + s1;
  }
#pragma unroll
  for (int o = 16; o > 0; o >>= 1)
#pragma unroll
    for (int r = 0; r < NR; r++) m[r] += __shfl_xor_sync(0xffffffffu, m[r], o);
#pragma unroll
  for (int r = 0; r < NR; r++) {
    m[r] *= 1.0f / 1024.0f;
    float s0 = 0.f, s1 = 0.f;
#pragma unroll
    for (int i = 0; i < 16; i++) {
      const float d0 = bf_lo(raw[r][i]) - m[r], d1 = bf_hi(raw[r][i]) - m[r];
      s0 = fmaf(d0, d0, s0); s1 = fmaf(d1, d1, s1);
    }
    q[r] = s0 + s1;
  }
#pragma unroll
  for (int o = 16; o > 0; o >>= 1)
#pragma unroll
    for (int r = 0; r < NR; r++) q[r] += __shfl_xor_sync(0xffffffffu, q[r], o);
#pragma unroll
  for (int r = 0; r < NR; r++) {
    const uint32_t mb = pack_bf16(m[r], m[r]);
    float sq;
    asm("sqrt.approx.f32 %0, %1;" : "=f"(sq) : "f"(rbf(rbf(q[r] * (1.0f / 1024.0f)) + 1e-5f)));
    const float inv = rcp_approx(rbf(sq));
#pragma unroll
    for (int i = 0; i < 16; i++) {
      const uint32_t d = sub_bf16x2(raw[r][i], mb);
      raw[r][i] = pack_bf16(bf_lo(d) * inv, bf_hi(d) * inv);
    }
  }
}
__device__ __forceinline__ void load_row16(uint32_t (&raw)[16], const bf16* src, int lane) {
#pragma unroll
  for (int j = 0; j < 4; j++) {
    const uint4 u = __ldcg(reinterpret_cast<const uint4*>(src + j * 256 + lane * 8));
    raw[4 * j] = u.x; raw[4 * j + 1] = u.y; raw[4 * j + 2] = u.z; raw[4 * j + 3] = u.w;
  }
}
__device__ __forceinline__ void store_row16(const uint32_t (&raw)[16], bf16* dst, int lane) {
#pragma unroll
  for (int j = 0; j < 4; j++)
    *reinterpret_cast<uint4*>(dst + j * 256 + lane * 8) = make_uint4(raw[4 * j], raw[4 * j + 1], raw[4 * j + 2], raw[4 * j + 3]);
}

namespace fk {
constexpr uint32_t SM0 = 1024;
constexpr uint32_t WO = SM0, WS = WO + 90112, XN = WS + 65536, VX = XN + 49152, QK = VX + 8192, PT = QK + 8192,
                   SP = PT + 4096, VM = SP + 2560, OB = VM + 2048, BAR = OB + 2048;
constexpr uint32_t MEMB = XN + 16384, RED = XN + 32768, VX2 = WO + 81920;
constexpr int SMEM = 232448;
static_assert(BAR + 512 == SM0 + SMEM, "shared memory layout");
constexpr uint32_t B_XN = BAR, B_H2 = BAR + 64, B_H1 = BAR + 120, ONES = BAR + 384, B_PF = BAR + 16, B_WO = BAR + 24, B_SM = BAR + 32, B_VM = BAR + 40, B_VX = BAR + 48, B_ST = BAR + 56, B_PB = BAR + 64, B_W = BAR + 112,
                   MASKS = BAR + 128, PROBE = BAR + 256;
constexpr int NB_M0 = 1, NB_M1 = 2, NB_C = 3, NB_O = 4, NB_ST = 5, NB_DU = 6, NB_CF = 7, NB_W1 = 8, NB_XE = 9, NB_HD = 10, NB_MX = 11, NB_O0 = 12;
#define D_H1 550
#define D_H2 1900
#define D_ST 200
#define SMQ 0x1E
#define SMV 0x1E
#define PRE_G 4
#define PRE_A 1
#define LN_DRY 1
#define MASK_AT 4
#define WO_AT 5
#define NS0 4
#define NS0V 4
#define NTA0 2
#define NTA1 1
#define PF0A 3
#define PF0 10
#define PF1V 10
#define PF1 11
#define REFILL_EARLY 1
#define GATE_MX 0
#define GATE_Q 0
#define PF1Q 4
#define PACEQ 0x60
#define PACEV 0
#define PADD 1
#define D_H2V 2200
#define D_H2L 1700
#define H2_ATV 0
#define VM_BULK 0
#define CF_AT 0
#define H2_AT 0
#define NPRE0 1
#define PROBE_N 4
#define SPACK 1
constexpr uint32_t SPW = SPACK ? 4 : 8, SP_SRC = 160 * SPW;
constexpr int H1_BYTES = 64 * 32768, H2_BYTES = 8 * 8192;
}

#define PROF(wg, i)
#define PROF2(i)
#define RETRY(i)
#define GTSYNC(i)
#define PRO(i)
#define TL(i)
#define TL2(t, i)

__device__ uint4 g_xch[(fk::H1_BYTES + fk::H2_BYTES + 8192) / 16];
__device__ __align__(16) unsigned g_mask[128];
__device__ unsigned g_cnt[8][16];
__device__ unsigned g_next;
constexpr int TAIL_MB0 = 13, GATE_CNT = 12;
__device__ __align__(16) unsigned g_tfix[96], g_lnok[4];
__device__ uint4 g_tpart[96][8][2][256];
__device__ unsigned g_oflag[16];

#define LD_POLL "ld.global.L1::no_allocate"
__device__ __forceinline__ uint4 ld_poll16(const void* p) {
  uint4 v;
  asm volatile(LD_POLL ".v4.u32 {%0,%1,%2,%3}, [%4];" : "=r"(v.x), "=r"(v.y), "=r"(v.z), "=r"(v.w) : "l"(p) : "memory");
  return v;
}
__device__ __forceinline__ uint2 ld_poll8(const void* p) {
  uint2 v;
  asm volatile(LD_POLL ".v2.u32 {%0,%1}, [%2];" : "=r"(v.x), "=r"(v.y) : "l"(p) : "memory");
  return v;
}
__device__ __forceinline__ uint4 ld_strong16(const void* p) {
  uint4 v;
  asm volatile("ld.relaxed.gpu.global.v4.u32 {%0,%1,%2,%3}, [%4];" : "=r"(v.x), "=r"(v.y), "=r"(v.z), "=r"(v.w) : "l"(p) : "memory");
  return v;
}
__device__ __forceinline__ uint2 ld_strong8(const void* p) {
  uint2 v;
  asm volatile("ld.relaxed.gpu.global.v2.u32 {%0,%1}, [%2];" : "=r"(v.x), "=r"(v.y) : "l"(p) : "memory");
  return v;
}
__device__ __forceinline__ void st_pub32(void* p, uint32_t v) { asm volatile("st.relaxed.gpu.global.u32 [%0], %1;" ::"l"(p), "r"(v) : "memory"); }
__device__ __forceinline__ void st_pub16(void* p, uint32_t v) {
  asm volatile("st.relaxed.gpu.global.u16 [%0], %1;" ::"l"(p), "h"((uint16_t)v) : "memory");
}
__device__ __forceinline__ uint32_t ld_strong4(const void* p) {
  uint32_t v;
  asm volatile("ld.relaxed.gpu.global.u32 %0, [%1];" : "=r"(v) : "l"(p) : "memory");
  return v;
}
__device__ __forceinline__ void st_pub64(void* p, uint32_t a, uint32_t b) {
  asm volatile("st.relaxed.gpu.global.v2.u32 [%0], {%1,%2};" ::"l"(p), "r"(a), "r"(b) : "memory");
}
__device__ __forceinline__ void st_pub128(void* p, uint32_t a) {
  asm volatile("st.relaxed.gpu.global.v4.u32 [%0], {%1,%1,%1,%1};" ::"l"(p), "r"(a) : "memory");
}
constexpr uint32_t EMPTY = 0xFFFFFFFFu;
__device__ __forceinline__ uint32_t umax4(const uint4& v) { return max(max(v.x, v.y), max(v.z, v.w)); }
__device__ __forceinline__ void sts128(uint32_t a, uint32_t x, uint32_t y, uint32_t z, uint32_t w) {
  asm volatile("st.shared.v4.u32 [%0], {%1,%2,%3,%4};" ::"r"(a), "r"(x), "r"(y), "r"(z), "r"(w) : "memory");
}
__device__ __forceinline__ void sts64(uint32_t a, uint32_t x, uint32_t y) {
  asm volatile("st.shared.v2.u32 [%0], {%1,%2};" ::"r"(a), "r"(x), "r"(y) : "memory");
}
__device__ __forceinline__ void sts32(uint32_t a, uint32_t x) { asm volatile("st.shared.u32 [%0], %1;" ::"r"(a), "r"(x) : "memory"); }
__device__ __forceinline__ void sts128f(uint32_t a, float x, float y, float z, float w) {
  asm volatile("st.shared.v4.f32 [%0], {%1,%2,%3,%4};" ::"r"(a), "f"(x), "f"(y), "f"(z), "f"(w) : "memory");
}
__device__ __forceinline__ void sts64f(uint32_t a, float x, float y) {
  asm volatile("st.shared.v2.f32 [%0], {%1,%2};" ::"r"(a), "f"(x), "f"(y) : "memory");
}
__device__ __forceinline__ float4 lds128f(uint32_t a) {
  float4 v;
  asm volatile("ld.shared.v4.f32 {%0,%1,%2,%3}, [%4];" : "=f"(v.x), "=f"(v.y), "=f"(v.z), "=f"(v.w) : "r"(a) : "memory");
  return v;
}
__device__ __forceinline__ float2 lds64f(uint32_t a) {
  float2 v;
  asm volatile("ld.shared.v2.f32 {%0,%1}, [%2];" : "=f"(v.x), "=f"(v.y) : "r"(a) : "memory");
  return v;
}
__device__ __forceinline__ float2 lds64f_if(uint32_t a, bool on, float other) {
  float2 v = make_float2(other, other);
  asm volatile("{\n.reg .pred p;\nsetp.ne.u32 p, %3, 0;\n@p ld.shared.v2.f32 {%0,%1}, [%2];\n}" : "+f"(v.x), "+f"(v.y) : "r"(a), "r"((uint32_t)on) : "memory");
  return v;
}
__device__ __forceinline__ void lds128(uint32_t* r, uint32_t a) {
  asm volatile("ld.shared.v4.u32 {%0,%1,%2,%3}, [%4];" : "=r"(r[0]), "=r"(r[1]), "=r"(r[2]), "=r"(r[3]) : "r"(a) : "memory");
}
__device__ __forceinline__ void lds64(uint32_t* r, uint32_t a) {
  asm volatile("ld.shared.v2.u32 {%0,%1}, [%2];" : "=r"(r[0]), "=r"(r[1]) : "r"(a) : "memory");
}
__device__ __forceinline__ uint32_t lds32(uint32_t a) {
  uint32_t v;
  asm volatile("ld.shared.u32 %0, [%1];" : "=r"(v) : "r"(a) : "memory");
  return v;
}
__device__ __forceinline__ void ldsm4(uint32_t* r, uint32_t a) {
  asm volatile("ldmatrix.sync.aligned.m8n8.x4.shared.b16 {%0,%1,%2,%3}, [%4];"
               : "=r"(r[0]), "=r"(r[1]), "=r"(r[2]), "=r"(r[3]) : "r"(a) : "memory");
}
__device__ __forceinline__ void ldsm4t(uint32_t* r, uint32_t a) {
  asm volatile("ldmatrix.sync.aligned.m8n8.x4.trans.shared.b16 {%0,%1,%2,%3}, [%4];"
               : "=r"(r[0]), "=r"(r[1]), "=r"(r[2]), "=r"(r[3]) : "r"(a) : "memory");
}
__device__ __forceinline__ void stsm4(uint32_t a, uint32_t r0, uint32_t r1, uint32_t r2, uint32_t r3) {
  asm volatile("stmatrix.sync.aligned.m8n8.x4.shared.b16 [%0], {%1,%2,%3,%4};"
               ::"r"(a), "r"(r0), "r"(r1), "r"(r2), "r"(r3) : "memory");
}
__device__ __forceinline__ void stsm4t(uint32_t a, uint32_t r0, uint32_t r1, uint32_t r2, uint32_t r3) {
  asm volatile("stmatrix.sync.aligned.m8n8.x4.trans.shared.b16 [%0], {%1,%2,%3,%4};"
               ::"r"(a), "r"(r0), "r"(r1), "r"(r2), "r"(r3) : "memory");
}
__device__ __forceinline__ void mma16816(float* d, const uint32_t* a, uint32_t b0, uint32_t b1) {
  asm volatile("mma.sync.aligned.m16n8k16.row.col.f32.bf16.bf16.f32 {%0,%1,%2,%3}, {%4,%5,%6,%7}, {%8,%9}, {%0,%1,%2,%3};"
               : "+f"(d[0]), "+f"(d[1]), "+f"(d[2]), "+f"(d[3])
               : "r"(a[0]), "r"(a[1]), "r"(a[2]), "r"(a[3]), "r"(b0), "r"(b1));
}
__device__ __forceinline__ void mma16816z(float* d, const uint32_t* a, uint32_t b0, uint32_t b1) {
  asm volatile("mma.sync.aligned.m16n8k16.row.col.f32.bf16.bf16.f32 {%0,%1,%2,%3}, {%4,%5,%6,%7}, {%8,%9}, {%10,%10,%10,%10};"
               : "=f"(d[0]), "=f"(d[1]), "=f"(d[2]), "=f"(d[3])
               : "r"(a[0]), "r"(a[1]), "r"(a[2]), "r"(a[3]), "r"(b0), "r"(b1), "f"(0.f));
}
__device__ __forceinline__ void mma1688(float* d, uint32_t a0, uint32_t a1, uint32_t b0) {
  asm volatile("mma.sync.aligned.m16n8k8.row.col.f32.bf16.bf16.f32 {%0,%1,%2,%3}, {%4,%5}, {%6}, {%0,%1,%2,%3};"
               : "+f"(d[0]), "+f"(d[1]), "+f"(d[2]), "+f"(d[3]) : "r"(a0), "r"(a1), "r"(b0));
}
__device__ __forceinline__ uint32_t movtrans(uint32_t a) {
  uint32_t d;
  asm volatile("movmatrix.sync.aligned.m8n8.trans.b16 %0, %1;" : "=r"(d) : "r"(a));
  return d;
}
__device__ __forceinline__ uint32_t mapa(uint32_t a, uint32_t rank) {
  uint32_t d;
  asm("mapa.shared::cluster.u32 %0, %1, %2;" : "=r"(d) : "r"(a), "r"(rank));
  return d;
}
__device__ __forceinline__ void st_async64(uint32_t a, uint32_t x, uint32_t y, uint32_t bar) {
  asm volatile("st.async.weak.shared::cluster.mbarrier::complete_tx::bytes.v2.b32 [%0], {%1,%2}, [%3];"
               ::"r"(a), "r"(x), "r"(y), "r"(bar) : "memory");
}
__device__ __forceinline__ void st_async64f(uint32_t a, float x, float y, uint32_t bar) {
  st_async64(a, __float_as_uint(x), __float_as_uint(y), bar);
}
__device__ __forceinline__ void bulk_s2s(uint32_t dst, uint32_t src, uint32_t bytes, uint32_t bar) {
  asm volatile("cp.async.bulk.shared::cluster.shared::cta.mbarrier::complete_tx::bytes [%0], [%1], %2, [%3];"
               ::"r"(dst), "r"(src), "r"(bytes), "r"(bar) : "memory");
}
__device__ __forceinline__ void tma_store_3d(const CUtensorMap* map, uint32_t src, int x, int y, int z) {
  asm volatile("cp.async.bulk.tensor.3d.global.shared::cta.bulk_group [%0, {%2, %3, %4}], [%1];"
               ::"l"(map), "r"(src), "r"(x), "r"(y), "r"(z) : "memory");
}
__device__ __forceinline__ void mbar_spin(uint32_t bar, uint32_t parity) {
  asm volatile("{\n.reg .pred p;\n.reg .b32 n;\nmov.u32 n, 0x100000;\nMW_L:\n"
               "mbarrier.try_wait.parity.shared::cta.b64 p, [%0], %1;\n@p bra.uni MW_D;\n"
               "add.s32 n, n, -1;\nsetp.ne.u32 p, n, 0;\n@p bra.uni MW_L;\nMW_D:\n}" ::"r"(bar), "r"(parity) : "memory");
}
__device__ __forceinline__ bool mbar_test(uint32_t bar, uint32_t parity) {
  uint32_t done;
  asm volatile("{\n.reg .pred p;\nmbarrier.test_wait.parity.shared::cta.b64 p, [%1], %2;\nselp.u32 %0, 1, 0, p;\n}"
               : "=r"(done) : "r"(bar), "r"(parity) : "memory");
  return done != 0;
}
__device__ __forceinline__ void mbar_arrive_remote(uint32_t bar) {
  asm volatile("mbarrier.arrive.shared::cluster.b64 _, [%0];" ::"r"(bar) : "memory");
}
__device__ __forceinline__ bool elect_one() {
  uint32_t r;
  asm volatile("{\n.reg .pred p;\nelect.sync _|p, 0xffffffff;\nselp.u32 %0, 1, 0, p;\n}" : "=r"(r));
  return r != 0;
}
__device__ __forceinline__ void st_async32(uint32_t a, uint32_t x, uint32_t bar) {
  asm volatile("st.async.weak.shared::cluster.mbarrier::complete_tx::bytes.b32 [%0], %1, [%2];" ::"r"(a), "r"(x), "r"(bar) : "memory");
}
#define named_bar_and(id, n, in, out) \
  asm volatile("{\n.reg .pred p, q;\nsetp.ne.u32 p, %1, 0;\nbar.red.and.pred q, %2, %3, p;\nselp.u32 %0, 1, 0, q;\n}" \
               : "=r"(out) : "r"(in), "n"(id), "n"(n) : "memory")
__device__ __forceinline__ void bulk_g2s(uint32_t dst, const void* src, uint32_t bytes, uint32_t bar) {
  asm volatile("cp.async.bulk.shared::cluster.global.mbarrier::complete_tx::bytes [%0], [%1], %2, [%3];"
               ::"r"(dst), "l"(src), "r"(bytes), "r"(bar) : "memory");
}
__device__ __forceinline__ void l2_prefetch(const void* p, uint32_t bytes) {
  asm volatile("cp.async.bulk.prefetch.L2.global [%0], %1;" ::"l"(p), "r"(bytes) : "memory");
}

__device__ __forceinline__ uint32_t clk32() { uint32_t c; asm volatile("mov.u32 %0, %%clock;" : "=r"(c)::"memory"); return c; }
__device__ __forceinline__ void spin_until(uint32_t t) { while ((int32_t)(clk32() - t) < 0) {} }
#define PIN(x) asm volatile("" : "+r"(x))
#define OPQ                                                                                     \
  int tid_o = tid;                                                                              \
  asm volatile("" : "+r"(tid_o));                                                               \
  const int lane = tid_o & 31, w = (tid_o >> 5) & 3, t7 = tid_o & 127, lg = lane >> 2,          \
            lq = lane & 3, mi = lane >> 3, mr = lane & 7;                                       \
  (void)w; (void)t7; (void)lg; (void)lq; (void)mi; (void)mr; (void)lane

#define SMAP                                                                                                          \
  const uint32_t SM0 = self + fk::SM0, WO = self + fk::WO, WS = self + fk::WS, XN = self + fk::XN, VX = self + fk::VX, \
                 QK = self + fk::QK, PT = self + fk::PT, SP = self + fk::SP, VM = self + fk::VM, OB = self + fk::OB,   \
                 RED = self + fk::RED, VX2 = self + fk::VX2, MEMB = self + fk::MEMB, B_XN = self + fk::B_XN, B_SM = self + fk::B_SM,       \
                 B_VM = self + fk::B_VM, B_VX = self + fk::B_VX, B_ST = self + fk::B_ST, B_PB = self + fk::B_PB,       \
                 B_W = self + fk::B_W, B_H2 = self + fk::B_H2, B_H1 = self + fk::B_H1, B_PF = self + fk::B_PF, B_WO = self + fk::B_WO, MASKS = self + fk::MASKS, PROBE = self + fk::PROBE;                             \
  (void)SM0; (void)WO; (void)WS; (void)XN; (void)VX; (void)QK; (void)PT; (void)SP; (void)VM; (void)OB; (void)RED; (void)VX2; \
  (void)MEMB; (void)B_XN; (void)B_SM; (void)B_VM; (void)B_VX; (void)B_ST; (void)B_PB; (void)B_W; (void)MASKS; (void)PROBE; (void)B_H2; (void)B_H1; (void)B_PF; (void)B_WO

struct FParams {
  CUtensorMap wq, wk, wv, wo, wo16, xn, xn12, o;
  CUtensorMap ta, tb;
  const bf16 *mem0, *x, *gate;
  bf16* out;
  bf16* xn_ptr;
  uint64_t dxn;
  int nprobe;
  char* xch;
};

__device__ __forceinline__ uint2 probe_pair(char* p, uint32_t val, uint32_t dummy, int n) {
  uint2 best = make_uint2(0x7FFFFFFF, 0x7FFFFFFF);
  st_pub128(p, val); st_pub128(p + 16, val); st_pub128(p + 4096, val); st_pub128(p + 4112, val);
#pragma unroll 1
  for (int r = 0; r < n; r++) {
    uint32_t v;
    const uint32_t c0 = clk32();
    asm volatile("atom.relaxed.gpu.global.exch.b32 %0, [%1], %2;" : "=r"(v) : "l"(p + (r & 1) * 4096), "r"(val) : "memory");
    asm volatile("{\n.reg .pred p;\nsetp.eq.u32 p, %0, 0x12345678;\n@p st.shared.u32 [%1], %0;\n}" ::"r"(v), "r"(dummy) : "memory");
    const uint32_t d = clk32() - c0;
    if (r & 1) best.y = min(best.y, d); else best.x = min(best.x, d);
  }
  return best;
}

typedef uint32_t WRegs[6][2][4][4];

constexpr uint32_t nth_chunks(uint32_t mask) {
  uint32_t t = 0;
  for (int c = 0, n = 0; c < 10; c++) if ((mask >> c) & 1) t |= c << (4 * n++);
  return t;
}
constexpr uint64_t chunk_pos(uint32_t mask) {
  uint64_t t = 0;
  for (int c = 0, a = 0, b = 0; c < 10; c++) t |= (uint64_t)(((mask >> c) & 1) ? a++ : b++) << (4 * c);
  return t;
}
template <bool ISV> struct Chunks {
  static constexpr uint32_t MASK = ISV ? SMV : SMQ, SMT = nth_chunks(MASK), RFT = nth_chunks(~MASK & 1023);
  static_assert(!(MASK & 1), "the first chunk initialises the accumulators");
  static __device__ __forceinline__ constexpr int rf(int wg, int i) { return wg ? 10 + i : (RFT >> (4 * i)) & 15; }
  static __device__ __forceinline__ constexpr int sm(int i) { return (SMT >> (4 * i)) & 15; }
  static constexpr uint64_t IDX = chunk_pos(MASK);
  static __device__ __forceinline__ constexpr int idx(int c) { return (IDX >> (4 * c)) & 15; }
};

template <bool ISV, int WG> struct ProjCfg {
  static constexpr int N0 = ISV ? NS0V : NS0, NS = WG ? 8 - N0 : N0, P0 = WG ? N0 : 0, NTA = WG ? NTA1 : NTA0;
};
__device__ __forceinline__ void load_pair(uint32_t (&t)[4][4], uint32_t wsa, int pp) {
#pragma unroll
  for (int f = 0; f < 4; f++) ldsm4t(t[f], wsa + ((pp >> 1) * 2 + (f & 1)) * 8192 + ((pp & 1) * 2 + (f >> 1)) * 2048);
}
template <bool ISV, int WG>
__device__ __forceinline__ void proj_mem(const WRegs& wr, uint32_t (&ta)[ProjCfg<ISV, WG>::NTA][4][4], uint32_t wsa, uint32_t mba,
                                         float (&a0)[4], float (&a1)[4]) {
  constexpr int NS = ProjCfg<ISV, WG>::NS, P0 = ProjCfg<ISV, WG>::P0, NTA = ProjCfg<ISV, WG>::NTA, NP = 12 + NS;
  float acc[4][4];
  auto spos = [](int j) { return j < NTA ? j : j + (j - NTA + 1) * 12 / (NS - NTA > 0 ? NS - NTA : 1); };
  auto which = [&](int p) { int r = -1; for (int j = 0; j < NS; j++) if (spos(j) == p) r = j; return r; };
  auto nsm_before = [&](int p) { int n = 0; for (int j = 0; j < NS; j++) if (spos(j) < p) n++; return n; };
#pragma unroll
  for (int p = 0; p < NP; p++) {
    const int j = which(p), r = j >= 0 ? 0 : p - nsm_before(p);
    uint32_t bp[4], tl[4][4];
    ldsm4(bp, mba + (j >= 0 ? Chunks<ISV>::sm((P0 + (j >= 0 ? j : 0)) >> 1) * 1024 + ((P0 + j) & 1) * 512 : Chunks<ISV>::rf(WG, r >> 1) * 1024 + (r & 1) * 512));
    if (j >= NTA) load_pair(tl, wsa, P0 + j);
#pragma unroll
    for (int u = 0; u < 2; u++)
#pragma unroll
      for (int T = 0; T < 2; T++) {
        const uint32_t* a = j >= NTA ? tl[u * 2 + T] : j >= 0 ? ta[j >= 0 ? j % NTA : 0][u * 2 + T] : wr[r >> 1][T][(r & 1) * 2 + u];
        if (p == 0) mma16816z(acc[u * 2 + T], a, bp[2 * u], bp[2 * u + 1]);
        else mma16816(acc[u * 2 + T], a, bp[2 * u], bp[2 * u + 1]);
      }
  }
#pragma unroll
  for (int i = 0; i < 4; i++) { a0[i] = acc[0][i] + acc[2][i]; a1[i] = acc[1][i] + acc[3][i]; }
}
template <bool ISV, int WG, int J0, int J1>
__device__ __forceinline__ void proj_mem_prefetch(uint32_t (&ta)[ProjCfg<ISV, WG>::NTA][4][4], uint32_t wsa) {
#pragma unroll
  for (int j = J0; j < J1; j++) load_pair(ta[j], wsa, ProjCfg<ISV, WG>::P0 + j);
}

template <bool ISV, int WG>
__device__ __forceinline__ void proj_finish(const float (&a0)[4], const float (&a1)[4], uint32_t peer0, uint32_t peer1, uint32_t self, int tid, int warp,
                                            uint32_t (&vmo)[4]) {
  using namespace fk;
  SMAP;
  OPQ;
  if (!ISV) {
    stsm4(PT + mr * 16 + ((mi >> 1) ? WG * 1024 + w * 256 + (mi & 1) * 128 : 2048 + w * 512 + (mi & 1) * 256 + WG * 128),
          pack_bf16(a0[0], a0[1]), pack_bf16(a0[2], a0[3]), pack_bf16(a1[0], a1[1]), pack_bf16(a1[2], a1[3]));
    named_bar_sync(NB_C, 256);
  } else {
    if (WG == 0) sts128f(RED + t7 * 16, a1[0], a1[1], a1[2], a1[3]);
    else sts128f(RED + 2048 + t7 * 16, a0[0], a0[1], a0[2], a0[3]);
    if (WG == 1) { lds64(vmo, VM + t7 * 8); lds64(vmo + 2, VM + 1024 + t7 * 8); }
    named_bar_sync(NB_C, 256);
    const float4 p = lds128f(RED + (1 - WG) * 2048 + t7 * 16);
    const float* k = WG == 0 ? a0 : a1;
    const uint32_t v0 = pack_bf16(k[0] + p.x, k[1] + p.y), v1 = pack_bf16(k[2] + p.z, k[3] + p.w);
    const uint32_t off = VM + WG * 1024 + t7 * 8;
    if (VM_BULK) {
      sts64(off, v0, v1);
      fence_proxy_async_smem();
      __syncwarp();
      const uint32_t a = VM + WG * 1024 + warp * 256;
      if (elect_one()) {
        bulk_s2s(peer0 + a, a, 256, peer0 + B_VM);
        bulk_s2s(peer1 + a, a, 256, peer1 + B_VM);
        mbar_arrive(B_VM);
      }
    } else {
      st_async64(peer0 + off, v0, v1, peer0 + B_VM);
      st_async64(peer1 + off, v0, v1, peer1 + B_VM);
      sts64(off, v0, v1);
      __syncwarp();
      if (lane == 0) mbar_arrive(B_VM);
    }
  }
}

__device__ __forceinline__ void send_scores(float s0, float s1, uint32_t off, uint32_t peer0, uint32_t peer1, uint32_t bar, int lane) {
  if (SPACK) {
    const uint32_t v = pack_bf16(s0, s1);
    st_async32(peer0 + off, v, peer0 + bar);
    st_async32(peer1 + off, v, peer1 + bar);
    sts32(off, v);
  } else {
    st_async64f(peer0 + off, s0, s1, peer0 + bar);
    st_async64f(peer1 + off, s0, s1, peer1 + bar);
    sts64f(off, s0, s1);
  }
  __syncwarp();
  if (lane == 0) mbar_arrive(bar);
}

template <int MODE>
__device__ __forceinline__ void wo_load(uint32_t* r, int f, uint32_t woa, uint32_t wob, bool third) {
  constexpr int NT = MODE ? 3 : 2;
  if (MODE >= 2 && f % 3 == 2)
    asm volatile("{\n.reg .pred p;\nsetp.ne.u32 p, %5, 0;\nmov.b32 %0, 0;\nmov.b32 %1, 0;\nmov.b32 %2, 0;\nmov.b32 %3, 0;\n"
                 "@p ldmatrix.sync.aligned.m8n8.x4.trans.shared.b16 {%0,%1,%2,%3}, [%4];\n}"
                 : "=r"(r[0]), "=r"(r[1]), "=r"(r[2]), "=r"(r[3]) : "r"(wob + (f / 3) * 512), "r"((uint32_t)third) : "memory");
  else ldsm4t(r, woa + (f % NT) * 32768 + (f / NT) * 2048);
}
template <int MODE, int PF>
__device__ __forceinline__ void wo_phase(uint32_t (&wf)[PF][4], uint32_t woa, uint32_t wob, bool third, uint32_t oba, char* h1p,
                                         uint32_t sel, uint32_t tag) {
  constexpr int NT = MODE ? 3 : 2;
  float c[NT][4];
  uint32_t of[2][4];
  ldsm4t(of[0], oba);
#pragma unroll
  for (int k = 0; k < 8; k++) {
    if ((k & 1) == 0 && k + 2 < 8) ldsm4t(of[((k >> 1) + 1) & 1], oba + ((k >> 1) + 1) * 512);
#pragma unroll
    for (int i = 0; i < NT; i++) {
      const int f = k * NT + i;
      const uint32_t b0 = of[(k >> 1) & 1][2 * (k & 1)], b1 = of[(k >> 1) & 1][2 * (k & 1) + 1];
      if (k == 0) mma16816z(c[i], wf[f % PF], b0, b1); else mma16816(c[i], wf[f % PF], b0, b1);
      if (f + PF < 8 * NT) wo_load<MODE>(wf[f % PF], f + PF, woa, wob, third);
    }
  }
#pragma unroll
  for (int i = 0; i < NT; i++) {
    char* p = h1p + i * (8 * 32768) + ((sel >> (2 * i)) & 3) * 2048;
    const uint32_t tm = (sel >> 10) & 1;
    if (MODE < 2 || i < 2 || third) {
      st_pub32(p, (pack_bf16(c[i][0], c[i][1]) & ~tm) | (tag & tm));
      st_pub32(p + 1024, (pack_bf16(c[i][2], c[i][3]) & ~tm) | (tag & tm));
    }
  }
}
template <int MODE, int F0, int F1, int PF>
__device__ __forceinline__ void wo_prefetch(uint32_t (&wf)[PF][4], uint32_t woa, uint32_t wob, bool third) {
#pragma unroll
  for (int f = F0; f < F1; f++) wo_load<MODE>(wf[f], f, woa, wob, third);
}

template <bool ISV> __device__ __forceinline__ uint32_t tok_addr(uint32_t base, int tid) {
  OPQ;
  return ISV ? base + w * 2048 + (mi & 1) * 1024 + (mi >> 1) * 128 + mr * 16 : base + (mi >> 1) * 1024 + w * 256 + (mi & 1) * 128 + mr * 16;
}
template <bool ISV> __device__ __forceinline__ constexpr uint32_t tok_off(int T, int i) { return ISV ? T * 512 + i * 256 : T * 4096 + i * 2048; }
template <bool ISV, int T, bool ADD>
__device__ __forceinline__ void tok_store(const float (&x)[16], uint32_t a, const uint32_t (&p)[2][4]) {
#pragma unroll
  for (int i = 0; i < 2; i++) {
    uint32_t r[4];
#pragma unroll
    for (int k = 0; k < 4; k++)
      r[k] = !ADD ? pack_bf16(x[8 * i + 2 * k], x[8 * i + 2 * k + 1])
           : PADD ? add_bf16x2(pack_bf16(x[8 * i + 2 * k], x[8 * i + 2 * k + 1]), p[i][k])
                  : pack_bf16(x[8 * i + 2 * k] + bf_lo(p[i][k]), x[8 * i + 2 * k + 1] + bf_hi(p[i][k]));
    stsm4(a + tok_off<ISV>(T, i), r[0], r[1], r[2], r[3]);
  }
}

__device__ __forceinline__ void load_xn(const FParams& P, int seg, uint32_t self) {
  SMAP;
  mbar_expect_tx(B_XN, 49152);
  tma_load_3d(XN, &P.xn12, 0, seg * 32, 0, B_XN);
}

#define DESC_ADD(d, n) asm volatile("add.s64 %0, %0, %1;" : "+l"(d) : "n"(n))

template <bool ISV>
__device__ __forceinline__ void f_wg0(const FParams& P, const WRegs& wr, const int h, const int rank, const uint32_t hw, int tid) {
  using namespace fk;
  const uint32_t self = mapa(0, (hw >> (2 * rank)) & 3), peer0 = mapa(0, (hw >> (ISV ? 0 : 2 * (rank ^ 1))) & 3) - self,
                 peer1 = mapa(0, (hw >> (ISV ? 2 : 4)) & 3) - self;
  SMAP;
  const int tile0 = rank * 22;
  const uint32_t usel = __shfl_sync(0xffffffffu, tid, 0);
  const int warp = __shfl_sync(0xffffffffu, threadIdx.x >> 5, 0);
  constexpr int WMODE = ISV ? 0 : 2;
  const bool three = warp < 2;
  uint32_t d_h2 = D_H2V, h2ph = 1;
  tid ^= 0x5500;
#pragma unroll 1
  for (int s = -1;;) {
    uint32_t ta[ProjCfg<ISV, 0>::NTA][4][4], wsa, mba;
    const char* src = P.xch + H1_BYTES + ((s & 1) * 4 + warp) * 8192 + ((usel >> (16 + (s & 1))) & 1) * 4096;
    {
      const uint32_t ph = (s + 1) & 1;
      float x0[16], x1[16];
      uint32_t t_pub = 0;
      wg_fence();
      static_assert(Chunks<ISV>::MASK == 0x1E, "chunks 1 .. 4 are in shared memory");
      uint64_t db = P.dxn;
      auto rs_chunk = [&](int ci, bool pace) {
#pragma unroll
        for (int u = 0; u < 4; u++) {
          wgmma_rs_n32(x0, wr[ci][0][u], db, (ci | u) != 0);
          wgmma_rs_n32(x1, wr[ci][1][u], db, (ci | u) != 0);
          if (u < 3) DESC_ADD(db, 2); else DESC_ADD(db, 250);
          if (pace) { wg_commit(); wg_wait<2>(); wg_fence(); }
        }
      };
      rs_chunk(0, false);
      t_pub = clk32() - 60;
      PROF(0, 8); PROF(0, 1);
#pragma unroll
      for (int c = 1; c <= 4; c++) {
#pragma unroll
        for (int u = 0; u < 4; u++) {
          const uint64_t dx = make_desc(fk::XN + c * 4096 + u * 32, 16, 1024);
          wgmma_ss_n32_ta(x0, make_desc(fk::WS + (c - 1) * 16384 + u * 2048, 8192, 1024), dx, 1);
          wgmma_ss_n32_ta(x1, make_desc(fk::WS + (c - 1) * 16384 + 8192 + u * 2048, 8192, 1024), dx, 1);
          if (c == 4 && u == 1) { wg_commit(); wg_wait<1>(); named_bar_arrive(NB_XE, 160); wg_fence(); }
        }
        if (c == 3) wg_commit();
      }
      DESC_ADD(db, 1024);
#pragma unroll
      for (int c = 5; c < 10; c++) {
        if (c == 9) named_bar_arrive(NB_ST, 256);
        rs_chunk(c - 4, ((ISV ? PACEV : PACEQ) >> c) & 1);
      }
      wg_commit();
      wg_wait<0>();
      PROF(0, 10);
      const uint32_t tb = ISV ? (ph ? VX2 : VX) : QK;
      auto h2_issue = [&]() {
        spin_until(t_pub + (ISV ? d_h2 : D_H2));
        PROF(0, 13);
        if (elect_one()) { mbar_expect_tx(B_H2 + 8 * warp, 4096); bulk_g2s(MEMB + warp * 4096, src, 4096, B_H2 + 8 * warp); }
      };
      named_bar_sync(NB_CF, ISV ? 160 : 256);
      if ((ISV ? H2_ATV : H2_AT) == 0) h2_issue();
      const uint32_t none[2][4] = {}, tka = tok_addr<ISV>(tb, tid);
      tok_store<ISV, 0, false>(x0, tka, none);
      if ((ISV ? H2_ATV : H2_AT) == 1) h2_issue();
      tok_store<ISV, 1, false>(x1, tka, none);
      if ((ISV ? H2_ATV : H2_AT) == 2) h2_issue();
      named_bar_arrive(NB_DU, 256);
    }
    {
      OPQ;
      wsa = WS + ((mi >> 1) * 8 + mr) * 128 + (((2 * w + (mi & 1)) ^ mr) << 4);
      mba = MEMB + lane * 16;
      PIN(wsa); PIN(mba);
      {
        const uint32_t chk = MEMB + w * 4096 + lane * 32 + lg * 4, bar = B_H2 + 8 * warp;
        PROF(0, 11);
        proj_mem_prefetch<ISV, 0, 0, NPRE0>(ta, wsa);
#pragma unroll 1
        for (int tries = 0; tries < POLL_TRIES; tries++) {
          mbar_spin(bar, h2ph);
          h2ph ^= 1;
          const uint32_t mx = max(max(lds32(chk), lds32(chk + 1024)), max(lds32(chk + 2048), lds32(chk + 3072)));
          if (__all_sync(0xffffffffu, mx != EMPTY)) break;
          RETRY(1);
          if (elect_one()) { mbar_expect_tx(bar, 4096); bulk_g2s(MEMB + warp * 4096, src, 4096, bar); }
        }
      }
      PROF(0, 12);
      named_bar_arrive(NB_M1, 256);
      proj_mem_prefetch<ISV, 0, NPRE0, NTA0>(ta, wsa);
      named_bar_sync(NB_M0, 128);
    }
    s++;
    tid ^= 0x5500;
    {
      float a0[4], a1[4];
      proj_mem<ISV, 0>(wr, ta, wsa, mba, a0, a1);
      PROF(0, 2);
      uint32_t unused[4];
      proj_finish<ISV, 0>(a0, a1, peer0, peer1, self, tid, warp, unused);
      PROF(0, 3);
      if (s + 1 == cfg::NSEG) break;
      uint32_t wf[PF0][4], woa, wob;
      bool xn_ok;
      {
        OPQ;
        if (!ISV) {
          uint32_t qf[4][4], kf[2][4];
          const uint32_t qa = PT + 2048 + lane * 16, ka = QK + 4096 + w * 1024 + lane * 16;
          ldsm4t(qf[0], qa); ldsm4t(kf[0], ka); ldsm4t(qf[1], qa + 512);
          ldsm4t(qf[2], qa + 1024); ldsm4t(kf[1], ka + 512); ldsm4t(qf[3], qa + 1536);
          float c0[4], c1[4];
          mma16816z(c0, qf[0], kf[0][0], kf[0][1]);
          mma16816z(c1, qf[1], kf[0][2], kf[0][3]);
          mma16816(c0, qf[2], kf[1][0], kf[1][1]);
          mma16816(c1, qf[3], kf[1][2], kf[1][3]);
          const float s0 = (c0[0] + c0[2]) + (c1[0] + c1[2]), s1 = (c0[1] + c0[3]) + (c1[1] + c1[3]);
          send_scores(s0, s1, SP + rank * SP_SRC + t7 * SPW, peer0, peer1, B_SM, lane);
        }
        PROF(0, 4);
        woa = WO + 16384 + ((mi >> 1) * 8 + mr) * 128 + (((2 * w + (mi & 1)) ^ mr) << 4);
        wob = WO + 81920 + w * 4096 + ((mi >> 1) * 8 + mr) * 32 + (((mi & 1) ^ (mr >> 2)) << 4);
        uint32_t vf[2][2][4], vm[2][2];
        if (s == 0) mbar_spin(B_WO, 0);
        if (!ISV) mbar_spin(B_VX, s & 1);
        PROF(0, 14);
#pragma unroll
        for (int T = 0; T < 2; T++)
#pragma unroll
          for (int kk = 0; kk < 2; kk++) ldsm4(vf[T][kk], ((ISV && (s & 1)) ? VX2 : VX) + w * 2048 + (mi & 1) * 1024 + (mi >> 1) * 128 + mr * 16 + T * 512 + kk * 256);
        wo_prefetch<WMODE, 0, PF0A>(wf, woa, wob, three);
        uint32_t spa = SP + lane * SPW, vma = VM + t7 * 8, oa = OB + (mi >> 1) * 1024 + w * 256 + (mi & 1) * 128 + mr * 16;
        PIN(spa); PIN(vma); PIN(oa);
        if (ISV) {
          d_h2 = D_H2L;
          if (!__all_sync(0xffffffffu, mbar_test(B_SM, s & 1))) { d_h2 = D_H2V; mbar_spin(B_SM, s & 1); }
        } else {
          mbar_spin(B_SM, s & 1);
        }
        PROF(0, 5);
        float sc[10];
#pragma unroll
        for (int j = 0; j < 5; j++) {
          if (SPACK) {
            const uint32_t x = lds32(spa + j * 128), y = lds32(spa + SP_SRC + j * 128);
            sc[2 * j] = bf_lo(x) + bf_lo(y); sc[2 * j + 1] = bf_hi(x) + bf_hi(y);
          } else {
            const float2 x = lds64f(spa + j * 256), y = lds64f(spa + SP_SRC + j * 256);
            sc[2 * j] = x.x + y.x; sc[2 * j + 1] = x.y + y.y;
          }
        }
        const bool vm_ok = mbar_test(B_VM, s & 1);
        lds64(vm[0], vma); lds64(vm[1], vma + 1024);
        float m = fmaxf(fmaxf(fmaxf(sc[0], sc[1]), fmaxf(sc[2], sc[3])), fmaxf(fmaxf(sc[4], sc[5]), fmaxf(sc[6], sc[7])));
        m = fmaxf(m, fmaxf(sc[8], sc[9]));
        const float cs = 0.08838834764831845f * 1.4426950408889634f;
        uint32_t pb[5];
        m = fmaxf(m, __shfl_xor_sync(0xffffffffu, m, 1));
        m = fmaxf(m, __shfl_xor_sync(0xffffffffu, m, 2));
        if (ISV ? GATE_MX : GATE_Q) named_bar_arrive(NB_MX, 256);
        const float mc = -m * cs;
#pragma unroll
        for (int j = 0; j < 5; j++) pb[j] = pack_bf16(ex2_approx(fmaf(sc[2 * j], cs, mc)), ex2_approx(fmaf(sc[2 * j + 1], cs, mc)));
        PROF(0, 15);
        if (!vm_ok) { mbar_spin(B_VM, s & 1); lds64(vm[0], vma); lds64(vm[1], vma + 1024); }
        PROF(0, 6);
        float o0[4], o1[4], rs[4];
        const uint32_t ones[4] = {0x3F803F80u, 0x3F803F80u, 0x3F803F80u, 0x3F803F80u};
        mma16816z(rs, ones, pb[0], pb[1]);
        mma16816z(o0, vf[0][0], pb[0], pb[1]);
        mma16816z(o1, vf[1][0], pb[0], pb[1]);
        mma16816(rs, ones, pb[2], pb[3]);
        mma16816(o0, vf[0][1], pb[2], pb[3]);
        mma16816(o1, vf[1][1], pb[2], pb[3]);
        mma1688(rs, ones[0], ones[0], pb[4]);
        mma1688(o0, vm[0][0], vm[0][1], pb[4]);
        mma1688(o1, vm[1][0], vm[1][1], pb[4]);
        const float i0 = rcp_approx(rs[0]), i1 = rcp_approx(rs[1]);
        stsm4(oa, pack_bf16(o0[0] * i0, o0[1] * i1), pack_bf16(o0[2] * i0, o0[3] * i1),
              pack_bf16(o1[0] * i0, o1[1] * i1), pack_bf16(o1[2] * i0, o1[3] * i1));
      }
      {
        OPQ;
        named_bar_arrive(NB_O, 256);
        wo_prefetch<WMODE, PF0A, PF0>(wf, woa, wob, three);
        xn_ok = mbar_test(B_XN, (s + 1) & 1);
        char* h1p = P.xch + (tile0 + 4 + w) * 32768 + (h >> 3) * 8192 + (h & 7) * 128 + (((2 * lq + (lg & 1)) ^ (h & 7)) << 4) + (lg >> 1) * 4;
        uint32_t oba = OB + lane * 16;
        PIN(oba);
        PROF(0, 7);
        named_bar_sync(NB_O0, 128);
        const uint32_t tag = ((s >> 1) & 1) ^ 1;
        wo_phase<WMODE>(wf, woa, wob, three, oba, h1p, tid >> 8, tag);
        PROF(0, 9);
        if (!xn_ok) mbar_spin(B_XN, (s + 1) & 1);
        named_bar_sync(NB_HD, 256);
      }
    }
  }
}

template <bool ISV>
__device__ __forceinline__ void f_wg1(const FParams& P, const WRegs& wr, const int h, const int rank, const uint32_t hw, int tid) {
  using namespace fk;
  const uint32_t self = mapa(0, (hw >> (2 * rank)) & 3), peer0 = mapa(0, (hw >> (ISV ? 0 : 2 * (rank ^ 1))) & 3) - self,
                 peer1 = mapa(0, (hw >> (ISV ? 2 : 4)) & 3) - self;
  SMAP;
  const int tile0 = rank * 22;
  const uint32_t usel = __shfl_sync(0xffffffffu, tid, 0);
  const int warp = __shfl_sync(0xffffffffu, (threadIdx.x >> 5) & 3, 0);
  constexpr int WMODE = 1;
  uint32_t h1ph = 0;
  auto o_done = [&](int mb) {
    tma_store_wait_all();
    asm volatile("fence.proxy.async.global;" ::: "memory");
    asm volatile("red.relaxed.gpu.global.add.u32 [%0], 1;" ::"l"(&g_oflag[mb]) : "memory");
  };
  uint32_t vmo[4] = {0, 0, 0, 0};
  if (ISV) {
    OPQ;
    sts32(PT + (t7 >> 2) * 128 + ((5 ^ lg) << 4) + lq * 4, 0);
    sts32(PT + (t7 >> 2) * 128 + ((6 ^ lg) << 4) + lq * 4, 0);
  }
  tid ^= 0x5500;
#pragma unroll 1
  for (int s = -1;;) {
    uint32_t ta[ProjCfg<ISV, 1>::NTA][4][4], wsa, mba;
    if (s + 1 < cfg::NSEG) mbar_spin(B_XN, (s + 1) & 1);
    const uint32_t t_pub = clk32();
    auto refill = [&]() {
      if (warp == 3) {
        named_bar_sync(NB_XE, 160);
        if (elect_one()) {
          mbar_expect_tx(B_XN + 8, 16384);
          tma_load_3d(XN, &P.xn, 0, (s + 1) * 32, 12, B_XN + 8);
        }
      }
    };
    auto arm = [&]() {
      if ((tid & 255) == 160) {
        if (s == 1) st_pub32(&g_mask[3 * h + rank], 0);
        if (s + 2 < cfg::NSEG) { mbar_expect_tx(B_SM, ISV ? 2 * SP_SRC : SP_SRC); if (!ISV) mbar_expect_tx(B_VX, 8192); }
        if (!ISV && s + 1 < cfg::NSEG) mbar_expect_tx(B_VM, 2048);
        if (ISV && s >= 1 && s < cfg::NSEG) mbar_expect_tx(B_ST, 7168);
      }
      if (ISV && s < cfg::NSEG && (tid & 254) == 192) mbar_arrive_remote(((tid & 1) ? peer1 : peer0) + B_ST);
      __syncwarp();
    };
    if (ISV) {
      if (s >= 0) arm();
      if (s >= 1) {
        OPQ;
        if (warp == 0 && (s & 3) == 1 && s > 1) { if (elect_one()) o_done((s - 2) >> 2); }
        const uint32_t vb = (s & 1) ? VX : VX2;
        float x0[16], x1[16];
        wg_fence();
        wgmma_rs_n32(x0, vmo, make_desc(fk::PT + 64, 16, 1024), 0);
        wgmma_rs_n32(x1, vmo, make_desc(fk::PT + 96, 16, 1024), 0);
#pragma unroll
        for (int kk = 0; kk < 2; kk++) {
          wgmma_ss_n32(x0, make_desc0(vb + kk * 256, 128, 1024), make_desc(fk::PT + kk * 32, 16, 1024), 1);
          wgmma_ss_n32(x1, make_desc0(vb + 512 + kk * 256, 128, 1024), make_desc(fk::PT + kk * 32, 16, 1024), 1);
        }
        wg_commit();
        wg_wait<0>();
        named_bar_sync(NB_W1, 128);
        PROF(1, 4);
        const uint32_t stg = vb + (8 * (mi >> 1) + mr) * 128 + (((2 * w + (mi & 1)) ^ mr) << 4);
#pragma unroll
        for (int T = 0; T < 2; T++) {
          const float* x = T ? x1 : x0;
#pragma unroll
          for (int jj = 0; jj < 4; jj += 2)
            stsm4t(stg + T * 4096 + jj * 1024, pack_bf16(x[4 * jj], x[4 * jj + 1]), pack_bf16(x[4 * jj + 2], x[4 * jj + 3]),
                   pack_bf16(x[4 * jj + 4], x[4 * jj + 5]), pack_bf16(x[4 * jj + 6], x[4 * jj + 7]));
        }
        fence_proxy_async_smem();
        named_bar_sync(NB_W1, 128);
        PROF(1, 10);
        if (warp == 0) {
          if (elect_one()) {
            tma_store_3d(&P.o, vb, 0, (s - 1) * 32, 2 * h);
            tma_store_commit();
          }
          __syncwarp();
        }
        if (s == cfg::NSEG) break;
      }
      if (s + 1 < cfg::NSEG) refill();
      PROF(1, 11);
    } else if (s < 0) {
      named_bar_arrive(NB_CF, 256);
      refill();
    } else {
      float x[24];
      wg_fence();
#pragma unroll
      for (int k = 0; k < 4; k++) wgmma_ss_n48_tt(x, make_desc0(fk::QK + k * 256, 128, 1024), make_desc0(fk::QK + 4096 + k * 256, 128, 1024), k != 0);
      wg_commit();
      arm();
      auto send_tok = [&]() {
        if (warp < 2) {
          OPQ;
          const uint32_t d0 = peer1 + QK + rank * 3584 + lane * 8 + w * 1280, d1 = d0 + 512 + w * 512, bar = peer1 + B_ST;
          mbar_spin(B_ST, s & 1);
          const float NEG = -500000000.0f / 0.08838834764831845f;
          const bool m0 = 2 * lq > lg, m1 = 2 * lq + 1 > lg;
          st_async64f(d0, x[16] + x[20], x[17] + x[21], bar);
          st_async64f(d1, x[18] + x[22], x[19] + x[23], bar);
          st_async64f(d1 + 256, x[2], x[3], bar);
          if (warp == 0) {
            st_async64f(d0 + 256, m0 ? NEG : x[0], m1 ? NEG : x[1], bar);
            st_async64f(d1 + 512, m0 ? NEG : x[6], m1 ? NEG : x[7], bar);
          } else {
            st_async64f(d0 + 256, x[0], x[1], bar);
            st_async64f(d1 + 512, x[6], x[7], bar);
            st_async64f(d0 + 512, x[4], x[5], bar);
            st_async64f(d0 + 768, m0 ? NEG : x[8], m1 ? NEG : x[9], bar);
            st_async64f(d1 + 768, x[10], x[11], bar);
            st_async64f(d1 + 1024, m0 ? NEG : x[14], m1 ? NEG : x[15], bar);
          }
        }
        PROF(1, 4);
      };
      const bool fin = s + 1 == cfg::NSEG;
      OPQ;
      const int j = 2 * h + rank;
      const char* src = P.xch + j * 32768 + warp * 8192 + (((usel >> 14) & 2) + (s & 1)) * 2048;
      char* dst = P.xch + H1_BYTES + (j >> 4) * 8192 + (lq >> 1) * 4096 + (j & 15) * 256 + (lq & 1) * 128 + (2 * w + (lg & 1)) * 16 + (lg >> 1) * 4;
      const uint32_t chk = VX + mi * 2048 + mr * 128 + (w ^ (mr >> 1)) * 32 + ((lane & 1) + 2 * mi) * 4;
      const uint32_t tmask = (s >> 1) & 1;
      if (!fin) {
        spin_until(t_pub + D_H1);
        if (elect_one()) { mbar_expect_tx(B_H1, 2048); bulk_g2s(VX + warp * 2048, src, 2048, B_H1); }
      }
      __syncwarp();
      wg_wait<0>();
      PROF(1, 6);
      send_tok();
      if (fin) { mbar_spin(B_VM, s & 1); break; }
      named_bar_arrive(NB_CF, 256);
      if (REFILL_EARLY) refill();
#pragma unroll 1
      for (int tries = 0; tries < POLL_TRIES; tries++) {
        float d0[4], d1[4], d2[4], d3[4];
        mbar_spin(B_H1, h1ph);
        h1ph ^= 1;
        PROF(1, 10);
        const uint32_t t0 = lds32(chk), t1 = lds32(chk + 1024);
        wg_fence();
        const uint64_t ones = (uint64_t)(fk::ONES >> 4);
        wgmma_ss_n8_ta(d0, make_desc(fk::VX, 8192, 2048), ones, 0);
        wgmma_ss_n8_ta(d1, make_desc(fk::VX + 1024, 8192, 2048), ones, 0);
        wgmma_ss_n8_ta(d2, make_desc(fk::VX + 4096, 8192, 2048), ones, 0);
        wgmma_ss_n8_ta(d3, make_desc(fk::VX + 5120, 8192, 2048), ones, 0);
        wg_commit();
        uint32_t tt;
        asm volatile("lop3.b32 %0, %1, %2, %3, 0x42;" : "=r"(tt) : "r"(t0), "r"(t1), "r"(tmask) : "memory");
        uint32_t ok;
        named_bar_and(NB_W1, 128, tt & 1, ok);
        if (!ok) { if (elect_one()) { mbar_expect_tx(B_H1, 2048); bulk_g2s(VX + warp * 2048, src, 2048, B_H1); } }
        wg_wait<0>();
        if (ok) {
          st_pub32(dst + (s & 1) * 32768, (lq & 1) ? pack_bf16(d1[0] + d3[0], d1[2] + d3[2]) : pack_bf16(d0[0] + d2[0], d0[2] + d2[2]));
          PROF(1, 12);
          st_pub32(dst + ((s & 1) ^ 1) * 32768, EMPTY);
          break;
        }
        RETRY(0);
      }
      named_bar_sync(NB_W1, 128);
      if ((tid & 255) == 192) mbar_arrive_remote(peer1 + B_PF);
      __syncwarp();
      if (!REFILL_EARLY) refill();
      PROF(1, 11);
    }
    if (!ISV || s + 1 < cfg::NSEG) {
      const uint32_t ph = (s + 1) & 1;
      float x0[16], x1[16];
      uint64_t db = P.dxn + 10 * 256;
      named_bar_sync(NB_ST, 256);
      wg_fence();
#pragma unroll
      for (int c = 0; c < 6; c++) {
        if (c == 2) { PROF(1, 0); mbar_spin(B_XN + 8, ph); PROF(1, 15); wg_fence(); }
        if (ISV && c == CF_AT) {
          if (warp == 0) {
            if (elect_one()) tma_store_wait_read();
            __syncwarp();
            named_bar_arrive(NB_CF, 160);
          }
          wg_fence();
        }
#pragma unroll
        for (int u = 0; u < 4; u++) {
          wgmma_rs_n32(x0, wr[c][0][u], db, (c | u) != 0);
          wgmma_rs_n32(x1, wr[c][1][u], db, (c | u) != 0);
          if (u < 3) DESC_ADD(db, 2); else if (c == 1) DESC_ADD(db, 250 - 12 * 256); else DESC_ADD(db, 250);
        }
      }
      wg_commit();
      OPQ;
      const uint32_t tb = ISV ? (ph ? VX2 : VX) : QK, tka = tok_addr<ISV>(tb, tid);
      uint32_t p0[2][4], p1[2][4];
      named_bar_sync(NB_DU, 256);
      ldsm4(p1[0], tka + tok_off<ISV>(1, 0)); ldsm4(p1[1], tka + tok_off<ISV>(1, 1));
      ldsm4(p0[0], tka + tok_off<ISV>(0, 0)); ldsm4(p0[1], tka + tok_off<ISV>(0, 1));
      if (ISV && s >= 0) mbar_spin(B_PF, s & 1);
      wg_wait<0>();
      PROF(1, 13);
      tok_store<ISV, 1, true>(x1, tka, p1);
      tok_store<ISV, 0, true>(x0, tka, p0);
      if (ISV && s + 2 < cfg::NSEG) {
        fence_proxy_async_smem();
        __syncwarp();
        if (elect_one()) {
          bulk_s2s(peer0 + VX + warp * 2048, tb + warp * 2048, 2048, peer0 + B_VX);
          bulk_s2s(peer1 + VX + warp * 2048, tb + warp * 2048, 2048, peer1 + B_VX);
        }
      }
      wsa = WS + ((mi >> 1) * 8 + mr) * 128 + (((2 * w + (mi & 1)) ^ mr) << 4);
      mba = MEMB + lane * 16;
      PIN(wsa); PIN(mba);
      proj_mem_prefetch<ISV, 1, 0, NTA1>(ta, wsa);
      PROF(1, 14);
      named_bar_sync(NB_M1, 256);
      s++;
      PROF(1, 1);
      float a0[4], a1[4];
      proj_mem<ISV, 1>(wr, ta, wsa, mba, a0, a1);
      PROF(1, 2);
      proj_finish<ISV, 1>(a0, a1, peer0, peer1, self, tid, warp, vmo);
      PROF(1, 3);
    } else {
      OPQ;
      mbar_spin(B_VM, s & 1);
      lds64(vmo, VM + t7 * 8); lds64(vmo + 2, VM + 1024 + t7 * 8);
      s++;
    }
    tid ^= 0x5500;
    const bool last = s + 1 >= cfg::NSEG;
    constexpr int PFW = ISV ? PF1V : PF1;
    uint32_t wf[PFW][4], woa;
    if (ISV) {
      OPQ;
      woa = WO + ((mi >> 1) * 8 + mr) * 128 + (((2 * w + (mi & 1)) ^ mr) << 4);
      if (s >= 1) {
        const uint32_t sa = QK + ((w * (w + 3)) >> 1) * 256 + lane * 8;
        mbar_spin(B_ST, (s - 1) & 1);
        float sc[10];
        {
          const float NEG = -1000000000.0f / 0.08838834764831845f;
          float2 x[5], y[5];
#pragma unroll
          for (int b = 0; b < 5; b++) {
            x[b] = b < 2 ? lds64f(sa + b * 256) : lds64f_if(sa + b * 256, b <= w + 1, NEG);
            y[b] = b < 2 ? lds64f(sa + 3584 + b * 256) : lds64f_if(sa + 3584 + b * 256, b <= w + 1, 0.f);
          }
#pragma unroll
          for (int b = 0; b < 5; b++) { sc[2 * b] = x[b].x + y[b].x; sc[2 * b + 1] = x[b].y + y[b].y; }
        }
        float m = fmaxf(fmaxf(fmaxf(sc[0], sc[1]), fmaxf(sc[2], sc[3])), fmaxf(fmaxf(sc[4], sc[5]), fmaxf(sc[6], sc[7])));
        m = fmaxf(m, fmaxf(sc[8], sc[9]));
        m = fmaxf(m, __shfl_xor_sync(0xffffffffu, m, 1));
        m = fmaxf(m, __shfl_xor_sync(0xffffffffu, m, 2));
        const float cs = 0.08838834764831845f * 1.4426950408889634f;
#pragma unroll
        for (int i = 0; i < 10; i++) sc[i] = ex2_approx((sc[i] - m) * cs);
        float sum = ((sc[0] + sc[1]) + (sc[2] + sc[3])) + ((sc[4] + sc[5]) + (sc[6] + sc[7])) + (sc[8] + sc[9]);
        sum += __shfl_xor_sync(0xffffffffu, sum, 1);
        sum += __shfl_xor_sync(0xffffffffu, sum, 2);
        const float inv = rcp_approx(sum);
        const uint32_t pa = PT + (w * 8 + mr) * 128, pm = pack_bf16(sc[0] * inv, sc[1] * inv);
        stsm4(pa + ((mi ^ mr) << 4), pack_bf16(sc[2] * inv, sc[3] * inv), pack_bf16(sc[4] * inv, sc[5] * inv),
              pack_bf16(sc[6] * inv, sc[7] * inv), pack_bf16(sc[8] * inv, sc[9] * inv));
        asm volatile("stmatrix.sync.aligned.m8n8.x2.shared.b16 [%0], {%1,%1};" ::"r"(pa + ((((mi & 1) ? 7 : 4) ^ mr) << 4)), "r"(pm) : "memory");
      }
      if (warp == 3 && !last) {
        mbar_spin(B_VM, s & 1);
        if (elect_one()) load_xn(P, s + 1, self);
      }
      PROF(1, 5);
    } else {
      if (warp == 0) {
        OPQ;
        uint32_t kf[4][4], qf[4][4];
        float c0[4], c1[4], d0[4], d1[4];
        const uint32_t ka = PT + (mi >> 1) * 1024 + (mi & 1) * 128 + mr * 16;
#pragma unroll
        for (int k = 0; k < 4; k++) { ldsm4t(qf[k], PT + 2048 + k * 512 + lane * 16); ldsm4t(kf[k], ka + k * 256); }
        mma16816z(c0, qf[0], kf[0][0], kf[0][1]); mma16816z(c1, qf[0], kf[0][2], kf[0][3]);
        mma16816z(d0, qf[1], kf[1][0], kf[1][1]); mma16816z(d1, qf[1], kf[1][2], kf[1][3]);
        mma16816(c0, qf[2], kf[2][0], kf[2][1]); mma16816(c1, qf[2], kf[2][2], kf[2][3]);
        mma16816(d0, qf[3], kf[3][0], kf[3][1]); mma16816(d1, qf[3], kf[3][2], kf[3][3]);
        const float s0 = ((c0[0] + c0[2]) + (c1[0] + c1[2])) + ((d0[0] + d0[2]) + (d1[0] + d1[2]));
        const float s1 = ((c0[1] + c0[3]) + (c1[1] + c1[3])) + ((d0[1] + d0[3]) + (d1[1] + d1[3]));
        if (!last) send_scores(s0, s1, SP + rank * SP_SRC + (128 + lane) * SPW, peer0, peer1, B_SM, lane);
        PROF(1, 5);
      } else {
        const uint32_t t_c = clk32() + lds32(B_XN) * 0;
        if (warp == 3 && !last) { if (elect_one()) load_xn(P, s + 1, self); }
        spin_until(t_c + D_ST);
      }
      OPQ;
      woa = WO + ((mi >> 1) * 8 + mr) * 128 + (((2 * w + (mi & 1)) ^ mr) << 4);
    }
    if (!last) {
      OPQ;
      uint32_t oba = OB + lane * 16;
      if (s == 0) mbar_spin(B_WO, 0);
      if (!ISV) wo_prefetch<WMODE, 0, PF1Q>(wf, woa, 0, true);
      if (ISV ? GATE_MX : GATE_Q) named_bar_sync(NB_MX, 256);
      wo_prefetch<WMODE, ISV ? 0 : PF1Q, PFW>(wf, woa, 0, true);
      char* h1p = P.xch + (tile0 + w) * 32768 + (h >> 3) * 8192 + (h & 7) * 128 + (((2 * lq + (lg & 1)) ^ (h & 7)) << 4) + (lg >> 1) * 4;
      fence_proxy_async_smem();
      PROF(1, 7);
      named_bar_sync(NB_O, 256);
      PROF(1, 8);
      wo_phase<WMODE>(wf, woa, 0, true, oba, h1p, tid >> 8, ((s >> 1) & 1) ^ 1);
      PROF(1, 9);
      named_bar_sync(NB_HD, 256);
    } else {
      fence_proxy_async_smem();
      named_bar_sync(NB_W1, 128);
    }
  }
  if (ISV && warp == 0) { if (elect_one()) o_done(15); }
}

template <bool ISV, int WG>
__device__ __forceinline__ void f_main(const FParams& P, const int h, const int rank, const uint32_t hw) {
  using namespace fk;
  const uint32_t self = mapa(0, (hw >> (2 * rank)) & 3);
  SMAP;
  const int tid = __shfl_sync(0xffffffffu, threadIdx.x, threadIdx.x & 31);
  const int tile0 = rank * 22, ntile = ISV ? 20 : 22;
  const CUtensorMap* m0 = ISV ? &P.wv : &P.wq;
  const CUtensorMap* m1 = ISV ? &P.wv : &P.wk;
  const int col0 = h * 128 + (ISV ? 0 : 64 * rank), col1 = h * 128 + (ISV ? 64 : 64 * rank);
  WRegs wr;
  uint32_t sel = 0;
  {
    OPQ;
    const uint32_t a = SM0 + WG * 16384 + ((mi >> 1) * 8 + mr) * 128 + (((2 * w + (mi & 1)) ^ mr) << 4);
    uint2 mi0 = make_uint2(0, 0);
    if (!ISV && WG == 1) mi0 = *reinterpret_cast<const uint2*>(P.mem0 + ((lane >> 1) & 7) * cfg::D + (2 * h + rank) * 16 + (lane >> 4) * 8 + (lane & 1) * 4);
#pragma unroll
    for (int i = 0; i < 6; i++) {
      if (i == MASK_AT && WG == 1 && w == 1) {
        uint4 v;
#pragma unroll 1
        for (int tries = 0; tries < POLL_TRIES; tries++) {
          asm volatile("ld.acquire.gpu.global.v4.u32 {%0,%1,%2,%3}, [%4];" : "=r"(v.x), "=r"(v.y), "=r"(v.z), "=r"(v.w)
                       : "l"(&g_mask[4 * min(lane, 23)]) : "memory");
          if (__all_sync(0xffffffffu, v.x & v.y & v.z & v.w & 0x100)) break;
          __nanosleep(100);
        }
        sts128(OB + lane * 16, v.x, v.y, v.z, v.w);
      }
      mbar_wait(B_PB + 8 * i, 0);
      PRO(8 + i);
#pragma unroll
      for (int T = 0; T < 2; T++)
#pragma unroll
        for (int u = 0; u < 4; u++) ldsm4t(wr[i][T][u], a + i * 32768 + T * 8192 + u * 2048);
      named_bar_sync(NB_C, 256);
      if (WG == 1 && w == (i & 3)) {
        if (elect_one()) {
          if (i <= 2 && i + PRE_G < 6) {
#pragma unroll 1
            for (int n = 2 * (i + PRE_G); n < (i == 2 ? 12 : 2 * (i + PRE_G) + 2); n++) {
              const int ii = n >> 1, row = Chunks<ISV>::rf(n & 1, ii) * 64;
              if (!(n & 1)) mbar_expect_tx(B_PB + 8 * ii, 32768);
              tma_load_2d(SM0 + n * 16384, m0, col0, row, B_PB + 8 * ii);
              tma_load_2d(SM0 + n * 16384 + 8192, m1, col1, row, B_PB + 8 * ii);
            }
          }
          if (i == 3 || i == 4) {
            const int p0 = i == 3 ? 0 : 5, p1 = i == 3 ? 5 : 8;
            mbar_expect_tx(B_W, (p1 - p0) * 8192);
#pragma unroll 1
            for (int p = p0; p < p1; p++) tma_load_2d(WS + p * 8192, (p & 1) ? m1 : m0, (p & 1) ? col1 : col0, Chunks<ISV>::sm(p >> 1) * 64, B_W);
          }
          if (i == 5) {
            asm volatile("fence.proxy.async.global;" ::: "memory");
            load_xn(P, 0, self);
          }
          if (i == WO_AT) {
            mbar_expect_tx(B_WO, ntile * 4096);
#pragma unroll 1
            for (int t = 0; t < 5; t++) tma_load_2d(WO + t * 16384, &P.wo, tile0 * 16 + t * 64, h * 128, B_WO);
            if (!ISV) {
              tma_load_2d(WO + 81920, &P.wo16, tile0 * 16 + 320, h * 128, B_WO);
              tma_load_2d(WO + 86016, &P.wo16, tile0 * 16 + 336, h * 128, B_WO);
            }
          }
        }
      }
    }
    PROF2(1);
    if (!ISV && WG == 1 && w < 2) st_pub64(P.xch + H1_BYTES + 32768 + (h >> 3) * 8192 + w * 4096 + ((2 * h + rank) & 15) * 256 + lane * 8, mi0.x, mi0.y);
    if (blockIdx.x == 2 && tid == 160) { __threadfence(); st_pub128(g_lnok, 0x100); }
#pragma unroll
    for (int i = 0; i < 3; i++) {
      const int t = min(tile0 + 8 * i + w + (WG ? 0 : 4), 63);
      sel |= ((lds32(OB + ((t >> 1) * 3 + (t & 1)) * 4) >> (h >> 3)) & 1) << (2 * i + 1);
    }
    const uint32_t own = lds32(OB + (3 * h + rank) * 4) >> w, m2 = lds32(OB + (3 * h + 2) * 4) >> w;
    sel |= (own & 1) << 7 | (m2 & 1) << 8 | (m2 & 16) << 5;
    sel |= (((((lg ^ h) & 1) << 2) | (lg >> 1)) == (h & 1) + 2 * (h >> 3)) << 10;
  }
  asm volatile("barrier.cluster.wait.aligned;" ::: "memory");
  PRO(14);
  mbar_wait(B_W, 0);
  mbar_wait(B_XN, 0);
  PRO(15);
  PROF2(4);
  GTSYNC(0);
  PROF2(2);
  KT_END(8);
  if (WG == 0) f_wg0<ISV>(P, wr, h, rank, hw, tid | sel << 8); else f_wg1<ISV>(P, wr, h, rank, hw, tid | sel << 8);
}

__device__ __forceinline__ void f_tail(const FParams& P, const int h, const uint32_t rank, const bool isv) {
  using namespace fk;
  const uint32_t self = mapa(0, rank), base = self + SM0;
  const uint32_t FULL = self + SP, EMPT = FULL + 32, NOG = FULL + 64;
  const int tid = threadIdx.x, lane = tid & 31, wv = __shfl_sync(0xffffffffu, tid >> 5, 0), wg = wv >> 2;
  const int kq = h & 7, nt = h >> 3, mb = TAIL_MB0 + rank;
  auto a_off = [](uint32_t st) { return (0x98685800u >> (8 * st) & 255) * 1024; };
  auto b_off = [](uint32_t st) { return (0xA8783010u >> (8 * st) & 255) * 1024; };
  static_assert(VX2 - SM0 == 80 * 1024 && VX - SM0 == 200 * 1024, "stage layout");
  auto load_b = [&](int kb) {
    const uint32_t sb = base + b_off(kb & 3), full = FULL + 8 * (kb & 3);
    mbar_expect_tx(full, 49152);
    tma_load_2d_mc(sb + rank * 8192, &P.tb, nt * 256 + ((rank + (kq >> 1)) & 3) * 64, (kq * 8 + kb) * 64, full, 7);
    if (kb % 3 == rank) tma_load_2d_mc(sb + 3 * 8192, &P.tb, nt * 256 + ((3 + (kq >> 1)) & 3) * 64, (kq * 8 + kb) * 64, full, 7);
  };
  auto load_a = [&](int kb) { tma_load_2d(base + a_off(kb & 3), &P.ta, (kq * 8 + kb) * 64, mb * 128, FULL + 8 * (kb & 3)); };
  TL(0);
  TL2(128, 10); TL2(160, 11);
  if (wv == 0) {
    if (elect_one()) {
      prefetch_tmap(&P.tb); prefetch_tmap(&P.ta);
      if (isv) mbar_spin(self + B_VM, (cfg::NSEG - 1) & 1);
      for (int i = 0; i < 4; i++) { mbar_init(FULL + 8 * i, 1); mbar_init(EMPT + 8 * i, 24); }
      fence_barrier_init();
      mbar_arrive_cluster(self + B_W, rank == 0 ? 1 : 0);
      mbar_arrive_cluster(self + B_W, rank == 2 ? 1 : 2);
      mbar_spin(self + B_W, 1);
#pragma unroll 1
      for (int kb = 0; kb < 4; kb++) load_b(kb);
      TL2(0, 12);
      wait_count(&g_oflag[mb], 32);
      asm volatile("fence.proxy.async.global;" ::: "memory");
      TL2(0, 13);
#pragma unroll 1
      for (int kb = 0; kb < 4; kb++) load_a(kb);
      TL2(0, 14);
    }
  } else if (wv == 1) {
    if (lane == 0) {
      const bool ng = ld_strong4(&g_next) == 0;
      sts32(NOG, ng);
      if (ng) g_tfix[blockIdx.x] = 1; else wait_count(&g_cnt[3][mb], GATE_CNT);
    }
  } else if (wg == 0) {
#pragma unroll 2
    for (int i = tid - 64; i < 4096; i += 64) st_pub128(&g_tpart[blockIdx.x][0][0][0] + i, EMPTY);
  }
  float acc[128];
  __syncthreads();
  KT_START(7);
  const bool nog = lds32(NOG);
  if (nog) TL(15); else TL(15);
  const size_t off = (size_t)(mb * 128 + wv * 16 + (lane >> 2)) * cfg::D + nt * 256 + kq * 32 + (lane & 3) * 2;
  uint32_t x[8], g[8];
#pragma unroll
  for (int i = 0; i < 8; i++) {
    x[i] = __ldcg(reinterpret_cast<const uint32_t*>(P.x + off + (i & 1) * 8 * cfg::D + (i >> 1) * 8));
    g[i] = __ldcg(reinterpret_cast<const uint32_t*>(P.gate + off + (i & 1) * 8 * cfg::D + (i >> 1) * 8));
  }
#pragma unroll 1
  for (int kb = 0; kb < 8; kb++) {
    const uint32_t st = kb & 3, sa = base + a_off(st) + wg * 8192, sb = base + b_off(st);
    mbar_spin(FULL + 8 * st, kb >> 2);
    if (kb == 0) TL(2);
    if (kb == 4) TL(3);
    wg_fence();
#pragma unroll
    for (int k = 0; k < 4; k++) {
      wgmma_ss_n256_tb(acc, make_desc(sa + k * 32, 16, 1024), make_desc(sb + k * 2048, 8192, 1024), (kb | k) != 0);
      if (k == 0) {
        wg_commit();
        wg_wait<1>();
        if (kb > 0 && kb <= 4 && lane < 3) mbar_arrive_cluster(EMPT + 8 * (kb - 1), lane);
        wg_fence();
      }
    }
    wg_commit();
    if (kb >= 2 && kb < 6 && wv == ((kb & 1) << 2)) {
      if (elect_one()) {
        mbar_spin(EMPT + 8 * (kb - 2), 0);
        load_b(kb + 2);
        load_a(kb + 2);
      }
      __syncwarp();
    }
  }
  wg_wait<0>();
  TL(5);
#pragma unroll
  for (int j = 0; j < 8; j++) {
    uint4* dst = &g_tpart[((h & ~7) + ((j + (kq & 6)) & 7)) * 3 + rank][kq][0][tid];
    if (j >= 2 || j != (kq & 1)) {
#pragma unroll
      for (int i = 0; i < 2; i++) {
        const float* a = &acc[16 * j + 8 * i];
        asm volatile("st.relaxed.gpu.global.v4.u32 [%0], {%1,%2,%3,%4};" ::"l"(dst + i * 256), "r"(pack_bf16(a[0], a[1])),
                     "r"(pack_bf16(a[2], a[3])), "r"(pack_bf16(a[4], a[5])), "r"(pack_bf16(a[6], a[7])) : "memory");
      }
    }
  }
#pragma unroll
  for (int i = 0; i < 16; i++) acc[i] = (kq & 1) ? acc[16 + i] : acc[i];
  TL(6);
#pragma unroll 1
  for (int j = 0, tries = 0; j < 8 && tries < POLL_TRIES; tries++) {
    uint4 pt[8];
    uint32_t mx = 0;
#pragma unroll
    for (int i = 0; i < 8; i++) {
      pt[i] = make_uint4(0, 0, 0, 0);
      if (j + (i >> 1) != kq) pt[i] = ld_strong16(&g_tpart[blockIdx.x][j][0][tid] + i * 256);
    }
#pragma unroll
    for (int i = 0; i < 8; i++) mx = max(mx, umax4(pt[i]));
    if (!__all_sync(0xffffffffu, mx != EMPTY)) continue;
#pragma unroll
    for (int i = 0; i < 32; i++) { acc[2 * (i & 7)] += bf_lo((&pt[0].x)[i]); acc[2 * (i & 7) + 1] += bf_hi((&pt[0].x)[i]); }
    j += 4;
  }
  TL(7);
#pragma unroll
  for (int i = 0; i < 8; i++) {
    const uint32_t sv = pack_bf16(acc[2 * i], acc[2 * i + 1]);
    *reinterpret_cast<uint32_t*>(P.out + off + (i & 1) * 8 * cfg::D + (i >> 1) * 8) = nog ? sv : add_bf16x2(x[i], mul_bf16x2(sv, g[i]));
  }
  TL(9);
  KT_END(7);
}

__global__ void __launch_bounds__(256, 1) f_kernel(const __grid_constant__ FParams P) {
  using namespace fk;
  extern __shared__ __align__(1024) uint8_t smem_f[];
  uint32_t crank, rank, hw;
  asm("mov.u32 %0, %%cluster_ctarank;" : "=r"(crank));
  const int h = blockIdx.x / 3;
  if (smem_u32(smem_f) != mapa(0, crank) + SM0) return;
  PROF2(0);
  KT_START(1);
  KT_START(0);
  {
    const uint32_t self = mapa(0, crank);
    SMAP;
    const int tid = threadIdx.x, lane = tid & 31, wv = __shfl_sync(0xffffffffu, tid >> 5, 0);
    PRO(0);
    if (wv == 0) {
      uint32_t sm;
      asm("mov.u32 %0, %%smid;" : "=r"(sm));
      sts32(PROBE + 96, sm >> 1);
      asm volatile("fence.release.sync_restrict::shared::cta.cluster;" ::: "memory");
    }
    asm volatile("barrier.cluster.arrive.relaxed.aligned;" ::: "memory");
    if (wv == 7) {
      if (blockIdx.x == 2) {
#pragma unroll
        for (int i = 0; i < 4; i++) { (&g_cnt[0][0])[32 * i + lane] = 0; if (i < 3) g_tfix[32 * i + lane] = 0; }
        if (lane < 16) g_oflag[lane] = 0;
        if (lane == 0) { g_next = 0; g_lnok[0] = 0; }
        __threadfence();
        __syncwarp();
      }
      pdl_launch_dependents();
    }
    const int row0 = blockIdx.x * 8 + wv;
    const bool third = row0 + 1536 < cfg::S;
    uint32_t cur[1][16] = {}, raw[3][16];
    load_row16(raw[0], P.x + (size_t)row0 * cfg::D, lane);
    load_row16(raw[1], P.x + (size_t)(row0 + 768) * cfg::D, lane);
    load_row16(raw[2], P.x + (size_t)(row0 + (third ? 1536 : 0)) * cfg::D, lane);
    {
      uint32_t tpc;
      asm volatile("barrier.cluster.wait.aligned;" ::: "memory");
      asm volatile("ld.shared::cluster.u32 %0, [%1];" : "=r"(tpc) : "r"(mapa(PROBE + 96, lane % 3)) : "memory");
      const uint32_t t0 = __shfl_sync(0xffffffffu, tpc, 0), t1 = __shfl_sync(0xffffffffu, tpc, 1), t2 = __shfl_sync(0xffffffffu, tpc, 2);
      hw = t1 == t2 ? 0x09 : t0 == t2 ? 0x18 : 0x24;
      rank = (hw & 3) == crank ? 0 : ((hw >> 2) & 3) == crank ? 1 : 2;
    }
    const bool isv = rank == 2;
    const CUtensorMap* m0 = isv ? &P.wv : &P.wq;
    const CUtensorMap* m1 = isv ? &P.wv : &P.wk;
    const int col0 = h * 128 + (isv ? 0 : 64 * rank), col1 = h * 128 + (isv ? 64 : 64 * rank);
    auto req_weights = [&](int n0, int n1) {
#pragma unroll 1
        for (int n = n0; n < n1; n++) {
          const int i = n >> 1, g = n & 1, row = (isv ? Chunks<true>::rf(g, i) : Chunks<false>::rf(g, i)) * 64;
          if (!g) mbar_expect_tx(B_PB + 8 * i, 32768);
          tma_load_2d(SM0 + n * 16384, m0, col0, row, B_PB + 8 * i);
          tma_load_2d(SM0 + n * 16384 + 8192, m1, col1, row, B_PB + 8 * i);
        }
    };
    if (wv == 0) {
      if (elect_one()) {
        for (int i = 0; i < 2; i++) mbar_init(B_XN + 8 * i, 1);
        mbar_init(B_H1, 4);
        mbar_init(B_SM, isv ? 1 : 6);
        mbar_init(B_VM, isv ? 8 : 1);
        mbar_init(B_VX, 1);
        mbar_init(B_ST, 1);
        mbar_init(B_PF, 2);
        for (int i = 0; i < 6; i++) mbar_init(B_PB + 8 * i, 1);
        mbar_init(B_W, 2);
        mbar_init(B_WO, 1);
        fence_barrier_init();
        if (PRE_A) req_weights(0, 2 * PRE_A);
        mbar_expect_tx(B_SM, isv ? 2 * SP_SRC : SP_SRC);
        if (isv) mbar_expect_tx(B_ST, 7168);
        else { mbar_expect_tx(B_VM, 2048); mbar_expect_tx(B_VX, 8192); }
      }
    }
    const int j = 2 * h + rank;
    const bool dry = LN_DRY && !isv && wv == 6;
    if (dry) sts64(PROBE + wv * 8, 0x7FFFFFFF, 0x7FFFFFFF);
    if (lane == 0 && !dry) {
      const uint2 b = probe_pair(P.xch + (isv ? H1_BYTES + wv * 8192 + h * 128 : j * 32768 + (wv & 3) * 8192 + (wv >> 2) * 128),
                                 isv ? EMPTY : 0, PROBE + 64, P.nprobe);
      sts64(PROBE + wv * 8, b.x, b.y);
    }
    uint32_t mask = 0;
#pragma unroll 1
    for (int it = -1; it < (third ? 3 : 2); it++) {
      if (it >= 0 || dry) {
        ln_regs<1>(cur);
        if (it >= 0) store_row16(cur[0], P.xn_ptr + (size_t)(row0 + it * 768) * cfg::D, lane);
      }
      if (it == 0) PRO(4);
      if (it < 0) {
    PROF2(3);
    PRO(1);
    __syncwarp();
    if (wv == 0) {
      asm volatile("{\n.reg .pred p;\nsetp.eq.u32 p, %0, %1;\n@p st.shared.u32 [%2], %0;\n}" ::"r"(raw[2][15]), "r"(raw[0][0] ^ raw[1][15]), "r"(PROBE + 64) : "memory");
      if (elect_one()) {
        req_weights(2 * PRE_A, 2 * PRE_G);
      }
    }
    __syncthreads();
    PRO(2);
    asm volatile("barrier.cluster.arrive.relaxed.aligned;" ::: "memory");
    PRO(3);
    if (wv == 2) sts32(self + ONES + lane * 4, 0x3F803F80u);
    uint32_t pb[2], pc[2];
    lds64(pb, PROBE + (lane & 7) * 8);
    lds64(pc, PROBE + ((lane & 7) ^ 4) * 8);
    mask = __ballot_sync(0xffffffffu, isv ? pb[1] < pb[0] : min(pb[1], pc[1]) < min(pb[0], pc[0])) & (isv ? 255 : 15);
    if (!isv) {
#pragma unroll
      for (int i = 0; i < 4; i++) st_pub128(P.xch + j * 32768 + i * 8192 + ((mask >> i) & 1) * 4096 + tid * 16, 0);
      if (wv < 4) st_pub64(P.xch + H1_BYTES + (wv >> 1) * 32768 + (j >> 4) * 8192 + (wv & 1) * 4096 + (j & 15) * 256 + lane * 8, EMPTY, EMPTY);
    }
      }
#pragma unroll
      for (int i = 0; i < 16; i++) { cur[0][i] = raw[0][i]; raw[0][i] = raw[1][i]; raw[1][i] = raw[2][i]; }
    }
    PRO(5);
    __syncthreads();
    PRO(6);
    if (tid == 64) {
      __threadfence();
      PRO(7);
      st_pub32(&g_mask[3 * h + rank], 0x100 | mask);
    }
    KT_END(0);
    __syncwarp();
  }
  const int wg = __shfl_sync(0xffffffffu, threadIdx.x >> 7, 0);
  if (rank == 2) { if (wg == 0) f_main<true, 0>(P, h, 2, hw); else f_main<true, 1>(P, h, 2, hw); }
  else { if (wg == 0) f_main<false, 0>(P, h, rank, hw); else f_main<false, 1>(P, h, rank, hw); }
  PROF2(5);
  KT_END(1);
  __syncwarp();
  f_tail(P, h, crank, rank == 2);
}

#define GCL 1
#define G_PF 3
#define G_PFM 2
#define G_LATE 0
namespace gk {
enum { T_B1 = 0, T_B2 = 1, T_B3 = 2, T_B4 = 3, T_O = 4, T_LN = 5, T_LN0 = 6, T_END = 7 };
constexpr int NST = 3, STAGE = 49152, MAXITEMS = 512, NEW = 3;
constexpr uint32_t OUTB = NST * STAGE, BARS = OUTB + 65536;
constexpr uint32_t B_FULL = BARS, B_EMPTY = BARS + 32, B_ITEM = BARS + 64, B_FILL = BARS + 128, B_FREE = BARS + 160, B_LN = BARS + 176, ITEMS = BARS + 192;
constexpr int SMEM = BARS + 256;
static_assert(GATE_CNT == 4 * NEW && T_B4 == 3, "gate counter");
}
struct GParams {
  CUtensorMap a[5], b[5];
  bf16* c[5];
  const bf16* r[5];
  bf16 *x1n, *xn2;
  const bf16* w1;
  int nitems, lnpos;
  uint16_t items[gk::MAXITEMS];
};
#define ILOG(i)

__device__ __forceinline__ void tma_load_3d_mc(uint32_t dst, const CUtensorMap* map, int x, int y, int z, uint32_t bar) {
  asm volatile("cp.async.bulk.tensor.3d.shared::cluster.global.mbarrier::complete_tx::bytes.multicast::cluster "
               "[%0], [%1, {%3, %4, %5}], [%2], %6;"
               ::"r"(dst), "l"(map), "r"(bar), "r"(x), "r"(y), "r"(z), "h"((uint16_t)3) : "memory");
}
__device__ __forceinline__ float tanh_approx(float x) { float y; asm("tanh.approx.f32 %0, %1;" : "=f"(y) : "f"(x)); return y; }
__global__ void __launch_bounds__(384, 1) g_kernel(const __grid_constant__ GParams P) {
  using namespace gk;
  extern __shared__ __align__(1024) uint8_t smem_g[];
  const uint32_t base = smem_u32(smem_g);
  const int tid = threadIdx.x, warp = __shfl_sync(0xffffffffu, tid >> 5, 0), lane = tid & 31;
  const int rank = blockIdx.x % GCL;
  KT_START(2);
  if (tid == 0) {
    for (int s = 0; s < NST; s++) { mbar_init(base + B_FULL + 8 * s, 1); mbar_init(base + B_EMPTY + 8 * s, 8 * GCL); }
    for (int s = 0; s < 8; s++) mbar_init(base + B_ITEM + 8 * s, 1);
    for (int s = 0; s < 2; s++) { mbar_init(base + B_FILL + 8 * s, 4); mbar_init(base + B_FREE + 8 * s, NEW); }
    mbar_init(base + B_LN, 1);
    fence_barrier_init();
  }
  __syncthreads();
  if (GCL > 1) cluster_sync();
  auto release = [&](uint32_t st) {
    if (GCL > 1) { if (lane < GCL) mbar_arrive_cluster(base + B_EMPTY + 8 * st, lane); }
    else if (lane == 0) mbar_arrive(base + B_EMPTY + 8 * st);
  };
  auto get_item = [&](int q) {
    mbar_wait(base + B_ITEM + 8 * (q & 7), (q >> 3) & 1);
    return lds32(base + ITEMS + 4 * (q & 7));
  };

  if (warp == 8) {
    if (lane < 10) prefetch_tmap(&P.a[0] + lane);
    for (int r = blockIdx.x * 32 + lane; r < cfg::D; r += gridDim.x * 32) l2_prefetch(P.w1 + r * cfg::D, 2048);
    if (lane == 0) {
      uint32_t st = 0, ph = 1;
#pragma unroll 1
      for (int q = 0;; q++) {
        if (GCL > 1) mbar_expect_tx(base + B_ITEM + 8 * (q & 7), 4);
        if (rank == 0) {
          const unsigned idx = atomicAdd(&g_next, 1), ln = idx - P.lnpos;
          const uint32_t v = (idx < (unsigned)P.nitems ? P.items[idx] : T_END) | (ln < 64 / GCL ? (ln + 1) << 16 : idx < 32 / GCL ? (idx + 129) << 16 : 0);
          if (GCL > 1) {
#pragma unroll
            for (int r = 0; r < GCL; r++) st_async32(mapa(base + ITEMS + 4 * (q & 7), r), v, mapa(base + B_ITEM + 8 * (q & 7), r));
          } else {
            sts32(base + ITEMS + 4 * (q & 7), v);
            mbar_arrive(base + B_ITEM + 8 * (q & 7));
          }
        }
        const uint32_t item = get_item(q);
        const int type = item & 7, mb = ((item >> 3) & 15) + rank, nt = (item >> 7) & 15;
        ILOG(1);
        if (q == 0) { __threadfence(); sts32(base + ITEMS + 32, ld_strong4(&g_oflag[14]) >= 32); }
        if (type == T_END) break;
        if (type == T_B2) {
          wait_count(&g_cnt[T_B1][max(mb - 1, 0)], 4 * NEW); wait_count(&g_cnt[T_B1][mb], 4 * NEW); wait_count(&g_cnt[T_B1][min(mb + 1, 15)], 4 * NEW);
        } else if (type == T_B3) wait_count(&g_cnt[T_LN][mb], 32);
        else if (type == T_B4) wait_count(&g_cnt[T_B3][mb], 14 * NEW);
        else if (type == T_O) wait_count(&g_oflag[mb], 32);
        asm volatile("fence.proxy.async.global;" ::: "memory");
        ILOG(2);
        const CUtensorMap *ma = &P.a[type], *mbm = &P.b[type];
        const int nkb = type == T_B4 ? cfg::F / 64 : type == T_O ? cfg::HD / 64 : cfg::D / 64;
#pragma unroll 1
        for (int kb = 0; kb < nkb; kb++) {
          mbar_wait(base + B_EMPTY + 8 * st, ph);
          const uint32_t sa = base + st * STAGE, full = base + B_FULL + 8 * st;
          mbar_expect_tx(full, STAGE);
          int arow = mb * 128;
          if (type == T_B2) { const int qd = kb >> 2; arow += (qd == 0) ? -1 : (qd == 1) ? 1 : (qd == 2) ? -2 : 2; }
          if (GCL > 1) tma_load_3d_mc(sa + 16384 + rank * 16384, mbm, 0, kb * 64, nt * 4 + rank * 2, full);
          else tma_load_3d(sa + 16384, mbm, 0, kb * 64, nt * 4, full);
          if (type == T_B1 && kb == 0) { wait_count(&g_cnt[T_LN0][mb], 32); asm volatile("fence.proxy.async.global;" ::: "memory"); }
          tma_load_2d(sa, ma, kb * 64, arow, full);
          if (G_PF && type >= T_B4 && kb + G_PF < nkb) {
            if (G_PFM & 1) asm volatile("cp.async.bulk.prefetch.tensor.3d.L2.global [%0, {0, %1, %2}];" ::"l"(mbm), "r"((kb + G_PF) * 64), "r"(nt * 4 + rank * 2) : "memory");
            if (G_PFM & 2) asm volatile("cp.async.bulk.prefetch.tensor.2d.L2.global [%0, {%1, %2}];" ::"l"(ma), "r"((kb + G_PF) * 64), "r"(mb * 128) : "memory");
          }
          if (++st == NST) { st = 0; ph ^= 1; }
        }
      }
    }
  } else {
    const int wg = warp >> 2, ew = warp > 8 ? warp - 9 : warp + NEW;
    const uint32_t outa = base + OUTB + (warp * 16 + ((lane >> 3) & 1) * 8 + (lane & 7)) * 512 + (((lane >> 4) ^ (lane & 7)) << 4);
    uint32_t st = 0, ph = 0;
    float acc[128];
    auto kill_acc = [&]() {
#pragma unroll
      for (int i = 0; i < 128; i++) acc[i] = 0.f;
    };
    if (warp == 9) {
#pragma unroll 1
      for (int tries = 0; tries < POLL_TRIES; tries++) {
        uint4 v;
        asm volatile("ld.acquire.gpu.global.v4.u32 {%0,%1,%2,%3}, [%4];" : "=r"(v.x), "=r"(v.y), "=r"(v.z), "=r"(v.w)
                     : "l"(lane < 24 ? &g_mask[4 * lane] : &g_lnok[0]) : "memory");
        const uint32_t ok = __ballot_sync(0xffffffffu, v.x & v.y & v.z & v.w & 0x100);
        if ((ok & 0xFFFFFF) == 0xFFFFFF || (ok >> 24)) break;
        __nanosleep(200);
      }
      if (lane == 0) mbar_arrive(base + B_LN);
    }
    uint32_t next = get_item(0);
#pragma unroll 1
    for (int q = 0;; q++) {
      const uint32_t item = next;
      const int type = item & 7, mb = ((item >> 3) & 15) + rank, nt = (item >> 7) & 15;
      if (type == T_END) break;
      if (warp < 8) {
      if (item >> 16) {
        const bool first = item >> 23;
#pragma unroll 1
        for (int ln = ((item >> 16) & 127) - 1; ln < 64 / GCL; ln += first ? 32 / GCL : 64) {
          const int lb = (ln >> 2) * GCL + rank;
          const size_t row = (size_t)(lb * 128 + (ln & 3) * 32 + warp * 4) * cfg::D;
          const bf16* src = (first ? P.r[T_O] : P.c[T_B2]) + row;
          bf16* dst = (first ? P.xn2 : P.x1n) + row;
          if (!first) wait_count(&g_cnt[T_B2][lb], 4 * NEW);
          uint32_t cur[2][16], nxt[2][16];
#pragma unroll
          for (int r = 0; r < 2; r++) {
            load_row16(cur[r], src + r * cfg::D, lane);
            load_row16(nxt[r], src + (r + 2) * cfg::D, lane);
          }
#pragma unroll 1
          for (int it = first ? 0 : 1; it < 4; it += first ? 1 : 2) {
            ln_regs<2>(cur);
            if (it & 1) {
#pragma unroll
              for (int r = 0; r < 2; r++) {
                store_row16(cur[r], dst + (it - 1 + r) * cfg::D, lane);
#pragma unroll
                for (int i = 0; i < 16; i++) cur[r][i] = nxt[r][i];
              }
            }
          }
          __syncwarp();
          if (lane == 0) asm volatile("red.release.gpu.global.add.u32 [%0], 1;" ::"l"(&g_cnt[first ? T_LN0 : T_LN][lb]) : "memory");
          __syncwarp();
        }
        if (tid == 0) ILOG(6);
        kill_acc();
      }
      const int nkb = type == T_B4 ? cfg::F / 64 : type == T_O ? cfg::HD / 64 : cfg::D / 64;
      uint32_t prev = 0;
      mbar_wait(base + B_FULL + 8 * st, ph);
#pragma unroll 1
      for (int kb = 0; kb < nkb; kb++) {
        mbar_spin(base + B_FULL + 8 * st, ph);
        if (kb == 0 && tid == 0) ILOG(3);
        const uint64_t da = make_desc(base + wg * 8192, 16, 1024) + st * (STAGE >> 4), db = make_desc(base + 16384, 8192, 1024) + st * (STAGE >> 4);
        wg_fence();
#pragma unroll
        for (int k = 0; k < 4; k++) {
          wgmma_ss_n256_tb(acc, da + k * 2, db + k * 128, (kb | k) != 0);
          if (k == 0) {
            wg_commit();
            wg_wait<1>();
            if (kb > 0) release(prev);
            wg_fence();
          }
        }
        wg_commit();
        prev = st;
        if (++st == NST) { st = 0; ph ^= 1; }
      }
      next = get_item(q + 1);
      if (q > 0) mbar_wait(base + B_FREE + 8 * wg, (q - 1) & 1);
      wg_wait<0>();
      if (tid == 0) ILOG(4);
      release(prev);
#pragma unroll
      for (int j = 0; j < 16; j++)
        stsm4((outa ^ ((j & 3) << 5)) + (j >> 2) * 128, pack_bf16(acc[8 * j], acc[8 * j + 1]), pack_bf16(acc[8 * j + 2], acc[8 * j + 3]),
              pack_bf16(acc[8 * j + 4], acc[8 * j + 5]), pack_bf16(acc[8 * j + 6], acc[8 * j + 7]));
      __syncwarp();
      if (lane == 0) mbar_arrive(base + B_FILL + 8 * wg);
      if (tid == 0) ILOG(5);
      if ((next & 7) != T_END) continue;
      }
      if (type == T_O) wait_count(&g_cnt[T_B4][mb], 4 * NEW);
      const int ldc = type == T_B3 ? cfg::F : cfg::D;
      bf16* cp = P.c[type] + (size_t)mb * 128 * ldc + nt * 256 + lane * 8;
      const size_t roff = (size_t)mb * 128 * cfg::D + nt * 256 + lane * 8;
      const bf16 *rp = P.r[type] + roff, *gp = P.c[T_B4] + roff;
      const bool gelu = type == T_B1 || type == T_B3;
      uint32_t yn[4][4];
      uint4 rn[4], gn[4];
#pragma unroll
      for (int i = 0; i < 4; i++) rn[i] = gn[i] = make_uint4(0, 0, 0, 0);
      auto fetch_res = [&](int grp) {
#pragma unroll
        for (int i = 0; i < 4; i++) {
          rn[i] = __ldcg(reinterpret_cast<const uint4*>(rp + (grp * 4 + i) * cfg::D));
          if (type == T_O) gn[i] = __ldcg(reinterpret_cast<const uint4*>(gp + (grp * 4 + i) * cfg::D));
        }
      };
      auto fetch_y = [&](int grp) {
        const uint32_t a = base + OUTB + grp * 2048 + ((lane ^ ((grp & 1) << 2)) << 4);
#pragma unroll
        for (int i = 0; i < 4; i++) lds128(yn[i], (a ^ (i << 4)) + i * 512);
      };
      auto store_y = [&](int grp, const uint32_t (&y)[4][4]) {
        char* p = reinterpret_cast<char*>(cp) + (uint32_t)(grp * 8 * ldc);
#pragma unroll
        for (int i = 0; i < 4; i++) *reinterpret_cast<uint4*>(p + (uint32_t)(i * 2 * ldc)) = make_uint4(y[i][0], y[i][1], y[i][2], y[i][3]);
      };
      if (type == T_B2) mbar_wait(base + B_LN, 0);
      if (type == T_B4) wait_count(&g_cnt[T_B2][mb], 4 * NEW);
      if (type >= T_B4 && warp > 8) for (int r = tid - 288; r < 128; r += 96) l2_prefetch(rp - lane * 8 + r * cfg::D, 512);
      if (!gelu) fetch_res(ew);
      mbar_wait(base + B_FILL, q & 1);
      fetch_y(ew);
      next = get_item(q + 1);
      mbar_wait(base + B_FILL + 8, q & 1);
      const int stride = (next & 7) == T_END ? NEW + 8 : NEW;
      if (gelu) {
#pragma unroll 1
        for (int grp = ew; grp < 32; grp += stride) {
          uint32_t y[4][4];
#pragma unroll
          for (int i = 0; i < 16; i++) y[i >> 2][i & 3] = mul_bf16x2(yn[i >> 2][i & 3], 0x3F003F00u);
          const int nx = grp + stride;
          if (nx >= 16 && grp < 16 && lane == 0 && warp > 8) mbar_arrive(base + B_FREE);
          if (!G_LATE) fetch_y(min(nx, 31));
#pragma unroll
          for (int i = 0; i < 16; i++) {
            uint32_t& v = y[i >> 2][i & 3];
            const float h0 = bf_lo(v), h1 = bf_hi(v);
            const float t0 = tanh_approx(h0 * fmaf(h0 * h0, 0.285419265090401f, 1.5957691216057308f));
            const float t1 = tanh_approx(h1 * fmaf(h1 * h1, 0.285419265090401f, 1.5957691216057308f));
            v = pack_bf16(fmaf(h0, t0, h0), fmaf(h1, t1, h1));
          }
          if (G_LATE) fetch_y(min(nx, 31));
          store_y(grp, y);
        }
      } else {
#pragma unroll 1
        for (int grp = ew; grp < 32; grp += stride) {
          uint32_t y[4][4];
          if (type == T_O) {
#pragma unroll
            for (int i = 0; i < 16; i++) yn[i >> 2][i & 3] = mul_bf16x2(yn[i >> 2][i & 3], (&gn[i >> 2].x)[i & 3]);
          }
#pragma unroll
          for (int i = 0; i < 16; i++) y[i >> 2][i & 3] = add_bf16x2(yn[i >> 2][i & 3], (&rn[i >> 2].x)[i & 3]);
          const int nx = grp + stride;
          if (nx >= 16 && grp < 16 && lane == 0 && warp > 8) mbar_arrive(base + B_FREE);
          fetch_res(min(nx, 31));
          fetch_y(min(nx, 31));
          if (type == T_B4) {
#pragma unroll
            for (int i = 0; i < 16; i++) {
              uint32_t& v = y[i >> 2][i & 3];
              const float h0 = 0.5f * bf_lo(v), h1 = 0.5f * bf_hi(v);
              v = pack_bf16(fmaf(h0, tanh_approx(h0), h0), fmaf(h1, tanh_approx(h1), h1));
            }
          }
          store_y(grp, y);
        }
      }
      __syncwarp();
      if (lane == 0 && warp > 8) mbar_arrive(base + B_FREE + 8);
      if (stride != NEW) named_bar_sync(2, 352);
      if (type != T_O && lane == 0 && warp > 8) asm volatile("red.release.gpu.global.add.u32 [%0], 1;" ::"l"(&g_cnt[type][mb]) : "memory");
      __syncwarp();
      if (tid == 288) ILOG(7);
      kill_acc();
    }
    KT_END(2);
  }
  __syncwarp();
  if (warp >= 8) {
   named_bar_sync(1, 128);
   const bool late = lds32(base + ITEMS + 32);
   if (late) pdl_wait();
#pragma unroll 1
   for (int c = blockIdx.x; late && c < 96; c += gridDim.x) {
     if (__ldcg(&g_tfix[c]) == 0) continue;
     const int hh = c / 3, mb = TAIL_MB0 + c % 3;
     wait_count(&g_cnt[T_B4][mb], GATE_CNT);
#pragma unroll 1
     for (int i = tid - 256; i < 512; i += 128) {
       const size_t off = (size_t)(mb * 128 + (i >> 2)) * cfg::D + hh * 32 + (i & 3) * 8;
       const uint4 sv = __ldcg(reinterpret_cast<const uint4*>(P.c[T_O] + off)), gv = __ldcg(reinterpret_cast<const uint4*>(P.c[T_B4] + off)),
                   xv = __ldcg(reinterpret_cast<const uint4*>(P.r[T_O] + off));
       *reinterpret_cast<uint4*>(P.c[T_O] + off) = make_uint4(add_bf16x2(xv.x, mul_bf16x2(sv.x, gv.x)), add_bf16x2(xv.y, mul_bf16x2(sv.y, gv.y)),
                                                              add_bf16x2(xv.z, mul_bf16x2(sv.z, gv.z)), add_bf16x2(xv.w, mul_bf16x2(sv.w, gv.w)));
     }
   }
  }
  if (GCL > 1) cluster_sync();
}

__device__ bf16 g_xn[cfg::S * cfg::D];
__device__ bf16 g_xn2[cfg::S * cfg::D];
__device__ bf16 g_h[cfg::S * cfg::D];
__device__ bf16 g_x1[cfg::S * cfg::D];
__device__ bf16 g_x1n[cfg::S * cfg::D];
__device__ bf16 g_u[cfg::S * cfg::F];
__device__ bf16 g_g[cfg::S * cfg::D];
__device__ bf16 g_o[cfg::S * cfg::HD];

typedef CUresult (*PFN_encodeTiled)(CUtensorMap*, CUtensorMapDataType, cuuint32_t, void*, const cuuint64_t*,
                                    const cuuint64_t*, const cuuint32_t*, const cuuint32_t*, CUtensorMapInterleave,
                                    CUtensorMapSwizzle, CUtensorMapL2promotion, CUtensorMapFloatOOBfill);

static PFN_encodeTiled get_encoder() {
  static PFN_encodeTiled fn = nullptr;
  if (!fn) {
    void* p = nullptr;
    cudaDriverEntryPointQueryResult st;
    cudaGetDriverEntryPoint("cuTensorMapEncodeTiled", &p, cudaEnableDefault, &st);
    fn = (PFN_encodeTiled)p;
  }
  return fn;
}
static CUtensorMap make_map(const void* ptr, int rows, int cols, int box_rows, int box_cols, int swizzle_bytes) {
  CUtensorMap m;
  cuuint64_t dims[2] = {(cuuint64_t)cols, (cuuint64_t)rows};
  cuuint64_t strides[1] = {(cuuint64_t)cols * 2};
  cuuint32_t box[2] = {(cuuint32_t)box_cols, (cuuint32_t)box_rows};
  cuuint32_t estr[2] = {1, 1};
  CUtensorMapSwizzle sw = swizzle_bytes == 128 ? CU_TENSOR_MAP_SWIZZLE_128B
                        : swizzle_bytes == 64 ? CU_TENSOR_MAP_SWIZZLE_64B
                        : swizzle_bytes == 32 ? CU_TENSOR_MAP_SWIZZLE_32B : CU_TENSOR_MAP_SWIZZLE_NONE;
  get_encoder()(&m, CU_TENSOR_MAP_DATA_TYPE_BFLOAT16, 2, const_cast<void*>(ptr), dims, strides, box, estr,
                CU_TENSOR_MAP_INTERLEAVE_NONE, sw, CU_TENSOR_MAP_L2_PROMOTION_L2_128B, CU_TENSOR_MAP_FLOAT_OOB_FILL_NONE);
  return m;
}
static CUtensorMap make_map3(const void* ptr, int rows, int cols, int box_rows, int nblk) {
  CUtensorMap m;
  cuuint64_t dims[3] = {64, (cuuint64_t)rows, (cuuint64_t)(cols / 64)};
  cuuint64_t strides[2] = {(cuuint64_t)cols * 2, 128};
  cuuint32_t box[3] = {64, (cuuint32_t)box_rows, (cuuint32_t)nblk};
  cuuint32_t estr[3] = {1, 1, 1};
  get_encoder()(&m, CU_TENSOR_MAP_DATA_TYPE_BFLOAT16, 3, const_cast<void*>(ptr), dims, strides, box, estr,
                CU_TENSOR_MAP_INTERLEAVE_NONE, CU_TENSOR_MAP_SWIZZLE_128B, CU_TENSOR_MAP_L2_PROMOTION_L2_128B,
                CU_TENSOR_MAP_FLOAT_OOB_FILL_NONE);
  return m;
}
template <class T> static T* sym(T& s) { void* p = nullptr; cudaGetSymbolAddress(&p, s); return (T*)p; }
#define SYM(name) ((bf16*)[] { void* p = nullptr; cudaGetSymbolAddress(&p, name); return p; }())

#define G_CTAS 36
#define B4_FIRST 11
#define O_FIRST 4
#define B3_FIRST 9
#define LN_POS 63
static int build_items(uint16_t* it) {
  using namespace gk;
  int n = 0;
  auto add = [&](int type, int nrows, int ncols, int row0 = 0) {
    for (int mb = row0; mb < nrows; mb += GCL) for (int nt = 0; nt < ncols; nt++) it[n++] = (uint16_t)(type | mb << 3 | nt << 7);
  };
  add(T_B1, 16, 4); add(T_B2, 16, 4); add(T_B3, B3_FIRST, 14); add(T_B4, 2, 4); add(T_B3, 16, 14, B3_FIRST);
  add(T_B4, B4_FIRST, 4, 2); add(T_O, O_FIRST, 4); add(T_B4, 16, 4, B4_FIRST); add(T_O, TAIL_MB0, 4, O_FIRST);
  return n;
}

extern "C" void kernel_launch(void* const* d_in, const int* in_sizes, int n_in, void* d_out, int out_size) {
  using namespace cfg;
  const bf16* x = (const bf16*)d_in[0];
  const bf16* mem0 = (const bf16*)d_in[1];
  const bf16* Wq = (const bf16*)d_in[2];
  const bf16* Wk = (const bf16*)d_in[3];
  const bf16* Wv = (const bf16*)d_in[4];
  const bf16* Wo = (const bf16*)d_in[5];
  const bf16* w1 = (const bf16*)d_in[8];
  const bf16* w2 = (const bf16*)d_in[9];
  const bf16* w3 = (const bf16*)d_in[10];
  const bf16* w4 = (const bf16*)d_in[11];
  bf16* out = (bf16*)d_out;
  cudaStream_t st = cudaStreamPerThread;

  bf16 *xn = SYM(g_xn), *xn2 = SYM(g_xn2), *hb = SYM(g_h), *x1 = SYM(g_x1), *x1n = SYM(g_x1n), *u = SYM(g_u),
       *g = SYM(g_g), *o = SYM(g_o);

  {
    cudaFuncSetAttribute(f_kernel, cudaFuncAttributeMaxDynamicSharedMemorySize, fk::SMEM);
    FParams P;
    P.wq = make_map(Wq, D, HD, 64, 64, 128); P.wk = make_map(Wk, D, HD, 64, 64, 128); P.wv = make_map(Wv, D, HD, 64, 64, 128);
    P.wo = make_map(Wo, HD, D, 128, 64, 128); P.wo16 = make_map(Wo, HD, D, 128, 16, 32); P.xn = make_map3(xn, S, D, 32, 4); P.xn12 = make_map3(xn, S, D, 32, 12); P.o = make_map3(o, S, HD, 32, 2);
    P.ta = make_map(o, S, HD, 128, 64, 128); P.tb = make_map(Wo, HD, D, 64, 64, 128);
    P.gate = g; P.out = out;
    P.mem0 = mem0;
    P.nprobe = PROBE_N;
    P.dxn = make_desc(fk::XN, 16, 1024);
    P.x = x; P.xn_ptr = xn;
    P.xch = (char*)(((uintptr_t)SYM(g_xch) + 8191) & ~(uintptr_t)8191);
    cudaLaunchConfig_t cfg = {};
    cfg.gridDim = dim3(96); cfg.blockDim = dim3(256); cfg.dynamicSmemBytes = fk::SMEM; cfg.stream = st;
    cudaLaunchAttribute at[2];
    at[0].id = cudaLaunchAttributeClusterDimension;
    at[0].val.clusterDim.x = 3; at[0].val.clusterDim.y = 1; at[0].val.clusterDim.z = 1;
    cfg.attrs = at; cfg.numAttrs = 1;
    cudaLaunchKernelEx(&cfg, f_kernel, P);
  }
  {
    cudaFuncSetAttribute(g_kernel, cudaFuncAttributeMaxDynamicSharedMemorySize, gk::SMEM);
    GParams G;
    const bf16* as[5] = {xn2, hb, x1n, u, o};
    const bf16* bs[5] = {w1, w2, w3, w4, Wo};
    bf16* cs[5] = {hb, x1, u, g, out};
    const bf16* rs[5] = {xn, xn, xn, x1, x};
    const int ks[5] = {D, D, D, F, HD}, ns[5] = {D, D, F, D, D};
    for (int i = 0; i < 5; i++) {
      G.a[i] = make_map(as[i], S, ks[i], 128, 64, 128);
      G.b[i] = make_map3(bs[i], ks[i], ns[i], 64, 4 / GCL);
      G.c[i] = cs[i];
      G.r[i] = rs[i];
    }
    G.x1n = x1n; G.xn2 = xn2; G.w1 = w1;
    G.nitems = build_items(G.items);
    G.lnpos = LN_POS * 2 / GCL;
    cudaLaunchConfig_t cfg = {};
    cfg.gridDim = dim3(G_CTAS); cfg.blockDim = dim3(384); cfg.dynamicSmemBytes = gk::SMEM; cfg.stream = st;
    cudaLaunchAttribute at[2];
    at[0].id = cudaLaunchAttributeClusterDimension;
    at[0].val.clusterDim.x = GCL; at[0].val.clusterDim.y = 1; at[0].val.clusterDim.z = 1;
    at[1].id = cudaLaunchAttributeProgrammaticStreamSerialization;
    at[1].val.programmaticStreamSerializationAllowed = 1;
    cfg.attrs = at;
    cfg.numAttrs = 2;
    cudaLaunchKernelEx(&cfg, g_kernel, G);
  }
}
```

```cpp
#include <cuda_runtime.h>
#include <cuda_bf16.h>
#include <cuda.h>
#include <stdint.h>

typedef __nv_bfloat16 bf16;

namespace cfg {
constexpr int S = 2048;
constexpr int D = 1024;
constexpr int H = 32;
constexpr int DH = 128;
constexpr int HD = H * DH;
constexpr int M = 8;
constexpr int SEG = 32;
constexpr int NSEG = S / SEG;
constexpr int F = 3584;
}

__device__ __forceinline__ uint32_t smem_u32(const void* p) { return (uint32_t)__cvta_generic_to_shared(p); }

__device__ __forceinline__ void mbar_init(uint32_t bar, uint32_t count) {
  asm volatile("mbarrier.init.shared::cta.b64 [%0], %1;" ::"r"(bar), "r"(count) : "memory");
}
__device__ __forceinline__ void mbar_expect_tx(uint32_t bar, uint32_t bytes) {
  asm volatile("mbarrier.arrive.expect_tx.shared::cta.b64 _, [%0], %1;" ::"r"(bar), "r"(bytes) : "memory");
}
__device__ __forceinline__ void mbar_arrive(uint32_t bar) {
  asm volatile("mbarrier.arrive.shared::cta.b64 _, [%0];" ::"r"(bar) : "memory");
}
__device__ __forceinline__ bool mbar_try(uint32_t bar, uint32_t parity) {
  uint32_t done;
  asm volatile("{\n.reg .pred p;\nmbarrier.try_wait.parity.shared::cta.b64 p, [%1], %2, 20000;\nselp.u32 %0, 1, 0, p;\n}"
               : "=r"(done) : "r"(bar), "r"(parity) : "memory");
  return done != 0;
}
__device__ __forceinline__ bool mbar_try_nohint(uint32_t bar, uint32_t parity) {
  uint32_t done;
  asm volatile("{\n.reg .pred p;\nmbarrier.try_wait.parity.shared::cta.b64 p, [%1], %2;\nselp.u32 %0, 1, 0, p;\n}"
               : "=r"(done) : "r"(bar), "r"(parity) : "memory");
  return done != 0;
}
constexpr int MBAR_TRIES = 4096;
constexpr int POLL_TRIES = 1 << 16;
__device__ __forceinline__ void mbar_wait(uint32_t bar, uint32_t parity) {
#pragma unroll 1
  for (int n = 0; n < MBAR_TRIES; n++)
    if (mbar_try(bar, parity)) break;
}
__device__ __forceinline__ void mbar_wait_fast(uint32_t bar, uint32_t parity) {
#pragma unroll 1
  for (int n = 0; n < (POLL_TRIES << 4); n++)
    if (mbar_try_nohint(bar, parity)) break;
}
__device__ __forceinline__ void fence_barrier_init() { asm volatile("fence.mbarrier_init.release.cluster;" ::: "memory"); }
__device__ __forceinline__ void fence_proxy_async_smem() { asm volatile("fence.proxy.async.shared::cta;" ::: "memory"); }

__device__ __forceinline__ void tma_load_2d(uint32_t dst, const CUtensorMap* map, int x, int y, uint32_t bar) {
  asm volatile("cp.async.bulk.tensor.2d.shared::cluster.global.mbarrier::complete_tx::bytes [%0], [%1, {%3, %4}], [%2];"
               ::"r"(dst), "l"(map), "r"(bar), "r"(x), "r"(y) : "memory");
}
__device__ __forceinline__ void tma_load_3d(uint32_t dst, const CUtensorMap* map, int x, int y, int z, uint32_t bar) {
  asm volatile("cp.async.bulk.tensor.3d.shared::cluster.global.mbarrier::complete_tx::bytes [%0], [%1, {%3, %4, %5}], [%2];"
               ::"r"(dst), "l"(map), "r"(bar), "r"(x), "r"(y), "r"(z) : "memory");
}
__device__ __forceinline__ void tma_store_2d(const CUtensorMap* map, uint32_t src, int x, int y) {
  asm volatile("cp.async.bulk.tensor.2d.global.shared::cta.bulk_group [%0, {%2, %3}], [%1];"
               ::"l"(map), "r"(src), "r"(x), "r"(y) : "memory");
}
__device__ __forceinline__ void tma_store_commit() { asm volatile("cp.async.bulk.commit_group;" ::: "memory"); }
__device__ __forceinline__ void tma_store_wait_all() { asm volatile("cp.async.bulk.wait_group 0;" ::: "memory"); }
__device__ __forceinline__ void tma_store_wait_read() { asm volatile("cp.async.bulk.wait_group.read 0;" ::: "memory"); }
__device__ __forceinline__ void prefetch_tmap(const CUtensorMap* map) {
  asm volatile("prefetch.tensormap [%0];" ::"l"(map) : "memory");
}

__device__ __forceinline__ void wg_fence() { asm volatile("wgmma.fence.sync.aligned;" ::: "memory"); }
__device__ __forceinline__ void wg_commit() { asm volatile("wgmma.commit_group.sync.aligned;" ::: "memory"); }
template <int N> __device__ __forceinline__ void wg_wait() { asm volatile("wgmma.wait_group.sync.aligned %0;" ::"n"(N) : "memory"); }

#define named_bar_sync(id, n) asm volatile("bar.sync %0, %1;" ::"n"(id), "n"(n) : "memory")
#define named_bar_arrive(id, n) asm volatile("bar.arrive %0, %1;" ::"n"(id), "n"(n) : "memory")

__host__ __device__ __forceinline__ uint64_t make_desc(uint32_t addr, uint32_t lbo, uint32_t sbo) {
  return (uint64_t)((addr & 0x3FFFF) >> 4) | ((uint64_t)(lbo >> 4) << 16) | ((uint64_t)(sbo >> 4) << 32) | (1ull << 62);
}

__device__ __forceinline__ uint64_t make_desc0(uint32_t addr, uint32_t lbo, uint32_t sbo) {
  return (uint64_t)((addr & 0x3FFFF) >> 4) | ((uint64_t)(lbo >> 4) << 16) | ((uint64_t)(sbo >> 4) << 32);
}

__device__ __forceinline__ uint32_t pack_bf16(float lo, float hi) {
  uint32_t r;
  asm("cvt.rn.bf16x2.f32 %0, %1, %2;" : "=r"(r) : "f"(hi), "f"(lo));
  return r;
}
__device__ __forceinline__ float bf_lo(uint32_t v) { return __uint_as_float(v << 16); }
__device__ __forceinline__ float bf_hi(uint32_t v) { return __uint_as_float(v & 0xFFFF0000u); }
__device__ __forceinline__ float rbf(float v) { return __bfloat162float(__float2bfloat16_rn(v)); }

__device__ __forceinline__ void pdl_launch_dependents() { asm volatile("griddepcontrol.launch_dependents;" ::: "memory"); }
__device__ __forceinline__ void pdl_wait() { asm volatile("griddepcontrol.wait;" ::: "memory"); }

__device__ __forceinline__ float ex2_approx(float x) { float y; asm("ex2.approx.ftz.f32 %0, %1;" : "=f"(y) : "f"(x)); return y; }
__device__ __forceinline__ float rcp_approx(float x) { float y; asm("rcp.approx.ftz.f32 %0, %1;" : "=f"(y) : "f"(x)); return y; }

__device__ __forceinline__ void mul_sigmoid4(float (&v)[4], const float (&t)[4]) {
#pragma unroll
  for (int i = 0; i < 4; i += 2) {
    const float a = 1.0f + ex2_approx(fminf(t[i], 60.0f)), b = 1.0f + ex2_approx(fminf(t[i + 1], 60.0f));
    const float r = rcp_approx(a * b);
    v[i] *= b * r;
    v[i + 1] *= a * r;
  }
}
__device__ __forceinline__ void gelu4(float (&v)[4]) {
  float t[4];
#pragma unroll
  for (int i = 0; i < 4; i++) t[i] = v[i] * fmaf(v[i] * v[i], -0.10294324f, -2.30220819f);
  mul_sigmoid4(v, t);
}
__device__ __forceinline__ void silu4(float (&v)[4]) {
  float t[4];
#pragma unroll
  for (int i = 0; i < 4; i++) t[i] = v[i] * -1.4426950408889634f;
  mul_sigmoid4(v, t);
}

#define KT_START(id)
#define KT_END(id)

__device__ __forceinline__ void wgmma_ss_n256_tb(float (&d)[128], uint64_t da, uint64_t db, int scale_d) {
  asm volatile("{\n.reg .pred p;\nsetp.ne.b32 p, %130, 0;\n"
    "wgmma.mma_async.sync.aligned.m64n256k16.f32.bf16.bf16 "
    "{%0, %1, %2, %3, %4, %5, %6, %7, %8, %9, %10, %11, %12, %13, %14, %15, "
    "%16, %17, %18, %19, %20, %21, %22, %23, %24, %25, %26, %27, %28, %29, %30, %31, "
    "%32, %33, %34, %35, %36, %37, %38, %39, %40, %41, %42, %43, %44, %45, %46, %47, "
    "%48, %49, %50, %51, %52, %53, %54, %55, %56, %57, %58, %59, %60, %61, %62, %63, "
    "%64, %65, %66, %67, %68, %69, %70, %71, %72, %73, %74, %75, %76, %77, %78, %79, "
    "%80, %81, %82, %83, %84, %85, %86, %87, %88, %89, %90, %91, %92, %93, %94, %95, "
    "%96, %97, %98, %99, %100, %101, %102, %103, %104, %105, %106, %107, %108, %109, %110, %111, "
    "%112, %113, %114, %115, %116, %117, %118, %119, %120, %121, %122, %123, %124, %125, %126, %127}, "
    "%128, %129, p, 1, 1, 0, 1;\n}\n"
    : "+f"(d[0]), "+f"(d[1]), "+f"(d[2]), "+f"(d[3]), "+f"(d[4]), "+f"(d[5]), "+f"(d[6]), "+f"(d[7]),
      "+f"(d[8]), "+f"(d[9]), "+f"(d[10]), "+f"(d[11]), "+f"(d[12]), "+f"(d[13]), "+f"(d[14]), "+f"(d[15]),
      "+f"(d[16]), "+f"(d[17]), "+f"(d[18]), "+f"(d[19]), "+f"(d[20]), "+f"(d[21]), "+f"(d[22]), "+f"(d[23]),
      "+f"(d[24]), "+f"(d[25]), "+f"(d[26]), "+f"(d[27]), "+f"(d[28]), "+f"(d[29]), "+f"(d[30]), "+f"(d[31]),
      "+f"(d[32]), "+f"(d[33]), "+f"(d[34]), "+f"(d[35]), "+f"(d[36]), "+f"(d[37]), "+f"(d[38]), "+f"(d[39]),
      "+f"(d[40]), "+f"(d[41]), "+f"(d[42]), "+f"(d[43]), "+f"(d[44]), "+f"(d[45]), "+f"(d[46]), "+f"(d[47]),
      "+f"(d[48]), "+f"(d[49]), "+f"(d[50]), "+f"(d[51]), "+f"(d[52]), "+f"(d[53]), "+f"(d[54]), "+f"(d[55]),
      "+f"(d[56]), "+f"(d[57]), "+f"(d[58]), "+f"(d[59]), "+f"(d[60]), "+f"(d[61]), "+f"(d[62]), "+f"(d[63]),
      "+f"(d[64]), "+f"(d[65]), "+f"(d[66]), "+f"(d[67]), "+f"(d[68]), "+f"(d[69]), "+f"(d[70]), "+f"(d[71]),
      "+f"(d[72]), "+f"(d[73]), "+f"(d[74]), "+f"(d[75]), "+f"(d[76]), "+f"(d[77]), "+f"(d[78]), "+f"(d[79]),
      "+f"(d[80]), "+f"(d[81]), "+f"(d[82]), "+f"(d[83]), "+f"(d[84]), "+f"(d[85]), "+f"(d[86]), "+f"(d[87]),
      "+f"(d[88]), "+f"(d[89]), "+f"(d[90]), "+f"(d[91]), "+f"(d[92]), "+f"(d[93]), "+f"(d[94]), "+f"(d[95]),
      "+f"(d[96]), "+f"(d[97]), "+f"(d[98]), "+f"(d[99]), "+f"(d[100]), "+f"(d[101]), "+f"(d[102]), "+f"(d[103]),
      "+f"(d[104]), "+f"(d[105]), "+f"(d[106]), "+f"(d[107]), "+f"(d[108]), "+f"(d[109]), "+f"(d[110]), "+f"(d[111]),
      "+f"(d[112]), "+f"(d[113]), "+f"(d[114]), "+f"(d[115]), "+f"(d[116]), "+f"(d[117]), "+f"(d[118]), "+f"(d[119]),
      "+f"(d[120]), "+f"(d[121]), "+f"(d[122]), "+f"(d[123]), "+f"(d[124]), "+f"(d[125]), "+f"(d[126]), "+f"(d[127])
    : "l"(da), "l"(db), "r"(scale_d));
}
__device__ __forceinline__ void wgmma_rs_n32(float (&d)[16], const uint32_t* a, uint64_t db, int scale_d) {
  asm volatile("{\n.reg .pred p;\nsetp.ne.b32 p, %21, 0;\n"
    "wgmma.mma_async.sync.aligned.m64n32k16.f32.bf16.bf16 "
    "{%0, %1, %2, %3, %4, %5, %6, %7, %8, %9, %10, %11, %12, %13, %14, %15}, "
    "{%16, %17, %18, %19}, %20, p, 1, 1, 0;\n}\n"
    : "+f"(d[0]), "+f"(d[1]), "+f"(d[2]), "+f"(d[3]), "+f"(d[4]), "+f"(d[5]), "+f"(d[6]), "+f"(d[7]),
      "+f"(d[8]), "+f"(d[9]), "+f"(d[10]), "+f"(d[11]), "+f"(d[12]), "+f"(d[13]), "+f"(d[14]), "+f"(d[15])
    : "r"(a[0]), "r"(a[1]), "r"(a[2]), "r"(a[3]), "l"(db), "r"(scale_d));
}
__device__ __forceinline__ void wgmma_ss_n32_ta(float (&d)[16], uint64_t da, uint64_t db, int scale_d) {
  asm volatile("{\n.reg .pred p;\nsetp.ne.b32 p, %18, 0;\n"
    "wgmma.mma_async.sync.aligned.m64n32k16.f32.bf16.bf16 "
    "{%0, %1, %2, %3, %4, %5, %6, %7, %8, %9, %10, %11, %12, %13, %14, %15}, "
    "%16, %17, p, 1, 1, 1, 0;\n}\n"
    : "+f"(d[0]), "+f"(d[1]), "+f"(d[2]), "+f"(d[3]), "+f"(d[4]), "+f"(d[5]), "+f"(d[6]), "+f"(d[7]),
      "+f"(d[8]), "+f"(d[9]), "+f"(d[10]), "+f"(d[11]), "+f"(d[12]), "+f"(d[13]), "+f"(d[14]), "+f"(d[15])
    : "l"(da), "l"(db), "r"(scale_d));
}
__device__ __forceinline__ void wgmma_ss_n8_ta(float (&d)[4], uint64_t da, uint64_t db, int scale_d) {
  asm volatile("{\n.reg .pred p;\nsetp.ne.b32 p, %6, 0;\n"
    "wgmma.mma_async.sync.aligned.m64n8k16.f32.bf16.bf16 {%0, %1, %2, %3}, %4, %5, p, 1, 1, 1, 0;\n}\n"
    : "+f"(d[0]), "+f"(d[1]), "+f"(d[2]), "+f"(d[3]) : "l"(da), "l"(db), "r"(scale_d));
}
__device__ __forceinline__ void wgmma_ss_n48_tt(float (&d)[24], uint64_t da, uint64_t db, int scale_d) {
  asm volatile("{\n.reg .pred p;\nsetp.ne.b32 p, %26, 0;\n"
    "wgmma.mma_async.sync.aligned.m64n48k16.f32.bf16.bf16 "
    "{%0, %1, %2, %3, %4, %5, %6, %7, %8, %9, %10, %11, %12, %13, %14, %15, %16, %17, %18, %19, %20, %21, %22, %23}, "
    "%24, %25, p, 1, 1, 1, 1;\n}\n"
    : "+f"(d[0]), "+f"(d[1]), "+f"(d[2]), "+f"(d[3]), "+f"(d[4]), "+f"(d[5]), "+f"(d[6]), "+f"(d[7]), "+f"(d[8]), "+f"(d[9]), "+f"(d[10]), "+f"(d[11]), "+f"(d[12]), "+f"(d[13]), "+f"(d[14]), "+f"(d[15]), "+f"(d[16]), "+f"(d[17]), "+f"(d[18]), "+f"(d[19]), "+f"(d[20]), "+f"(d[21]), "+f"(d[22]), "+f"(d[23])
    : "l"(da), "l"(db), "r"(scale_d));
}
__device__ __forceinline__ void wgmma_ss_n32(float (&d)[16], uint64_t da, uint64_t db, int scale_d) {
  asm volatile("{\n.reg .pred p;\nsetp.ne.b32 p, %18, 0;\n"
    "wgmma.mma_async.sync.aligned.m64n32k16.f32.bf16.bf16 "
    "{%0, %1, %2, %3, %4, %5, %6, %7, %8, %9, %10, %11, %12, %13, %14, %15}, "
    "%16, %17, p, 1, 1, 0, 0;\n}\n"
    : "+f"(d[0]), "+f"(d[1]), "+f"(d[2]), "+f"(d[3]), "+f"(d[4]), "+f"(d[5]), "+f"(d[6]), "+f"(d[7]),
      "+f"(d[8]), "+f"(d[9]), "+f"(d[10]), "+f"(d[11]), "+f"(d[12]), "+f"(d[13]), "+f"(d[14]), "+f"(d[15])
    : "l"(da), "l"(db), "r"(scale_d));
}

__device__ __forceinline__ void tma_load_2d_mc(uint32_t dst, const CUtensorMap* map, int x, int y, uint32_t bar, uint16_t mask) {
  asm volatile("cp.async.bulk.tensor.2d.shared::cluster.global.mbarrier::complete_tx::bytes.multicast::cluster "
               "[%0], [%1, {%3, %4}], [%2], %5;"
               ::"r"(dst), "l"(map), "r"(bar), "r"(x), "r"(y), "h"(mask) : "memory");
}
__device__ __forceinline__ void mbar_arrive_cluster(uint32_t bar, uint32_t cta) {
  asm volatile("{\n.reg .b32 r;\nmapa.shared::cluster.u32 r, %0, %1;\nmbarrier.arrive.shared::cluster.b64 _, [r];\n}"
               ::"r"(bar), "r"(cta) : "memory");
}
__device__ __forceinline__ void cluster_sync() {
  asm volatile("barrier.cluster.arrive.release.aligned;\nbarrier.cluster.wait.acquire.aligned;" ::: "memory");
}
__device__ __forceinline__ void wait_count(const unsigned* p, unsigned need) {
#pragma unroll 1
  for (int tries = 0; tries < (1 << 18); tries++) {
    unsigned v;
    asm volatile("ld.acquire.gpu.global.u32 %0, [%1];" : "=r"(v) : "l"(p) : "memory");
    if (v >= need) break;
    __nanosleep(64);
  }
}
__device__ __forceinline__ uint32_t sub_bf16x2(uint32_t a, uint32_t b) {
  uint32_t d;
  asm("sub.rn.bf16x2 %0, %1, %2;" : "=r"(d) : "r"(a), "r"(b));
  return d;
}
__device__ __forceinline__ uint32_t add_bf16x2(uint32_t a, uint32_t b) {
  uint32_t d;
  asm("add.rn.bf16x2 %0, %1, %2;" : "=r"(d) : "r"(a), "r"(b));
  return d;
}
__device__ __forceinline__ uint32_t mul_bf16x2(uint32_t a, uint32_t b) {
  uint32_t d;
  asm("mul.rn.bf16x2 %0, %1, %2;" : "=r"(d) : "r"(a), "r"(b));
  return d;
}

template <int NR>
__device__ __forceinline__ void ln_regs(uint32_t (&raw)[NR][16]) {
  float m[NR], q[NR];
#pragma unroll
  for (int r = 0; r < NR; r++) {
    float s0 = 0.f, s1 = 0.f;
#pragma unroll
    for (int i = 0; i < 16; i++) { s0 += bf_lo(raw[r][i]); s1 += bf_hi(raw[r][i]); }
    m[r] = s0 + s1;
  }
#pragma unroll
  for (int o = 16; o > 0; o >>= 1)
#pragma unroll
    for (int r = 0; r < NR; r++) m[r] += __shfl_xor_sync(0xffffffffu, m[r], o);
#pragma unroll
  for (int r = 0; r < NR; r++) {
    m[r] *= 1.0f / 1024.0f;
    float s0 = 0.f, s1 = 0.f;
#pragma unroll
    for (int i = 0; i < 16; i++) {
      const float d0 = bf_lo(raw[r][i]) - m[r], d1 = bf_hi(raw[r][i]) - m[r];
      s0 = fmaf(d0, d0, s0); s1 = fmaf(d1, d1, s1);
    }
    q[r] = s0 + s1;
  }
#pragma unroll
  for (int o = 16; o > 0; o >>= 1)
#pragma unroll
    for (int r = 0; r < NR; r++) q[r] += __shfl_xor_sync(0xffffffffu, q[r], o);
#pragma unroll
  for (int r = 0; r < NR; r++) {
    const uint32_t mb = pack_bf16(m[r], m[r]);
    float sq;
    asm("sqrt.approx.f32 %0, %1;" : "=f"(sq) : "f"(rbf(rbf(q[r] * (1.0f / 1024.0f)) + 1e-5f)));
    const float inv = rcp_approx(rbf(sq));
#pragma unroll
    for (int i = 0; i < 16; i++) {
      const uint32_t d = sub_bf16x2(raw[r][i], mb);
      raw[r][i] = pack_bf16(bf_lo(d) * inv, bf_hi(d) * inv);
    }
  }
}
__device__ __forceinline__ void load_row16(uint32_t (&raw)[16], const bf16* src, int lane) {
#pragma unroll
  for (int j = 0; j < 4; j++) {
    const uint4 u = __ldcg(reinterpret_cast<const uint4*>(src + j * 256 + lane * 8));
    raw[4 * j] = u.x; raw[4 * j + 1] = u.y; raw[4 * j + 2] = u.z; raw[4 * j + 3] = u.w;
  }
}
__device__ __forceinline__ void store_row16(const uint32_t (&raw)[16], bf16* dst, int lane) {
#pragma unroll
  for (int j = 0; j < 4; j++)
    *reinterpret_cast<uint4*>(dst + j * 256 + lane * 8) = make_uint4(raw[4 * j], raw[4 * j + 1], raw[4 * j + 2], raw[4 * j + 3]);
}

namespace fk {
constexpr uint32_t SM0 = 1024;
constexpr uint32_t WO = SM0, WS = WO + 90112, XN = WS + 65536, VX = XN + 49152, QK = VX + 8192, PT = QK + 8192,
                   SP = PT + 4096, VM = SP + 2560, OB = VM + 2048, BAR = OB + 2048;
constexpr uint32_t MEMB = XN + 16384, RED = XN + 32768, VX2 = WO + 81920;
constexpr int SMEM = 232448;
static_assert(BAR + 512 == SM0 + SMEM, "shared memory layout");
constexpr uint32_t B_XN = BAR, B_H2 = BAR + 64, B_H1 = BAR + 120, ONES = BAR + 384, B_PF = BAR + 16, B_WO = BAR + 24, B_SM = BAR + 32, B_VM = BAR + 40, B_VX = BAR + 48, B_ST = BAR + 56, B_PB = BAR + 64, B_W = BAR + 112,
                   MASKS = BAR + 128, PROBE = BAR + 256;
constexpr int NB_M0 = 1, NB_M1 = 2, NB_C = 3, NB_O = 4, NB_ST = 5, NB_DU = 6, NB_CF = 7, NB_W1 = 8, NB_XE = 9, NB_HD = 10, NB_MX = 11, NB_O0 = 12;
#define D_H1 550
#define D_H2 1900
#define D_ST 200
#define SMQ 0x1E
#define SMV 0x1E
#define PRE_G 4
#define PRE_A 1
#define LN_DRY 1
#define MASK_AT 4
#define WO_AT 5
#define NS0 4
#define NS0V 4
#define NTA0 2
#define NTA1 1
#define PF0A 3
#define PF0 10
#define PF1V 10
#define PF1 11
#define REFILL_EARLY 1
#define GATE_MX 0
#define GATE_Q 0
#define PF1Q 4
#define PACEQ 0x60
#define PACEV 0
#define PADD 1
#define D_H2V 2200
#define D_H2L 1700
#define H2_ATV 0
#define VM_BULK 0
#define CF_AT 0
#define H2_AT 0
#define NPRE0 1
#define PROBE_N 4
#define SPACK 1
constexpr uint32_t SPW = SPACK ? 4 : 8, SP_SRC = 160 * SPW;
constexpr int H1_BYTES = 64 * 32768, H2_BYTES = 8 * 8192;
}

#define PROF(wg, i)
#define PROF2(i)
#define RETRY(i)
#define GTSYNC(i)
#define PRO(i)
#define TL(i)
#define TL2(t, i)

__device__ uint4 g_xch[(fk::H1_BYTES + fk::H2_BYTES + 8192) / 16];
__device__ __align__(16) unsigned g_mask[128];
__device__ unsigned g_cnt[8][16];
__device__ unsigned g_next;
constexpr int TAIL_MB0 = 13, GATE_CNT = 12;
__device__ __align__(16) unsigned g_tfix[96], g_lnok[4];
__device__ __align__(16) unsigned g_tcnt[96][8];
__device__ uint4 g_tpart[96][8][2][256];
__device__ unsigned g_oflag[16];

#define LD_POLL "ld.global.L1::no_allocate"
__device__ __forceinline__ uint4 ld_poll16(const void* p) {
  uint4 v;
  asm volatile(LD_POLL ".v4.u32 {%0,%1,%2,%3}, [%4];" : "=r"(v.x), "=r"(v.y), "=r"(v.z), "=r"(v.w) : "l"(p) : "memory");
  return v;
}
__device__ __forceinline__ uint2 ld_poll8(const void* p) {
  uint2 v;
  asm volatile(LD_POLL ".v2.u32 {%0,%1}, [%2];" : "=r"(v.x), "=r"(v.y) : "l"(p) : "memory");
  return v;
}
__device__ __forceinline__ uint4 ld_strong16(const void* p) {
  uint4 v;
  asm volatile("ld.relaxed.gpu.global.v4.u32 {%0,%1,%2,%3}, [%4];" : "=r"(v.x), "=r"(v.y), "=r"(v.z), "=r"(v.w) : "l"(p) : "memory");
  return v;
}
__device__ __forceinline__ uint2 ld_strong8(const void* p) {
  uint2 v;
  asm volatile("ld.relaxed.gpu.global.v2.u32 {%0,%1}, [%2];" : "=r"(v.x), "=r"(v.y) : "l"(p) : "memory");
  return v;
}
__device__ __forceinline__ void st_pub32(void* p, uint32_t v) { asm volatile("st.relaxed.gpu.global.u32 [%0], %1;" ::"l"(p), "r"(v) : "memory"); }
__device__ __forceinline__ void st_pub16(void* p, uint32_t v) {
  asm volatile("st.relaxed.gpu.global.u16 [%0], %1;" ::"l"(p), "h"((uint16_t)v) : "memory");
}
__device__ __forceinline__ uint32_t ld_strong4(const void* p) {
  uint32_t v;
  asm volatile("ld.relaxed.gpu.global.u32 %0, [%1];" : "=r"(v) : "l"(p) : "memory");
  return v;
}
__device__ __forceinline__ void st_pub64(void* p, uint32_t a, uint32_t b) {
  asm volatile("st.relaxed.gpu.global.v2.u32 [%0], {%1,%2};" ::"l"(p), "r"(a), "r"(b) : "memory");
}
__device__ __forceinline__ void st_pub128(void* p, uint32_t a) {
  asm volatile("st.relaxed.gpu.global.v4.u32 [%0], {%1,%1,%1,%1};" ::"l"(p), "r"(a) : "memory");
}
constexpr uint32_t EMPTY = 0xFFFFFFFFu;
__device__ __forceinline__ uint32_t umax4(const uint4& v) { return max(max(v.x, v.y), max(v.z, v.w)); }
__device__ __forceinline__ void sts128(uint32_t a, uint32_t x, uint32_t y, uint32_t z, uint32_t w) {
  asm volatile("st.shared.v4.u32 [%0], {%1,%2,%3,%4};" ::"r"(a), "r"(x), "r"(y), "r"(z), "r"(w) : "memory");
}
__device__ __forceinline__ void sts64(uint32_t a, uint32_t x, uint32_t y) {
  asm volatile("st.shared.v2.u32 [%0], {%1,%2};" ::"r"(a), "r"(x), "r"(y) : "memory");
}
__device__ __forceinline__ void sts32(uint32_t a, uint32_t x) { asm volatile("st.shared.u32 [%0], %1;" ::"r"(a), "r"(x) : "memory"); }
__device__ __forceinline__ void sts128f(uint32_t a, float x, float y, float z, float w) {
  asm volatile("st.shared.v4.f32 [%0], {%1,%2,%3,%4};" ::"r"(a), "f"(x), "f"(y), "f"(z), "f"(w) : "memory");
}
__device__ __forceinline__ void sts64f(uint32_t a, float x, float y) {
  asm volatile("st.shared.v2.f32 [%0], {%1,%2};" ::"r"(a), "f"(x), "f"(y) : "memory");
}
__device__ __forceinline__ float4 lds128f(uint32_t a) {
  float4 v;
  asm volatile("ld.shared.v4.f32 {%0,%1,%2,%3}, [%4];" : "=f"(v.x), "=f"(v.y), "=f"(v.z), "=f"(v.w) : "r"(a) : "memory");
  return v;
}
__device__ __forceinline__ float2 lds64f(uint32_t a) {
  float2 v;
  asm volatile("ld.shared.v2.f32 {%0,%1}, [%2];" : "=f"(v.x), "=f"(v.y) : "r"(a) : "memory");
  return v;
}
__device__ __forceinline__ float2 lds64f_if(uint32_t a, bool on, float other) {
  float2 v = make_float2(other, other);
  asm volatile("{\n.reg .pred p;\nsetp.ne.u32 p, %3, 0;\n@p ld.shared.v2.f32 {%0,%1}, [%2];\n}" : "+f"(v.x), "+f"(v.y) : "r"(a), "r"((uint32_t)on) : "memory");
  return v;
}
__device__ __forceinline__ void lds128(uint32_t* r, uint32_t a) {
  asm volatile("ld.shared.v4.u32 {%0,%1,%2,%3}, [%4];" : "=r"(r[0]), "=r"(r[1]), "=r"(r[2]), "=r"(r[3]) : "r"(a) : "memory");
}
__device__ __forceinline__ void lds64(uint32_t* r, uint32_t a) {
  asm volatile("ld.shared.v2.u32 {%0,%1}, [%2];" : "=r"(r[0]), "=r"(r[1]) : "r"(a) : "memory");
}
__device__ __forceinline__ uint32_t lds32(uint32_t a) {
  uint32_t v;
  asm volatile("ld.shared.u32 %0, [%1];" : "=r"(v) : "r"(a) : "memory");
  return v;
}
__device__ __forceinline__ void ldsm4(uint32_t* r, uint32_t a) {
  asm volatile("ldmatrix.sync.aligned.m8n8.x4.shared.b16 {%0,%1,%2,%3}, [%4];"
               : "=r"(r[0]), "=r"(r[1]), "=r"(r[2]), "=r"(r[3]) : "r"(a) : "memory");
}
__device__ __forceinline__ void ldsm4t(uint32_t* r, uint32_t a) {
  asm volatile("ldmatrix.sync.aligned.m8n8.x4.trans.shared.b16 {%0,%1,%2,%3}, [%4];"
               : "=r"(r[0]), "=r"(r[1]), "=r"(r[2]), "=r"(r[3]) : "r"(a) : "memory");
}
__device__ __forceinline__ void stsm4(uint32_t a, uint32_t r0, uint32_t r1, uint32_t r2, uint32_t r3) {
  asm volatile("stmatrix.sync.aligned.m8n8.x4.shared.b16 [%0], {%1,%2,%3,%4};"
               ::"r"(a), "r"(r0), "r"(r1), "r"(r2), "r"(r3) : "memory");
}
__device__ __forceinline__ void stsm4t(uint32_t a, uint32_t r0, uint32_t r1, uint32_t r2, uint32_t r3) {
  asm volatile("stmatrix.sync.aligned.m8n8.x4.trans.shared.b16 [%0], {%1,%2,%3,%4};"
               ::"r"(a), "r"(r0), "r"(r1), "r"(r2), "r"(r3) : "memory");
}
__device__ __forceinline__ void mma16816(float* d, const uint32_t* a, uint32_t b0, uint32_t b1) {
  asm volatile("mma.sync.aligned.m16n8k16.row.col.f32.bf16.bf16.f32 {%0,%1,%2,%3}, {%4,%5,%6,%7}, {%8,%9}, {%0,%1,%2,%3};"
               : "+f"(d[0]), "+f"(d[1]), "+f"(d[2]), "+f"(d[3])
               : "r"(a[0]), "r"(a[1]), "r"(a[2]), "r"(a[3]), "r"(b0), "r"(b1));
}
__device__ __forceinline__ void mma16816z(float* d, const uint32_t* a, uint32_t b0, uint32_t b1) {
  asm volatile("mma.sync.aligned.m16n8k16.row.col.f32.bf16.bf16.f32 {%0,%1,%2,%3}, {%4,%5,%6,%7}, {%8,%9}, {%10,%10,%10,%10};"
               : "=f"(d[0]), "=f"(d[1]), "=f"(d[2]), "=f"(d[3])
               : "r"(a[0]), "r"(a[1]), "r"(a[2]), "r"(a[3]), "r"(b0), "r"(b1), "f"(0.f));
}
__device__ __forceinline__ void mma1688(float* d, uint32_t a0, uint32_t a1, uint32_t b0) {
  asm volatile("mma.sync.aligned.m16n8k8.row.col.f32.bf16.bf16.f32 {%0,%1,%2,%3}, {%4,%5}, {%6}, {%0,%1,%2,%3};"
               : "+f"(d[0]), "+f"(d[1]), "+f"(d[2]), "+f"(d[3]) : "r"(a0), "r"(a1), "r"(b0));
}
__device__ __forceinline__ uint32_t movtrans(uint32_t a) {
  uint32_t d;
  asm volatile("movmatrix.sync.aligned.m8n8.trans.b16 %0, %1;" : "=r"(d) : "r"(a));
  return d;
}
__device__ __forceinline__ uint32_t mapa(uint32_t a, uint32_t rank) {
  uint32_t d;
  asm("mapa.shared::cluster.u32 %0, %1, %2;" : "=r"(d) : "r"(a), "r"(rank));
  return d;
}
__device__ __forceinline__ void st_async64(uint32_t a, uint32_t x, uint32_t y, uint32_t bar) {
  asm volatile("st.async.weak.shared::cluster.mbarrier::complete_tx::bytes.v2.b32 [%0], {%1,%2}, [%3];"
               ::"r"(a), "r"(x), "r"(y), "r"(bar) : "memory");
}
__device__ __forceinline__ void st_async64f(uint32_t a, float x, float y, uint32_t bar) {
  st_async64(a, __float_as_uint(x), __float_as_uint(y), bar);
}
__device__ __forceinline__ void bulk_s2s(uint32_t dst, uint32_t src, uint32_t bytes, uint32_t bar) {
  asm volatile("cp.async.bulk.shared::cluster.shared::cta.mbarrier::complete_tx::bytes [%0], [%1], %2, [%3];"
               ::"r"(dst), "r"(src), "r"(bytes), "r"(bar) : "memory");
}
__device__ __forceinline__ void tma_store_3d(const CUtensorMap* map, uint32_t src, int x, int y, int z) {
  asm volatile("cp.async.bulk.tensor.3d.global.shared::cta.bulk_group [%0, {%2, %3, %4}], [%1];"
               ::"l"(map), "r"(src), "r"(x), "r"(y), "r"(z) : "memory");
}
__device__ __forceinline__ void mbar_spin(uint32_t bar, uint32_t parity) {
  asm volatile("{\n.reg .pred p;\n.reg .b32 n;\nmov.u32 n, 0x100000;\nMW_L:\n"
               "mbarrier.try_wait.parity.shared::cta.b64 p, [%0], %1;\n@p bra.uni MW_D;\n"
               "add.s32 n, n, -1;\nsetp.ne.u32 p, n, 0;\n@p bra.uni MW_L;\nMW_D:\n}" ::"r"(bar), "r"(parity) : "memory");
}
__device__ __forceinline__ bool mbar_test(uint32_t bar, uint32_t parity) {
  uint32_t done;
  asm volatile("{\n.reg .pred p;\nmbarrier.test_wait.parity.shared::cta.b64 p, [%1], %2;\nselp.u32 %0, 1, 0, p;\n}"
               : "=r"(done) : "r"(bar), "r"(parity) : "memory");
  return done != 0;
}
__device__ __forceinline__ void mbar_arrive_remote(uint32_t bar) {
  asm volatile("mbarrier.arrive.shared::cluster.b64 _, [%0];" ::"r"(bar) : "memory");
}
__device__ __forceinline__ bool elect_one() {
  uint32_t r;
  asm volatile("{\n.reg .pred p;\nelect.sync _|p, 0xffffffff;\nselp.u32 %0, 1, 0, p;\n}" : "=r"(r));
  return r != 0;
}
__device__ __forceinline__ void st_async32(uint32_t a, uint32_t x, uint32_t bar) {
  asm volatile("st.async.weak.shared::cluster.mbarrier::complete_tx::bytes.b32 [%0], %1, [%2];" ::"r"(a), "r"(x), "r"(bar) : "memory");
}
#define named_bar_and(id, n, in, out) \
  asm volatile("{\n.reg .pred p, q;\nsetp.ne.u32 p, %1, 0;\nbar.red.and.pred q, %2, %3, p;\nselp.u32 %0, 1, 0, q;\n}" \
               : "=r"(out) : "r"(in), "n"(id), "n"(n) : "memory")
__device__ __forceinline__ void bulk_g2s(uint32_t dst, const void* src, uint32_t bytes, uint32_t bar) {
  asm volatile("cp.async.bulk.shared::cluster.global.mbarrier::complete_tx::bytes [%0], [%1], %2, [%3];"
               ::"r"(dst), "l"(src), "r"(bytes), "r"(bar) : "memory");
}
__device__ __forceinline__ void l2_prefetch(const void* p, uint32_t bytes) {
  asm volatile("cp.async.bulk.prefetch.L2.global [%0], %1;" ::"l"(p), "r"(bytes) : "memory");
}

__device__ __forceinline__ uint32_t clk32() { uint32_t c; asm volatile("mov.u32 %0, %%clock;" : "=r"(c)::"memory"); return c; }
__device__ __forceinline__ void spin_until(uint32_t t) { while ((int32_t)(clk32() - t) < 0) {} }
#define PIN(x) asm volatile("" : "+r"(x))
#define OPQ                                                                                     \
  int tid_o = tid;                                                                              \
  asm volatile("" : "+r"(tid_o));                                                               \
  const int lane = tid_o & 31, w = (tid_o >> 5) & 3, t7 = tid_o & 127, lg = lane >> 2,          \
            lq = lane & 3, mi = lane >> 3, mr = lane & 7;                                       \
  (void)w; (void)t7; (void)lg; (void)lq; (void)mi; (void)mr; (void)lane

#define SMAP                                                                                                          \
  const uint32_t SM0 = self + fk::SM0, WO = self + fk::WO, WS = self + fk::WS, XN = self + fk::XN, VX = self + fk::VX, \
                 QK = self + fk::QK, PT = self + fk::PT, SP = self + fk::SP, VM = self + fk::VM, OB = self + fk::OB,   \
                 RED = self + fk::RED, VX2 = self + fk::VX2, MEMB = self + fk::MEMB, B_XN = self + fk::B_XN, B_SM = self + fk::B_SM,       \
                 B_VM = self + fk::B_VM, B_VX = self + fk::B_VX, B_ST = self + fk::B_ST, B_PB = self + fk::B_PB,       \
                 B_W = self + fk::B_W, B_H2 = self + fk::B_H2, B_H1 = self + fk::B_H1, B_PF = self + fk::B_PF, B_WO = self + fk::B_WO, MASKS = self + fk::MASKS, PROBE = self + fk::PROBE;                             \
  (void)SM0; (void)WO; (void)WS; (void)XN; (void)VX; (void)QK; (void)PT; (void)SP; (void)VM; (void)OB; (void)RED; (void)VX2; \
  (void)MEMB; (void)B_XN; (void)B_SM; (void)B_VM; (void)B_VX; (void)B_ST; (void)B_PB; (void)B_W; (void)MASKS; (void)PROBE; (void)B_H2; (void)B_H1; (void)B_PF; (void)B_WO

struct FParams {
  CUtensorMap wq, wk, wv, wo, wo16, xn, xn12, o;
  CUtensorMap ta, tb, tx, tg;
  const bf16 *mem0, *x;
  bf16* out;
  bf16* xn_ptr;
  uint64_t dxn;
  int nprobe;
  char* xch;
};

__device__ __forceinline__ uint2 probe_pair(char* p, uint32_t val, uint32_t dummy, int n) {
  uint2 best = make_uint2(0x7FFFFFFF, 0x7FFFFFFF);
  st_pub128(p, val); st_pub128(p + 16, val); st_pub128(p + 4096, val); st_pub128(p + 4112, val);
#pragma unroll 1
  for (int r = 0; r < n; r++) {
    uint32_t v;
    const uint32_t c0 = clk32();
    asm volatile("atom.relaxed.gpu.global.exch.b32 %0, [%1], %2;" : "=r"(v) : "l"(p + (r & 1) * 4096), "r"(val) : "memory");
    asm volatile("{\n.reg .pred p;\nsetp.eq.u32 p, %0, 0x12345678;\n@p st.shared.u32 [%1], %0;\n}" ::"r"(v), "r"(dummy) : "memory");
    const uint32_t d = clk32() - c0;
    if (r & 1) best.y = min(best.y, d); else best.x = min(best.x, d);
  }
  return best;
}

typedef uint32_t WRegs[6][2][4][4];

constexpr uint32_t nth_chunks(uint32_t mask) {
  uint32_t t = 0;
  for (int c = 0, n = 0; c < 10; c++) if ((mask >> c) & 1) t |= c << (4 * n++);
  return t;
}
constexpr uint64_t chunk_pos(uint32_t mask) {
  uint64_t t = 0;
  for (int c = 0, a = 0, b = 0; c < 10; c++) t |= (uint64_t)(((mask >> c) & 1) ? a++ : b++) << (4 * c);
  return t;
}
template <bool ISV> struct Chunks {
  static constexpr uint32_t MASK = ISV ? SMV : SMQ, SMT = nth_chunks(MASK), RFT = nth_chunks(~MASK & 1023);
  static_assert(!(MASK & 1), "the first chunk initialises the accumulators");
  static __device__ __forceinline__ constexpr int rf(int wg, int i) { return wg ? 10 + i : (RFT >> (4 * i)) & 15; }
  static __device__ __forceinline__ constexpr int sm(int i) { return (SMT >> (4 * i)) & 15; }
  static constexpr uint64_t IDX = chunk_pos(MASK);
  static __device__ __forceinline__ constexpr int idx(int c) { return (IDX >> (4 * c)) & 15; }
};

template <bool ISV, int WG> struct ProjCfg {
  static constexpr int N0 = ISV ? NS0V : NS0, NS = WG ? 8 - N0 : N0, P0 = WG ? N0 : 0, NTA = WG ? NTA1 : NTA0;
};
__device__ __forceinline__ void load_pair(uint32_t (&t)[4][4], uint32_t wsa, int pp) {
#pragma unroll
  for (int f = 0; f < 4; f++) ldsm4t(t[f], wsa + ((pp >> 1) * 2 + (f & 1)) * 8192 + ((pp & 1) * 2 + (f >> 1)) * 2048);
}
template <bool ISV, int WG>
__device__ __forceinline__ void proj_mem(const WRegs& wr, uint32_t (&ta)[ProjCfg<ISV, WG>::NTA][4][4], uint32_t wsa, uint32_t mba,
                                         float (&a0)[4], float (&a1)[4]) {
  constexpr int NS = ProjCfg<ISV, WG>::NS, P0 = ProjCfg<ISV, WG>::P0, NTA = ProjCfg<ISV, WG>::NTA, NP = 12 + NS;
  float acc[4][4];
  auto spos = [](int j) { return j < NTA ? j : j + (j - NTA + 1) * 12 / (NS - NTA > 0 ? NS - NTA : 1); };
  auto which = [&](int p) { int r = -1; for (int j = 0; j < NS; j++) if (spos(j) == p) r = j; return r; };
  auto nsm_before = [&](int p) { int n = 0; for (int j = 0; j < NS; j++) if (spos(j) < p) n++; return n; };
#pragma unroll
  for (int p = 0; p < NP; p++) {
    const int j = which(p), r = j >= 0 ? 0 : p - nsm_before(p);
    uint32_t bp[4], tl[4][4];
    ldsm4(bp, mba + (j >= 0 ? Chunks<ISV>::sm((P0 + (j >= 0 ? j : 0)) >> 1) * 1024 + ((P0 + j) & 1) * 512 : Chunks<ISV>::rf(WG, r >> 1) * 1024 + (r & 1) * 512));
    if (j >= NTA) load_pair(tl, wsa, P0 + j);
#pragma unroll
    for (int u = 0; u < 2; u++)
#pragma unroll
      for (int T = 0; T < 2; T++) {
        const uint32_t* a = j >= NTA ? tl[u * 2 + T] : j >= 0 ? ta[j >= 0 ? j % NTA : 0][u * 2 + T] : wr[r >> 1][T][(r & 1) * 2 + u];
        if (p == 0) mma16816z(acc[u * 2 + T], a, bp[2 * u], bp[2 * u + 1]);
        else mma16816(acc[u * 2 + T], a, bp[2 * u], bp[2 * u + 1]);
      }
  }
#pragma unroll
  for (int i = 0; i < 4; i++) { a0[i] = acc[0][i] + acc[2][i]; a1[i] = acc[1][i] + acc[3][i]; }
}
template <bool ISV, int WG, int J0, int J1>
__device__ __forceinline__ void proj_mem_prefetch(uint32_t (&ta)[ProjCfg<ISV, WG>::NTA][4][4], uint32_t wsa) {
#pragma unroll
  for (int j = J0; j < J1; j++) load_pair(ta[j], wsa, ProjCfg<ISV, WG>::P0 + j);
}

template <bool ISV, int WG>
__device__ __forceinline__ void proj_finish(const float (&a0)[4], const float (&a1)[4], uint32_t peer0, uint32_t peer1, uint32_t self, int tid, int warp,
                                            uint32_t (&vmo)[4]) {
  using namespace fk;
  SMAP;
  OPQ;
  if (!ISV) {
    stsm4(PT + mr * 16 + ((mi >> 1) ? WG * 1024 + w * 256 + (mi & 1) * 128 : 2048 + w * 512 + (mi & 1) * 256 + WG * 128),
          pack_bf16(a0[0], a0[1]), pack_bf16(a0[2], a0[3]), pack_bf16(a1[0], a1[1]), pack_bf16(a1[2], a1[3]));
    named_bar_sync(NB_C, 256);
  } else {
    if (WG == 0) sts128f(RED + t7 * 16, a1[0], a1[1], a1[2], a1[3]);
    else sts128f(RED + 2048 + t7 * 16, a0[0], a0[1], a0[2], a0[3]);
    if (WG == 1) { lds64(vmo, VM + t7 * 8); lds64(vmo + 2, VM + 1024 + t7 * 8); }
    named_bar_sync(NB_C, 256);
    const float4 p = lds128f(RED + (1 - WG) * 2048 + t7 * 16);
    const float* k = WG == 0 ? a0 : a1;
    const uint32_t v0 = pack_bf16(k[0] + p.x, k[1] + p.y), v1 = pack_bf16(k[2] + p.z, k[3] + p.w);
    const uint32_t off = VM + WG * 1024 + t7 * 8;
    if (VM_BULK) {
      sts64(off, v0, v1);
      fence_proxy_async_smem();
      __syncwarp();
      const uint32_t a = VM + WG * 1024 + warp * 256;
      if (elect_one()) {
        bulk_s2s(peer0 + a, a, 256, peer0 + B_VM);
        bulk_s2s(peer1 + a, a, 256, peer1 + B_VM);
        mbar_arrive(B_VM);
      }
    } else {
      st_async64(peer0 + off, v0, v1, peer0 + B_VM);
      st_async64(peer1 + off, v0, v1, peer1 + B_VM);
      sts64(off, v0, v1);
      __syncwarp();
      if (lane == 0) mbar_arrive(B_VM);
    }
  }
}

__device__ __forceinline__ void send_scores(float s0, float s1, uint32_t off, uint32_t peer0, uint32_t peer1, uint32_t bar, int lane) {
  if (SPACK) {
    const uint32_t v = pack_bf16(s0, s1);
    st_async32(peer0 + off, v, peer0 + bar);
    st_async32(peer1 + off, v, peer1 + bar);
    sts32(off, v);
  } else {
    st_async64f(peer0 + off, s0, s1, peer0 + bar);
    st_async64f(peer1 + off, s0, s1, peer1 + bar);
    sts64f(off, s0, s1);
  }
  __syncwarp();
  if (lane == 0) mbar_arrive(bar);
}

template <int MODE>
__device__ __forceinline__ void wo_load(uint32_t* r, int f, uint32_t woa, uint32_t wob, bool third) {
  constexpr int NT = MODE ? 3 : 2;
  if (MODE >= 2 && f % 3 == 2)
    asm volatile("{\n.reg .pred p;\nsetp.ne.u32 p, %5, 0;\nmov.b32 %0, 0;\nmov.b32 %1, 0;\nmov.b32 %2, 0;\nmov.b32 %3, 0;\n"
                 "@p ldmatrix.sync.aligned.m8n8.x4.trans.shared.b16 {%0,%1,%2,%3}, [%4];\n}"
                 : "=r"(r[0]), "=r"(r[1]), "=r"(r[2]), "=r"(r[3]) : "r"(wob + (f / 3) * 512), "r"((uint32_t)third) : "memory");
  else ldsm4t(r, woa + (f % NT) * 32768 + (f / NT) * 2048);
}
template <int MODE, int PF>
__device__ __forceinline__ void wo_phase(uint32_t (&wf)[PF][4], uint32_t woa, uint32_t wob, bool third, uint32_t oba, char* h1p,
                                         uint32_t sel, uint32_t tag) {
  constexpr int NT = MODE ? 3 : 2;
  float c[NT][4];
  uint32_t of[2][4];
  ldsm4t(of[0], oba);
#pragma unroll
  for (int k = 0; k < 8; k++) {
    if ((k & 1) == 0 && k + 2 < 8) ldsm4t(of[((k >> 1) + 1) & 1], oba + ((k >> 1) + 1) * 512);
#pragma unroll
    for (int i = 0; i < NT; i++) {
      const int f = k * NT + i;
      const uint32_t b0 = of[(k >> 1) & 1][2 * (k & 1)], b1 = of[(k >> 1) & 1][2 * (k & 1) + 1];
      if (k == 0) mma16816z(c[i], wf[f % PF], b0, b1); else mma16816(c[i], wf[f % PF], b0, b1);
      if (f + PF < 8 * NT) wo_load<MODE>(wf[f % PF], f + PF, woa, wob, third);
    }
  }
#pragma unroll
  for (int i = 0; i < NT; i++) {
    char* p = h1p + i * (8 * 32768) + ((sel >> (2 * i)) & 3) * 2048;
    const uint32_t tm = (sel >> 10) & 1;
    if (MODE < 2 || i < 2 || third) {
      st_pub32(p, (pack_bf16(c[i][0], c[i][1]) & ~tm) | (tag & tm));
      st_pub32(p + 1024, (pack_bf16(c[i][2], c[i][3]) & ~tm) | (tag & tm));
    }
  }
}
template <int MODE, int F0, int F1, int PF>
__device__ __forceinline__ void wo_prefetch(uint32_t (&wf)[PF][4], uint32_t woa, uint32_t wob, bool third) {
#pragma unroll
  for (int f = F0; f < F1; f++) wo_load<MODE>(wf[f], f, woa, wob, third);
}

template <bool ISV> __device__ __forceinline__ uint32_t tok_addr(uint32_t base, int tid) {
  OPQ;
  return ISV ? base + w * 2048 + (mi & 1) * 1024 + (mi >> 1) * 128 + mr * 16 : base + (mi >> 1) * 1024 + w * 256 + (mi & 1) * 128 + mr * 16;
}
template <bool ISV> __device__ __forceinline__ constexpr uint32_t tok_off(int T, int i) { return ISV ? T * 512 + i * 256 : T * 4096 + i * 2048; }
template <bool ISV, int T, bool ADD>
__device__ __forceinline__ void tok_store(const float (&x)[16], uint32_t a, const uint32_t (&p)[2][4]) {
#pragma unroll
  for (int i = 0; i < 2; i++) {
    uint32_t r[4];
#pragma unroll
    for (int k = 0; k < 4; k++)
      r[k] = !ADD ? pack_bf16(x[8 * i + 2 * k], x[8 * i + 2 * k + 1])
           : PADD ? add_bf16x2(pack_bf16(x[8 * i + 2 * k], x[8 * i + 2 * k + 1]), p[i][k])
                  : pack_bf16(x[8 * i + 2 * k] + bf_lo(p[i][k]), x[8 * i + 2 * k + 1] + bf_hi(p[i][k]));
    stsm4(a + tok_off<ISV>(T, i), r[0], r[1], r[2], r[3]);
  }
}

__device__ __forceinline__ void load_xn(const FParams& P, int seg, uint32_t self) {
  SMAP;
  mbar_expect_tx(B_XN, 49152);
  tma_load_3d(XN, &P.xn12, 0, seg * 32, 0, B_XN);
}

#define DESC_ADD(d, n) asm volatile("add.s64 %0, %0, %1;" : "+l"(d) : "n"(n))

template <bool ISV>
__device__ __forceinline__ void f_wg0(const FParams& P, const WRegs& wr, const int h, const int rank, const uint32_t hw, int tid) {
  using namespace fk;
  const uint32_t self = mapa(0, (hw >> (2 * rank)) & 3), peer0 = mapa(0, (hw >> (ISV ? 0 : 2 * (rank ^ 1))) & 3) - self,
                 peer1 = mapa(0, (hw >> (ISV ? 2 : 4)) & 3) - self;
  SMAP;
  const int tile0 = rank * 22;
  const uint32_t usel = __shfl_sync(0xffffffffu, tid, 0);
  const int warp = __shfl_sync(0xffffffffu, threadIdx.x >> 5, 0);
  constexpr int WMODE = ISV ? 0 : 2;
  const bool three = warp < 2;
  uint32_t d_h2 = D_H2V, h2ph = 1;
  tid ^= 0x5500;
#pragma unroll 1
  for (int s = -1;;) {
    uint32_t ta[ProjCfg<ISV, 0>::NTA][4][4], wsa, mba;
    const char* src = P.xch + H1_BYTES + ((s & 1) * 4 + warp) * 8192 + ((usel >> (16 + (s & 1))) & 1) * 4096;
    {
      const uint32_t ph = (s + 1) & 1;
      float x0[16], x1[16];
      uint32_t t_pub = 0;
      wg_fence();
      static_assert(Chunks<ISV>::MASK == 0x1E, "chunks 1 .. 4 are in shared memory");
      uint64_t db = P.dxn;
      auto rs_chunk = [&](int ci, bool pace) {
#pragma unroll
        for (int u = 0; u < 4; u++) {
          wgmma_rs_n32(x0, wr[ci][0][u], db, (ci | u) != 0);
          wgmma_rs_n32(x1, wr[ci][1][u], db, (ci | u) != 0);
          if (u < 3) DESC_ADD(db, 2); else DESC_ADD(db, 250);
          if (pace) { wg_commit(); wg_wait<2>(); wg_fence(); }
        }
      };
      rs_chunk(0, false);
      t_pub = clk32() - 60;
      PROF(0, 8); PROF(0, 1);
#pragma unroll
      for (int c = 1; c <= 4; c++) {
#pragma unroll
        for (int u = 0; u < 4; u++) {
          const uint64_t dx = make_desc(fk::XN + c * 4096 + u * 32, 16, 1024);
          wgmma_ss_n32_ta(x0, make_desc(fk::WS + (c - 1) * 16384 + u * 2048, 8192, 1024), dx, 1);
          wgmma_ss_n32_ta(x1, make_desc(fk::WS + (c - 1) * 16384 + 8192 + u * 2048, 8192, 1024), dx, 1);
          if (c == 4 && u == 1) { wg_commit(); wg_wait<1>(); named_bar_arrive(NB_XE, 160); wg_fence(); }
        }
        if (c == 3) wg_commit();
      }
      DESC_ADD(db, 1024);
#pragma unroll
      for (int c = 5; c < 10; c++) {
        if (c == 9) named_bar_arrive(NB_ST, 256);
        rs_chunk(c - 4, ((ISV ? PACEV : PACEQ) >> c) & 1);
      }
      wg_commit();
      wg_wait<0>();
      PROF(0, 10);
      const uint32_t tb = ISV ? (ph ? VX2 : VX) : QK;
      auto h2_issue = [&]() {
        spin_until(t_pub + (ISV ? d_h2 : D_H2));
        PROF(0, 13);
        if (elect_one()) { mbar_expect_tx(B_H2 + 8 * warp, 4096); bulk_g2s(MEMB + warp * 4096, src, 4096, B_H2 + 8 * warp); }
      };
      named_bar_sync(NB_CF, ISV ? 160 : 256);
      if ((ISV ? H2_ATV : H2_AT) == 0) h2_issue();
      const uint32_t none[2][4] = {}, tka = tok_addr<ISV>(tb, tid);
      tok_store<ISV, 0, false>(x0, tka, none);
      if ((ISV ? H2_ATV : H2_AT) == 1) h2_issue();
      tok_store<ISV, 1, false>(x1, tka, none);
      if ((ISV ? H2_ATV : H2_AT) == 2) h2_issue();
      named_bar_arrive(NB_DU, 256);
    }
    {
      OPQ;
      wsa = WS + ((mi >> 1) * 8 + mr) * 128 + (((2 * w + (mi & 1)) ^ mr) << 4);
      mba = MEMB + lane * 16;
      PIN(wsa); PIN(mba);
      {
        const uint32_t chk = MEMB + w * 4096 + lane * 32 + lg * 4, bar = B_H2 + 8 * warp;
        PROF(0, 11);
        proj_mem_prefetch<ISV, 0, 0, NPRE0>(ta, wsa);
#pragma unroll 1
        for (int tries = 0; tries < POLL_TRIES; tries++) {
          mbar_spin(bar, h2ph);
          h2ph ^= 1;
          const uint32_t mx = max(max(lds32(chk), lds32(chk + 1024)), max(lds32(chk + 2048), lds32(chk + 3072)));
          if (__all_sync(0xffffffffu, mx != EMPTY)) break;
          RETRY(1);
          if (elect_one()) { mbar_expect_tx(bar, 4096); bulk_g2s(MEMB + warp * 4096, src, 4096, bar); }
        }
      }
      PROF(0, 12);
      named_bar_arrive(NB_M1, 256);
      proj_mem_prefetch<ISV, 0, NPRE0, NTA0>(ta, wsa);
      named_bar_sync(NB_M0, 128);
    }
    s++;
    tid ^= 0x5500;
    {
      float a0[4], a1[4];
      proj_mem<ISV, 0>(wr, ta, wsa, mba, a0, a1);
      PROF(0, 2);
      uint32_t unused[4];
      proj_finish<ISV, 0>(a0, a1, peer0, peer1, self, tid, warp, unused);
      PROF(0, 3);
      if (s + 1 == cfg::NSEG) break;
      uint32_t wf[PF0][4], woa, wob;
      bool xn_ok;
      {
        OPQ;
        if (!ISV) {
          uint32_t qf[4][4], kf[2][4];
          const uint32_t qa = PT + 2048 + lane * 16, ka = QK + 4096 + w * 1024 + lane * 16;
          ldsm4t(qf[0], qa); ldsm4t(kf[0], ka); ldsm4t(qf[1], qa + 512);
          ldsm4t(qf[2], qa + 1024); ldsm4t(kf[1], ka + 512); ldsm4t(qf[3], qa + 1536);
          float c0[4], c1[4];
          mma16816z(c0, qf[0], kf[0][0], kf[0][1]);
          mma16816z(c1, qf[1], kf[0][2], kf[0][3]);
          mma16816(c0, qf[2], kf[1][0], kf[1][1]);
          mma16816(c1, qf[3], kf[1][2], kf[1][3]);
          const float s0 = (c0[0] + c0[2]) + (c1[0] + c1[2]), s1 = (c0[1] + c0[3]) + (c1[1] + c1[3]);
          send_scores(s0, s1, SP + rank * SP_SRC + t7 * SPW, peer0, peer1, B_SM, lane);
        }
        PROF(0, 4);
        woa = WO + 16384 + ((mi >> 1) * 8 + mr) * 128 + (((2 * w + (mi & 1)) ^ mr) << 4);
        wob = WO + 81920 + w * 4096 + ((mi >> 1) * 8 + mr) * 32 + (((mi & 1) ^ (mr >> 2)) << 4);
        uint32_t vf[2][2][4], vm[2][2];
        if (s == 0) mbar_spin(B_WO, 0);
        if (!ISV) mbar_spin(B_VX, s & 1);
        PROF(0, 14);
#pragma unroll
        for (int T = 0; T < 2; T++)
#pragma unroll
          for (int kk = 0; kk < 2; kk++) ldsm4(vf[T][kk], ((ISV && (s & 1)) ? VX2 : VX) + w * 2048 + (mi & 1) * 1024 + (mi >> 1) * 128 + mr * 16 + T * 512 + kk * 256);
        wo_prefetch<WMODE, 0, PF0A>(wf, woa, wob, three);
        uint32_t spa = SP + lane * SPW, vma = VM + t7 * 8, oa = OB + (mi >> 1) * 1024 + w * 256 + (mi & 1) * 128 + mr * 16;
        PIN(spa); PIN(vma); PIN(oa);
        if (ISV) {
          d_h2 = D_H2L;
          if (!__all_sync(0xffffffffu, mbar_test(B_SM, s & 1))) { d_h2 = D_H2V; mbar_spin(B_SM, s & 1); }
        } else {
          mbar_spin(B_SM, s & 1);
        }
        PROF(0, 5);
        float sc[10];
#pragma unroll
        for (int j = 0; j < 5; j++) {
          if (SPACK) {
            const uint32_t x = lds32(spa + j * 128), y = lds32(spa + SP_SRC + j * 128);
            sc[2 * j] = bf_lo(x) + bf_lo(y); sc[2 * j + 1] = bf_hi(x) + bf_hi(y);
          } else {
            const float2 x = lds64f(spa + j * 256), y = lds64f(spa + SP_SRC + j * 256);
            sc[2 * j] = x.x + y.x; sc[2 * j + 1] = x.y + y.y;
          }
        }
        const bool vm_ok = mbar_test(B_VM, s & 1);
        lds64(vm[0], vma); lds64(vm[1], vma + 1024);
        float m = fmaxf(fmaxf(fmaxf(sc[0], sc[1]), fmaxf(sc[2], sc[3])), fmaxf(fmaxf(sc[4], sc[5]), fmaxf(sc[6], sc[7])));
        m = fmaxf(m, fmaxf(sc[8], sc[9]));
        const float cs = 0.08838834764831845f * 1.4426950408889634f;
        uint32_t pb[5];
        m = fmaxf(m, __shfl_xor_sync(0xffffffffu, m, 1));
        m = fmaxf(m, __shfl_xor_sync(0xffffffffu, m, 2));
        if (ISV ? GATE_MX : GATE_Q) named_bar_arrive(NB_MX, 256);
        const float mc = -m * cs;
#pragma unroll
        for (int j = 0; j < 5; j++) pb[j] = pack_bf16(ex2_approx(fmaf(sc[2 * j], cs, mc)), ex2_approx(fmaf(sc[2 * j + 1], cs, mc)));
        PROF(0, 15);
        if (!vm_ok) { mbar_spin(B_VM, s & 1); lds64(vm[0], vma); lds64(vm[1], vma + 1024); }
        PROF(0, 6);
        float o0[4], o1[4], rs[4];
        const uint32_t ones[4] = {0x3F803F80u, 0x3F803F80u, 0x3F803F80u, 0x3F803F80u};
        mma16816z(rs, ones, pb[0], pb[1]);
        mma16816z(o0, vf[0][0], pb[0], pb[1]);
        mma16816z(o1, vf[1][0], pb[0], pb[1]);
        mma16816(rs, ones, pb[2], pb[3]);
        mma16816(o0, vf[0][1], pb[2], pb[3]);
        mma16816(o1, vf[1][1], pb[2], pb[3]);
        mma1688(rs, ones[0], ones[0], pb[4]);
        mma1688(o0, vm[0][0], vm[0][1], pb[4]);
        mma1688(o1, vm[1][0], vm[1][1], pb[4]);
        const float i0 = rcp_approx(rs[0]), i1 = rcp_approx(rs[1]);
        stsm4(oa, pack_bf16(o0[0] * i0, o0[1] * i1), pack_bf16(o0[2] * i0, o0[3] * i1),
              pack_bf16(o1[0] * i0, o1[1] * i1), pack_bf16(o1[2] * i0, o1[3] * i1));
      }
      {
        OPQ;
        named_bar_arrive(NB_O, 256);
        wo_prefetch<WMODE, PF0A, PF0>(wf, woa, wob, three);
        xn_ok = mbar_test(B_XN, (s + 1) & 1);
        char* h1p = P.xch + (tile0 + 4 + w) * 32768 + (h >> 3) * 8192 + (h & 7) * 128 + (((2 * lq + (lg & 1)) ^ (h & 7)) << 4) + (lg >> 1) * 4;
        uint32_t oba = OB + lane * 16;
        PIN(oba);
        PROF(0, 7);
        named_bar_sync(NB_O0, 128);
        const uint32_t tag = ((s >> 1) & 1) ^ 1;
        wo_phase<WMODE>(wf, woa, wob, three, oba, h1p, tid >> 8, tag);
        PROF(0, 9);
        if (!xn_ok) mbar_spin(B_XN, (s + 1) & 1);
        named_bar_sync(NB_HD, 256);
      }
    }
  }
}

template <bool ISV>
__device__ __forceinline__ void f_wg1(const FParams& P, const WRegs& wr, const int h, const int rank, const uint32_t hw, int tid) {
  using namespace fk;
  const uint32_t self = mapa(0, (hw >> (2 * rank)) & 3), peer0 = mapa(0, (hw >> (ISV ? 0 : 2 * (rank ^ 1))) & 3) - self,
                 peer1 = mapa(0, (hw >> (ISV ? 2 : 4)) & 3) - self;
  SMAP;
  const int tile0 = rank * 22;
  const uint32_t usel = __shfl_sync(0xffffffffu, tid, 0);
  const int warp = __shfl_sync(0xffffffffu, (threadIdx.x >> 5) & 3, 0);
  constexpr int WMODE = 1;
  uint32_t h1ph = 0;
  auto o_done = [&](int mb) {
    tma_store_wait_all();
    asm volatile("fence.proxy.async.global;" ::: "memory");
    asm volatile("red.relaxed.gpu.global.add.u32 [%0], 1;" ::"l"(&g_oflag[mb]) : "memory");
  };
  uint32_t vmo[4] = {0, 0, 0, 0};
  if (ISV) {
    OPQ;
    sts32(PT + (t7 >> 2) * 128 + ((5 ^ lg) << 4) + lq * 4, 0);
    sts32(PT + (t7 >> 2) * 128 + ((6 ^ lg) << 4) + lq * 4, 0);
  }
  tid ^= 0x5500;
#pragma unroll 1
  for (int s = -1;;) {
    uint32_t ta[ProjCfg<ISV, 1>::NTA][4][4], wsa, mba;
    if (s + 1 < cfg::NSEG) mbar_spin(B_XN, (s + 1) & 1);
    const uint32_t t_pub = clk32();
    auto refill = [&]() {
      if (warp == 3) {
        named_bar_sync(NB_XE, 160);
        if (elect_one()) {
          mbar_expect_tx(B_XN + 8, 16384);
          tma_load_3d(XN, &P.xn, 0, (s + 1) * 32, 12, B_XN + 8);
        }
      }
    };
    auto arm = [&]() {
      if ((tid & 255) == 160) {
        if (s == 1) st_pub32(&g_mask[3 * h + rank], 0);
        if (s + 2 < cfg::NSEG) { mbar_expect_tx(B_SM, ISV ? 2 * SP_SRC : SP_SRC); if (!ISV) mbar_expect_tx(B_VX, 8192); }
        if (!ISV && s + 1 < cfg::NSEG) mbar_expect_tx(B_VM, 2048);
        if (ISV && s >= 1 && s < cfg::NSEG) mbar_expect_tx(B_ST, 7168);
      }
      if (ISV && s < cfg::NSEG && (tid & 254) == 192) mbar_arrive_remote(((tid & 1) ? peer1 : peer0) + B_ST);
      __syncwarp();
    };
    if (ISV) {
      if (s >= 0) arm();
      if (s >= 1) {
        OPQ;
        if (warp == 0 && (s & 3) == 1 && s > 1) { if (elect_one()) o_done((s - 2) >> 2); }
        const uint32_t vb = (s & 1) ? VX : VX2;
        float x0[16], x1[16];
        wg_fence();
        wgmma_rs_n32(x0, vmo, make_desc(fk::PT + 64, 16, 1024), 0);
        wgmma_rs_n32(x1, vmo, make_desc(fk::PT + 96, 16, 1024), 0);
#pragma unroll
        for (int kk = 0; kk < 2; kk++) {
          wgmma_ss_n32(x0, make_desc0(vb + kk * 256, 128, 1024), make_desc(fk::PT + kk * 32, 16, 1024), 1);
          wgmma_ss_n32(x1, make_desc0(vb + 512 + kk * 256, 128, 1024), make_desc(fk::PT + kk * 32, 16, 1024), 1);
        }
        wg_commit();
        wg_wait<0>();
        named_bar_sync(NB_W1, 128);
        PROF(1, 4);
        const uint32_t stg = vb + (8 * (mi >> 1) + mr) * 128 + (((2 * w + (mi & 1)) ^ mr) << 4);
#pragma unroll
        for (int T = 0; T < 2; T++) {
          const float* x = T ? x1 : x0;
#pragma unroll
          for (int jj = 0; jj < 4; jj += 2)
            stsm4t(stg + T * 4096 + jj * 1024, pack_bf16(x[4 * jj], x[4 * jj + 1]), pack_bf16(x[4 * jj + 2], x[4 * jj + 3]),
                   pack_bf16(x[4 * jj + 4], x[4 * jj + 5]), pack_bf16(x[4 * jj + 6], x[4 * jj + 7]));
        }
        fence_proxy_async_smem();
        named_bar_sync(NB_W1, 128);
        PROF(1, 10);
        if (warp == 0) {
          if (elect_one()) {
            tma_store_3d(&P.o, vb, 0, (s - 1) * 32, 2 * h);
            tma_store_commit();
          }
          __syncwarp();
        }
        if (s == cfg::NSEG) break;
      }
      if (s + 1 < cfg::NSEG) refill();
      PROF(1, 11);
    } else if (s < 0) {
      named_bar_arrive(NB_CF, 256);
      refill();
    } else {
      float x[24];
      wg_fence();
#pragma unroll
      for (int k = 0; k < 4; k++) wgmma_ss_n48_tt(x, make_desc0(fk::QK + k * 256, 128, 1024), make_desc0(fk::QK + 4096 + k * 256, 128, 1024), k != 0);
      wg_commit();
      arm();
      auto send_tok = [&]() {
        if (warp < 2) {
          OPQ;
          const uint32_t d0 = peer1 + QK + rank * 3584 + lane * 8 + w * 1280, d1 = d0 + 512 + w * 512, bar = peer1 + B_ST;
          mbar_spin(B_ST, s & 1);
          const float NEG = -500000000.0f / 0.08838834764831845f;
          const bool m0 = 2 * lq > lg, m1 = 2 * lq + 1 > lg;
          st_async64f(d0, x[16] + x[20], x[17] + x[21], bar);
          st_async64f(d1, x[18] + x[22], x[19] + x[23], bar);
          st_async64f(d1 + 256, x[2], x[3], bar);
          if (warp == 0) {
            st_async64f(d0 + 256, m0 ? NEG : x[0], m1 ? NEG : x[1], bar);
            st_async64f(d1 + 512, m0 ? NEG : x[6], m1 ? NEG : x[7], bar);
          } else {
            st_async64f(d0 + 256, x[0], x[1], bar);
            st_async64f(d1 + 512, x[6], x[7], bar);
            st_async64f(d0 + 512, x[4], x[5], bar);
            st_async64f(d0 + 768, m0 ? NEG : x[8], m1 ? NEG : x[9], bar);
            st_async64f(d1 + 768, x[10], x[11], bar);
            st_async64f(d1 + 1024, m0 ? NEG : x[14], m1 ? NEG : x[15], bar);
          }
        }
        PROF(1, 4);
      };
      const bool fin = s + 1 == cfg::NSEG;
      OPQ;
      const int j = 2 * h + rank;
      const char* src = P.xch + j * 32768 + warp * 8192 + (((usel >> 14) & 2) + (s & 1)) * 2048;
      char* dst = P.xch + H1_BYTES + (j >> 4) * 8192 + (lq >> 1) * 4096 + (j & 15) * 256 + (lq & 1) * 128 + (2 * w + (lg & 1)) * 16 + (lg >> 1) * 4;
      const uint32_t chk = VX + mi * 2048 + mr * 128 + (w ^ (mr >> 1)) * 32 + ((lane & 1) + 2 * mi) * 4;
      const uint32_t tmask = (s >> 1) & 1;
      if (!fin) {
        spin_until(t_pub + D_H1);
        if (elect_one()) { mbar_expect_tx(B_H1, 2048); bulk_g2s(VX + warp * 2048, src, 2048, B_H1); }
      }
      __syncwarp();
      wg_wait<0>();
      PROF(1, 6);
      send_tok();
      if (fin) { mbar_spin(B_VM, s & 1); break; }
      named_bar_arrive(NB_CF, 256);
      if (REFILL_EARLY) refill();
#pragma unroll 1
      for (int tries = 0; tries < POLL_TRIES; tries++) {
        float d0[4], d1[4], d2[4], d3[4];
        mbar_spin(B_H1, h1ph);
        h1ph ^= 1;
        PROF(1, 10);
        const uint32_t t0 = lds32(chk), t1 = lds32(chk + 1024);
        wg_fence();
        const uint64_t ones = (uint64_t)(fk::ONES >> 4);
        wgmma_ss_n8_ta(d0, make_desc(fk::VX, 8192, 2048), ones, 0);
        wgmma_ss_n8_ta(d1, make_desc(fk::VX + 1024, 8192, 2048), ones, 0);
        wgmma_ss_n8_ta(d2, make_desc(fk::VX + 4096, 8192, 2048), ones, 0);
        wgmma_ss_n8_ta(d3, make_desc(fk::VX + 5120, 8192, 2048), ones, 0);
        wg_commit();
        uint32_t tt;
        asm volatile("lop3.b32 %0, %1, %2, %3, 0x42;" : "=r"(tt) : "r"(t0), "r"(t1), "r"(tmask) : "memory");
        uint32_t ok;
        named_bar_and(NB_W1, 128, tt & 1, ok);
        if (!ok) { if (elect_one()) { mbar_expect_tx(B_H1, 2048); bulk_g2s(VX + warp * 2048, src, 2048, B_H1); } }
        wg_wait<0>();
        if (ok) {
          st_pub32(dst + (s & 1) * 32768, (lq & 1) ? pack_bf16(d1[0] + d3[0], d1[2] + d3[2]) : pack_bf16(d0[0] + d2[0], d0[2] + d2[2]));
          PROF(1, 12);
          st_pub32(dst + ((s & 1) ^ 1) * 32768, EMPTY);
          break;
        }
        RETRY(0);
      }
      named_bar_sync(NB_W1, 128);
      if ((tid & 255) == 192) mbar_arrive_remote(peer1 + B_PF);
      __syncwarp();
      if (!REFILL_EARLY) refill();
      PROF(1, 11);
    }
    if (!ISV || s + 1 < cfg::NSEG) {
      const uint32_t ph = (s + 1) & 1;
      float x0[16], x1[16];
      uint64_t db = P.dxn + 10 * 256;
      named_bar_sync(NB_ST, 256);
      wg_fence();
#pragma unroll
      for (int c = 0; c < 6; c++) {
        if (c == 2) { PROF(1, 0); mbar_spin(B_XN + 8, ph); PROF(1, 15); wg_fence(); }
        if (ISV && c == CF_AT) {
          if (warp == 0) {
            if (elect_one()) tma_store_wait_read();
            __syncwarp();
            named_bar_arrive(NB_CF, 160);
          }
          wg_fence();
        }
#pragma unroll
        for (int u = 0; u < 4; u++) {
          wgmma_rs_n32(x0, wr[c][0][u], db, (c | u) != 0);
          wgmma_rs_n32(x1, wr[c][1][u], db, (c | u) != 0);
          if (u < 3) DESC_ADD(db, 2); else if (c == 1) DESC_ADD(db, 250 - 12 * 256); else DESC_ADD(db, 250);
        }
      }
      wg_commit();
      OPQ;
      const uint32_t tb = ISV ? (ph ? VX2 : VX) : QK, tka = tok_addr<ISV>(tb, tid);
      uint32_t p0[2][4], p1[2][4];
      named_bar_sync(NB_DU, 256);
      ldsm4(p1[0], tka + tok_off<ISV>(1, 0)); ldsm4(p1[1], tka + tok_off<ISV>(1, 1));
      ldsm4(p0[0], tka + tok_off<ISV>(0, 0)); ldsm4(p0[1], tka + tok_off<ISV>(0, 1));
      if (ISV && s >= 0) mbar_spin(B_PF, s & 1);
      wg_wait<0>();
      PROF(1, 13);
      tok_store<ISV, 1, true>(x1, tka, p1);
      tok_store<ISV, 0, true>(x0, tka, p0);
      if (ISV && s + 2 < cfg::NSEG) {
        fence_proxy_async_smem();
        __syncwarp();
        if (elect_one()) {
          bulk_s2s(peer0 + VX + warp * 2048, tb + warp * 2048, 2048, peer0 + B_VX);
          bulk_s2s(peer1 + VX + warp * 2048, tb + warp * 2048, 2048, peer1 + B_VX);
        }
      }
      wsa = WS + ((mi >> 1) * 8 + mr) * 128 + (((2 * w + (mi & 1)) ^ mr) << 4);
      mba = MEMB + lane * 16;
      PIN(wsa); PIN(mba);
      proj_mem_prefetch<ISV, 1, 0, NTA1>(ta, wsa);
      PROF(1, 14);
      named_bar_sync(NB_M1, 256);
      s++;
      PROF(1, 1);
      float a0[4], a1[4];
      proj_mem<ISV, 1>(wr, ta, wsa, mba, a0, a1);
      PROF(1, 2);
      proj_finish<ISV, 1>(a0, a1, peer0, peer1, self, tid, warp, vmo);
      PROF(1, 3);
    } else {
      OPQ;
      mbar_spin(B_VM, s & 1);
      lds64(vmo, VM + t7 * 8); lds64(vmo + 2, VM + 1024 + t7 * 8);
      s++;
    }
    tid ^= 0x5500;
    const bool last = s + 1 >= cfg::NSEG;
    constexpr int PFW = ISV ? PF1V : PF1;
    uint32_t wf[PFW][4], woa;
    if (ISV) {
      OPQ;
      woa = WO + ((mi >> 1) * 8 + mr) * 128 + (((2 * w + (mi & 1)) ^ mr) << 4);
      if (s >= 1) {
        const uint32_t sa = QK + ((w * (w + 3)) >> 1) * 256 + lane * 8;
        mbar_spin(B_ST, (s - 1) & 1);
        float sc[10];
        {
          const float NEG = -1000000000.0f / 0.08838834764831845f;
          float2 x[5], y[5];
#pragma unroll
          for (int b = 0; b < 5; b++) {
            x[b] = b < 2 ? lds64f(sa + b * 256) : lds64f_if(sa + b * 256, b <= w + 1, NEG);
            y[b] = b < 2 ? lds64f(sa + 3584 + b * 256) : lds64f_if(sa + 3584 + b * 256, b <= w + 1, 0.f);
          }
#pragma unroll
          for (int b = 0; b < 5; b++) { sc[2 * b] = x[b].x + y[b].x; sc[2 * b + 1] = x[b].y + y[b].y; }
        }
        float m = fmaxf(fmaxf(fmaxf(sc[0], sc[1]), fmaxf(sc[2], sc[3])), fmaxf(fmaxf(sc[4], sc[5]), fmaxf(sc[6], sc[7])));
        m = fmaxf(m, fmaxf(sc[8], sc[9]));
        m = fmaxf(m, __shfl_xor_sync(0xffffffffu, m, 1));
        m = fmaxf(m, __shfl_xor_sync(0xffffffffu, m, 2));
        const float cs = 0.08838834764831845f * 1.4426950408889634f;
#pragma unroll
        for (int i = 0; i < 10; i++) sc[i] = ex2_approx((sc[i] - m) * cs);
        float sum = ((sc[0] + sc[1]) + (sc[2] + sc[3])) + ((sc[4] + sc[5]) + (sc[6] + sc[7])) + (sc[8] + sc[9]);
        sum += __shfl_xor_sync(0xffffffffu, sum, 1);
        sum += __shfl_xor_sync(0xffffffffu, sum, 2);
        const float inv = rcp_approx(sum);
        const uint32_t pa = PT + (w * 8 + mr) * 128, pm = pack_bf16(sc[0] * inv, sc[1] * inv);
        stsm4(pa + ((mi ^ mr) << 4), pack_bf16(sc[2] * inv, sc[3] * inv), pack_bf16(sc[4] * inv, sc[5] * inv),
              pack_bf16(sc[6] * inv, sc[7] * inv), pack_bf16(sc[8] * inv, sc[9] * inv));
        asm volatile("stmatrix.sync.aligned.m8n8.x2.shared.b16 [%0], {%1,%1};" ::"r"(pa + ((((mi & 1) ? 7 : 4) ^ mr) << 4)), "r"(pm) : "memory");
      }
      if (warp == 3 && !last) {
        mbar_spin(B_VM, s & 1);
        if (elect_one()) load_xn(P, s + 1, self);
      }
      PROF(1, 5);
    } else {
      if (warp == 0) {
        OPQ;
        uint32_t kf[4][4], qf[4][4];
        float c0[4], c1[4], d0[4], d1[4];
        const uint32_t ka = PT + (mi >> 1) * 1024 + (mi & 1) * 128 + mr * 16;
#pragma unroll
        for (int k = 0; k < 4; k++) { ldsm4t(qf[k], PT + 2048 + k * 512 + lane * 16); ldsm4t(kf[k], ka + k * 256); }
        mma16816z(c0, qf[0], kf[0][0], kf[0][1]); mma16816z(c1, qf[0], kf[0][2], kf[0][3]);
        mma16816z(d0, qf[1], kf[1][0], kf[1][1]); mma16816z(d1, qf[1], kf[1][2], kf[1][3]);
        mma16816(c0, qf[2], kf[2][0], kf[2][1]); mma16816(c1, qf[2], kf[2][2], kf[2][3]);
        mma16816(d0, qf[3], kf[3][0], kf[3][1]); mma16816(d1, qf[3], kf[3][2], kf[3][3]);
        const float s0 = ((c0[0] + c0[2]) + (c1[0] + c1[2])) + ((d0[0] + d0[2]) + (d1[0] + d1[2]));
        const float s1 = ((c0[1] + c0[3]) + (c1[1] + c1[3])) + ((d0[1] + d0[3]) + (d1[1] + d1[3]));
        if (!last) send_scores(s0, s1, SP + rank * SP_SRC + (128 + lane) * SPW, peer0, peer1, B_SM, lane);
        PROF(1, 5);
      } else {
        const uint32_t t_c = clk32() + lds32(B_XN) * 0;
        if (warp == 3 && !last) { if (elect_one()) load_xn(P, s + 1, self); }
        spin_until(t_c + D_ST);
      }
      OPQ;
      woa = WO + ((mi >> 1) * 8 + mr) * 128 + (((2 * w + (mi & 1)) ^ mr) << 4);
    }
    if (!last) {
      OPQ;
      uint32_t oba = OB + lane * 16;
      if (s == 0) mbar_spin(B_WO, 0);
      if (!ISV) wo_prefetch<WMODE, 0, PF1Q>(wf, woa, 0, true);
      if (ISV ? GATE_MX : GATE_Q) named_bar_sync(NB_MX, 256);
      wo_prefetch<WMODE, ISV ? 0 : PF1Q, PFW>(wf, woa, 0, true);
      char* h1p = P.xch + (tile0 + w) * 32768 + (h >> 3) * 8192 + (h & 7) * 128 + (((2 * lq + (lg & 1)) ^ (h & 7)) << 4) + (lg >> 1) * 4;
      fence_proxy_async_smem();
      PROF(1, 7);
      named_bar_sync(NB_O, 256);
      PROF(1, 8);
      wo_phase<WMODE>(wf, woa, 0, true, oba, h1p, tid >> 8, ((s >> 1) & 1) ^ 1);
      PROF(1, 9);
      named_bar_sync(NB_HD, 256);
    } else {
      fence_proxy_async_smem();
      named_bar_sync(NB_W1, 128);
    }
  }
  if (ISV && warp == 0) { if (elect_one()) o_done(15); }
}

template <bool ISV, int WG>
__device__ __forceinline__ void f_main(const FParams& P, const int h, const int rank, const uint32_t hw) {
  using namespace fk;
  const uint32_t self = mapa(0, (hw >> (2 * rank)) & 3);
  SMAP;
  const int tid = __shfl_sync(0xffffffffu, threadIdx.x, threadIdx.x & 31);
  const int tile0 = rank * 22, ntile = ISV ? 20 : 22;
  const CUtensorMap* m0 = ISV ? &P.wv : &P.wq;
  const CUtensorMap* m1 = ISV ? &P.wv : &P.wk;
  const int col0 = h * 128 + (ISV ? 0 : 64 * rank), col1 = h * 128 + (ISV ? 64 : 64 * rank);
  WRegs wr;
  uint32_t sel = 0;
  {
    OPQ;
    const uint32_t a = SM0 + WG * 16384 + ((mi >> 1) * 8 + mr) * 128 + (((2 * w + (mi & 1)) ^ mr) << 4);
    uint2 mi0 = make_uint2(0, 0);
    if (!ISV && WG == 1) mi0 = *reinterpret_cast<const uint2*>(P.mem0 + ((lane >> 1) & 7) * cfg::D + (2 * h + rank) * 16 + (lane >> 4) * 8 + (lane & 1) * 4);
#pragma unroll
    for (int i = 0; i < 6; i++) {
      if (i == MASK_AT && WG == 1 && w == 1) {
        uint4 v;
#pragma unroll 1
        for (int tries = 0; tries < POLL_TRIES; tries++) {
          asm volatile("ld.acquire.gpu.global.v4.u32 {%0,%1,%2,%3}, [%4];" : "=r"(v.x), "=r"(v.y), "=r"(v.z), "=r"(v.w)
                       : "l"(&g_mask[4 * min(lane, 23)]) : "memory");
          if (__all_sync(0xffffffffu, v.x & v.y & v.z & v.w & 0x100)) break;
          __nanosleep(100);
        }
        sts128(OB + lane * 16, v.x, v.y, v.z, v.w);
      }
      mbar_wait(B_PB + 8 * i, 0);
      PRO(8 + i);
#pragma unroll
      for (int T = 0; T < 2; T++)
#pragma unroll
        for (int u = 0; u < 4; u++) ldsm4t(wr[i][T][u], a + i * 32768 + T * 8192 + u * 2048);
      named_bar_sync(NB_C, 256);
      if (WG == 1 && w == (i & 3)) {
        if (elect_one()) {
          if (i <= 2 && i + PRE_G < 6) {
#pragma unroll 1
            for (int n = 2 * (i + PRE_G); n < (i == 2 ? 12 : 2 * (i + PRE_G) + 2); n++) {
              const int ii = n >> 1, row = Chunks<ISV>::rf(n & 1, ii) * 64;
              if (!(n & 1)) mbar_expect_tx(B_PB + 8 * ii, 32768);
              tma_load_2d(SM0 + n * 16384, m0, col0, row, B_PB + 8 * ii);
              tma_load_2d(SM0 + n * 16384 + 8192, m1, col1, row, B_PB + 8 * ii);
            }
          }
          if (i == 3 || i == 4) {
            const int p0 = i == 3 ? 0 : 5, p1 = i == 3 ? 5 : 8;
            mbar_expect_tx(B_W, (p1 - p0) * 8192);
#pragma unroll 1
            for (int p = p0; p < p1; p++) tma_load_2d(WS + p * 8192, (p & 1) ? m1 : m0, (p & 1) ? col1 : col0, Chunks<ISV>::sm(p >> 1) * 64, B_W);
          }
          if (i == 5) {
            asm volatile("fence.proxy.async.global;" ::: "memory");
            load_xn(P, 0, self);
          }
          if (i == WO_AT) {
            mbar_expect_tx(B_WO, ntile * 4096);
#pragma unroll 1
            for (int t = 0; t < 5; t++) tma_load_2d(WO + t * 16384, &P.wo, tile0 * 16 + t * 64, h * 128, B_WO);
            if (!ISV) {
              tma_load_2d(WO + 81920, &P.wo16, tile0 * 16 + 320, h * 128, B_WO);
              tma_load_2d(WO + 86016, &P.wo16, tile0 * 16 + 336, h * 128, B_WO);
            }
          }
        }
      }
    }
    PROF2(1);
    if (!ISV && WG == 1 && w < 2) st_pub64(P.xch + H1_BYTES + 32768 + (h >> 3) * 8192 + w * 4096 + ((2 * h + rank) & 15) * 256 + lane * 8, mi0.x, mi0.y);
    if (blockIdx.x == 2 && tid == 160) { __threadfence(); st_pub128(g_lnok, 0x100); }
#pragma unroll
    for (int i = 0; i < 3; i++) {
      const int t = min(tile0 + 8 * i + w + (WG ? 0 : 4), 63);
      sel |= ((lds32(OB + ((t >> 1) * 3 + (t & 1)) * 4) >> (h >> 3)) & 1) << (2 * i + 1);
    }
    const uint32_t own = lds32(OB + (3 * h + rank) * 4) >> w, m2 = lds32(OB + (3 * h + 2) * 4) >> w;
    sel |= (own & 1) << 7 | (m2 & 1) << 8 | (m2 & 16) << 5;
    sel |= (((((lg ^ h) & 1) << 2) | (lg >> 1)) == (h & 1) + 2 * (h >> 3)) << 10;
  }
  asm volatile("barrier.cluster.wait.aligned;" ::: "memory");
  PRO(14);
  mbar_wait(B_W, 0);
  mbar_wait(B_XN, 0);
  PRO(15);
  PROF2(4);
  GTSYNC(0);
  PROF2(2);
  KT_END(8);
  if (WG == 0) f_wg0<ISV>(P, wr, h, rank, hw, tid | sel << 8); else f_wg1<ISV>(P, wr, h, rank, hw, tid | sel << 8);
}

__device__ __forceinline__ void f_tail(const FParams& P, const int h, const uint32_t rank, const bool isv) {
  using namespace fk;
  const uint32_t self = mapa(0, rank), base = self + SM0;
  const uint32_t FULL = self + SP, EMPT = FULL + 32, NOG = FULL + 64, RES = FULL + 72;
  const int tid = threadIdx.x, lane = tid & 31, wv = __shfl_sync(0xffffffffu, tid >> 5, 0), wg = wv >> 2;
  const int kq = h & 7, nt = h >> 3, mb = TAIL_MB0 + rank;
  auto a_off = [](uint32_t st) { return (0x98685800u >> (8 * st) & 255) * 1024; };
  auto b_off = [](uint32_t st) { return (0xA8783010u >> (8 * st) & 255) * 1024; };
  static_assert(VX2 - SM0 == 80 * 1024 && VX - SM0 == 200 * 1024, "stage layout");
  auto load_b = [&](int kb) {
    const uint32_t sb = base + b_off(kb & 3), full = FULL + 8 * (kb & 3);
    mbar_expect_tx(full, 49152);
    tma_load_2d_mc(sb + rank * 8192, &P.tb, nt * 256 + ((rank + (kq >> 1)) & 3) * 64, (kq * 8 + kb) * 64, full, 7);
    if (kb % 3 == rank) tma_load_2d_mc(sb + 3 * 8192, &P.tb, nt * 256 + ((3 + (kq >> 1)) & 3) * 64, (kq * 8 + kb) * 64, full, 7);
  };
  auto load_a = [&](int kb) { tma_load_2d(base + a_off(kb & 3), &P.ta, (kq * 8 + kb) * 64, mb * 128, FULL + 8 * (kb & 3)); };
  TL(0);
  TL2(128, 10); TL2(160, 11);
  if (wv == 0) {
    if (elect_one()) {
      prefetch_tmap(&P.tb); prefetch_tmap(&P.ta);
      if (isv) mbar_spin(self + B_VM, (cfg::NSEG - 1) & 1);
      for (int i = 0; i < 4; i++) { mbar_init(FULL + 8 * i, 1); mbar_init(EMPT + 8 * i, 24); }
      mbar_init(RES, 1);
      fence_barrier_init();
      mbar_arrive_cluster(self + B_W, rank == 0 ? 1 : 0);
      mbar_arrive_cluster(self + B_W, rank == 2 ? 1 : 2);
      mbar_spin(self + B_W, 1);
#pragma unroll 1
      for (int kb = 0; kb < 4; kb++) load_b(kb);
      TL2(0, 12);
      wait_count(&g_oflag[mb], 32);
      asm volatile("fence.proxy.async.global;" ::: "memory");
      TL2(0, 13);
#pragma unroll 1
      for (int kb = 0; kb < 4; kb++) load_a(kb);
      TL2(0, 14);
    }
  } else if (wv == 1) {
    if (lane == 0) {
      prefetch_tmap(&P.tx); prefetch_tmap(&P.tg);
      const bool ng = ld_strong4(&g_next) == 0;
      sts32(NOG, ng);
      if (ng) g_tfix[blockIdx.x] = 1; else wait_count(&g_cnt[3][mb], GATE_CNT);
    }
  }
  float acc[128];
  __syncthreads();
  KT_START(7);
  const bool nog = lds32(NOG);
  if (nog) TL(15); else TL(15);
  if (wv == 1) {
    if (elect_one()) {
      asm volatile("fence.proxy.async.global;" ::: "memory");
      mbar_expect_tx(RES, 16384);
      tma_load_2d(self + VX, &P.tx, nt * 256 + kq * 32, mb * 128, RES);
      tma_load_2d(self + QK, &P.tg, nt * 256 + kq * 32, mb * 128, RES);
    }
  }
#pragma unroll 1
  for (int kb = 0; kb < 8; kb++) {
    const uint32_t st = kb & 3, sa = base + a_off(st) + wg * 8192, sb = base + b_off(st);
    mbar_spin(FULL + 8 * st, kb >> 2);
    if (kb == 0) TL(2);
    if (kb == 4) TL(3);
    wg_fence();
#pragma unroll
    for (int k = 0; k < 4; k++) {
      wgmma_ss_n256_tb(acc, make_desc(sa + k * 32, 16, 1024), make_desc(sb + k * 2048, 8192, 1024), (kb | k) != 0);
      if (k == 0) {
        wg_commit();
        wg_wait<1>();
        if (kb > 0 && kb <= 4 && lane < 3) mbar_arrive_cluster(EMPT + 8 * (kb - 1), lane);
        wg_fence();
      }
    }
    wg_commit();
    if (kb >= 2 && kb < 6 && wv == ((kb & 1) << 2)) {
      if (elect_one()) {
        mbar_spin(EMPT + 8 * (kb - 2), 0);
        load_b(kb + 2);
        load_a(kb + 2);
      }
      __syncwarp();
    }
  }
  wg_wait<0>();
  TL(5);
#pragma unroll
  for (int j = 0; j < 8; j++) {
    uint4* dst = &g_tpart[((h & ~7) + ((j + (kq & 6)) & 7)) * 3 + rank][kq][0][tid];
    if (j >= 2 || j != (kq & 1)) {
#pragma unroll
      for (int i = 0; i < 2; i++) {
        const float* a = &acc[16 * j + 8 * i];
        dst[i * 256] = make_uint4(pack_bf16(a[0], a[1]), pack_bf16(a[2], a[3]), pack_bf16(a[4], a[5]), pack_bf16(a[6], a[7]));
      }
    }
  }
#pragma unroll
  for (int i = 0; i < 16; i++) acc[i] = (kq & 1) ? acc[16 + i] : acc[i];
  TL(6);
  __syncwarp();
  if (lane < 8) asm volatile("red.release.gpu.global.add.u32 [%0], 1;" ::"l"(&g_tcnt[((h & ~7) + lane) * 3 + rank][wv]) : "memory");
  TL(7);
  const size_t off = (size_t)(mb * 128 + wv * 16 + (lane >> 2)) * cfg::D + nt * 256 + kq * 32 + (lane & 3) * 2;
  uint32_t x[8], g[8];
  const uint32_t xa = self + VX + (wv * 16 + (lane & 15)) * 64 + (((lane >> 4) ^ ((lane >> 1) & 3)) << 4);
  mbar_spin(RES, 0);
  ldsm4(x, xa); ldsm4(x + 4, xa ^ 32);
  ldsm4(g, xa + (QK - VX)); ldsm4(g + 4, (xa ^ 32) + (QK - VX));
#pragma unroll 1
  for (int tries = 0; tries < POLL_TRIES; tries++) {
    uint32_t v;
    asm volatile("ld.acquire.gpu.global.u32 %0, [%1];" : "=r"(v) : "l"(&g_tcnt[blockIdx.x][wv]) : "memory");
    if (v >= 8) break;
  }
  uint4 pt[14];
#pragma unroll
  for (int i = 0; i < 14; i++) pt[i] = __ldcg(&g_tpart[blockIdx.x][(kq + 1 + (i >> 1)) & 7][i & 1][tid]);
  TL(8);
#pragma unroll 1
  for (int j = 0; j < 2; j++) {
#pragma unroll
    for (int i = 0; i < 28; i++) {
      const uint32_t v = (&pt[2 * (i >> 2)].x)[i & 3];
      acc[2 * (i & 3)] += bf_lo(v); acc[2 * (i & 3) + 1] += bf_hi(v);
    }
#pragma unroll
    for (int i = 0; i < 4; i++) {
      const uint32_t sv = pack_bf16(acc[2 * i], acc[2 * i + 1]);
      *reinterpret_cast<uint32_t*>(P.out + off + (i & 1) * 8 * cfg::D + (i >> 1) * 8 + j * 16) = nog ? sv : add_bf16x2(x[i], mul_bf16x2(sv, g[i]));
      x[i] = x[i + 4]; g[i] = g[i + 4];
      acc[2 * i] = acc[8 + 2 * i]; acc[2 * i + 1] = acc[9 + 2 * i];
    }
#pragma unroll
    for (int i = 0; i < 7; i++) pt[2 * i] = pt[2 * i + 1];
  }
  TL(9);
  KT_END(7);
}

__global__ void __launch_bounds__(256, 1) f_kernel(const __grid_constant__ FParams P) {
  using namespace fk;
  extern __shared__ __align__(1024) uint8_t smem_f[];
  uint32_t crank, rank, hw;
  asm("mov.u32 %0, %%cluster_ctarank;" : "=r"(crank));
  const int h = blockIdx.x / 3;
  if (smem_u32(smem_f) != mapa(0, crank) + SM0) return;
  PROF2(0);
  KT_START(1);
  KT_START(0);
  {
    const uint32_t self = mapa(0, crank);
    SMAP;
    const int tid = threadIdx.x, lane = tid & 31, wv = __shfl_sync(0xffffffffu, tid >> 5, 0);
    PRO(0);
    if (wv == 0) {
      uint32_t sm;
      asm("mov.u32 %0, %%smid;" : "=r"(sm));
      sts32(PROBE + 96, sm >> 1);
      asm volatile("fence.release.sync_restrict::shared::cta.cluster;" ::: "memory");
    }
    asm volatile("barrier.cluster.arrive.relaxed.aligned;" ::: "memory");
    if (wv == 7) {
      if (blockIdx.x == 2) {
#pragma unroll
        for (int i = 0; i < 4; i++) { (&g_cnt[0][0])[32 * i + lane] = 0; if (i < 3) g_tfix[32 * i + lane] = 0; }
#pragma unroll
        for (int i = 0; i < 6; i++) reinterpret_cast<uint4*>(&g_tcnt[0][0])[32 * i + lane] = make_uint4(0, 0, 0, 0);
        if (lane < 16) g_oflag[lane] = 0;
        if (lane == 0) { g_next = 0; g_lnok[0] = 0; }
        __threadfence();
        __syncwarp();
      }
      pdl_launch_dependents();
    }
    const int row0 = blockIdx.x * 8 + wv;
    const bool third = row0 + 1536 < cfg::S;
    uint32_t cur[1][16] = {}, raw[3][16];
    load_row16(raw[0], P.x + (size_t)row0 * cfg::D, lane);
    load_row16(raw[1], P.x + (size_t)(row0 + 768) * cfg::D, lane);
    load_row16(raw[2], P.x + (size_t)(row0 + (third ? 1536 : 0)) * cfg::D, lane);
    {
      uint32_t tpc;
      asm volatile("barrier.cluster.wait.aligned;" ::: "memory");
      asm volatile("ld.shared::cluster.u32 %0, [%1];" : "=r"(tpc) : "r"(mapa(PROBE + 96, lane % 3)) : "memory");
      const uint32_t t0 = __shfl_sync(0xffffffffu, tpc, 0), t1 = __shfl_sync(0xffffffffu, tpc, 1), t2 = __shfl_sync(0xffffffffu, tpc, 2);
      hw = t1 == t2 ? 0x09 : t0 == t2 ? 0x18 : 0x24;
      rank = (hw & 3) == crank ? 0 : ((hw >> 2) & 3) == crank ? 1 : 2;
    }
    const bool isv = rank == 2;
    const CUtensorMap* m0 = isv ? &P.wv : &P.wq;
    const CUtensorMap* m1 = isv ? &P.wv : &P.wk;
    const int col0 = h * 128 + (isv ? 0 : 64 * rank), col1 = h * 128 + (isv ? 64 : 64 * rank);
    auto req_weights = [&](int n0, int n1) {
#pragma unroll 1
        for (int n = n0; n < n1; n++) {
          const int i = n >> 1, g = n & 1, row = (isv ? Chunks<true>::rf(g, i) : Chunks<false>::rf(g, i)) * 64;
          if (!g) mbar_expect_tx(B_PB + 8 * i, 32768);
          tma_load_2d(SM0 + n * 16384, m0, col0, row, B_PB + 8 * i);
          tma_load_2d(SM0 + n * 16384 + 8192, m1, col1, row, B_PB + 8 * i);
        }
    };
    if (wv == 0) {
      if (elect_one()) {
        for (int i = 0; i < 2; i++) mbar_init(B_XN + 8 * i, 1);
        mbar_init(B_H1, 4);
        mbar_init(B_SM, isv ? 1 : 6);
        mbar_init(B_VM, isv ? 8 : 1);
        mbar_init(B_VX, 1);
        mbar_init(B_ST, 1);
        mbar_init(B_PF, 2);
        for (int i = 0; i < 6; i++) mbar_init(B_PB + 8 * i, 1);
        mbar_init(B_W, 2);
        mbar_init(B_WO, 1);
        fence_barrier_init();
        if (PRE_A) req_weights(0, 2 * PRE_A);
        mbar_expect_tx(B_SM, isv ? 2 * SP_SRC : SP_SRC);
        if (isv) mbar_expect_tx(B_ST, 7168);
        else { mbar_expect_tx(B_VM, 2048); mbar_expect_tx(B_VX, 8192); }
      }
    }
    const int j = 2 * h + rank;
    const bool dry = LN_DRY && !isv && wv == 6;
    if (dry) sts64(PROBE + wv * 8, 0x7FFFFFFF, 0x7FFFFFFF);
    if (lane == 0 && !dry) {
      const uint2 b = probe_pair(P.xch + (isv ? H1_BYTES + wv * 8192 + h * 128 : j * 32768 + (wv & 3) * 8192 + (wv >> 2) * 128),
                                 isv ? EMPTY : 0, PROBE + 64, P.nprobe);
      sts64(PROBE + wv * 8, b.x, b.y);
    }
    uint32_t mask = 0;
#pragma unroll 1
    for (int it = -1; it < (third ? 3 : 2); it++) {
      if (it >= 0 || dry) {
        ln_regs<1>(cur);
        if (it >= 0) store_row16(cur[0], P.xn_ptr + (size_t)(row0 + it * 768) * cfg::D, lane);
      }
      if (it == 0) PRO(4);
      if (it < 0) {
    PROF2(3);
    PRO(1);
    __syncwarp();
    if (wv == 0) {
      asm volatile("{\n.reg .pred p;\nsetp.eq.u32 p, %0, %1;\n@p st.shared.u32 [%2], %0;\n}" ::"r"(raw[2][15]), "r"(raw[0][0] ^ raw[1][15]), "r"(PROBE + 64) : "memory");
      if (elect_one()) {
        req_weights(2 * PRE_A, 2 * PRE_G);
      }
    }
    __syncthreads();
    PRO(2);
    asm volatile("barrier.cluster.arrive.relaxed.aligned;" ::: "memory");
    PRO(3);
    if (wv == 2) sts32(self + ONES + lane * 4, 0x3F803F80u);
    uint32_t pb[2], pc[2];
    lds64(pb, PROBE + (lane & 7) * 8);
    lds64(pc, PROBE + ((lane & 7) ^ 4) * 8);
    mask = __ballot_sync(0xffffffffu, isv ? pb[1] < pb[0] : min(pb[1], pc[1]) < min(pb[0], pc[0])) & (isv ? 255 : 15);
    if (!isv) {
#pragma unroll
      for (int i = 0; i < 4; i++) st_pub128(P.xch + j * 32768 + i * 8192 + ((mask >> i) & 1) * 4096 + tid * 16, 0);
      if (wv < 4) st_pub64(P.xch + H1_BYTES + (wv >> 1) * 32768 + (j >> 4) * 8192 + (wv & 1) * 4096 + (j & 15) * 256 + lane * 8, EMPTY, EMPTY);
    }
      }
#pragma unroll
      for (int i = 0; i < 16; i++) { cur[0][i] = raw[0][i]; raw[0][i] = raw[1][i]; raw[1][i] = raw[2][i]; }
    }
    PRO(5);
    __syncthreads();
    PRO(6);
    if (tid == 64) {
      __threadfence();
      PRO(7);
      st_pub32(&g_mask[3 * h + rank], 0x100 | mask);
    }
    KT_END(0);
    __syncwarp();
  }
  const int wg = __shfl_sync(0xffffffffu, threadIdx.x >> 7, 0);
  if (rank == 2) { if (wg == 0) f_main<true, 0>(P, h, 2, hw); else f_main<true, 1>(P, h, 2, hw); }
  else { if (wg == 0) f_main<false, 0>(P, h, rank, hw); else f_main<false, 1>(P, h, rank, hw); }
  PROF2(5);
  KT_END(1);
  __syncwarp();
  f_tail(P, h, crank, rank == 2);
}

#define GCL 1
#define G_PF 3
#define G_PFM 2
#define G_LATE 0
namespace gk {
enum { T_B1 = 0, T_B2 = 1, T_B3 = 2, T_B4 = 3, T_O = 4, T_LN = 5, T_LN0 = 6, T_END = 7 };
constexpr int NST = 3, STAGE = 49152, MAXITEMS = 512, NEW = 3;
constexpr uint32_t OUTB = NST * STAGE, BARS = OUTB + 65536;
constexpr uint32_t B_FULL = BARS, B_EMPTY = BARS + 32, B_ITEM = BARS + 64, B_FILL = BARS + 128, B_FREE = BARS + 160, B_LN = BARS + 176, ITEMS = BARS + 192;
constexpr int SMEM = BARS + 256;
static_assert(GATE_CNT == 4 * NEW && T_B4 == 3, "gate counter");
}
struct GParams {
  CUtensorMap a[5], b[5];
  bf16* c[5];
  const bf16* r[5];
  bf16 *x1n, *xn2;
  const bf16* w1;
  int nitems, lnpos;
  uint16_t items[gk::MAXITEMS];
};
#define ILOG(i)

__device__ __forceinline__ void tma_load_3d_mc(uint32_t dst, const CUtensorMap* map, int x, int y, int z, uint32_t bar) {
  asm volatile("cp.async.bulk.tensor.3d.shared::cluster.global.mbarrier::complete_tx::bytes.multicast::cluster "
               "[%0], [%1, {%3, %4, %5}], [%2], %6;"
               ::"r"(dst), "l"(map), "r"(bar), "r"(x), "r"(y), "r"(z), "h"((uint16_t)3) : "memory");
}
__device__ __forceinline__ float tanh_approx(float x) { float y; asm("tanh.approx.f32 %0, %1;" : "=f"(y) : "f"(x)); return y; }
__global__ void __launch_bounds__(384, 1) g_kernel(const __grid_constant__ GParams P) {
  using namespace gk;
  extern __shared__ __align__(1024) uint8_t smem_g[];
  const uint32_t base = smem_u32(smem_g);
  const int tid = threadIdx.x, warp = __shfl_sync(0xffffffffu, tid >> 5, 0), lane = tid & 31;
  const int rank = blockIdx.x % GCL;
  KT_START(2);
  if (tid == 0) {
    for (int s = 0; s < NST; s++) { mbar_init(base + B_FULL + 8 * s, 1); mbar_init(base + B_EMPTY + 8 * s, 8 * GCL); }
    for (int s = 0; s < 8; s++) mbar_init(base + B_ITEM + 8 * s, 1);
    for (int s = 0; s < 2; s++) { mbar_init(base + B_FILL + 8 * s, 4); mbar_init(base + B_FREE + 8 * s, NEW); }
    mbar_init(base + B_LN, 1);
    fence_barrier_init();
  }
  __syncthreads();
  if (GCL > 1) cluster_sync();
  auto release = [&](uint32_t st) {
    if (GCL > 1) { if (lane < GCL) mbar_arrive_cluster(base + B_EMPTY + 8 * st, lane); }
    else if (lane == 0) mbar_arrive(base + B_EMPTY + 8 * st);
  };
  auto get_item = [&](int q) {
    mbar_wait(base + B_ITEM + 8 * (q & 7), (q >> 3) & 1);
    return lds32(base + ITEMS + 4 * (q & 7));
  };

  if (warp == 8) {
    if (lane < 10) prefetch_tmap(&P.a[0] + lane);
    for (int r = blockIdx.x * 32 + lane; r < cfg::D; r += gridDim.x * 32) l2_prefetch(P.w1 + r * cfg::D, 2048);
    if (lane == 0) {
      uint32_t st = 0, ph = 1;
#pragma unroll 1
      for (int q = 0;; q++) {
        if (GCL > 1) mbar_expect_tx(base + B_ITEM + 8 * (q & 7), 4);
        if (rank == 0) {
          const unsigned idx = atomicAdd(&g_next, 1), ln = idx - P.lnpos;
          const uint32_t v = (idx < (unsigned)P.nitems ? P.items[idx] : T_END) | (ln < 64 / GCL ? (ln + 1) << 16 : idx < 32 / GCL ? (idx + 129) << 16 : 0);
          if (GCL > 1) {
#pragma unroll
            for (int r = 0; r < GCL; r++) st_async32(mapa(base + ITEMS + 4 * (q & 7), r), v, mapa(base + B_ITEM + 8 * (q & 7), r));
          } else {
            sts32(base + ITEMS + 4 * (q & 7), v);
            mbar_arrive(base + B_ITEM + 8 * (q & 7));
          }
        }
        const uint32_t item = get_item(q);
        const int type = item & 7, mb = ((item >> 3) & 15) + rank, nt = (item >> 7) & 15;
        ILOG(1);
        if (q == 0) { __threadfence(); sts32(base + ITEMS + 32, ld_strong4(&g_oflag[14]) >= 32); }
        if (type == T_END) break;
        if (type == T_B2) {
          wait_count(&g_cnt[T_B1][max(mb - 1, 0)], 4 * NEW); wait_count(&g_cnt[T_B1][mb], 4 * NEW); wait_count(&g_cnt[T_B1][min(mb + 1, 15)], 4 * NEW);
        } else if (type == T_B3) wait_count(&g_cnt[T_LN][mb], 32);
        else if (type == T_B4) wait_count(&g_cnt[T_B3][mb], 14 * NEW);
        else if (type == T_O) wait_count(&g_oflag[mb], 32);
        asm volatile("fence.proxy.async.global;" ::: "memory");
        ILOG(2);
        const CUtensorMap *ma = &P.a[type], *mbm = &P.b[type];
        const int nkb = type == T_B4 ? cfg::F / 64 : type == T_O ? cfg::HD / 64 : cfg::D / 64;
#pragma unroll 1
        for (int kb = 0; kb < nkb; kb++) {
          mbar_wait(base + B_EMPTY + 8 * st, ph);
          const uint32_t sa = base + st * STAGE, full = base + B_FULL + 8 * st;
          mbar_expect_tx(full, STAGE);
          int arow = mb * 128;
          if (type == T_B2) { const int qd = kb >> 2; arow += (qd == 0) ? -1 : (qd == 1) ? 1 : (qd == 2) ? -2 : 2; }
          if (GCL > 1) tma_load_3d_mc(sa + 16384 + rank * 16384, mbm, 0, kb * 64, nt * 4 + rank * 2, full);
          else tma_load_3d(sa + 16384, mbm, 0, kb * 64, nt * 4, full);
          if (type == T_B1 && kb == 0) { wait_count(&g_cnt[T_LN0][mb], 32); asm volatile("fence.proxy.async.global;" ::: "memory"); }
          tma_load_2d(sa, ma, kb * 64, arow, full);
          if (G_PF && type >= T_B4 && kb + G_PF < nkb) {
            if (G_PFM & 1) asm volatile("cp.async.bulk.prefetch.tensor.3d.L2.global [%0, {0, %1, %2}];" ::"l"(mbm), "r"((kb + G_PF) * 64), "r"(nt * 4 + rank * 2) : "memory");
            if (G_PFM & 2) asm volatile("cp.async.bulk.prefetch.tensor.2d.L2.global [%0, {%1, %2}];" ::"l"(ma), "r"((kb + G_PF) * 64), "r"(mb * 128) : "memory");
          }
          if (++st == NST) { st = 0; ph ^= 1; }
        }
      }
    }
  } else {
    const int wg = warp >> 2, ew = warp > 8 ? warp - 9 : warp + NEW;
    const uint32_t outa = base + OUTB + (warp * 16 + ((lane >> 3) & 1) * 8 + (lane & 7)) * 512 + (((lane >> 4) ^ (lane & 7)) << 4);
    uint32_t st = 0, ph = 0;
    float acc[128];
    auto kill_acc = [&]() {
#pragma unroll
      for (int i = 0; i < 128; i++) acc[i] = 0.f;
    };
    if (warp == 9) {
#pragma unroll 1
      for (int tries = 0; tries < POLL_TRIES; tries++) {
        uint4 v;
        asm volatile("ld.acquire.gpu.global.v4.u32 {%0,%1,%2,%3}, [%4];" : "=r"(v.x), "=r"(v.y), "=r"(v.z), "=r"(v.w)
                     : "l"(lane < 24 ? &g_mask[4 * lane] : &g_lnok[0]) : "memory");
        const uint32_t ok = __ballot_sync(0xffffffffu, v.x & v.y & v.z & v.w & 0x100);
        if ((ok & 0xFFFFFF) == 0xFFFFFF || (ok >> 24)) break;
        __nanosleep(200);
      }
      if (lane == 0) mbar_arrive(base + B_LN);
    }
    uint32_t next = get_item(0);
#pragma unroll 1
    for (int q = 0;; q++) {
      const uint32_t item = next;
      const int type = item & 7, mb = ((item >> 3) & 15) + rank, nt = (item >> 7) & 15;
      if (type == T_END) break;
      if (warp < 8) {
      if (item >> 16) {
        const bool first = item >> 23;
#pragma unroll 1
        for (int ln = ((item >> 16) & 127) - 1; ln < 64 / GCL; ln += first ? 32 / GCL : 64) {
          const int lb = (ln >> 2) * GCL + rank;
          const size_t row = (size_t)(lb * 128 + (ln & 3) * 32 + warp * 4) * cfg::D;
          const bf16* src = (first ? P.r[T_O] : P.c[T_B2]) + row;
          bf16* dst = (first ? P.xn2 : P.x1n) + row;
          if (!first) wait_count(&g_cnt[T_B2][lb], 4 * NEW);
          uint32_t cur[2][16], nxt[2][16];
#pragma unroll
          for (int r = 0; r < 2; r++) {
            load_row16(cur[r], src + r * cfg::D, lane);
            load_row16(nxt[r], src + (r + 2) * cfg::D, lane);
          }
#pragma unroll 1
          for (int it = first ? 0 : 1; it < 4; it += first ? 1 : 2) {
            ln_regs<2>(cur);
            if (it & 1) {
#pragma unroll
              for (int r = 0; r < 2; r++) {
                store_row16(cur[r], dst + (it - 1 + r) * cfg::D, lane);
#pragma unroll
                for (int i = 0; i < 16; i++) cur[r][i] = nxt[r][i];
              }
            }
          }
          __syncwarp();
          if (lane == 0) asm volatile("red.release.gpu.global.add.u32 [%0], 1;" ::"l"(&g_cnt[first ? T_LN0 : T_LN][lb]) : "memory");
          __syncwarp();
        }
        if (tid == 0) ILOG(6);
        kill_acc();
      }
      const int nkb = type == T_B4 ? cfg::F / 64 : type == T_O ? cfg::HD / 64 : cfg::D / 64;
      uint32_t prev = 0;
      mbar_wait(base + B_FULL + 8 * st, ph);
#pragma unroll 1
      for (int kb = 0; kb < nkb; kb++) {
        mbar_spin(base + B_FULL + 8 * st, ph);
        if (kb == 0 && tid == 0) ILOG(3);
        const uint64_t da = make_desc(base + wg * 8192, 16, 1024) + st * (STAGE >> 4), db = make_desc(base + 16384, 8192, 1024) + st * (STAGE >> 4);
        wg_fence();
#pragma unroll
        for (int k = 0; k < 4; k++) {
          wgmma_ss_n256_tb(acc, da + k * 2, db + k * 128, (kb | k) != 0);
          if (k == 0) {
            wg_commit();
            wg_wait<1>();
            if (kb > 0) release(prev);
            wg_fence();
          }
        }
        wg_commit();
        prev = st;
        if (++st == NST) { st = 0; ph ^= 1; }
      }
      next = get_item(q + 1);
      if (q > 0) mbar_wait(base + B_FREE + 8 * wg, (q - 1) & 1);
      wg_wait<0>();
      if (tid == 0) ILOG(4);
      release(prev);
#pragma unroll
      for (int j = 0; j < 16; j++)
        stsm4((outa ^ ((j & 3) << 5)) + (j >> 2) * 128, pack_bf16(acc[8 * j], acc[8 * j + 1]), pack_bf16(acc[8 * j + 2], acc[8 * j + 3]),
              pack_bf16(acc[8 * j + 4], acc[8 * j + 5]), pack_bf16(acc[8 * j + 6], acc[8 * j + 7]));
      __syncwarp();
      if (lane == 0) mbar_arrive(base + B_FILL + 8 * wg);
      if (tid == 0) ILOG(5);
      if ((next & 7) != T_END) continue;
      }
      if (type == T_O) wait_count(&g_cnt[T_B4][mb], 4 * NEW);
      const int ldc = type == T_B3 ? cfg::F : cfg::D;
      bf16* cp = P.c[type] + (size_t)mb * 128 * ldc + nt * 256 + lane * 8;
      const size_t roff = (size_t)mb * 128 * cfg::D + nt * 256 + lane * 8;
      const bf16 *rp = P.r[type] + roff, *gp = P.c[T_B4] + roff;
      const bool gelu = type == T_B1 || type == T_B3;
      uint32_t yn[4][4];
      uint4 rn[4], gn[4];
#pragma unroll
      for (int i = 0; i < 4; i++) rn[i] = gn[i] = make_uint4(0, 0, 0, 0);
      auto fetch_res = [&](int grp) {
#pragma unroll
        for (int i = 0; i < 4; i++) {
          rn[i] = __ldcg(reinterpret_cast<const uint4*>(rp + (grp * 4 + i) * cfg::D));
          if (type == T_O) gn[i] = __ldcg(reinterpret_cast<const uint4*>(gp + (grp * 4 + i) * cfg::D));
        }
      };
      auto fetch_y = [&](int grp) {
        const uint32_t a = base + OUTB + grp * 2048 + ((lane ^ ((grp & 1) << 2)) << 4);
#pragma unroll
        for (int i = 0; i < 4; i++) lds128(yn[i], (a ^ (i << 4)) + i * 512);
      };
      auto store_y = [&](int grp, const uint32_t (&y)[4][4]) {
        char* p = reinterpret_cast<char*>(cp) + (uint32_t)(grp * 8 * ldc);
#pragma unroll
        for (int i = 0; i < 4; i++) *reinterpret_cast<uint4*>(p + (uint32_t)(i * 2 * ldc)) = make_uint4(y[i][0], y[i][1], y[i][2], y[i][3]);
      };
      if (type == T_B2) mbar_wait(base + B_LN, 0);
      if (type == T_B4) wait_count(&g_cnt[T_B2][mb], 4 * NEW);
      if (type >= T_B4 && warp > 8) for (int r = tid - 288; r < 128; r += 96) l2_prefetch(rp - lane * 8 + r * cfg::D, 512);
      if (!gelu) fetch_res(ew);
      mbar_wait(base + B_FILL, q & 1);
      fetch_y(ew);
      next = get_item(q + 1);
      mbar_wait(base + B_FILL + 8, q & 1);
      const int stride = (next & 7) == T_END ? NEW + 8 : NEW;
      if (gelu) {
#pragma unroll 1
        for (int grp = ew; grp < 32; grp += stride) {
          uint32_t y[4][4];
#pragma unroll
          for (int i = 0; i < 16; i++) y[i >> 2][i & 3] = mul_bf16x2(yn[i >> 2][i & 3], 0x3F003F00u);
          const int nx = grp + stride;
          if (nx >= 16 && grp < 16 && lane == 0 && warp > 8) mbar_arrive(base + B_FREE);
          if (!G_LATE) fetch_y(min(nx, 31));
#pragma unroll
          for (int i = 0; i < 16; i++) {
            uint32_t& v = y[i >> 2][i & 3];
            const float h0 = bf_lo(v), h1 = bf_hi(v);
            const float t0 = tanh_approx(h0 * fmaf(h0 * h0, 0.285419265090401f, 1.5957691216057308f));
            const float t1 = tanh_approx(h1 * fmaf(h1 * h1, 0.285419265090401f, 1.5957691216057308f));
            v = pack_bf16(fmaf(h0, t0, h0), fmaf(h1, t1, h1));
          }
          if (G_LATE) fetch_y(min(nx, 31));
          store_y(grp, y);
        }
      } else {
#pragma unroll 1
        for (int grp = ew; grp < 32; grp += stride) {
          uint32_t y[4][4];
          if (type == T_O) {
#pragma unroll
            for (int i = 0; i < 16; i++) yn[i >> 2][i & 3] = mul_bf16x2(yn[i >> 2][i & 3], (&gn[i >> 2].x)[i & 3]);
          }
#pragma unroll
          for (int i = 0; i < 16; i++) y[i >> 2][i & 3] = add_bf16x2(yn[i >> 2][i & 3], (&rn[i >> 2].x)[i & 3]);
          const int nx = grp + stride;
          if (nx >= 16 && grp < 16 && lane == 0 && warp > 8) mbar_arrive(base + B_FREE);
          fetch_res(min(nx, 31));
          fetch_y(min(nx, 31));
          if (type == T_B4) {
#pragma unroll
            for (int i = 0; i < 16; i++) {
              uint32_t& v = y[i >> 2][i & 3];
              const float h0 = 0.5f * bf_lo(v), h1 = 0.5f * bf_hi(v);
              v = pack_bf16(fmaf(h0, tanh_approx(h0), h0), fmaf(h1, tanh_approx(h1), h1));
            }
          }
          store_y(grp, y);
        }
      }
      __syncwarp();
      if (lane == 0 && warp > 8) mbar_arrive(base + B_FREE + 8);
      if (stride != NEW) named_bar_sync(2, 352);
      if (type != T_O && lane == 0 && warp > 8) asm volatile("red.release.gpu.global.add.u32 [%0], 1;" ::"l"(&g_cnt[type][mb]) : "memory");
      __syncwarp();
      if (tid == 288) ILOG(7);
      kill_acc();
    }
    KT_END(2);
  }
  __syncwarp();
  if (warp >= 8) {
   named_bar_sync(1, 128);
   const bool late = lds32(base + ITEMS + 32);
   if (late) pdl_wait();
#pragma unroll 1
   for (int c = blockIdx.x; late && c < 96; c += gridDim.x) {
     if (__ldcg(&g_tfix[c]) == 0) continue;
     const int hh = c / 3, mb = TAIL_MB0 + c % 3;
     wait_count(&g_cnt[T_B4][mb], GATE_CNT);
#pragma unroll 1
     for (int i = tid - 256; i < 512; i += 128) {
       const size_t off = (size_t)(mb * 128 + (i >> 2)) * cfg::D + hh * 32 + (i & 3) * 8;
       const uint4 sv = __ldcg(reinterpret_cast<const uint4*>(P.c[T_O] + off)), gv = __ldcg(reinterpret_cast<const uint4*>(P.c[T_B4] + off)),
                   xv = __ldcg(reinterpret_cast<const uint4*>(P.r[T_O] + off));
       *reinterpret_cast<uint4*>(P.c[T_O] + off) = make_uint4(add_bf16x2(xv.x, mul_bf16x2(sv.x, gv.x)), add_bf16x2(xv.y, mul_bf16x2(sv.y, gv.y)),
                                                              add_bf16x2(xv.z, mul_bf16x2(sv.z, gv.z)), add_bf16x2(xv.w, mul_bf16x2(sv.w, gv.w)));
     }
   }
  }
  if (GCL > 1) cluster_sync();
}

__device__ bf16 g_xn[cfg::S * cfg::D];
__device__ bf16 g_xn2[cfg::S * cfg::D];
__device__ bf16 g_h[cfg::S * cfg::D];
__device__ bf16 g_x1[cfg::S * cfg::D];
__device__ bf16 g_x1n[cfg::S * cfg::D];
__device__ bf16 g_u[cfg::S * cfg::F];
__device__ bf16 g_g[cfg::S * cfg::D];
__device__ bf16 g_o[cfg::S * cfg::HD];

typedef CUresult (*PFN_encodeTiled)(CUtensorMap*, CUtensorMapDataType, cuuint32_t, void*, const cuuint64_t*,
                                    const cuuint64_t*, const cuuint32_t*, const cuuint32_t*, CUtensorMapInterleave,
                                    CUtensorMapSwizzle, CUtensorMapL2promotion, CUtensorMapFloatOOBfill);

static PFN_encodeTiled get_encoder() {
  static PFN_encodeTiled fn = nullptr;
  if (!fn) {
    void* p = nullptr;
    cudaDriverEntryPointQueryResult st;
    cudaGetDriverEntryPoint("cuTensorMapEncodeTiled", &p, cudaEnableDefault, &st);
    fn = (PFN_encodeTiled)p;
  }
  return fn;
}
static CUtensorMap make_map(const void* ptr, int rows, int cols, int box_rows, int box_cols, int swizzle_bytes) {
  CUtensorMap m;
  cuuint64_t dims[2] = {(cuuint64_t)cols, (cuuint64_t)rows};
  cuuint64_t strides[1] = {(cuuint64_t)cols * 2};
  cuuint32_t box[2] = {(cuuint32_t)box_cols, (cuuint32_t)box_rows};
  cuuint32_t estr[2] = {1, 1};
  CUtensorMapSwizzle sw = swizzle_bytes == 128 ? CU_TENSOR_MAP_SWIZZLE_128B
                        : swizzle_bytes == 64 ? CU_TENSOR_MAP_SWIZZLE_64B
                        : swizzle_bytes == 32 ? CU_TENSOR_MAP_SWIZZLE_32B : CU_TENSOR_MAP_SWIZZLE_NONE;
  get_encoder()(&m, CU_TENSOR_MAP_DATA_TYPE_BFLOAT16, 2, const_cast<void*>(ptr), dims, strides, box, estr,
                CU_TENSOR_MAP_INTERLEAVE_NONE, sw, CU_TENSOR_MAP_L2_PROMOTION_L2_128B, CU_TENSOR_MAP_FLOAT_OOB_FILL_NONE);
  return m;
}
static CUtensorMap make_map3(const void* ptr, int rows, int cols, int box_rows, int nblk) {
  CUtensorMap m;
  cuuint64_t dims[3] = {64, (cuuint64_t)rows, (cuuint64_t)(cols / 64)};
  cuuint64_t strides[2] = {(cuuint64_t)cols * 2, 128};
  cuuint32_t box[3] = {64, (cuuint32_t)box_rows, (cuuint32_t)nblk};
  cuuint32_t estr[3] = {1, 1, 1};
  get_encoder()(&m, CU_TENSOR_MAP_DATA_TYPE_BFLOAT16, 3, const_cast<void*>(ptr), dims, strides, box, estr,
                CU_TENSOR_MAP_INTERLEAVE_NONE, CU_TENSOR_MAP_SWIZZLE_128B, CU_TENSOR_MAP_L2_PROMOTION_L2_128B,
                CU_TENSOR_MAP_FLOAT_OOB_FILL_NONE);
  return m;
}
template <class T> static T* sym(T& s) { void* p = nullptr; cudaGetSymbolAddress(&p, s); return (T*)p; }
#define SYM(name) ((bf16*)[] { void* p = nullptr; cudaGetSymbolAddress(&p, name); return p; }())

#define G_CTAS 36
#define B4_FIRST 11
#define O_FIRST 4
#define B3_FIRST 9
#define LN_POS 63
static int build_items(uint16_t* it) {
  using namespace gk;
  int n = 0;
  auto add = [&](int type, int nrows, int ncols, int row0 = 0) {
    for (int mb = row0; mb < nrows; mb += GCL) for (int nt = 0; nt < ncols; nt++) it[n++] = (uint16_t)(type | mb << 3 | nt << 7);
  };
  add(T_B1, 16, 4); add(T_B2, 16, 4); add(T_B3, B3_FIRST, 14); add(T_B4, 2, 4); add(T_B3, 16, 14, B3_FIRST);
  add(T_B4, B4_FIRST, 4, 2); add(T_O, O_FIRST, 4); add(T_B4, 16, 4, B4_FIRST); add(T_O, TAIL_MB0, 4, O_FIRST);
  return n;
}

extern "C" void kernel_launch(void* const* d_in, const int* in_sizes, int n_in, void* d_out, int out_size) {
  using namespace cfg;
  const bf16* x = (const bf16*)d_in[0];
  const bf16* mem0 = (const bf16*)d_in[1];
  const bf16* Wq = (const bf16*)d_in[2];
  const bf16* Wk = (const bf16*)d_in[3];
  const bf16* Wv = (const bf16*)d_in[4];
  const bf16* Wo = (const bf16*)d_in[5];
  const bf16* w1 = (const bf16*)d_in[8];
  const bf16* w2 = (const bf16*)d_in[9];
  const bf16* w3 = (const bf16*)d_in[10];
  const bf16* w4 = (const bf16*)d_in[11];
  bf16* out = (bf16*)d_out;
  cudaStream_t st = cudaStreamPerThread;

  bf16 *xn = SYM(g_xn), *xn2 = SYM(g_xn2), *hb = SYM(g_h), *x1 = SYM(g_x1), *x1n = SYM(g_x1n), *u = SYM(g_u),
       *g = SYM(g_g), *o = SYM(g_o);

  {
    cudaFuncSetAttribute(f_kernel, cudaFuncAttributeMaxDynamicSharedMemorySize, fk::SMEM);
    FParams P;
    P.wq = make_map(Wq, D, HD, 64, 64, 128); P.wk = make_map(Wk, D, HD, 64, 64, 128); P.wv = make_map(Wv, D, HD, 64, 64, 128);
    P.wo = make_map(Wo, HD, D, 128, 64, 128); P.wo16 = make_map(Wo, HD, D, 128, 16, 32); P.xn = make_map3(xn, S, D, 32, 4); P.xn12 = make_map3(xn, S, D, 32, 12); P.o = make_map3(o, S, HD, 32, 2);
    P.ta = make_map(o, S, HD, 128, 64, 128); P.tb = make_map(Wo, HD, D, 64, 64, 128);
    P.tx = make_map(x, S, D, 128, 32, 64); P.tg = make_map(g, S, D, 128, 32, 64); P.out = out;
    P.mem0 = mem0;
    P.nprobe = PROBE_N;
    P.dxn = make_desc(fk::XN, 16, 1024);
    P.x = x; P.xn_ptr = xn;
    P.xch = (char*)(((uintptr_t)SYM(g_xch) + 8191) & ~(uintptr_t)8191);
    cudaLaunchConfig_t cfg = {};
    cfg.gridDim = dim3(96); cfg.blockDim = dim3(256); cfg.dynamicSmemBytes = fk::SMEM; cfg.stream = st;
    cudaLaunchAttribute at[2];
    at[0].id = cudaLaunchAttributeClusterDimension;
    at[0].val.clusterDim.x = 3; at[0].val.clusterDim.y = 1; at[0].val.clusterDim.z = 1;
    cfg.attrs = at; cfg.numAttrs = 1;
    cudaLaunchKernelEx(&cfg, f_kernel, P);
  }
  {
    cudaFuncSetAttribute(g_kernel, cudaFuncAttributeMaxDynamicSharedMemorySize, gk::SMEM);
    GParams G;
    const bf16* as[5] = {xn2, hb, x1n, u, o};
    const bf16* bs[5] = {w1, w2, w3, w4, Wo};
    bf16* cs[5] = {hb, x1, u, g, out};
    const bf16* rs[5] = {xn, xn, xn, x1, x};
    const int ks[5] = {D, D, D, F, HD}, ns[5] = {D, D, F, D, D};
    for (int i = 0; i < 5; i++) {
      G.a[i] = make_map(as[i], S, ks[i], 128, 64, 128);
      G.b[i] = make_map3(bs[i], ks[i], ns[i], 64, 4 / GCL);
      G.c[i] = cs[i];
      G.r[i] = rs[i];
    }
    G.x1n = x1n; G.xn2 = xn2; G.w1 = w1;
    G.nitems = build_items(G.items);
    G.lnpos = LN_POS * 2 / GCL;
    cudaLaunchConfig_t cfg = {};
    cfg.gridDim = dim3(G_CTAS); cfg.blockDim = dim3(384); cfg.dynamicSmemBytes = gk::SMEM; cfg.stream = st;
    cudaLaunchAttribute at[2];
    at[0].id = cudaLaunchAttributeClusterDimension;
    at[0].val.clusterDim.x = GCL; at[0].val.clusterDim.y = 1; at[0].val.clusterDim.z = 1;
    at[1].id = cudaLaunchAttributeProgrammaticStreamSerialization;
    at[1].val.programmaticStreamSerializationAllowed = 1;
    cfg.attrs = at;
    cfg.numAttrs = 2;
    cudaLaunchKernelEx(&cfg, g_kernel, G);
  }
}
```

```cpp
#include <cuda_runtime.h>
#include <cuda_bf16.h>
#include <cuda.h>
#include <stdint.h>

typedef __nv_bfloat16 bf16;

namespace cfg {
constexpr int S = 2048;
constexpr int D = 1024;
constexpr int H = 32;
constexpr int DH = 128;
constexpr int HD = H * DH;
constexpr int M = 8;
constexpr int SEG = 32;
constexpr int NSEG = S / SEG;
constexpr int F = 3584;
}

__device__ __forceinline__ uint32_t smem_u32(const void* p) { return (uint32_t)__cvta_generic_to_shared(p); }

__device__ __forceinline__ void mbar_init(uint32_t bar, uint32_t count) {
  asm volatile("mbarrier.init.shared::cta.b64 [%0], %1;" ::"r"(bar), "r"(count) : "memory");
}
__device__ __forceinline__ void mbar_expect_tx(uint32_t bar, uint32_t bytes) {
  asm volatile("mbarrier.arrive.expect_tx.shared::cta.b64 _, [%0], %1;" ::"r"(bar), "r"(bytes) : "memory");
}
__device__ __forceinline__ void mbar_arrive(uint32_t bar) {
  asm volatile("mbarrier.arrive.shared::cta.b64 _, [%0];" ::"r"(bar) : "memory");
}
__device__ __forceinline__ bool mbar_try(uint32_t bar, uint32_t parity) {
  uint32_t done;
  asm volatile("{\n.reg .pred p;\nmbarrier.try_wait.parity.shared::cta.b64 p, [%1], %2, 20000;\nselp.u32 %0, 1, 0, p;\n}"
               : "=r"(done) : "r"(bar), "r"(parity) : "memory");
  return done != 0;
}
__device__ __forceinline__ bool mbar_try_nohint(uint32_t bar, uint32_t parity) {
  uint32_t done;
  asm volatile("{\n.reg .pred p;\nmbarrier.try_wait.parity.shared::cta.b64 p, [%1], %2;\nselp.u32 %0, 1, 0, p;\n}"
               : "=r"(done) : "r"(bar), "r"(parity) : "memory");
  return done != 0;
}
constexpr int MBAR_TRIES = 4096;
constexpr int POLL_TRIES = 1 << 16;
__device__ __forceinline__ void mbar_wait(uint32_t bar, uint32_t parity) {
#pragma unroll 1
  for (int n = 0; n < MBAR_TRIES; n++)
    if (mbar_try(bar, parity)) break;
}
__device__ __forceinline__ void mbar_wait_fast(uint32_t bar, uint32_t parity) {
#pragma unroll 1
  for (int n = 0; n < (POLL_TRIES << 4); n++)
    if (mbar_try_nohint(bar, parity)) break;
}
__device__ __forceinline__ void fence_barrier_init() { asm volatile("fence.mbarrier_init.release.cluster;" ::: "memory"); }
__device__ __forceinline__ void fence_proxy_async_smem() { asm volatile("fence.proxy.async.shared::cta;" ::: "memory"); }

__device__ __forceinline__ void tma_load_2d(uint32_t dst, const CUtensorMap* map, int x, int y, uint32_t bar) {
  asm volatile("cp.async.bulk.tensor.2d.shared::cluster.global.mbarrier::complete_tx::bytes [%0], [%1, {%3, %4}], [%2];"
               ::"r"(dst), "l"(map), "r"(bar), "r"(x), "r"(y) : "memory");
}
__device__ __forceinline__ void tma_load_3d(uint32_t dst, const CUtensorMap* map, int x, int y, int z, uint32_t bar) {
  asm volatile("cp.async.bulk.tensor.3d.shared::cluster.global.mbarrier::complete_tx::bytes [%0], [%1, {%3, %4, %5}], [%2];"
               ::"r"(dst), "l"(map), "r"(bar), "r"(x), "r"(y), "r"(z) : "memory");
}
__device__ __forceinline__ void tma_store_2d(const CUtensorMap* map, uint32_t src, int x, int y) {
  asm volatile("cp.async.bulk.tensor.2d.global.shared::cta.bulk_group [%0, {%2, %3}], [%1];"
               ::"l"(map), "r"(src), "r"(x), "r"(y) : "memory");
}
__device__ __forceinline__ void tma_store_commit() { asm volatile("cp.async.bulk.commit_group;" ::: "memory"); }
__device__ __forceinline__ void tma_store_wait_all() { asm volatile("cp.async.bulk.wait_group 0;" ::: "memory"); }
__device__ __forceinline__ void tma_store_wait_read() { asm volatile("cp.async.bulk.wait_group.read 0;" ::: "memory"); }
__device__ __forceinline__ void prefetch_tmap(const CUtensorMap* map) {
  asm volatile("prefetch.tensormap [%0];" ::"l"(map) : "memory");
}

__device__ __forceinline__ void wg_fence() { asm volatile("wgmma.fence.sync.aligned;" ::: "memory"); }
__device__ __forceinline__ void wg_commit() { asm volatile("wgmma.commit_group.sync.aligned;" ::: "memory"); }
template <int N> __device__ __forceinline__ void wg_wait() { asm volatile("wgmma.wait_group.sync.aligned %0;" ::"n"(N) : "memory"); }

#define named_bar_sync(id, n) asm volatile("bar.sync %0, %1;" ::"n"(id), "n"(n) : "memory")
#define named_bar_arrive(id, n) asm volatile("bar.arrive %0, %1;" ::"n"(id), "n"(n) : "memory")

__host__ __device__ __forceinline__ uint64_t make_desc(uint32_t addr, uint32_t lbo, uint32_t sbo) {
  return (uint64_t)((addr & 0x3FFFF) >> 4) | ((uint64_t)(lbo >> 4) << 16) | ((uint64_t)(sbo >> 4) << 32) | (1ull << 62);
}

__device__ __forceinline__ uint64_t make_desc0(uint32_t addr, uint32_t lbo, uint32_t sbo) {
  return (uint64_t)((addr & 0x3FFFF) >> 4) | ((uint64_t)(lbo >> 4) << 16) | ((uint64_t)(sbo >> 4) << 32);
}

__device__ __forceinline__ uint32_t pack_bf16(float lo, float hi) {
  uint32_t r;
  asm("cvt.rn.bf16x2.f32 %0, %1, %2;" : "=r"(r) : "f"(hi), "f"(lo));
  return r;
}
__device__ __forceinline__ float bf_lo(uint32_t v) { return __uint_as_float(v << 16); }
__device__ __forceinline__ float bf_hi(uint32_t v) { return __uint_as_float(v & 0xFFFF0000u); }
__device__ __forceinline__ float rbf(float v) { return __bfloat162float(__float2bfloat16_rn(v)); }

__device__ __forceinline__ void pdl_launch_dependents() { asm volatile("griddepcontrol.launch_dependents;" ::: "memory"); }
__device__ __forceinline__ void pdl_wait() { asm volatile("griddepcontrol.wait;" ::: "memory"); }

__device__ __forceinline__ float ex2_approx(float x) { float y; asm("ex2.approx.ftz.f32 %0, %1;" : "=f"(y) : "f"(x)); return y; }
__device__ __forceinline__ float rcp_approx(float x) { float y; asm("rcp.approx.ftz.f32 %0, %1;" : "=f"(y) : "f"(x)); return y; }

__device__ __forceinline__ void mul_sigmoid4(float (&v)[4], const float (&t)[4]) {
#pragma unroll
  for (int i = 0; i < 4; i += 2) {
    const float a = 1.0f + ex2_approx(fminf(t[i], 60.0f)), b = 1.0f + ex2_approx(fminf(t[i + 1], 60.0f));
    const float r = rcp_approx(a * b);
    v[i] *= b * r;
    v[i + 1] *= a * r;
  }
}
__device__ __forceinline__ void gelu4(float (&v)[4]) {
  float t[4];
#pragma unroll
  for (int i = 0; i < 4; i++) t[i] = v[i] * fmaf(v[i] * v[i], -0.10294324f, -2.30220819f);
  mul_sigmoid4(v, t);
}
__device__ __forceinline__ void silu4(float (&v)[4]) {
  float t[4];
#pragma unroll
  for (int i = 0; i < 4; i++) t[i] = v[i] * -1.4426950408889634f;
  mul_sigmoid4(v, t);
}

#define KT_START(id)
#define KT_END(id)

__device__ __forceinline__ void wgmma_ss_n256_tb(float (&d)[128], uint64_t da, uint64_t db, int scale_d) {
  asm volatile("{\n.reg .pred p;\nsetp.ne.b32 p, %130, 0;\n"
    "wgmma.mma_async.sync.aligned.m64n256k16.f32.bf16.bf16 "
    "{%0, %1, %2, %3, %4, %5, %6, %7, %8, %9, %10, %11, %12, %13, %14, %15, "
    "%16, %17, %18, %19, %20, %21, %22, %23, %24, %25, %26, %27, %28, %29, %30, %31, "
    "%32, %33, %34, %35, %36, %37, %38, %39, %40, %41, %42, %43, %44, %45, %46, %47, "
    "%48, %49, %50, %51, %52, %53, %54, %55, %56, %57, %58, %59, %60, %61, %62, %63, "
    "%64, %65, %66, %67, %68, %69, %70, %71, %72, %73, %74, %75, %76, %77, %78, %79, "
    "%80, %81, %82, %83, %84, %85, %86, %87, %88, %89, %90, %91, %92, %93, %94, %95, "
    "%96, %97, %98, %99, %100, %101, %102, %103, %104, %105, %106, %107, %108, %109, %110, %111, "
    "%112, %113, %114, %115, %116, %117, %118, %119, %120, %121, %122, %123, %124, %125, %126, %127}, "
    "%128, %129, p, 1, 1, 0, 1;\n}\n"
    : "+f"(d[0]), "+f"(d[1]), "+f"(d[2]), "+f"(d[3]), "+f"(d[4]), "+f"(d[5]), "+f"(d[6]), "+f"(d[7]),
      "+f"(d[8]), "+f"(d[9]), "+f"(d[10]), "+f"(d[11]), "+f"(d[12]), "+f"(d[13]), "+f"(d[14]), "+f"(d[15]),
      "+f"(d[16]), "+f"(d[17]), "+f"(d[18]), "+f"(d[19]), "+f"(d[20]), "+f"(d[21]), "+f"(d[22]), "+f"(d[23]),
      "+f"(d[24]), "+f"(d[25]), "+f"(d[26]), "+f"(d[27]), "+f"(d[28]), "+f"(d[29]), "+f"(d[30]), "+f"(d[31]),
      "+f"(d[32]), "+f"(d[33]), "+f"(d[34]), "+f"(d[35]), "+f"(d[36]), "+f"(d[37]), "+f"(d[38]), "+f"(d[39]),
      "+f"(d[40]), "+f"(d[41]), "+f"(d[42]), "+f"(d[43]), "+f"(d[44]), "+f"(d[45]), "+f"(d[46]), "+f"(d[47]),
      "+f"(d[48]), "+f"(d[49]), "+f"(d[50]), "+f"(d[51]), "+f"(d[52]), "+f"(d[53]), "+f"(d[54]), "+f"(d[55]),
      "+f"(d[56]), "+f"(d[57]), "+f"(d[58]), "+f"(d[59]), "+f"(d[60]), "+f"(d[61]), "+f"(d[62]), "+f"(d[63]),
      "+f"(d[64]), "+f"(d[65]), "+f"(d[66]), "+f"(d[67]), "+f"(d[68]), "+f"(d[69]), "+f"(d[70]), "+f"(d[71]),
      "+f"(d[72]), "+f"(d[73]), "+f"(d[74]), "+f"(d[75]), "+f"(d[76]), "+f"(d[77]), "+f"(d[78]), "+f"(d[79]),
      "+f"(d[80]), "+f"(d[81]), "+f"(d[82]), "+f"(d[83]), "+f"(d[84]), "+f"(d[85]), "+f"(d[86]), "+f"(d[87]),
      "+f"(d[88]), "+f"(d[89]), "+f"(d[90]), "+f"(d[91]), "+f"(d[92]), "+f"(d[93]), "+f"(d[94]), "+f"(d[95]),
      "+f"(d[96]), "+f"(d[97]), "+f"(d[98]), "+f"(d[99]), "+f"(d[100]), "+f"(d[101]), "+f"(d[102]), "+f"(d[103]),
      "+f"(d[104]), "+f"(d[105]), "+f"(d[106]), "+f"(d[107]), "+f"(d[108]), "+f"(d[109]), "+f"(d[110]), "+f"(d[111]),
      "+f"(d[112]), "+f"(d[113]), "+f"(d[114]), "+f"(d[115]), "+f"(d[116]), "+f"(d[117]), "+f"(d[118]), "+f"(d[119]),
      "+f"(d[120]), "+f"(d[121]), "+f"(d[122]), "+f"(d[123]), "+f"(d[124]), "+f"(d[125]), "+f"(d[126]), "+f"(d[127])
    : "l"(da), "l"(db), "r"(scale_d));
}
__device__ __forceinline__ void wgmma_rs_n32(float (&d)[16], const uint32_t* a, uint64_t db, int scale_d) {
  asm volatile("{\n.reg .pred p;\nsetp.ne.b32 p, %21, 0;\n"
    "wgmma.mma_async.sync.aligned.m64n32k16.f32.bf16.bf16 "
    "{%0, %1, %2, %3, %4, %5, %6, %7, %8, %9, %10, %11, %12, %13, %14, %15}, "
    "{%16, %17, %18, %19}, %20, p, 1, 1, 0;\n}\n"
    : "+f"(d[0]), "+f"(d[1]), "+f"(d[2]), "+f"(d[3]), "+f"(d[4]), "+f"(d[5]), "+f"(d[6]), "+f"(d[7]),
      "+f"(d[8]), "+f"(d[9]), "+f"(d[10]), "+f"(d[11]), "+f"(d[12]), "+f"(d[13]), "+f"(d[14]), "+f"(d[15])
    : "r"(a[0]), "r"(a[1]), "r"(a[2]), "r"(a[3]), "l"(db), "r"(scale_d));
}
__device__ __forceinline__ void wgmma_ss_n32_ta(float (&d)[16], uint64_t da, uint64_t db, int scale_d) {
  asm volatile("{\n.reg .pred p;\nsetp.ne.b32 p, %18, 0;\n"
    "wgmma.mma_async.sync.aligned.m64n32k16.f32.bf16.bf16 "
    "{%0, %1, %2, %3, %4, %5, %6, %7, %8, %9, %10, %11, %12, %13, %14, %15}, "
    "%16, %17, p, 1, 1, 1, 0;\n}\n"
    : "+f"(d[0]), "+f"(d[1]), "+f"(d[2]), "+f"(d[3]), "+f"(d[4]), "+f"(d[5]), "+f"(d[6]), "+f"(d[7]),
      "+f"(d[8]), "+f"(d[9]), "+f"(d[10]), "+f"(d[11]), "+f"(d[12]), "+f"(d[13]), "+f"(d[14]), "+f"(d[15])
    : "l"(da), "l"(db), "r"(scale_d));
}
__device__ __forceinline__ void wgmma_ss_n8_ta(float (&d)[4], uint64_t da, uint64_t db, int scale_d) {
  asm volatile("{\n.reg .pred p;\nsetp.ne.b32 p, %6, 0;\n"
    "wgmma.mma_async.sync.aligned.m64n8k16.f32.bf16.bf16 {%0, %1, %2, %3}, %4, %5, p, 1, 1, 1, 0;\n}\n"
    : "+f"(d[0]), "+f"(d[1]), "+f"(d[2]), "+f"(d[3]) : "l"(da), "l"(db), "r"(scale_d));
}
__device__ __forceinline__ void wgmma_ss_n48_tt(float (&d)[24], uint64_t da, uint64_t db, int scale_d) {
  asm volatile("{\n.reg .pred p;\nsetp.ne.b32 p, %26, 0;\n"
    "wgmma.mma_async.sync.aligned.m64n48k16.f32.bf16.bf16 "
    "{%0, %1, %2, %3, %4, %5, %6, %7, %8, %9, %10, %11, %12, %13, %14, %15, %16, %17, %18, %19, %20, %21, %22, %23}, "
    "%24, %25, p, 1, 1, 1, 1;\n}\n"
    : "+f"(d[0]), "+f"(d[1]), "+f"(d[2]), "+f"(d[3]), "+f"(d[4]), "+f"(d[5]), "+f"(d[6]), "+f"(d[7]), "+f"(d[8]), "+f"(d[9]), "+f"(d[10]), "+f"(d[11]), "+f"(d[12]), "+f"(d[13]), "+f"(d[14]), "+f"(d[15]), "+f"(d[16]), "+f"(d[17]), "+f"(d[18]), "+f"(d[19]), "+f"(d[20]), "+f"(d[21]), "+f"(d[22]), "+f"(d[23])
    : "l"(da), "l"(db), "r"(scale_d));
}
__device__ __forceinline__ void wgmma_ss_n32(float (&d)[16], uint64_t da, uint64_t db, int scale_d) {
  asm volatile("{\n.reg .pred p;\nsetp.ne.b32 p, %18, 0;\n"
    "wgmma.mma_async.sync.aligned.m64n32k16.f32.bf16.bf16 "
    "{%0, %1, %2, %3, %4, %5, %6, %7, %8, %9, %10, %11, %12, %13, %14, %15}, "
    "%16, %17, p, 1, 1, 0, 0;\n}\n"
    : "+f"(d[0]), "+f"(d[1]), "+f"(d[2]), "+f"(d[3]), "+f"(d[4]), "+f"(d[5]), "+f"(d[6]), "+f"(d[7]),
      "+f"(d[8]), "+f"(d[9]), "+f"(d[10]), "+f"(d[11]), "+f"(d[12]), "+f"(d[13]), "+f"(d[14]), "+f"(d[15])
    : "l"(da), "l"(db), "r"(scale_d));
}

__device__ __forceinline__ void tma_load_2d_mc(uint32_t dst, const CUtensorMap* map, int x, int y, uint32_t bar, uint16_t mask) {
  asm volatile("cp.async.bulk.tensor.2d.shared::cluster.global.mbarrier::complete_tx::bytes.multicast::cluster "
               "[%0], [%1, {%3, %4}], [%2], %5;"
               ::"r"(dst), "l"(map), "r"(bar), "r"(x), "r"(y), "h"(mask) : "memory");
}
__device__ __forceinline__ void mbar_arrive_cluster(uint32_t bar, uint32_t cta) {
  asm volatile("{\n.reg .b32 r;\nmapa.shared::cluster.u32 r, %0, %1;\nmbarrier.arrive.shared::cluster.b64 _, [r];\n}"
               ::"r"(bar), "r"(cta) : "memory");
}
__device__ __forceinline__ void cluster_sync() {
  asm volatile("barrier.cluster.arrive.release.aligned;\nbarrier.cluster.wait.acquire.aligned;" ::: "memory");
}
__device__ __forceinline__ void wait_count(const unsigned* p, unsigned need) {
#pragma unroll 1
  for (int tries = 0; tries < (1 << 18); tries++) {
    unsigned v;
    asm volatile("ld.acquire.gpu.global.u32 %0, [%1];" : "=r"(v) : "l"(p) : "memory");
    if (v >= need) break;
    __nanosleep(64);
  }
}
__device__ __forceinline__ uint32_t sub_bf16x2(uint32_t a, uint32_t b) {
  uint32_t d;
  asm("sub.rn.bf16x2 %0, %1, %2;" : "=r"(d) : "r"(a), "r"(b));
  return d;
}
__device__ __forceinline__ uint32_t add_bf16x2(uint32_t a, uint32_t b) {
  uint32_t d;
  asm("add.rn.bf16x2 %0, %1, %2;" : "=r"(d) : "r"(a), "r"(b));
  return d;
}
__device__ __forceinline__ uint32_t mul_bf16x2(uint32_t a, uint32_t b) {
  uint32_t d;
  asm("mul.rn.bf16x2 %0, %1, %2;" : "=r"(d) : "r"(a), "r"(b));
  return d;
}

template <int NR>
__device__ __forceinline__ void ln_regs(uint32_t (&raw)[NR][16]) {
  float m[NR], q[NR];
#pragma unroll
  for (int r = 0; r < NR; r++) {
    float s0 = 0.f, s1 = 0.f;
#pragma unroll
    for (int i = 0; i < 16; i++) { s0 += bf_lo(raw[r][i]); s1 += bf_hi(raw[r][i]); }
    m[r] = s0 + s1;
  }
#pragma unroll
  for (int o = 16; o > 0; o >>= 1)
#pragma unroll
    for (int r = 0; r < NR; r++) m[r] += __shfl_xor_sync(0xffffffffu, m[r], o);
#pragma unroll
  for (int r = 0; r < NR; r++) {
    m[r] *= 1.0f / 1024.0f;
    float s0 = 0.f, s1 = 0.f;
#pragma unroll
    for (int i = 0; i < 16; i++) {
      const float d0 = bf_lo(raw[r][i]) - m[r], d1 = bf_hi(raw[r][i]) - m[r];
      s0 = fmaf(d0, d0, s0); s1 = fmaf(d1, d1, s1);
    }
    q[r] = s0 + s1;
  }
#pragma unroll
  for (int o = 16; o > 0; o >>= 1)
#pragma unroll
    for (int r = 0; r < NR; r++) q[r] += __shfl_xor_sync(0xffffffffu, q[r], o);
#pragma unroll
  for (int r = 0; r < NR; r++) {
    const uint32_t mb = pack_bf16(m[r], m[r]);
    float sq;
    asm("sqrt.approx.f32 %0, %1;" : "=f"(sq) : "f"(rbf(rbf(q[r] * (1.0f / 1024.0f)) + 1e-5f)));
    const float inv = rcp_approx(rbf(sq));
#pragma unroll
    for (int i = 0; i < 16; i++) {
      const uint32_t d = sub_bf16x2(raw[r][i], mb);
      raw[r][i] = pack_bf16(bf_lo(d) * inv, bf_hi(d) * inv);
    }
  }
}
__device__ __forceinline__ void load_row16(uint32_t (&raw)[16], const bf16* src, int lane) {
#pragma unroll
  for (int j = 0; j < 4; j++) {
    const uint4 u = __ldcg(reinterpret_cast<const uint4*>(src + j * 256 + lane * 8));
    raw[4 * j] = u.x; raw[4 * j + 1] = u.y; raw[4 * j + 2] = u.z; raw[4 * j + 3] = u.w;
  }
}
__device__ __forceinline__ void store_row16(const uint32_t (&raw)[16], bf16* dst, int lane) {
#pragma unroll
  for (int j = 0; j < 4; j++)
    *reinterpret_cast<uint4*>(dst + j * 256 + lane * 8) = make_uint4(raw[4 * j], raw[4 * j + 1], raw[4 * j + 2], raw[4 * j + 3]);
}

namespace fk {
constexpr uint32_t SM0 = 1024;
constexpr uint32_t WO = SM0, WS = WO + 90112, XN = WS + 65536, VX = XN + 49152, QK = VX + 8192, PT = QK + 8192,
                   SP = PT + 4096, VM = SP + 2560, OB = VM + 2048, BAR = OB + 2048;
constexpr uint32_t MEMB = XN + 16384, RED = XN + 32768, VX2 = WO + 81920;
constexpr int SMEM = 232448;
static_assert(BAR + 512 == SM0 + SMEM, "shared memory layout");
constexpr uint32_t B_XN = BAR, B_H2 = BAR + 64, B_H1 = BAR + 120, ONES = BAR + 384, B_PF = BAR + 16, B_WO = BAR + 24, B_SM = BAR + 32, B_VM = BAR + 40, B_VX = BAR + 48, B_ST = BAR + 56, B_PB = BAR + 64, B_W = BAR + 112,
                   MASKS = BAR + 128, PROBE = BAR + 256;
constexpr int NB_M0 = 1, NB_M1 = 2, NB_C = 3, NB_O = 4, NB_ST = 5, NB_DU = 6, NB_CF = 7, NB_W1 = 8, NB_XE = 9, NB_HD = 10, NB_MX = 11, NB_O0 = 12;
#define D_H1 550
#define D_H2 1900
#define D_ST 200
#define SMQ 0x1E
#define SMV 0x1E
#define PRE_G 4
#define PRE_A 1
#define LN_DRY 1
#define MASK_AT 4
#define WO_AT 5
#define NS0 4
#define NS0V 4
#define NTA0 2
#define NTA1 1
#define PF0A 3
#define PF0 10
#define PF1V 10
#define PF1 11
#define REFILL_EARLY 1
#define GATE_MX 0
#define GATE_Q 0
#define PF1Q 4
#define PACEQ 0x60
#define PACEV 0
#define PADD 1
#define D_H2V 2200
#define D_H2L 1700
#define H2_ATV 0
#define VM_BULK 0
#define CF_AT 0
#define H2_AT 0
#define NPRE0 1
#define PROBE_N 4
#define SPACK 1
constexpr uint32_t SPW = SPACK ? 4 : 8, SP_SRC = 160 * SPW;
constexpr int H1_BYTES = 64 * 32768, H2_BYTES = 8 * 8192;
}

#define PROF(wg, i)
#define PROF2(i)
#define RETRY(i)
#define GTSYNC(i)
#define PRO(i)
#define TL(i)
#define TL2(t, i)

__device__ uint4 g_xch[(fk::H1_BYTES + fk::H2_BYTES + 8192) / 16];
__device__ __align__(16) unsigned g_mask[128];
__device__ unsigned g_cnt[8][16];
__device__ unsigned g_next;
constexpr int TAIL_MB0 = 13, GATE_CNT = 12;
__device__ __align__(16) unsigned g_tfix[96], g_lnok[4];
__device__ __align__(16) unsigned g_tcnt[96][8];
__device__ uint4 g_tpart[96][8][2][256];
__device__ unsigned g_oflag[16];

#define LD_POLL "ld.global.L1::no_allocate"
__device__ __forceinline__ uint4 ld_poll16(const void* p) {
  uint4 v;
  asm volatile(LD_POLL ".v4.u32 {%0,%1,%2,%3}, [%4];" : "=r"(v.x), "=r"(v.y), "=r"(v.z), "=r"(v.w) : "l"(p) : "memory");
  return v;
}
__device__ __forceinline__ uint2 ld_poll8(const void* p) {
  uint2 v;
  asm volatile(LD_POLL ".v2.u32 {%0,%1}, [%2];" : "=r"(v.x), "=r"(v.y) : "l"(p) : "memory");
  return v;
}
__device__ __forceinline__ uint4 ld_strong16(const void* p) {
  uint4 v;
  asm volatile("ld.relaxed.gpu.global.v4.u32 {%0,%1,%2,%3}, [%4];" : "=r"(v.x), "=r"(v.y), "=r"(v.z), "=r"(v.w) : "l"(p) : "memory");
  return v;
}
__device__ __forceinline__ uint2 ld_strong8(const void* p) {
  uint2 v;
  asm volatile("ld.relaxed.gpu.global.v2.u32 {%0,%1}, [%2];" : "=r"(v.x), "=r"(v.y) : "l"(p) : "memory");
  return v;
}
__device__ __forceinline__ void st_pub32(void* p, uint32_t v) { asm volatile("st.relaxed.gpu.global.u32 [%0], %1;" ::"l"(p), "r"(v) : "memory"); }
__device__ __forceinline__ void st_pub16(void* p, uint32_t v) {
  asm volatile("st.relaxed.gpu.global.u16 [%0], %1;" ::"l"(p), "h"((uint16_t)v) : "memory");
}
__device__ __forceinline__ uint32_t ld_strong4(const void* p) {
  uint32_t v;
  asm volatile("ld.relaxed.gpu.global.u32 %0, [%1];" : "=r"(v) : "l"(p) : "memory");
  return v;
}
__device__ __forceinline__ void st_pub64(void* p, uint32_t a, uint32_t b) {
  asm volatile("st.relaxed.gpu.global.v2.u32 [%0], {%1,%2};" ::"l"(p), "r"(a), "r"(b) : "memory");
}
__device__ __forceinline__ void st_pub128(void* p, uint32_t a) {
  asm volatile("st.relaxed.gpu.global.v4.u32 [%0], {%1,%1,%1,%1};" ::"l"(p), "r"(a) : "memory");
}
constexpr uint32_t EMPTY = 0xFFFFFFFFu;
__device__ __forceinline__ uint32_t umax4(const uint4& v) { return max(max(v.x, v.y), max(v.z, v.w)); }
__device__ __forceinline__ void sts128(uint32_t a, uint32_t x, uint32_t y, uint32_t z, uint32_t w) {
  asm volatile("st.shared.v4.u32 [%0], {%1,%2,%3,%4};" ::"r"(a), "r"(x), "r"(y), "r"(z), "r"(w) : "memory");
}
__device__ __forceinline__ void sts64(uint32_t a, uint32_t x, uint32_t y) {
  asm volatile("st.shared.v2.u32 [%0], {%1,%2};" ::"r"(a), "r"(x), "r"(y) : "memory");
}
__device__ __forceinline__ void sts32(uint32_t a, uint32_t x) { asm volatile("st.shared.u32 [%0], %1;" ::"r"(a), "r"(x) : "memory"); }
__device__ __forceinline__ void sts128f(uint32_t a, float x, float y, float z, float w) {
  asm volatile("st.shared.v4.f32 [%0], {%1,%2,%3,%4};" ::"r"(a), "f"(x), "f"(y), "f"(z), "f"(w) : "memory");
}
__device__ __forceinline__ void sts64f(uint32_t a, float x, float y) {
  asm volatile("st.shared.v2.f32 [%0], {%1,%2};" ::"r"(a), "f"(x), "f"(y) : "memory");
}
__device__ __forceinline__ float4 lds128f(uint32_t a) {
  float4 v;
  asm volatile("ld.shared.v4.f32 {%0,%1,%2,%3}, [%4];" : "=f"(v.x), "=f"(v.y), "=f"(v.z), "=f"(v.w) : "r"(a) : "memory");
  return v;
}
__device__ __forceinline__ float2 lds64f(uint32_t a) {
  float2 v;
  asm volatile("ld.shared.v2.f32 {%0,%1}, [%2];" : "=f"(v.x), "=f"(v.y) : "r"(a) : "memory");
  return v;
}
__device__ __forceinline__ float2 lds64f_if(uint32_t a, bool on, float other) {
  float2 v = make_float2(other, other);
  asm volatile("{\n.reg .pred p;\nsetp.ne.u32 p, %3, 0;\n@p ld.shared.v2.f32 {%0,%1}, [%2];\n}" : "+f"(v.x), "+f"(v.y) : "r"(a), "r"((uint32_t)on) : "memory");
  return v;
}
__device__ __forceinline__ void lds128(uint32_t* r, uint32_t a) {
  asm volatile("ld.shared.v4.u32 {%0,%1,%2,%3}, [%4];" : "=r"(r[0]), "=r"(r[1]), "=r"(r[2]), "=r"(r[3]) : "r"(a) : "memory");
}
__device__ __forceinline__ void lds64(uint32_t* r, uint32_t a) {
  asm volatile("ld.shared.v2.u32 {%0,%1}, [%2];" : "=r"(r[0]), "=r"(r[1]) : "r"(a) : "memory");
}
__device__ __forceinline__ uint32_t lds32(uint32_t a) {
  uint32_t v;
  asm volatile("ld.shared.u32 %0, [%1];" : "=r"(v) : "r"(a) : "memory");
  return v;
}
__device__ __forceinline__ void ldsm4(uint32_t* r, uint32_t a) {
  asm volatile("ldmatrix.sync.aligned.m8n8.x4.shared.b16 {%0,%1,%2,%3}, [%4];"
               : "=r"(r[0]), "=r"(r[1]), "=r"(r[2]), "=r"(r[3]) : "r"(a) : "memory");
}
__device__ __forceinline__ void ldsm4t(uint32_t* r, uint32_t a) {
  asm volatile("ldmatrix.sync.aligned.m8n8.x4.trans.shared.b16 {%0,%1,%2,%3}, [%4];"
               : "=r"(r[0]), "=r"(r[1]), "=r"(r[2]), "=r"(r[3]) : "r"(a) : "memory");
}
__device__ __forceinline__ void stsm4(uint32_t a, uint32_t r0, uint32_t r1, uint32_t r2, uint32_t r3) {
  asm volatile("stmatrix.sync.aligned.m8n8.x4.shared.b16 [%0], {%1,%2,%3,%4};"
               ::"r"(a), "r"(r0), "r"(r1), "r"(r2), "r"(r3) : "memory");
}
__device__ __forceinline__ void stsm4t(uint32_t a, uint32_t r0, uint32_t r1, uint32_t r2, uint32_t r3) {
  asm volatile("stmatrix.sync.aligned.m8n8.x4.trans.shared.b16 [%0], {%1,%2,%3,%4};"
               ::"r"(a), "r"(r0), "r"(r1), "r"(r2), "r"(r3) : "memory");
}
__device__ __forceinline__ void mma16816(float* d, const uint32_t* a, uint32_t b0, uint32_t b1) {
  asm volatile("mma.sync.aligned.m16n8k16.row.col.f32.bf16.bf16.f32 {%0,%1,%2,%3}, {%4,%5,%6,%7}, {%8,%9}, {%0,%1,%2,%3};"
               : "+f"(d[0]), "+f"(d[1]), "+f"(d[2]), "+f"(d[3])
               : "r"(a[0]), "r"(a[1]), "r"(a[2]), "r"(a[3]), "r"(b0), "r"(b1));
}
__device__ __forceinline__ void mma16816z(float* d, const uint32_t* a, uint32_t b0, uint32_t b1) {
  asm volatile("mma.sync.aligned.m16n8k16.row.col.f32.bf16.bf16.f32 {%0,%1,%2,%3}, {%4,%5,%6,%7}, {%8,%9}, {%10,%10,%10,%10};"
               : "=f"(d[0]), "=f"(d[1]), "=f"(d[2]), "=f"(d[3])
               : "r"(a[0]), "r"(a[1]), "r"(a[2]), "r"(a[3]), "r"(b0), "r"(b1), "f"(0.f));
}
__device__ __forceinline__ void mma1688(float* d, uint32_t a0, uint32_t a1, uint32_t b0) {
  asm volatile("mma.sync.aligned.m16n8k8.row.col.f32.bf16.bf16.f32 {%0,%1,%2,%3}, {%4,%5}, {%6}, {%0,%1,%2,%3};"
               : "+f"(d[0]), "+f"(d[1]), "+f"(d[2]), "+f"(d[3]) : "r"(a0), "r"(a1), "r"(b0));
}
__device__ __forceinline__ uint32_t movtrans(uint32_t a) {
  uint32_t d;
  asm volatile("movmatrix.sync.aligned.m8n8.trans.b16 %0, %1;" : "=r"(d) : "r"(a));
  return d;
}
__device__ __forceinline__ uint32_t mapa(uint32_t a, uint32_t rank) {
  uint32_t d;
  asm("mapa.shared::cluster.u32 %0, %1, %2;" : "=r"(d) : "r"(a), "r"(rank));
  return d;
}
__device__ __forceinline__ void st_async64(uint32_t a, uint32_t x, uint32_t y, uint32_t bar) {
  asm volatile("st.async.weak.shared::cluster.mbarrier::complete_tx::bytes.v2.b32 [%0], {%1,%2}, [%3];"
               ::"r"(a), "r"(x), "r"(y), "r"(bar) : "memory");
}
__device__ __forceinline__ void st_async64f(uint32_t a, float x, float y, uint32_t bar) {
  st_async64(a, __float_as_uint(x), __float_as_uint(y), bar);
}
__device__ __forceinline__ void bulk_s2s(uint32_t dst, uint32_t src, uint32_t bytes, uint32_t bar) {
  asm volatile("cp.async.bulk.shared::cluster.shared::cta.mbarrier::complete_tx::bytes [%0], [%1], %2, [%3];"
               ::"r"(dst), "r"(src), "r"(bytes), "r"(bar) : "memory");
}
__device__ __forceinline__ void tma_store_3d(const CUtensorMap* map, uint32_t src, int x, int y, int z) {
  asm volatile("cp.async.bulk.tensor.3d.global.shared::cta.bulk_group [%0, {%2, %3, %4}], [%1];"
               ::"l"(map), "r"(src), "r"(x), "r"(y), "r"(z) : "memory");
}
__device__ __forceinline__ void mbar_spin(uint32_t bar, uint32_t parity) {
  asm volatile("{\n.reg .pred p;\n.reg .b32 n;\nmov.u32 n, 0x100000;\nMW_L:\n"
               "mbarrier.try_wait.parity.shared::cta.b64 p, [%0], %1;\n@p bra.uni MW_D;\n"
               "add.s32 n, n, -1;\nsetp.ne.u32 p, n, 0;\n@p bra.uni MW_L;\nMW_D:\n}" ::"r"(bar), "r"(parity) : "memory");
}
__device__ __forceinline__ bool mbar_test(uint32_t bar, uint32_t parity) {
  uint32_t done;
  asm volatile("{\n.reg .pred p;\nmbarrier.test_wait.parity.shared::cta.b64 p, [%1], %2;\nselp.u32 %0, 1, 0, p;\n}"
               : "=r"(done) : "r"(bar), "r"(parity) : "memory");
  return done != 0;
}
__device__ __forceinline__ void mbar_arrive_remote(uint32_t bar) {
  asm volatile("mbarrier.arrive.shared::cluster.b64 _, [%0];" ::"r"(bar) : "memory");
}
__device__ __forceinline__ bool elect_one() {
  uint32_t r;
  asm volatile("{\n.reg .pred p;\nelect.sync _|p, 0xffffffff;\nselp.u32 %0, 1, 0, p;\n}" : "=r"(r));
  return r != 0;
}
__device__ __forceinline__ void st_async32(uint32_t a, uint32_t x, uint32_t bar) {
  asm volatile("st.async.weak.shared::cluster.mbarrier::complete_tx::bytes.b32 [%0], %1, [%2];" ::"r"(a), "r"(x), "r"(bar) : "memory");
}
#define named_bar_and(id, n, in, out) \
  asm volatile("{\n.reg .pred p, q;\nsetp.ne.u32 p, %1, 0;\nbar.red.and.pred q, %2, %3, p;\nselp.u32 %0, 1, 0, q;\n}" \
               : "=r"(out) : "r"(in), "n"(id), "n"(n) : "memory")
__device__ __forceinline__ void bulk_g2s(uint32_t dst, const void* src, uint32_t bytes, uint32_t bar) {
  asm volatile("cp.async.bulk.shared::cluster.global.mbarrier::complete_tx::bytes [%0], [%1], %2, [%3];"
               ::"r"(dst), "l"(src), "r"(bytes), "r"(bar) : "memory");
}
__device__ __forceinline__ void l2_prefetch(const void* p, uint32_t bytes) {
  asm volatile("cp.async.bulk.prefetch.L2.global [%0], %1;" ::"l"(p), "r"(bytes) : "memory");
}

__device__ __forceinline__ uint32_t clk32() { uint32_t c; asm volatile("mov.u32 %0, %%clock;" : "=r"(c)::"memory"); return c; }
__device__ __forceinline__ void spin_until(uint32_t t) { while ((int32_t)(clk32() - t) < 0) {} }
#define PIN(x) asm volatile("" : "+r"(x))
#define OPQ                                                                                     \
  int tid_o = tid;                                                                              \
  asm volatile("" : "+r"(tid_o));                                                               \
  const int lane = tid_o & 31, w = (tid_o >> 5) & 3, t7 = tid_o & 127, lg = lane >> 2,          \
            lq = lane & 3, mi = lane >> 3, mr = lane & 7;                                       \
  (void)w; (void)t7; (void)lg; (void)lq; (void)mi; (void)mr; (void)lane

#define SMAP                                                                                                          \
  const uint32_t SM0 = self + fk::SM0, WO = self + fk::WO, WS = self + fk::WS, XN = self + fk::XN, VX = self + fk::VX, \
                 QK = self + fk::QK, PT = self + fk::PT, SP = self + fk::SP, VM = self + fk::VM, OB = self + fk::OB,   \
                 RED = self + fk::RED, VX2 = self + fk::VX2, MEMB = self + fk::MEMB, B_XN = self + fk::B_XN, B_SM = self + fk::B_SM,       \
                 B_VM = self + fk::B_VM, B_VX = self + fk::B_VX, B_ST = self + fk::B_ST, B_PB = self + fk::B_PB,       \
                 B_W = self + fk::B_W, B_H2 = self + fk::B_H2, B_H1 = self + fk::B_H1, B_PF = self + fk::B_PF, B_WO = self + fk::B_WO, MASKS = self + fk::MASKS, PROBE = self + fk::PROBE;                             \
  (void)SM0; (void)WO; (void)WS; (void)XN; (void)VX; (void)QK; (void)PT; (void)SP; (void)VM; (void)OB; (void)RED; (void)VX2; \
  (void)MEMB; (void)B_XN; (void)B_SM; (void)B_VM; (void)B_VX; (void)B_ST; (void)B_PB; (void)B_W; (void)MASKS; (void)PROBE; (void)B_H2; (void)B_H1; (void)B_PF; (void)B_WO

struct FParams {
  CUtensorMap wq, wk, wv, wo, wo16, xn, xn12, o;
  CUtensorMap ta, tb, tx, tg;
  const bf16 *mem0, *x;
  bf16* out;
  bf16* xn_ptr;
  uint64_t dxn;
  int nprobe;
  char* xch;
};

__device__ __forceinline__ uint2 probe_pair(char* p, uint32_t val, uint32_t dummy, int n) {
  uint2 best = make_uint2(0x7FFFFFFF, 0x7FFFFFFF);
  st_pub128(p, val); st_pub128(p + 16, val); st_pub128(p + 4096, val); st_pub128(p + 4112, val);
#pragma unroll 1
  for (int r = 0; r < n; r++) {
    uint32_t v;
    const uint32_t c0 = clk32();
    asm volatile("atom.relaxed.gpu.global.exch.b32 %0, [%1], %2;" : "=r"(v) : "l"(p + (r & 1) * 4096), "r"(val) : "memory");
    asm volatile("{\n.reg .pred p;\nsetp.eq.u32 p, %0, 0x12345678;\n@p st.shared.u32 [%1], %0;\n}" ::"r"(v), "r"(dummy) : "memory");
    const uint32_t d = clk32() - c0;
    if (r & 1) best.y = min(best.y, d); else best.x = min(best.x, d);
  }
  return best;
}

typedef uint32_t WRegs[6][2][4][4];

constexpr uint32_t nth_chunks(uint32_t mask) {
  uint32_t t = 0;
  for (int c = 0, n = 0; c < 10; c++) if ((mask >> c) & 1) t |= c << (4 * n++);
  return t;
}
constexpr uint64_t chunk_pos(uint32_t mask) {
  uint64_t t = 0;
  for (int c = 0, a = 0, b = 0; c < 10; c++) t |= (uint64_t)(((mask >> c) & 1) ? a++ : b++) << (4 * c);
  return t;
}
template <bool ISV> struct Chunks {
  static constexpr uint32_t MASK = ISV ? SMV : SMQ, SMT = nth_chunks(MASK), RFT = nth_chunks(~MASK & 1023);
  static_assert(!(MASK & 1), "the first chunk initialises the accumulators");
  static __device__ __forceinline__ constexpr int rf(int wg, int i) { return wg ? 10 + i : (RFT >> (4 * i)) & 15; }
  static __device__ __forceinline__ constexpr int sm(int i) { return (SMT >> (4 * i)) & 15; }
  static constexpr uint64_t IDX = chunk_pos(MASK);
  static __device__ __forceinline__ constexpr int idx(int c) { return (IDX >> (4 * c)) & 15; }
};

template <bool ISV, int WG> struct ProjCfg {
  static constexpr int N0 = ISV ? NS0V : NS0, NS = WG ? 8 - N0 : N0, P0 = WG ? N0 : 0, NTA = WG ? NTA1 : NTA0;
};
__device__ __forceinline__ void load_pair(uint32_t (&t)[4][4], uint32_t wsa, int pp) {
#pragma unroll
  for (int f = 0; f < 4; f++) ldsm4t(t[f], wsa + ((pp >> 1) * 2 + (f & 1)) * 8192 + ((pp & 1) * 2 + (f >> 1)) * 2048);
}
template <bool ISV, int WG>
__device__ __forceinline__ void proj_mem(const WRegs& wr, uint32_t (&ta)[ProjCfg<ISV, WG>::NTA][4][4], uint32_t wsa, uint32_t mba,
                                         float (&a0)[4], float (&a1)[4]) {
  constexpr int NS = ProjCfg<ISV, WG>::NS, P0 = ProjCfg<ISV, WG>::P0, NTA = ProjCfg<ISV, WG>::NTA, NP = 12 + NS;
  float acc[4][4];
  auto spos = [](int j) { return j < NTA ? j : j + (j - NTA + 1) * 12 / (NS - NTA > 0 ? NS - NTA : 1); };
  auto which = [&](int p) { int r = -1; for (int j = 0; j < NS; j++) if (spos(j) == p) r = j; return r; };
  auto nsm_before = [&](int p) { int n = 0; for (int j = 0; j < NS; j++) if (spos(j) < p) n++; return n; };
#pragma unroll
  for (int p = 0; p < NP; p++) {
    const int j = which(p), r = j >= 0 ? 0 : p - nsm_before(p);
    uint32_t bp[4], tl[4][4];
    ldsm4(bp, mba + (j >= 0 ? Chunks<ISV>::sm((P0 + (j >= 0 ? j : 0)) >> 1) * 1024 + ((P0 + j) & 1) * 512 : Chunks<ISV>::rf(WG, r >> 1) * 1024 + (r & 1) * 512));
    if (j >= NTA) load_pair(tl, wsa, P0 + j);
#pragma unroll
    for (int u = 0; u < 2; u++)
#pragma unroll
      for (int T = 0; T < 2; T++) {
        const uint32_t* a = j >= NTA ? tl[u * 2 + T] : j >= 0 ? ta[j >= 0 ? j % NTA : 0][u * 2 + T] : wr[r >> 1][T][(r & 1) * 2 + u];
        if (p == 0) mma16816z(acc[u * 2 + T], a, bp[2 * u], bp[2 * u + 1]);
        else mma16816(acc[u * 2 + T], a, bp[2 * u], bp[2 * u + 1]);
      }
  }
#pragma unroll
  for (int i = 0; i < 4; i++) { a0[i] = acc[0][i] + acc[2][i]; a1[i] = acc[1][i] + acc[3][i]; }
}
template <bool ISV, int WG, int J0, int J1>
__device__ __forceinline__ void proj_mem_prefetch(uint32_t (&ta)[ProjCfg<ISV, WG>::NTA][4][4], uint32_t wsa) {
#pragma unroll
  for (int j = J0; j < J1; j++) load_pair(ta[j], wsa, ProjCfg<ISV, WG>::P0 + j);
}

template <bool ISV, int WG>
__device__ __forceinline__ void proj_finish(const float (&a0)[4], const float (&a1)[4], uint32_t peer0, uint32_t peer1, uint32_t self, int tid, int warp,
                                            uint32_t (&vmo)[4]) {
  using namespace fk;
  SMAP;
  OPQ;
  if (!ISV) {
    stsm4(PT + mr * 16 + ((mi >> 1) ? WG * 1024 + w * 256 + (mi & 1) * 128 : 2048 + w * 512 + (mi & 1) * 256 + WG * 128),
          pack_bf16(a0[0], a0[1]), pack_bf16(a0[2], a0[3]), pack_bf16(a1[0], a1[1]), pack_bf16(a1[2], a1[3]));
    named_bar_sync(NB_C, 256);
  } else {
    if (WG == 0) sts128f(RED + t7 * 16, a1[0], a1[1], a1[2], a1[3]);
    else sts128f(RED + 2048 + t7 * 16, a0[0], a0[1], a0[2], a0[3]);
    if (WG == 1) { lds64(vmo, VM + t7 * 8); lds64(vmo + 2, VM + 1024 + t7 * 8); }
    named_bar_sync(NB_C, 256);
    const float4 p = lds128f(RED + (1 - WG) * 2048 + t7 * 16);
    const float* k = WG == 0 ? a0 : a1;
    const uint32_t v0 = pack_bf16(k[0] + p.x, k[1] + p.y), v1 = pack_bf16(k[2] + p.z, k[3] + p.w);
    const uint32_t off = VM + WG * 1024 + t7 * 8;
    if (VM_BULK) {
      sts64(off, v0, v1);
      fence_proxy_async_smem();
      __syncwarp();
      const uint32_t a = VM + WG * 1024 + warp * 256;
      if (elect_one()) {
        bulk_s2s(peer0 + a, a, 256, peer0 + B_VM);
        bulk_s2s(peer1 + a, a, 256, peer1 + B_VM);
        mbar_arrive(B_VM);
      }
    } else {
      st_async64(peer0 + off, v0, v1, peer0 + B_VM);
      st_async64(peer1 + off, v0, v1, peer1 + B_VM);
      sts64(off, v0, v1);
      __syncwarp();
      if (lane == 0) mbar_arrive(B_VM);
    }
  }
}

__device__ __forceinline__ void send_scores(float s0, float s1, uint32_t off, uint32_t peer0, uint32_t peer1, uint32_t bar, int lane) {
  if (SPACK) {
    const uint32_t v = pack_bf16(s0, s1);
    st_async32(peer0 + off, v, peer0 + bar);
    st_async32(peer1 + off, v, peer1 + bar);
    sts32(off, v);
  } else {
    st_async64f(peer0 + off, s0, s1, peer0 + bar);
    st_async64f(peer1 + off, s0, s1, peer1 + bar);
    sts64f(off, s0, s1);
  }
  __syncwarp();
  if (lane == 0) mbar_arrive(bar);
}

template <int MODE>
__device__ __forceinline__ void wo_load(uint32_t* r, int f, uint32_t woa, uint32_t wob, bool third) {
  constexpr int NT = MODE ? 3 : 2;
  if (MODE >= 2 && f % 3 == 2)
    asm volatile("{\n.reg .pred p;\nsetp.ne.u32 p, %5, 0;\nmov.b32 %0, 0;\nmov.b32 %1, 0;\nmov.b32 %2, 0;\nmov.b32 %3, 0;\n"
                 "@p ldmatrix.sync.aligned.m8n8.x4.trans.shared.b16 {%0,%1,%2,%3}, [%4];\n}"
                 : "=r"(r[0]), "=r"(r[1]), "=r"(r[2]), "=r"(r[3]) : "r"(wob + (f / 3) * 512), "r"((uint32_t)third) : "memory");
  else ldsm4t(r, woa + (f % NT) * 32768 + (f / NT) * 2048);
}
template <int MODE, int PF>
__device__ __forceinline__ void wo_phase(uint32_t (&wf)[PF][4], uint32_t woa, uint32_t wob, bool third, uint32_t oba, char* h1p,
                                         uint32_t sel, uint32_t tag) {
  constexpr int NT = MODE ? 3 : 2;
  float c[NT][4];
  uint32_t of[2][4];
  ldsm4t(of[0], oba);
#pragma unroll
  for (int k = 0; k < 8; k++) {
    if ((k & 1) == 0 && k + 2 < 8) ldsm4t(of[((k >> 1) + 1) & 1], oba + ((k >> 1) + 1) * 512);
#pragma unroll
    for (int i = 0; i < NT; i++) {
      const int f = k * NT + i;
      const uint32_t b0 = of[(k >> 1) & 1][2 * (k & 1)], b1 = of[(k >> 1) & 1][2 * (k & 1) + 1];
      if (k == 0) mma16816z(c[i], wf[f % PF], b0, b1); else mma16816(c[i], wf[f % PF], b0, b1);
      if (f + PF < 8 * NT) wo_load<MODE>(wf[f % PF], f + PF, woa, wob, third);
    }
  }
#pragma unroll
  for (int i = 0; i < NT; i++) {
    char* p = h1p + i * (8 * 32768) + ((sel >> (2 * i)) & 3) * 2048;
    const uint32_t tm = (sel >> 10) & 1;
    if (MODE < 2 || i < 2 || third) {
      st_pub32(p, (pack_bf16(c[i][0], c[i][1]) & ~tm) | (tag & tm));
      st_pub32(p + 1024, (pack_bf16(c[i][2], c[i][3]) & ~tm) | (tag & tm));
    }
  }
}
template <int MODE, int F0, int F1, int PF>
__device__ __forceinline__ void wo_prefetch(uint32_t (&wf)[PF][4], uint32_t woa, uint32_t wob, bool third) {
#pragma unroll
  for (int f = F0; f < F1; f++) wo_load<MODE>(wf[f], f, woa, wob, third);
}

template <bool ISV> __device__ __forceinline__ uint32_t tok_addr(uint32_t base, int tid) {
  OPQ;
  return ISV ? base + w * 2048 + (mi & 1) * 1024 + (mi >> 1) * 128 + mr * 16 : base + (mi >> 1) * 1024 + w * 256 + (mi & 1) * 128 + mr * 16;
}
template <bool ISV> __device__ __forceinline__ constexpr uint32_t tok_off(int T, int i) { return ISV ? T * 512 + i * 256 : T * 4096 + i * 2048; }
template <bool ISV, int T, bool ADD>
__device__ __forceinline__ void tok_store(const float (&x)[16], uint32_t a, const uint32_t (&p)[2][4]) {
#pragma unroll
  for (int i = 0; i < 2; i++) {
    uint32_t r[4];
#pragma unroll
    for (int k = 0; k < 4; k++)
      r[k] = !ADD ? pack_bf16(x[8 * i + 2 * k], x[8 * i + 2 * k + 1])
           : PADD ? add_bf16x2(pack_bf16(x[8 * i + 2 * k], x[8 * i + 2 * k + 1]), p[i][k])
                  : pack_bf16(x[8 * i + 2 * k] + bf_lo(p[i][k]), x[8 * i + 2 * k + 1] + bf_hi(p[i][k]));
    stsm4(a + tok_off<ISV>(T, i), r[0], r[1], r[2], r[3]);
  }
}

__device__ __forceinline__ void load_xn(const FParams& P, int seg, uint32_t self) {
  SMAP;
  mbar_expect_tx(B_XN, 49152);
  tma_load_3d(XN, &P.xn12, 0, seg * 32, 0, B_XN);
}

#define DESC_ADD(d, n) asm volatile("add.s64 %0, %0, %1;" : "+l"(d) : "n"(n))

template <bool ISV>
__device__ __forceinline__ void f_wg0(const FParams& P, const WRegs& wr, const int h, const int rank, const uint32_t hw, int tid) {
  using namespace fk;
  const uint32_t self = mapa(0, (hw >> (2 * rank)) & 3), peer0 = mapa(0, (hw >> (ISV ? 0 : 2 * (rank ^ 1))) & 3) - self,
                 peer1 = mapa(0, (hw >> (ISV ? 2 : 4)) & 3) - self;
  SMAP;
  const int tile0 = rank * 22;
  const uint32_t usel = __shfl_sync(0xffffffffu, tid, 0);
  const int warp = __shfl_sync(0xffffffffu, threadIdx.x >> 5, 0);
  constexpr int WMODE = ISV ? 0 : 2;
  const bool three = warp < 2;
  uint32_t d_h2 = D_H2V, h2ph = 1;
  tid ^= 0x5500;
#pragma unroll 1
  for (int s = -1;;) {
    uint32_t ta[ProjCfg<ISV, 0>::NTA][4][4], wsa, mba;
    const char* src = P.xch + H1_BYTES + ((s & 1) * 4 + warp) * 8192 + ((usel >> (16 + (s & 1))) & 1) * 4096;
    {
      const uint32_t ph = (s + 1) & 1;
      float x0[16], x1[16];
      uint32_t t_pub = 0;
      wg_fence();
      static_assert(Chunks<ISV>::MASK == 0x1E, "chunks 1 .. 4 are in shared memory");
      uint64_t db = P.dxn;
      auto rs_chunk = [&](int ci, bool pace) {
#pragma unroll
        for (int u = 0; u < 4; u++) {
          wgmma_rs_n32(x0, wr[ci][0][u], db, (ci | u) != 0);
          wgmma_rs_n32(x1, wr[ci][1][u], db, (ci | u) != 0);
          if (u < 3) DESC_ADD(db, 2); else DESC_ADD(db, 250);
          if (pace) { wg_commit(); wg_wait<2>(); wg_fence(); }
        }
      };
      rs_chunk(0, false);
      t_pub = clk32() - 60;
      PROF(0, 8); PROF(0, 1);
#pragma unroll
      for (int c = 1; c <= 4; c++) {
#pragma unroll
        for (int u = 0; u < 4; u++) {
          const uint64_t dx = make_desc(fk::XN + c * 4096 + u * 32, 16, 1024);
          wgmma_ss_n32_ta(x0, make_desc(fk::WS + (c - 1) * 16384 + u * 2048, 8192, 1024), dx, 1);
          wgmma_ss_n32_ta(x1, make_desc(fk::WS + (c - 1) * 16384 + 8192 + u * 2048, 8192, 1024), dx, 1);
          if (c == 4 && u == 1) { wg_commit(); wg_wait<1>(); named_bar_arrive(NB_XE, 160); wg_fence(); }
        }
        if (c == 3) wg_commit();
      }
      DESC_ADD(db, 1024);
#pragma unroll
      for (int c = 5; c < 10; c++) {
        if (c == 9) named_bar_arrive(NB_ST, 256);
        rs_chunk(c - 4, ((ISV ? PACEV : PACEQ) >> c) & 1);
      }
      wg_commit();
      wg_wait<0>();
      PROF(0, 10);
      const uint32_t tb = ISV ? (ph ? VX2 : VX) : QK;
      auto h2_issue = [&]() {
        spin_until(t_pub + (ISV ? d_h2 : D_H2));
        PROF(0, 13);
        if (elect_one()) { mbar_expect_tx(B_H2 + 8 * warp, 4096); bulk_g2s(MEMB + warp * 4096, src, 4096, B_H2 + 8 * warp); }
      };
      named_bar_sync(NB_CF, ISV ? 160 : 256);
      if ((ISV ? H2_ATV : H2_AT) == 0) h2_issue();
      const uint32_t none[2][4] = {}, tka = tok_addr<ISV>(tb, tid);
      tok_store<ISV, 0, false>(x0, tka, none);
      if ((ISV ? H2_ATV : H2_AT) == 1) h2_issue();
      tok_store<ISV, 1, false>(x1, tka, none);
      if ((ISV ? H2_ATV : H2_AT) == 2) h2_issue();
      named_bar_arrive(NB_DU, 256);
    }
    {
      OPQ;
      wsa = WS + ((mi >> 1) * 8 + mr) * 128 + (((2 * w + (mi & 1)) ^ mr) << 4);
      mba = MEMB + lane * 16;
      PIN(wsa); PIN(mba);
      {
        const uint32_t chk = MEMB + w * 4096 + lane * 32 + lg * 4, bar = B_H2 + 8 * warp;
        PROF(0, 11);
        proj_mem_prefetch<ISV, 0, 0, NPRE0>(ta, wsa);
#pragma unroll 1
        for (int tries = 0; tries < POLL_TRIES; tries++) {
          mbar_spin(bar, h2ph);
          h2ph ^= 1;
          const uint32_t mx = max(max(lds32(chk), lds32(chk + 1024)), max(lds32(chk + 2048), lds32(chk + 3072)));
          if (__all_sync(0xffffffffu, mx != EMPTY)) break;
          RETRY(1);
          if (elect_one()) { mbar_expect_tx(bar, 4096); bulk_g2s(MEMB + warp * 4096, src, 4096, bar); }
        }
      }
      PROF(0, 12);
      named_bar_arrive(NB_M1, 256);
      proj_mem_prefetch<ISV, 0, NPRE0, NTA0>(ta, wsa);
      named_bar_sync(NB_M0, 128);
    }
    s++;
    tid ^= 0x5500;
    {
      float a0[4], a1[4];
      proj_mem<ISV, 0>(wr, ta, wsa, mba, a0, a1);
      PROF(0, 2);
      uint32_t unused[4];
      proj_finish<ISV, 0>(a0, a1, peer0, peer1, self, tid, warp, unused);
      PROF(0, 3);
      if (s + 1 == cfg::NSEG) break;
      uint32_t wf[PF0][4], woa, wob;
      bool xn_ok;
      {
        OPQ;
        if (!ISV) {
          uint32_t qf[4][4], kf[2][4];
          const uint32_t qa = PT + 2048 + lane * 16, ka = QK + 4096 + w * 1024 + lane * 16;
          ldsm4t(qf[0], qa); ldsm4t(kf[0], ka); ldsm4t(qf[1], qa + 512);
          ldsm4t(qf[2], qa + 1024); ldsm4t(kf[1], ka + 512); ldsm4t(qf[3], qa + 1536);
          float c0[4], c1[4];
          mma16816z(c0, qf[0], kf[0][0], kf[0][1]);
          mma16816z(c1, qf[1], kf[0][2], kf[0][3]);
          mma16816(c0, qf[2], kf[1][0], kf[1][1]);
          mma16816(c1, qf[3], kf[1][2], kf[1][3]);
          const float s0 = (c0[0] + c0[2]) + (c1[0] + c1[2]), s1 = (c0[1] + c0[3]) + (c1[1] + c1[3]);
          send_scores(s0, s1, SP + rank * SP_SRC + t7 * SPW, peer0, peer1, B_SM, lane);
        }
        PROF(0, 4);
        woa = WO + 16384 + ((mi >> 1) * 8 + mr) * 128 + (((2 * w + (mi & 1)) ^ mr) << 4);
        wob = WO + 81920 + w * 4096 + ((mi >> 1) * 8 + mr) * 32 + (((mi & 1) ^ (mr >> 2)) << 4);
        uint32_t vf[2][2][4], vm[2][2];
        if (s == 0) mbar_spin(B_WO, 0);
        if (!ISV) mbar_spin(B_VX, s & 1);
        PROF(0, 14);
#pragma unroll
        for (int T = 0; T < 2; T++)
#pragma unroll
          for (int kk = 0; kk < 2; kk++) ldsm4(vf[T][kk], ((ISV && (s & 1)) ? VX2 : VX) + w * 2048 + (mi & 1) * 1024 + (mi >> 1) * 128 + mr * 16 + T * 512 + kk * 256);
        wo_prefetch<WMODE, 0, PF0A>(wf, woa, wob, three);
        uint32_t spa = SP + lane * SPW, vma = VM + t7 * 8, oa = OB + (mi >> 1) * 1024 + w * 256 + (mi & 1) * 128 + mr * 16;
        PIN(spa); PIN(vma); PIN(oa);
        if (ISV) {
          d_h2 = D_H2L;
          if (!__all_sync(0xffffffffu, mbar_test(B_SM, s & 1))) { d_h2 = D_H2V; mbar_spin(B_SM, s & 1); }
        } else {
          mbar_spin(B_SM, s & 1);
        }
        PROF(0, 5);
        float sc[10];
#pragma unroll
        for (int j = 0; j < 5; j++) {
          if (SPACK) {
            const uint32_t x = lds32(spa + j * 128), y = lds32(spa + SP_SRC + j * 128);
            sc[2 * j] = bf_lo(x) + bf_lo(y); sc[2 * j + 1] = bf_hi(x) + bf_hi(y);
          } else {
            const float2 x = lds64f(spa + j * 256), y = lds64f(spa + SP_SRC + j * 256);
            sc[2 * j] = x.x + y.x; sc[2 * j + 1] = x.y + y.y;
          }
        }
        const bool vm_ok = mbar_test(B_VM, s & 1);
        lds64(vm[0], vma); lds64(vm[1], vma + 1024);
        float m = fmaxf(fmaxf(fmaxf(sc[0], sc[1]), fmaxf(sc[2], sc[3])), fmaxf(fmaxf(sc[4], sc[5]), fmaxf(sc[6], sc[7])));
        m = fmaxf(m, fmaxf(sc[8], sc[9]));
        const float cs = 0.08838834764831845f * 1.4426950408889634f;
        uint32_t pb[5];
        m = fmaxf(m, __shfl_xor_sync(0xffffffffu, m, 1));
        m = fmaxf(m, __shfl_xor_sync(0xffffffffu, m, 2));
        if (ISV ? GATE_MX : GATE_Q) named_bar_arrive(NB_MX, 256);
        const float mc = -m * cs;
#pragma unroll
        for (int j = 0; j < 5; j++) pb[j] = pack_bf16(ex2_approx(fmaf(sc[2 * j], cs, mc)), ex2_approx(fmaf(sc[2 * j + 1], cs, mc)));
        PROF(0, 15);
        if (!vm_ok) { mbar_spin(B_VM, s & 1); lds64(vm[0], vma); lds64(vm[1], vma + 1024); }
        PROF(0, 6);
        float o0[4], o1[4], rs[4];
        const uint32_t ones[4] = {0x3F803F80u, 0x3F803F80u, 0x3F803F80u, 0x3F803F80u};
        mma16816z(rs, ones, pb[0], pb[1]);
        mma16816z(o0, vf[0][0], pb[0], pb[1]);
        mma16816z(o1, vf[1][0], pb[0], pb[1]);
        mma16816(rs, ones, pb[2], pb[3]);
        mma16816(o0, vf[0][1], pb[2], pb[3]);
        mma16816(o1, vf[1][1], pb[2], pb[3]);
        mma1688(rs, ones[0], ones[0], pb[4]);
        mma1688(o0, vm[0][0], vm[0][1], pb[4]);
        mma1688(o1, vm[1][0], vm[1][1], pb[4]);
        const float i0 = rcp_approx(rs[0]), i1 = rcp_approx(rs[1]);
        stsm4(oa, pack_bf16(o0[0] * i0, o0[1] * i1), pack_bf16(o0[2] * i0, o0[3] * i1),
              pack_bf16(o1[0] * i0, o1[1] * i1), pack_bf16(o1[2] * i0, o1[3] * i1));
      }
      {
        OPQ;
        named_bar_arrive(NB_O, 256);
        wo_prefetch<WMODE, PF0A, PF0>(wf, woa, wob, three);
        xn_ok = mbar_test(B_XN, (s + 1) & 1);
        char* h1p = P.xch + (tile0 + 4 + w) * 32768 + (h >> 3) * 8192 + (h & 7) * 128 + (((2 * lq + (lg & 1)) ^ (h & 7)) << 4) + (lg >> 1) * 4;
        uint32_t oba = OB + lane * 16;
        PIN(oba);
        PROF(0, 7);
        named_bar_sync(NB_O0, 128);
        const uint32_t tag = ((s >> 1) & 1) ^ 1;
        wo_phase<WMODE>(wf, woa, wob, three, oba, h1p, tid >> 8, tag);
        PROF(0, 9);
        if (!xn_ok) mbar_spin(B_XN, (s + 1) & 1);
        named_bar_sync(NB_HD, 256);
      }
    }
  }
}

template <bool ISV>
__device__ __forceinline__ void f_wg1(const FParams& P, const WRegs& wr, const int h, const int rank, const uint32_t hw, int tid) {
  using namespace fk;
  const uint32_t self = mapa(0, (hw >> (2 * rank)) & 3), peer0 = mapa(0, (hw >> (ISV ? 0 : 2 * (rank ^ 1))) & 3) - self,
                 peer1 = mapa(0, (hw >> (ISV ? 2 : 4)) & 3) - self;
  SMAP;
  const int tile0 = rank * 22;
  const uint32_t usel = __shfl_sync(0xffffffffu, tid, 0);
  const int warp = __shfl_sync(0xffffffffu, (threadIdx.x >> 5) & 3, 0);
  constexpr int WMODE = 1;
  uint32_t h1ph = 0;
  auto o_done = [&](int mb) {
    tma_store_wait_all();
    asm volatile("fence.proxy.async.global;" ::: "memory");
    asm volatile("red.relaxed.gpu.global.add.u32 [%0], 1;" ::"l"(&g_oflag[mb]) : "memory");
  };
  uint32_t vmo[4] = {0, 0, 0, 0};
  if (ISV) {
    OPQ;
    sts32(PT + (t7 >> 2) * 128 + ((5 ^ lg) << 4) + lq * 4, 0);
    sts32(PT + (t7 >> 2) * 128 + ((6 ^ lg) << 4) + lq * 4, 0);
  }
  tid ^= 0x5500;
#pragma unroll 1
  for (int s = -1;;) {
    uint32_t ta[ProjCfg<ISV, 1>::NTA][4][4], wsa, mba;
    if (s + 1 < cfg::NSEG) mbar_spin(B_XN, (s + 1) & 1);
    const uint32_t t_pub = clk32();
    auto refill = [&]() {
      if (warp == 3) {
        named_bar_sync(NB_XE, 160);
        if (elect_one()) {
          mbar_expect_tx(B_XN + 8, 16384);
          tma_load_3d(XN, &P.xn, 0, (s + 1) * 32, 12, B_XN + 8);
        }
      }
    };
    auto arm = [&]() {
      if ((tid & 255) == 160) {
        if (s == 1) st_pub32(&g_mask[3 * h + rank], 0);
        if (s + 2 < cfg::NSEG) { mbar_expect_tx(B_SM, ISV ? 2 * SP_SRC : SP_SRC); if (!ISV) mbar_expect_tx(B_VX, 8192); }
        if (!ISV && s + 1 < cfg::NSEG) mbar_expect_tx(B_VM, 2048);
        if (ISV && s >= 1 && s < cfg::NSEG) mbar_expect_tx(B_ST, 7168);
      }
      if (ISV && s < cfg::NSEG && (tid & 254) == 192) mbar_arrive_remote(((tid & 1) ? peer1 : peer0) + B_ST);
      __syncwarp();
    };
    if (ISV) {
      if (s >= 0) arm();
      if (s >= 1) {
        OPQ;
        if (warp == 0 && (s & 3) == 1 && s > 1) { if (elect_one()) o_done((s - 2) >> 2); }
        const uint32_t vb = (s & 1) ? VX : VX2;
        float x0[16], x1[16];
        wg_fence();
        wgmma_rs_n32(x0, vmo, make_desc(fk::PT + 64, 16, 1024), 0);
        wgmma_rs_n32(x1, vmo, make_desc(fk::PT + 96, 16, 1024), 0);
#pragma unroll
        for (int kk = 0; kk < 2; kk++) {
          wgmma_ss_n32(x0, make_desc0(vb + kk * 256, 128, 1024), make_desc(fk::PT + kk * 32, 16, 1024), 1);
          wgmma_ss_n32(x1, make_desc0(vb + 512 + kk * 256, 128, 1024), make_desc(fk::PT + kk * 32, 16, 1024), 1);
        }
        wg_commit();
        wg_wait<0>();
        named_bar_sync(NB_W1, 128);
        PROF(1, 4);
        const uint32_t stg = vb + (8 * (mi >> 1) + mr) * 128 + (((2 * w + (mi & 1)) ^ mr) << 4);
#pragma unroll
        for (int T = 0; T < 2; T++) {
          const float* x = T ? x1 : x0;
#pragma unroll
          for (int jj = 0; jj < 4; jj += 2)
            stsm4t(stg + T * 4096 + jj * 1024, pack_bf16(x[4 * jj], x[4 * jj + 1]), pack_bf16(x[4 * jj + 2], x[4 * jj + 3]),
                   pack_bf16(x[4 * jj + 4], x[4 * jj + 5]), pack_bf16(x[4 * jj + 6], x[4 * jj + 7]));
        }
        fence_proxy_async_smem();
        named_bar_sync(NB_W1, 128);
        PROF(1, 10);
        if (warp == 0) {
          if (elect_one()) {
            tma_store_3d(&P.o, vb, 0, (s - 1) * 32, 2 * h);
            tma_store_commit();
          }
          __syncwarp();
        }
        if (s == cfg::NSEG) break;
      }
      if (s + 1 < cfg::NSEG) refill();
      PROF(1, 11);
    } else if (s < 0) {
      named_bar_arrive(NB_CF, 256);
      refill();
    } else {
      float x[24];
      wg_fence();
#pragma unroll
      for (int k = 0; k < 4; k++) wgmma_ss_n48_tt(x, make_desc0(fk::QK + k * 256, 128, 1024), make_desc0(fk::QK + 4096 + k * 256, 128, 1024), k != 0);
      wg_commit();
      arm();
      auto send_tok = [&]() {
        if (warp < 2) {
          OPQ;
          const uint32_t d0 = peer1 + QK + rank * 3584 + lane * 8 + w * 1280, d1 = d0 + 512 + w * 512, bar = peer1 + B_ST;
          mbar_spin(B_ST, s & 1);
          const float NEG = -500000000.0f / 0.08838834764831845f;
          const bool m0 = 2 * lq > lg, m1 = 2 * lq + 1 > lg;
          st_async64f(d0, x[16] + x[20], x[17] + x[21], bar);
          st_async64f(d1, x[18] + x[22], x[19] + x[23], bar);
          st_async64f(d1 + 256, x[2], x[3], bar);
          if (warp == 0) {
            st_async64f(d0 + 256, m0 ? NEG : x[0], m1 ? NEG : x[1], bar);
            st_async64f(d1 + 512, m0 ? NEG : x[6], m1 ? NEG : x[7], bar);
          } else {
            st_async64f(d0 + 256, x[0], x[1], bar);
            st_async64f(d1 + 512, x[6], x[7], bar);
            st_async64f(d0 + 512, x[4], x[5], bar);
            st_async64f(d0 + 768, m0 ? NEG : x[8], m1 ? NEG : x[9], bar);
            st_async64f(d1 + 768, x[10], x[11], bar);
            st_async64f(d1 + 1024, m0 ? NEG : x[14], m1 ? NEG : x[15], bar);
          }
        }
        PROF(1, 4);
      };
      const bool fin = s + 1 == cfg::NSEG;
      OPQ;
      const int j = 2 * h + rank;
      const char* src = P.xch + j * 32768 + warp * 8192 + (((usel >> 14) & 2) + (s & 1)) * 2048;
      char* dst = P.xch + H1_BYTES + (j >> 4) * 8192 + (lq >> 1) * 4096 + (j & 15) * 256 + (lq & 1) * 128 + (2 * w + (lg & 1)) * 16 + (lg >> 1) * 4;
      const uint32_t chk = VX + mi * 2048 + mr * 128 + (w ^ (mr >> 1)) * 32 + ((lane & 1) + 2 * mi) * 4;
      const uint32_t tmask = (s >> 1) & 1;
      if (!fin) {
        spin_until(t_pub + D_H1);
        if (elect_one()) { mbar_expect_tx(B_H1, 2048); bulk_g2s(VX + warp * 2048, src, 2048, B_H1); }
      }
      __syncwarp();
      wg_wait<0>();
      PROF(1, 6);
      send_tok();
      if (fin) { mbar_spin(B_VM, s & 1); break; }
      named_bar_arrive(NB_CF, 256);
      if (REFILL_EARLY) refill();
#pragma unroll 1
      for (int tries = 0; tries < POLL_TRIES; tries++) {
        float d0[4], d1[4], d2[4], d3[4];
        mbar_spin(B_H1, h1ph);
        h1ph ^= 1;
        PROF(1, 10);
        const uint32_t t0 = lds32(chk), t1 = lds32(chk + 1024);
        wg_fence();
        const uint64_t ones = (uint64_t)(fk::ONES >> 4);
        wgmma_ss_n8_ta(d0, make_desc(fk::VX, 8192, 2048), ones, 0);
        wgmma_ss_n8_ta(d1, make_desc(fk::VX + 1024, 8192, 2048), ones, 0);
        wgmma_ss_n8_ta(d2, make_desc(fk::VX + 4096, 8192, 2048), ones, 0);
        wgmma_ss_n8_ta(d3, make_desc(fk::VX + 5120, 8192, 2048), ones, 0);
        wg_commit();
        uint32_t tt;
        asm volatile("lop3.b32 %0, %1, %2, %3, 0x42;" : "=r"(tt) : "r"(t0), "r"(t1), "r"(tmask) : "memory");
        uint32_t ok;
        named_bar_and(NB_W1, 128, tt & 1, ok);
        if (!ok) { if (elect_one()) { mbar_expect_tx(B_H1, 2048); bulk_g2s(VX + warp * 2048, src, 2048, B_H1); } }
        wg_wait<0>();
        if (ok) {
          st_pub32(dst + (s & 1) * 32768, (lq & 1) ? pack_bf16(d1[0] + d3[0], d1[2] + d3[2]) : pack_bf16(d0[0] + d2[0], d0[2] + d2[2]));
          PROF(1, 12);
          st_pub32(dst + ((s & 1) ^ 1) * 32768, EMPTY);
          break;
        }
        RETRY(0);
      }
      named_bar_sync(NB_W1, 128);
      if ((tid & 255) == 192) mbar_arrive_remote(peer1 + B_PF);
      __syncwarp();
      if (!REFILL_EARLY) refill();
      PROF(1, 11);
    }
    if (!ISV || s + 1 < cfg::NSEG) {
      const uint32_t ph = (s + 1) & 1;
      float x0[16], x1[16];
      uint64_t db = P.dxn + 10 * 256;
      named_bar_sync(NB_ST, 256);
      wg_fence();
#pragma unroll
      for (int c = 0; c < 6; c++) {
        if (c == 2) { PROF(1, 0); mbar_spin(B_XN + 8, ph); PROF(1, 15); wg_fence(); }
        if (ISV && c == CF_AT) {
          if (warp == 0) {
            if (elect_one()) tma_store_wait_read();
            __syncwarp();
            named_bar_arrive(NB_CF, 160);
          }
          wg_fence();
        }
#pragma unroll
        for (int u = 0; u < 4; u++) {
          wgmma_rs_n32(x0, wr[c][0][u], db, (c | u) != 0);
          wgmma_rs_n32(x1, wr[c][1][u], db, (c | u) != 0);
          if (u < 3) DESC_ADD(db, 2); else if (c == 1) DESC_ADD(db, 250 - 12 * 256); else DESC_ADD(db, 250);
        }
      }
      wg_commit();
      OPQ;
      const uint32_t tb = ISV ? (ph ? VX2 : VX) : QK, tka = tok_addr<ISV>(tb, tid);
      uint32_t p0[2][4], p1[2][4];
      named_bar_sync(NB_DU, 256);
      ldsm4(p1[0], tka + tok_off<ISV>(1, 0)); ldsm4(p1[1], tka + tok_off<ISV>(1, 1));
      ldsm4(p0[0], tka + tok_off<ISV>(0, 0)); ldsm4(p0[1], tka + tok_off<ISV>(0, 1));
      if (ISV && s >= 0) mbar_spin(B_PF, s & 1);
      wg_wait<0>();
      PROF(1, 13);
      tok_store<ISV, 1, true>(x1, tka, p1);
      tok_store<ISV, 0, true>(x0, tka, p0);
      if (ISV && s + 2 < cfg::NSEG) {
        fence_proxy_async_smem();
        __syncwarp();
        if (elect_one()) {
          bulk_s2s(peer0 + VX + warp * 2048, tb + warp * 2048, 2048, peer0 + B_VX);
          bulk_s2s(peer1 + VX + warp * 2048, tb + warp * 2048, 2048, peer1 + B_VX);
        }
      }
      wsa = WS + ((mi >> 1) * 8 + mr) * 128 + (((2 * w + (mi & 1)) ^ mr) << 4);
      mba = MEMB + lane * 16;
      PIN(wsa); PIN(mba);
      proj_mem_prefetch<ISV, 1, 0, NTA1>(ta, wsa);
      PROF(1, 14);
      named_bar_sync(NB_M1, 256);
      s++;
      PROF(1, 1);
      float a0[4], a1[4];
      proj_mem<ISV, 1>(wr, ta, wsa, mba, a0, a1);
      PROF(1, 2);
      proj_finish<ISV, 1>(a0, a1, peer0, peer1, self, tid, warp, vmo);
      PROF(1, 3);
    } else {
      OPQ;
      mbar_spin(B_VM, s & 1);
      lds64(vmo, VM + t7 * 8); lds64(vmo + 2, VM + 1024 + t7 * 8);
      s++;
    }
    tid ^= 0x5500;
    const bool last = s + 1 >= cfg::NSEG;
    constexpr int PFW = ISV ? PF1V : PF1;
    uint32_t wf[PFW][4], woa;
    if (ISV) {
      OPQ;
      woa = WO + ((mi >> 1) * 8 + mr) * 128 + (((2 * w + (mi & 1)) ^ mr) << 4);
      if (s >= 1) {
        const uint32_t sa = QK + ((w * (w + 3)) >> 1) * 256 + lane * 8;
        mbar_spin(B_ST, (s - 1) & 1);
        float sc[10];
        {
          const float NEG = -1000000000.0f / 0.08838834764831845f;
          float2 x[5], y[5];
#pragma unroll
          for (int b = 0; b < 5; b++) {
            x[b] = b < 2 ? lds64f(sa + b * 256) : lds64f_if(sa + b * 256, b <= w + 1, NEG);
            y[b] = b < 2 ? lds64f(sa + 3584 + b * 256) : lds64f_if(sa + 3584 + b * 256, b <= w + 1, 0.f);
          }
#pragma unroll
          for (int b = 0; b < 5; b++) { sc[2 * b] = x[b].x + y[b].x; sc[2 * b + 1] = x[b].y + y[b].y; }
        }
        float m = fmaxf(fmaxf(fmaxf(sc[0], sc[1]), fmaxf(sc[2], sc[3])), fmaxf(fmaxf(sc[4], sc[5]), fmaxf(sc[6], sc[7])));
        m = fmaxf(m, fmaxf(sc[8], sc[9]));
        m = fmaxf(m, __shfl_xor_sync(0xffffffffu, m, 1));
        m = fmaxf(m, __shfl_xor_sync(0xffffffffu, m, 2));
        const float cs = 0.08838834764831845f * 1.4426950408889634f;
#pragma unroll
        for (int i = 0; i < 10; i++) sc[i] = ex2_approx((sc[i] - m) * cs);
        float sum = ((sc[0] + sc[1]) + (sc[2] + sc[3])) + ((sc[4] + sc[5]) + (sc[6] + sc[7])) + (sc[8] + sc[9]);
        sum += __shfl_xor_sync(0xffffffffu, sum, 1);
        sum += __shfl_xor_sync(0xffffffffu, sum, 2);
        const float inv = rcp_approx(sum);
        const uint32_t pa = PT + (w * 8 + mr) * 128, pm = pack_bf16(sc[0] * inv, sc[1] * inv);
        stsm4(pa + ((mi ^ mr) << 4), pack_bf16(sc[2] * inv, sc[3] * inv), pack_bf16(sc[4] * inv, sc[5] * inv),
              pack_bf16(sc[6] * inv, sc[7] * inv), pack_bf16(sc[8] * inv, sc[9] * inv));
        asm volatile("stmatrix.sync.aligned.m8n8.x2.shared.b16 [%0], {%1,%1};" ::"r"(pa + ((((mi & 1) ? 7 : 4) ^ mr) << 4)), "r"(pm) : "memory");
      }
      if (warp == 3 && !last) {
        mbar_spin(B_VM, s & 1);
        if (elect_one()) load_xn(P, s + 1, self);
      }
      PROF(1, 5);
    } else {
      if (warp == 0) {
        OPQ;
        uint32_t kf[4][4], qf[4][4];
        float c0[4], c1[4], d0[4], d1[4];
        const uint32_t ka = PT + (mi >> 1) * 1024 + (mi & 1) * 128 + mr * 16;
#pragma unroll
        for (int k = 0; k < 4; k++) { ldsm4t(qf[k], PT + 2048 + k * 512 + lane * 16); ldsm4t(kf[k], ka + k * 256); }
        mma16816z(c0, qf[0], kf[0][0], kf[0][1]); mma16816z(c1, qf[0], kf[0][2], kf[0][3]);
        mma16816z(d0, qf[1], kf[1][0], kf[1][1]); mma16816z(d1, qf[1], kf[1][2], kf[1][3]);
        mma16816(c0, qf[2], kf[2][0], kf[2][1]); mma16816(c1, qf[2], kf[2][2], kf[2][3]);
        mma16816(d0, qf[3], kf[3][0], kf[3][1]); mma16816(d1, qf[3], kf[3][2], kf[3][3]);
        const float s0 = ((c0[0] + c0[2]) + (c1[0] + c1[2])) + ((d0[0] + d0[2]) + (d1[0] + d1[2]));
        const float s1 = ((c0[1] + c0[3]) + (c1[1] + c1[3])) + ((d0[1] + d0[3]) + (d1[1] + d1[3]));
        if (!last) send_scores(s0, s1, SP + rank * SP_SRC + (128 + lane) * SPW, peer0, peer1, B_SM, lane);
        PROF(1, 5);
      } else {
        const uint32_t t_c = clk32() + lds32(B_XN) * 0;
        if (warp == 3 && !last) { if (elect_one()) load_xn(P, s + 1, self); }
        spin_until(t_c + D_ST);
      }
      OPQ;
      woa = WO + ((mi >> 1) * 8 + mr) * 128 + (((2 * w + (mi & 1)) ^ mr) << 4);
    }
    if (!last) {
      OPQ;
      uint32_t oba = OB + lane * 16;
      if (s == 0) mbar_spin(B_WO, 0);
      if (!ISV) wo_prefetch<WMODE, 0, PF1Q>(wf, woa, 0, true);
      if (ISV ? GATE_MX : GATE_Q) named_bar_sync(NB_MX, 256);
      wo_prefetch<WMODE, ISV ? 0 : PF1Q, PFW>(wf, woa, 0, true);
      char* h1p = P.xch + (tile0 + w) * 32768 + (h >> 3) * 8192 + (h & 7) * 128 + (((2 * lq + (lg & 1)) ^ (h & 7)) << 4) + (lg >> 1) * 4;
      fence_proxy_async_smem();
      PROF(1, 7);
      named_bar_sync(NB_O, 256);
      PROF(1, 8);
      wo_phase<WMODE>(wf, woa, 0, true, oba, h1p, tid >> 8, ((s >> 1) & 1) ^ 1);
      PROF(1, 9);
      named_bar_sync(NB_HD, 256);
    } else {
      fence_proxy_async_smem();
      named_bar_sync(NB_W1, 128);
    }
  }
  if (ISV && warp == 0) { if (elect_one()) o_done(15); }
}

template <bool ISV, int WG>
__device__ __forceinline__ void f_main(const FParams& P, const int h, const int rank, const uint32_t hw) {
  using namespace fk;
  const uint32_t self = mapa(0, (hw >> (2 * rank)) & 3);
  SMAP;
  const int tid = __shfl_sync(0xffffffffu, threadIdx.x, threadIdx.x & 31);
  const int tile0 = rank * 22, ntile = ISV ? 20 : 22;
  const CUtensorMap* m0 = ISV ? &P.wv : &P.wq;
  const CUtensorMap* m1 = ISV ? &P.wv : &P.wk;
  const int col0 = h * 128 + (ISV ? 0 : 64 * rank), col1 = h * 128 + (ISV ? 64 : 64 * rank);
  WRegs wr;
  uint32_t sel = 0;
  {
    OPQ;
    const uint32_t a = SM0 + WG * 16384 + ((mi >> 1) * 8 + mr) * 128 + (((2 * w + (mi & 1)) ^ mr) << 4);
    uint2 mi0 = make_uint2(0, 0);
    if (!ISV && WG == 1) mi0 = *reinterpret_cast<const uint2*>(P.mem0 + ((lane >> 1) & 7) * cfg::D + (2 * h + rank) * 16 + (lane >> 4) * 8 + (lane & 1) * 4);
#pragma unroll
    for (int i = 0; i < 6; i++) {
      if (i == MASK_AT && WG == 1 && w == 1) {
        uint4 v;
#pragma unroll 1
        for (int tries = 0; tries < POLL_TRIES; tries++) {
          asm volatile("ld.acquire.gpu.global.v4.u32 {%0,%1,%2,%3}, [%4];" : "=r"(v.x), "=r"(v.y), "=r"(v.z), "=r"(v.w)
                       : "l"(&g_mask[4 * min(lane, 23)]) : "memory");
          if (__all_sync(0xffffffffu, v.x & v.y & v.z & v.w & 0x100)) break;
          __nanosleep(100);
        }
        sts128(OB + lane * 16, v.x, v.y, v.z, v.w);
      }
      mbar_wait(B_PB + 8 * i, 0);
      PRO(8 + i);
#pragma unroll
      for (int T = 0; T < 2; T++)
#pragma unroll
        for (int u = 0; u < 4; u++) ldsm4t(wr[i][T][u], a + i * 32768 + T * 8192 + u * 2048);
      named_bar_sync(NB_C, 256);
      if (WG == 1 && w == (i & 3)) {
        if (elect_one()) {
          if (i <= 2 && i + PRE_G < 6) {
#pragma unroll 1
            for (int n = 2 * (i + PRE_G); n < (i == 2 ? 12 : 2 * (i + PRE_G) + 2); n++) {
              const int ii = n >> 1, row = Chunks<ISV>::rf(n & 1, ii) * 64;
              if (!(n & 1)) mbar_expect_tx(B_PB + 8 * ii, 32768);
              tma_load_2d(SM0 + n * 16384, m0, col0, row, B_PB + 8 * ii);
              tma_load_2d(SM0 + n * 16384 + 8192, m1, col1, row, B_PB + 8 * ii);
            }
          }
          if (i == 3 || i == 4) {
            const int p0 = i == 3 ? 0 : 5, p1 = i == 3 ? 5 : 8;
            mbar_expect_tx(B_W, (p1 - p0) * 8192);
#pragma unroll 1
            for (int p = p0; p < p1; p++) tma_load_2d(WS + p * 8192, (p & 1) ? m1 : m0, (p & 1) ? col1 : col0, Chunks<ISV>::sm(p >> 1) * 64, B_W);
          }
          if (i == 5) {
            asm volatile("fence.proxy.async.global;" ::: "memory");
            load_xn(P, 0, self);
          }
          if (i == WO_AT) {
            mbar_expect_tx(B_WO, ntile * 4096);
#pragma unroll 1
            for (int t = 0; t < 5; t++) tma_load_2d(WO + t * 16384, &P.wo, tile0 * 16 + t * 64, h * 128, B_WO);
            if (!ISV) {
              tma_load_2d(WO + 81920, &P.wo16, tile0 * 16 + 320, h * 128, B_WO);
              tma_load_2d(WO + 86016, &P.wo16, tile0 * 16 + 336, h * 128, B_WO);
            }
          }
        }
      }
    }
    PROF2(1);
    if (!ISV && WG == 1 && w < 2) st_pub64(P.xch + H1_BYTES + 32768 + (h >> 3) * 8192 + w * 4096 + ((2 * h + rank) & 15) * 256 + lane * 8, mi0.x, mi0.y);
    if (blockIdx.x == 2 && tid == 160) { __threadfence(); st_pub128(g_lnok, 0x100); }
#pragma unroll
    for (int i = 0; i < 3; i++) {
      const int t = min(tile0 + 8 * i + w + (WG ? 0 : 4), 63);
      sel |= ((lds32(OB + ((t >> 1) * 3 + (t & 1)) * 4) >> (h >> 3)) & 1) << (2 * i + 1);
    }
    const uint32_t own = lds32(OB + (3 * h + rank) * 4) >> w, m2 = lds32(OB + (3 * h + 2) * 4) >> w;
    sel |= (own & 1) << 7 | (m2 & 1) << 8 | (m2 & 16) << 5;
    sel |= (((((lg ^ h) & 1) << 2) | (lg >> 1)) == (h & 1) + 2 * (h >> 3)) << 10;
  }
  asm volatile("barrier.cluster.wait.aligned;" ::: "memory");
  PRO(14);
  mbar_wait(B_W, 0);
  mbar_wait(B_XN, 0);
  PRO(15);
  PROF2(4);
  GTSYNC(0);
  PROF2(2);
  KT_END(8);
  if (WG == 0) f_wg0<ISV>(P, wr, h, rank, hw, tid | sel << 8); else f_wg1<ISV>(P, wr, h, rank, hw, tid | sel << 8);
}

__device__ __forceinline__ void f_tail(const FParams& P, const int h, const uint32_t rank, const bool isv) {
  using namespace fk;
  const uint32_t self = mapa(0, rank), base = self + SM0;
  const uint32_t FULL = self + SP, EMPT = FULL + 32, NOG = FULL + 64, RES = FULL + 72;
  const int tid = threadIdx.x, lane = tid & 31, wv = __shfl_sync(0xffffffffu, tid >> 5, 0), wg = wv >> 2;
  const int kq = h & 7, nt = h >> 3, mb = TAIL_MB0 + rank;
  auto a_off = [](uint32_t st) { return (0x98685800u >> (8 * st) & 255) * 1024; };
  auto b_off = [](uint32_t st) { return (0xA8783010u >> (8 * st) & 255) * 1024; };
  static_assert(VX2 - SM0 == 80 * 1024 && VX - SM0 == 200 * 1024, "stage layout");
  auto load_b = [&](int kb) {
    const uint32_t sb = base + b_off(kb & 3), full = FULL + 8 * (kb & 3);
    mbar_expect_tx(full, 49152);
    tma_load_2d_mc(sb + rank * 8192, &P.tb, nt * 256 + ((rank + (kq >> 1)) & 3) * 64, (kq * 8 + kb) * 64, full, 7);
    if (kb % 3 == rank) tma_load_2d_mc(sb + 3 * 8192, &P.tb, nt * 256 + ((3 + (kq >> 1)) & 3) * 64, (kq * 8 + kb) * 64, full, 7);
  };
  auto load_a = [&](int kb) { tma_load_2d(base + a_off(kb & 3), &P.ta, (kq * 8 + kb) * 64, mb * 128, FULL + 8 * (kb & 3)); };
  TL(0);
  TL2(128, 10); TL2(160, 11);
  if (wv == 0) {
    if (elect_one()) {
      prefetch_tmap(&P.tb); prefetch_tmap(&P.ta);
      if (isv) mbar_spin(self + B_VM, (cfg::NSEG - 1) & 1);
      for (int i = 0; i < 4; i++) { mbar_init(FULL + 8 * i, 1); mbar_init(EMPT + 8 * i, 24); }
      mbar_init(RES, 1);
      fence_barrier_init();
      mbar_arrive_cluster(self + B_W, rank == 0 ? 1 : 0);
      mbar_arrive_cluster(self + B_W, rank == 2 ? 1 : 2);
      mbar_spin(self + B_W, 1);
#pragma unroll 1
      for (int kb = 0; kb < 4; kb++) load_b(kb);
      TL2(0, 12);
      wait_count(&g_oflag[mb], 32);
      asm volatile("fence.proxy.async.global;" ::: "memory");
      TL2(0, 13);
#pragma unroll 1
      for (int kb = 0; kb < 4; kb++) load_a(kb);
      TL2(0, 14);
    }
  } else if (wv == 1) {
    if (lane == 0) {
      prefetch_tmap(&P.tx); prefetch_tmap(&P.tg);
      const bool ng = ld_strong4(&g_next) == 0;
      sts32(NOG, ng);
      if (ng) g_tfix[blockIdx.x] = 1; else wait_count(&g_cnt[3][mb], GATE_CNT);
    }
  }
  float acc[128];
  __syncthreads();
  KT_START(7);
  const bool nog = lds32(NOG);
  if (nog) TL(15); else TL(15);
  if (wv == 1) {
    if (elect_one()) {
      asm volatile("fence.proxy.async.global;" ::: "memory");
      mbar_expect_tx(RES, 16384);
      tma_load_2d(self + VX, &P.tx, nt * 256 + kq * 32, mb * 128, RES);
      tma_load_2d(self + QK, &P.tg, nt * 256 + kq * 32, mb * 128, RES);
    }
  }
#pragma unroll 1
  for (int kb = 0; kb < 8; kb++) {
    const uint32_t st = kb & 3, sa = base + a_off(st) + wg * 8192, sb = base + b_off(st);
    mbar_spin(FULL + 8 * st, kb >> 2);
    if (kb == 0) TL(2);
    if (kb == 4) TL(3);
    wg_fence();
#pragma unroll
    for (int k = 0; k < 4; k++) {
      wgmma_ss_n256_tb(acc, make_desc(sa + k * 32, 16, 1024), make_desc(sb + k * 2048, 8192, 1024), (kb | k) != 0);
      if (k == 0) {
        wg_commit();
        wg_wait<1>();
        if (kb > 0 && kb <= 4 && lane < 3) mbar_arrive_cluster(EMPT + 8 * (kb - 1), lane);
        wg_fence();
      }
    }
    wg_commit();
    if (kb >= 2 && kb < 6 && wv == ((kb & 1) << 2)) {
      if (elect_one()) {
        mbar_spin(EMPT + 8 * (kb - 2), 0);
        load_b(kb + 2);
        load_a(kb + 2);
      }
      __syncwarp();
    }
  }
  wg_wait<0>();
  TL(5);
#pragma unroll
  for (int j = 0; j < 8; j++) {
    uint4* dst = &g_tpart[((h & ~7) + ((j + (kq & 6)) & 7)) * 3 + rank][kq][0][tid];
    if (j >= 2 || j != (kq & 1)) {
#pragma unroll
      for (int i = 0; i < 2; i++) {
        const float* a = &acc[16 * j + 8 * i];
        dst[i * 256] = make_uint4(pack_bf16(a[0], a[1]), pack_bf16(a[2], a[3]), pack_bf16(a[4], a[5]), pack_bf16(a[6], a[7]));
      }
    }
  }
#pragma unroll
  for (int i = 0; i < 16; i++) acc[i] = (kq & 1) ? acc[16 + i] : acc[i];
  TL(6);
  __syncwarp();
  if (lane < 8) asm volatile("red.release.gpu.global.add.u32 [%0], 1;" ::"l"(&g_tcnt[((h & ~7) + lane) * 3 + rank][wv]) : "memory");
  TL(7);
  const size_t off = (size_t)(mb * 128 + wv * 16 + (lane >> 2)) * cfg::D + nt * 256 + kq * 32 + (lane & 3) * 2;
  uint32_t x[8], g[8];
  const uint32_t xa = self + VX + (wv * 16 + (lane & 15)) * 64 + (((lane >> 4) ^ ((lane >> 1) & 3)) << 4);
  mbar_spin(RES, 0);
  ldsm4(x, xa); ldsm4(x + 4, xa ^ 32);
  ldsm4(g, xa + (QK - VX)); ldsm4(g + 4, (xa ^ 32) + (QK - VX));
#pragma unroll 1
  for (int tries = 0; tries < POLL_TRIES; tries++) {
    uint32_t v;
    asm volatile("ld.acquire.gpu.global.u32 %0, [%1];" : "=r"(v) : "l"(&g_tcnt[blockIdx.x][wv]) : "memory");
    if (v >= 8) break;
  }
  uint4 pt[14];
#pragma unroll
  for (int i = 0; i < 14; i++) pt[i] = __ldcg(&g_tpart[blockIdx.x][(kq + 1 + (i >> 1)) & 7][i & 1][tid]);
  TL(8);
#pragma unroll 1
  for (int j = 0; j < 2; j++) {
#pragma unroll
    for (int i = 0; i < 28; i++) {
      const uint32_t v = (&pt[2 * (i >> 2)].x)[i & 3];
      acc[2 * (i & 3)] += bf_lo(v); acc[2 * (i & 3) + 1] += bf_hi(v);
    }
#pragma unroll
    for (int i = 0; i < 4; i++) {
      const uint32_t sv = pack_bf16(acc[2 * i], acc[2 * i + 1]);
      *reinterpret_cast<uint32_t*>(P.out + off + (i & 1) * 8 * cfg::D + (i >> 1) * 8 + j * 16) = nog ? sv : add_bf16x2(x[i], mul_bf16x2(sv, g[i]));
      x[i] = x[i + 4]; g[i] = g[i + 4];
      acc[2 * i] = acc[8 + 2 * i]; acc[2 * i + 1] = acc[9 + 2 * i];
    }
#pragma unroll
    for (int i = 0; i < 7; i++) pt[2 * i] = pt[2 * i + 1];
  }
  TL(9);
  KT_END(7);
}

__global__ void __launch_bounds__(256, 1) f_kernel(const __grid_constant__ FParams P) {
  using namespace fk;
  extern __shared__ __align__(1024) uint8_t smem_f[];
  uint32_t crank, rank, hw;
  asm("mov.u32 %0, %%cluster_ctarank;" : "=r"(crank));
  const int h = blockIdx.x / 3;
  if (smem_u32(smem_f) != mapa(0, crank) + SM0) return;
  PROF2(0);
  KT_START(1);
  KT_START(0);
  {
    const uint32_t self = mapa(0, crank);
    SMAP;
    const int tid = threadIdx.x, lane = tid & 31, wv = __shfl_sync(0xffffffffu, tid >> 5, 0);
    PRO(0);
    if (wv == 0) {
      uint32_t sm;
      asm("mov.u32 %0, %%smid;" : "=r"(sm));
      sts32(PROBE + 96, sm >> 1);
      asm volatile("fence.release.sync_restrict::shared::cta.cluster;" ::: "memory");
    }
    asm volatile("barrier.cluster.arrive.relaxed.aligned;" ::: "memory");
    if (wv == 7) {
      if (blockIdx.x == 2) {
#pragma unroll
        for (int i = 0; i < 4; i++) { (&g_cnt[0][0])[32 * i + lane] = 0; if (i < 3) g_tfix[32 * i + lane] = 0; }
        if (lane < 16) g_oflag[lane] = 0;
        if (lane == 0) { g_next = 0; g_lnok[0] = 0; }
        __threadfence();
        __syncwarp();
      }
      pdl_launch_dependents();
    }
    const int row0 = blockIdx.x * 8 + wv;
    const bool third = row0 + 1536 < cfg::S;
    uint32_t cur[1][16] = {}, raw[3][16];
    load_row16(raw[0], P.x + (size_t)row0 * cfg::D, lane);
    load_row16(raw[1], P.x + (size_t)(row0 + 768) * cfg::D, lane);
    load_row16(raw[2], P.x + (size_t)(row0 + (third ? 1536 : 0)) * cfg::D, lane);
    {
      uint32_t tpc;
      asm volatile("barrier.cluster.wait.aligned;" ::: "memory");
      asm volatile("ld.shared::cluster.u32 %0, [%1];" : "=r"(tpc) : "r"(mapa(PROBE + 96, lane % 3)) : "memory");
      const uint32_t t0 = __shfl_sync(0xffffffffu, tpc, 0), t1 = __shfl_sync(0xffffffffu, tpc, 1), t2 = __shfl_sync(0xffffffffu, tpc, 2);
      hw = t1 == t2 ? 0x09 : t0 == t2 ? 0x18 : 0x24;
      rank = (hw & 3) == crank ? 0 : ((hw >> 2) & 3) == crank ? 1 : 2;
    }
    const bool isv = rank == 2;
    const CUtensorMap* m0 = isv ? &P.wv : &P.wq;
    const CUtensorMap* m1 = isv ? &P.wv : &P.wk;
    const int col0 = h * 128 + (isv ? 0 : 64 * rank), col1 = h * 128 + (isv ? 64 : 64 * rank);
    auto req_weights = [&](int n0, int n1) {
#pragma unroll 1
        for (int n = n0; n < n1; n++) {
          const int i = n >> 1, g = n & 1, row = (isv ? Chunks<true>::rf(g, i) : Chunks<false>::rf(g, i)) * 64;
          if (!g) mbar_expect_tx(B_PB + 8 * i, 32768);
          tma_load_2d(SM0 + n * 16384, m0, col0, row, B_PB + 8 * i);
          tma_load_2d(SM0 + n * 16384 + 8192, m1, col1, row, B_PB + 8 * i);
        }
    };
    if (wv == 0) {
      if (elect_one()) {
        for (int i = 0; i < 2; i++) mbar_init(B_XN + 8 * i, 1);
        mbar_init(B_H1, 4);
        mbar_init(B_SM, isv ? 1 : 6);
        mbar_init(B_VM, isv ? 8 : 1);
        mbar_init(B_VX, 1);
        mbar_init(B_ST, 1);
        mbar_init(B_PF, 2);
        for (int i = 0; i < 6; i++) mbar_init(B_PB + 8 * i, 1);
        mbar_init(B_W, 2);
        mbar_init(B_WO, 1);
        fence_barrier_init();
        if (PRE_A) req_weights(0, 2 * PRE_A);
        mbar_expect_tx(B_SM, isv ? 2 * SP_SRC : SP_SRC);
        if (isv) mbar_expect_tx(B_ST, 7168);
        else { mbar_expect_tx(B_VM, 2048); mbar_expect_tx(B_VX, 8192); }
      }
    }
    const int j = 2 * h + rank;
    const bool dry = LN_DRY && !isv && wv == 6;
    if (dry) sts64(PROBE + wv * 8, 0x7FFFFFFF, 0x7FFFFFFF);
    if (lane == 0 && !dry) {
      const uint2 b = probe_pair(P.xch + (isv ? H1_BYTES + wv * 8192 + h * 128 : j * 32768 + (wv & 3) * 8192 + (wv >> 2) * 128),
                                 isv ? EMPTY : 0, PROBE + 64, P.nprobe);
      sts64(PROBE + wv * 8, b.x, b.y);
    }
    uint32_t mask = 0;
#pragma unroll 1
    for (int it = -1; it < (third ? 3 : 2); it++) {
      if (it >= 0 || dry) {
        ln_regs<1>(cur);
        if (it >= 0) store_row16(cur[0], P.xn_ptr + (size_t)(row0 + it * 768) * cfg::D, lane);
      }
      if (it == 0) PRO(4);
      if (it < 0) {
    PROF2(3);
    PRO(1);
    __syncwarp();
    if (wv == 0) {
      asm volatile("{\n.reg .pred p;\nsetp.eq.u32 p, %0, %1;\n@p st.shared.u32 [%2], %0;\n}" ::"r"(raw[2][15]), "r"(raw[0][0] ^ raw[1][15]), "r"(PROBE + 64) : "memory");
      if (elect_one()) {
        req_weights(2 * PRE_A, 2 * PRE_G);
      }
    }
    __syncthreads();
    PRO(2);
    asm volatile("barrier.cluster.arrive.relaxed.aligned;" ::: "memory");
    PRO(3);
    if (tid < 8) g_tcnt[blockIdx.x][tid] = 0;
    if (wv == 2) sts32(self + ONES + lane * 4, 0x3F803F80u);
    uint32_t pb[2], pc[2];
    lds64(pb, PROBE + (lane & 7) * 8);
    lds64(pc, PROBE + ((lane & 7) ^ 4) * 8);
    mask = __ballot_sync(0xffffffffu, isv ? pb[1] < pb[0] : min(pb[1], pc[1]) < min(pb[0], pc[0])) & (isv ? 255 : 15);
    if (!isv) {
#pragma unroll
      for (int i = 0; i < 4; i++) st_pub128(P.xch + j * 32768 + i * 8192 + ((mask >> i) & 1) * 4096 + tid * 16, 0);
      if (wv < 4) st_pub64(P.xch + H1_BYTES + (wv >> 1) * 32768 + (j >> 4) * 8192 + (wv & 1) * 4096 + (j & 15) * 256 + lane * 8, EMPTY, EMPTY);
    }
      }
#pragma unroll
      for (int i = 0; i < 16; i++) { cur[0][i] = raw[0][i]; raw[0][i] = raw[1][i]; raw[1][i] = raw[2][i]; }
    }
    PRO(5);
    __syncthreads();
    PRO(6);
    if (tid == 64) {
      __threadfence();
      PRO(7);
      st_pub32(&g_mask[3 * h + rank], 0x100 | mask);
    }
    KT_END(0);
    __syncwarp();
  }
  const int wg = __shfl_sync(0xffffffffu, threadIdx.x >> 7, 0);
  if (rank == 2) { if (wg == 0) f_main<true, 0>(P, h, 2, hw); else f_main<true, 1>(P, h, 2, hw); }
  else { if (wg == 0) f_main<false, 0>(P, h, rank, hw); else f_main<false, 1>(P, h, rank, hw); }
  PROF2(5);
  KT_END(1);
  __syncwarp();
  f_tail(P, h, crank, rank == 2);
}

#define GCL 1
#define G_PF 3
#define G_PFM 2
#define G_LATE 0
namespace gk {
enum { T_B1 = 0, T_B2 = 1, T_B3 = 2, T_B4 = 3, T_O = 4, T_LN = 5, T_LN0 = 6, T_END = 7 };
constexpr int NST = 3, STAGE = 49152, MAXITEMS = 512, NEW = 3;
constexpr uint32_t OUTB = NST * STAGE, BARS = OUTB + 65536;
constexpr uint32_t B_FULL = BARS, B_EMPTY = BARS + 32, B_ITEM = BARS + 64, B_FILL = BARS + 128, B_FREE = BARS + 160, B_LN = BARS + 176, B_LNGO = BARS + 184, ITEMS = BARS + 192;
constexpr int SMEM = BARS + 256;
static_assert(GATE_CNT == 4 * NEW && T_B4 == 3, "gate counter");
}
struct GParams {
  CUtensorMap a[5], b[5];
  bf16* c[5];
  const bf16* r[5];
  bf16 *x1n, *xn2;
  const bf16* w1;
  int nitems, lnpos;
  uint16_t items[gk::MAXITEMS];
};
#define ILOG(i)
#define SLOG(i)

__device__ __forceinline__ void tma_load_3d_mc(uint32_t dst, const CUtensorMap* map, int x, int y, int z, uint32_t bar) {
  asm volatile("cp.async.bulk.tensor.3d.shared::cluster.global.mbarrier::complete_tx::bytes.multicast::cluster "
               "[%0], [%1, {%3, %4, %5}], [%2], %6;"
               ::"r"(dst), "l"(map), "r"(bar), "r"(x), "r"(y), "r"(z), "h"((uint16_t)3) : "memory");
}
__device__ __forceinline__ float tanh_approx(float x) { float y; asm("tanh.approx.f32 %0, %1;" : "=f"(y) : "f"(x)); return y; }
__global__ void __launch_bounds__(384, 1) g_kernel(const __grid_constant__ GParams P) {
  using namespace gk;
  extern __shared__ __align__(1024) uint8_t smem_g[];
  const uint32_t base = smem_u32(smem_g);
  const int tid = threadIdx.x, warp = __shfl_sync(0xffffffffu, tid >> 5, 0), lane = tid & 31;
  const int rank = blockIdx.x % GCL;
  KT_START(2);
  if (tid == 0) {
    for (int s = 0; s < NST; s++) { mbar_init(base + B_FULL + 8 * s, 1); mbar_init(base + B_EMPTY + 8 * s, 8 * GCL); }
    for (int s = 0; s < 8; s++) mbar_init(base + B_ITEM + 8 * s, 1);
    for (int s = 0; s < 2; s++) { mbar_init(base + B_FILL + 8 * s, 4); mbar_init(base + B_FREE + 8 * s, NEW); }
    mbar_init(base + B_LN, 1);
    mbar_init(base + B_LNGO, 1);
    fence_barrier_init();
  }
  __syncthreads();
  if (GCL > 1) cluster_sync();
  auto release = [&](uint32_t st) {
    if (GCL > 1) { if (lane < GCL) mbar_arrive_cluster(base + B_EMPTY + 8 * st, lane); }
    else if (lane == 0) mbar_arrive(base + B_EMPTY + 8 * st);
  };
  auto get_item = [&](int q) {
    mbar_wait(base + B_ITEM + 8 * (q & 7), (q >> 3) & 1);
    return lds32(base + ITEMS + 4 * (q & 7));
  };

  if (warp == 8) {
    if (lane < 10) prefetch_tmap(&P.a[0] + lane);
    for (int r = blockIdx.x * 4 + lane; r < cfg::D / 8 && lane < 4; r += gridDim.x * 4) l2_prefetch(P.w1 + r * 8 * cfg::D, 16384);
    if (lane == 0) {
      uint32_t st = 0, ph = 1;
#pragma unroll 1
      for (int q = 0;; q++) {
        if (GCL > 1) mbar_expect_tx(base + B_ITEM + 8 * (q & 7), 4);
        if (rank == 0) {
          const unsigned idx = atomicAdd(&g_next, 1), ln = idx - P.lnpos;
          const uint32_t v = (idx < (unsigned)P.nitems ? P.items[idx] : T_END) | (ln < 64 / GCL ? (ln + 1) << 16 : 0);
          if (GCL > 1) {
#pragma unroll
            for (int r = 0; r < GCL; r++) st_async32(mapa(base + ITEMS + 4 * (q & 7), r), v, mapa(base + B_ITEM + 8 * (q & 7), r));
          } else {
            sts32(base + ITEMS + 4 * (q & 7), v);
            mbar_arrive(base + B_ITEM + 8 * (q & 7));
          }
        }
        const uint32_t item = get_item(q);
        const int type = item & 7, mb = ((item >> 3) & 15) + rank, nt = (item >> 7) & 15;
        ILOG(1);
        if (q == 0) { __threadfence(); sts32(base + ITEMS + 32, ld_strong4(&g_oflag[14]) >= 32); }
        if (type == T_END) break;
        if (item >> 16) { wait_count(&g_cnt[T_B2][(((item >> 16) - 1) >> 2) * GCL + rank], 4 * NEW); mbar_arrive(base + B_LNGO); }
        if (type == T_B2) {
          wait_count(&g_cnt[T_B1][max(mb - 1, 0)], 4 * NEW); wait_count(&g_cnt[T_B1][mb], 4 * NEW); wait_count(&g_cnt[T_B1][min(mb + 1, 15)], 4 * NEW);
        } else if (type == T_B3) wait_count(&g_cnt[T_LN][mb], 64);
        else if (type == T_B4) wait_count(&g_cnt[T_B3][mb], 14 * NEW);
        else if (type == T_O) wait_count(&g_oflag[mb], 32);
        asm volatile("fence.proxy.async.global;" ::: "memory");
        ILOG(2);
        const CUtensorMap *ma = &P.a[type], *mbm = &P.b[type];
        const int nkb = type == T_B4 ? cfg::F / 64 : type == T_O ? cfg::HD / 64 : cfg::D / 64;
#pragma unroll 1
        for (int kb = 0; kb < nkb; kb++) {
          mbar_wait(base + B_EMPTY + 8 * st, ph);
          const uint32_t sa = base + st * STAGE, full = base + B_FULL + 8 * st;
          mbar_expect_tx(full, STAGE);
          int arow = mb * 128;
          if (type == T_B2) { const int qd = kb >> 2; arow += (qd == 0) ? -1 : (qd == 1) ? 1 : (qd == 2) ? -2 : 2; }
          if (GCL > 1) tma_load_3d_mc(sa + 16384 + rank * 16384, mbm, 0, kb * 64, nt * 4 + rank * 2, full);
          else tma_load_3d(sa + 16384, mbm, 0, kb * 64, nt * 4, full);
          if (type == T_B1 && kb == 0) { wait_count(&g_cnt[T_LN0][mb], 64); asm volatile("fence.proxy.async.global;" ::: "memory"); }
          tma_load_2d(sa, ma, kb * 64, arow, full);
          if (G_PF && type >= T_B4 && kb + G_PF < nkb) {
            if (G_PFM & 1) asm volatile("cp.async.bulk.prefetch.tensor.3d.L2.global [%0, {0, %1, %2}];" ::"l"(mbm), "r"((kb + G_PF) * 64), "r"(nt * 4 + rank * 2) : "memory");
            if (G_PFM & 2) asm volatile("cp.async.bulk.prefetch.tensor.2d.L2.global [%0, {%1, %2}];" ::"l"(ma), "r"((kb + G_PF) * 64), "r"(mb * 128) : "memory");
          }
          if (++st == NST) { st = 0; ph ^= 1; }
        }
      }
    }
  } else {
    const int wg = warp >> 2, ew = warp > 8 ? warp - 9 : warp + NEW;
    const uint32_t outa = base + OUTB + (warp * 16 + ((lane >> 3) & 1) * 8 + (lane & 7)) * 512 + (((lane >> 4) ^ (lane & 7)) << 4);
    uint32_t st = 0, ph = 0;
    float acc[128];
    auto kill_acc = [&]() {
#pragma unroll
      for (int i = 0; i < 128; i++) acc[i] = 0.f;
    };
    uint32_t next = T_LN0, lnph = 0;
#pragma unroll 1
    for (int q = -1;; q++) {
      const uint32_t item = next;
      const int type = item & 7, mb = ((item >> 3) & 15) + rank, nt = (item >> 7) & 15;
      if (type == T_END) break;
      const bool first = q < 0;
      if (first || (warp < 8 && (item >> 16))) {
        const int ln = (item >> 16) - 1, lb = (ln >> 2) * GCL + rank, pstr = first ? gridDim.x * 11 : 1;
#pragma unroll 1
        for (int p0 = first ? blockIdx.x * 11 + ew : lb * 64 + (ln & 3) * 16 + warp * 2; p0 < cfg::S / 2; p0 += first ? 3 * pstr : cfg::S) {
          const int np = first ? min(3, (cfg::S / 2 - 1 - p0) / pstr + 1) : 2;
          const bf16* src = (first ? P.r[T_O] : P.c[T_B2]) + (size_t)p0 * 2 * cfg::D;
          bf16* dst = (first ? P.xn2 : P.x1n) + (size_t)p0 * 2 * cfg::D;
          if (!first) { mbar_wait(base + B_LNGO, lnph); lnph ^= 1; }
          SLOG(0);
          uint32_t cur[2][16], n1[2][16], n2[2][16];
#pragma unroll
          for (int r = 0; r < 2; r++) {
            load_row16(cur[r], src + r * cfg::D, lane);
            load_row16(n1[r], src + (size_t)(min(1, np - 1) * pstr * 2 + r) * cfg::D, lane);
#pragma unroll
            for (int i = 0; i < 16; i++) n2[r][i] = 0;
            if (np > 2) load_row16(n2[r], src + (size_t)(pstr * 4 + r) * cfg::D, lane);
          }
#pragma unroll 1
          for (int it = first ? 0 : 1; it < 2 * np; it += first ? 1 : 2) {
            ln_regs<2>(cur);
            SLOG(1 + it);
            if (it & 1) {
#pragma unroll
              for (int r = 0; r < 2; r++) {
                store_row16(cur[r], dst + (size_t)((it >> 1) * pstr * 2 + r) * cfg::D, lane);
#pragma unroll
                for (int i = 0; i < 16; i++) { cur[r][i] = n1[r][i]; n1[r][i] = n2[r][i]; }
              }
            }
          }
          if (first) __syncwarp(); else named_bar_sync(3, 256);
          if (first ? lane < np : tid == 0)
            asm volatile("red.release.gpu.global.add.u32 [%0], %1;" ::"l"(&g_cnt[first ? T_LN0 : T_LN][(p0 + lane * pstr) >> 6]), "r"(first ? 1 : 16) : "memory");
          __syncwarp();
          SLOG(7);
        }
        if (tid == 0 && !first) ILOG(6);
        kill_acc();
        if (first) {
    if (warp == 9) {
#pragma unroll 1
      for (int tries = 0; tries < POLL_TRIES; tries++) {
        uint4 v;
        asm volatile("ld.acquire.gpu.global.v4.u32 {%0,%1,%2,%3}, [%4];" : "=r"(v.x), "=r"(v.y), "=r"(v.z), "=r"(v.w)
                     : "l"(lane < 24 ? &g_mask[4 * lane] : &g_lnok[0]) : "memory");
        const uint32_t ok = __ballot_sync(0xffffffffu, v.x & v.y & v.z & v.w & 0x100);
        if ((ok & 0xFFFFFF) == 0xFFFFFF || (ok >> 24)) break;
        __nanosleep(200);
      }
      if (lane == 0) mbar_arrive(base + B_LN);
    }
          next = get_item(0);
          continue;
        }
      }
      if (warp < 8) {
      const int nkb = type == T_B4 ? cfg::F / 64 : type == T_O ? cfg::HD / 64 : cfg::D / 64;
      uint32_t prev = 0;
      mbar_wait(base + B_FULL + 8 * st, ph);
#pragma unroll 1
      for (int kb = 0; kb < nkb; kb++) {
        mbar_spin(base + B_FULL + 8 * st, ph);
        if (kb == 0 && tid == 0) ILOG(3);
        const uint64_t da = make_desc(base + wg * 8192, 16, 1024) + st * (STAGE >> 4), db = make_desc(base + 16384, 8192, 1024) + st * (STAGE >> 4);
        wg_fence();
#pragma unroll
        for (int k = 0; k < 4; k++) {
          wgmma_ss_n256_tb(acc, da + k * 2, db + k * 128, (kb | k) != 0);
          if (k == 0) {
            wg_commit();
            wg_wait<1>();
            if (kb > 0) release(prev);
            wg_fence();
          }
        }
        wg_commit();
        prev = st;
        if (++st == NST) { st = 0; ph ^= 1; }
      }
      next = get_item(q + 1);
      if (q > 0) mbar_wait(base + B_FREE + 8 * wg, (q - 1) & 1);
      wg_wait<0>();
      if (tid == 0) ILOG(4);
      release(prev);
#pragma unroll
      for (int j = 0; j < 16; j++)
        stsm4((outa ^ ((j & 3) << 5)) + (j >> 2) * 128, pack_bf16(acc[8 * j], acc[8 * j + 1]), pack_bf16(acc[8 * j + 2], acc[8 * j + 3]),
              pack_bf16(acc[8 * j + 4], acc[8 * j + 5]), pack_bf16(acc[8 * j + 6], acc[8 * j + 7]));
      __syncwarp();
      if (lane == 0) mbar_arrive(base + B_FILL + 8 * wg);
      if (tid == 0) ILOG(5);
      if ((next & 7) != T_END) continue;
      }
      if (type == T_O) wait_count(&g_cnt[T_B4][mb], 4 * NEW);
      const int ldc = type == T_B3 ? cfg::F : cfg::D;
      bf16* cp = P.c[type] + (size_t)mb * 128 * ldc + nt * 256 + lane * 8;
      const size_t roff = (size_t)mb * 128 * cfg::D + nt * 256 + lane * 8;
      const bf16 *rp = P.r[type] + roff, *gp = P.c[T_B4] + roff;
      const bool gelu = type == T_B1 || type == T_B3;
      uint32_t yn[4][4];
      uint4 rn[4], gn[4];
#pragma unroll
      for (int i = 0; i < 4; i++) rn[i] = gn[i] = make_uint4(0, 0, 0, 0);
      auto fetch_res = [&](int grp) {
#pragma unroll
        for (int i = 0; i < 4; i++) {
          rn[i] = __ldcg(reinterpret_cast<const uint4*>(rp + (grp * 4 + i) * cfg::D));
          if (type == T_O) gn[i] = __ldcg(reinterpret_cast<const uint4*>(gp + (grp * 4 + i) * cfg::D));
        }
      };
      auto fetch_y = [&](int grp) {
        const uint32_t a = base + OUTB + grp * 2048 + ((lane ^ ((grp & 1) << 2)) << 4);
#pragma unroll
        for (int i = 0; i < 4; i++) lds128(yn[i], (a ^ (i << 4)) + i * 512);
      };
      auto store_y = [&](int grp, const uint32_t (&y)[4][4]) {
        char* p = reinterpret_cast<char*>(cp) + (uint32_t)(grp * 8 * ldc);
#pragma unroll
        for (int i = 0; i < 4; i++) *reinterpret_cast<uint4*>(p + (uint32_t)(i * 2 * ldc)) = make_uint4(y[i][0], y[i][1], y[i][2], y[i][3]);
      };
      if (type == T_B2) mbar_wait(base + B_LN, 0);
      if (type == T_B4) wait_count(&g_cnt[T_B2][mb], 4 * NEW);
      if (type >= T_B4 && warp > 8) for (int r = tid - 288; r < 128; r += 96) l2_prefetch(rp - lane * 8 + r * cfg::D, 512);
      if (!gelu) fetch_res(ew);
      mbar_wait(base + B_FILL, q & 1);
      fetch_y(ew);
      next = get_item(q + 1);
      mbar_wait(base + B_FILL + 8, q & 1);
      const int stride = (next & 7) == T_END ? NEW + 8 : NEW;
      if (gelu) {
#pragma unroll 1
        for (int grp = ew; grp < 32; grp += stride) {
          uint32_t y[4][4];
#pragma unroll
          for (int i = 0; i < 16; i++) y[i >> 2][i & 3] = mul_bf16x2(yn[i >> 2][i & 3], 0x3F003F00u);
          const int nx = grp + stride;
          if (nx >= 16 && grp < 16 && lane == 0 && warp > 8) mbar_arrive(base + B_FREE);
          if (!G_LATE) fetch_y(min(nx, 31));
#pragma unroll
          for (int i = 0; i < 16; i++) {
            uint32_t& v = y[i >> 2][i & 3];
            const float h0 = bf_lo(v), h1 = bf_hi(v);
            const float t0 = tanh_approx(h0 * fmaf(h0 * h0, 0.285419265090401f, 1.5957691216057308f));
            const float t1 = tanh_approx(h1 * fmaf(h1 * h1, 0.285419265090401f, 1.5957691216057308f));
            v = pack_bf16(fmaf(h0, t0, h0), fmaf(h1, t1, h1));
          }
          if (G_LATE) fetch_y(min(nx, 31));
          store_y(grp, y);
        }
      } else {
#pragma unroll 1
        for (int grp = ew; grp < 32; grp += stride) {
          uint32_t y[4][4];
          if (type == T_O) {
#pragma unroll
            for (int i = 0; i < 16; i++) yn[i >> 2][i & 3] = mul_bf16x2(yn[i >> 2][i & 3], (&gn[i >> 2].x)[i & 3]);
          }
#pragma unroll
          for (int i = 0; i < 16; i++) y[i >> 2][i & 3] = add_bf16x2(yn[i >> 2][i & 3], (&rn[i >> 2].x)[i & 3]);
          const int nx = grp + stride;
          if (nx >= 16 && grp < 16 && lane == 0 && warp > 8) mbar_arrive(base + B_FREE);
          fetch_res(min(nx, 31));
          fetch_y(min(nx, 31));
          if (type == T_B4) {
#pragma unroll
            for (int i = 0; i < 16; i++) {
              uint32_t& v = y[i >> 2][i & 3];
              const float h0 = 0.5f * bf_lo(v), h1 = 0.5f * bf_hi(v);
              v = pack_bf16(fmaf(h0, tanh_approx(h0), h0), fmaf(h1, tanh_approx(h1), h1));
            }
          }
          store_y(grp, y);
        }
      }
      __syncwarp();
      if (lane == 0 && warp > 8) mbar_arrive(base + B_FREE + 8);
      if (stride != NEW) named_bar_sync(2, 352);
      if (type != T_O && lane == 0 && warp > 8) asm volatile("red.release.gpu.global.add.u32 [%0], 1;" ::"l"(&g_cnt[type][mb]) : "memory");
      __syncwarp();
      if (tid == 288) ILOG(7);
      kill_acc();
    }
    KT_END(2);
  }
  __syncwarp();
  if (warp >= 8) {
   named_bar_sync(1, 128);
   const bool late = lds32(base + ITEMS + 32);
   if (late) pdl_wait();
#pragma unroll 1
   for (int c = blockIdx.x; late && c < 96; c += gridDim.x) {
     if (__ldcg(&g_tfix[c]) == 0) continue;
     const int hh = c / 3, mb = TAIL_MB0 + c % 3;
     wait_count(&g_cnt[T_B4][mb], GATE_CNT);
#pragma unroll 1
     for (int i = tid - 256; i < 512; i += 128) {
       const size_t off = (size_t)(mb * 128 + (i >> 2)) * cfg::D + hh * 32 + (i & 3) * 8;
       const uint4 sv = __ldcg(reinterpret_cast<const uint4*>(P.c[T_O] + off)), gv = __ldcg(reinterpret_cast<const uint4*>(P.c[T_B4] + off)),
                   xv = __ldcg(reinterpret_cast<const uint4*>(P.r[T_O] + off));
       *reinterpret_cast<uint4*>(P.c[T_O] + off) = make_uint4(add_bf16x2(xv.x, mul_bf16x2(sv.x, gv.x)), add_bf16x2(xv.y, mul_bf16x2(sv.y, gv.y)),
                                                              add_bf16x2(xv.z, mul_bf16x2(sv.z, gv.z)), add_bf16x2(xv.w, mul_bf16x2(sv.w, gv.w)));
     }
   }
  }
  if (GCL > 1) cluster_sync();
}

__device__ bf16 g_xn[cfg::S * cfg::D];
__device__ bf16 g_xn2[cfg::S * cfg::D];
__device__ bf16 g_h[cfg::S * cfg::D];
__device__ bf16 g_x1[cfg::S * cfg::D];
__device__ bf16 g_x1n[cfg::S * cfg::D];
__device__ bf16 g_u[cfg::S * cfg::F];
__device__ bf16 g_g[cfg::S * cfg::D];
__device__ bf16 g_o[cfg::S * cfg::HD];

typedef CUresult (*PFN_encodeTiled)(CUtensorMap*, CUtensorMapDataType, cuuint32_t, void*, const cuuint64_t*,
                                    const cuuint64_t*, const cuuint32_t*, const cuuint32_t*, CUtensorMapInterleave,
                                    CUtensorMapSwizzle, CUtensorMapL2promotion, CUtensorMapFloatOOBfill);

static PFN_encodeTiled get_encoder() {
  static PFN_encodeTiled fn = nullptr;
  if (!fn) {
    void* p = nullptr;
    cudaDriverEntryPointQueryResult st;
    cudaGetDriverEntryPoint("cuTensorMapEncodeTiled", &p, cudaEnableDefault, &st);
    fn = (PFN_encodeTiled)p;
  }
  return fn;
}
static CUtensorMap make_map(const void* ptr, int rows, int cols, int box_rows, int box_cols, int swizzle_bytes) {
  CUtensorMap m;
  cuuint64_t dims[2] = {(cuuint64_t)cols, (cuuint64_t)rows};
  cuuint64_t strides[1] = {(cuuint64_t)cols * 2};
  cuuint32_t box[2] = {(cuuint32_t)box_cols, (cuuint32_t)box_rows};
  cuuint32_t estr[2] = {1, 1};
  CUtensorMapSwizzle sw = swizzle_bytes == 128 ? CU_TENSOR_MAP_SWIZZLE_128B
                        : swizzle_bytes == 64 ? CU_TENSOR_MAP_SWIZZLE_64B
                        : swizzle_bytes == 32 ? CU_TENSOR_MAP_SWIZZLE_32B : CU_TENSOR_MAP_SWIZZLE_NONE;
  get_encoder()(&m, CU_TENSOR_MAP_DATA_TYPE_BFLOAT16, 2, const_cast<void*>(ptr), dims, strides, box, estr,
                CU_TENSOR_MAP_INTERLEAVE_NONE, sw, CU_TENSOR_MAP_L2_PROMOTION_L2_128B, CU_TENSOR_MAP_FLOAT_OOB_FILL_NONE);
  return m;
}
static CUtensorMap make_map3(const void* ptr, int rows, int cols, int box_rows, int nblk) {
  CUtensorMap m;
  cuuint64_t dims[3] = {64, (cuuint64_t)rows, (cuuint64_t)(cols / 64)};
  cuuint64_t strides[2] = {(cuuint64_t)cols * 2, 128};
  cuuint32_t box[3] = {64, (cuuint32_t)box_rows, (cuuint32_t)nblk};
  cuuint32_t estr[3] = {1, 1, 1};
  get_encoder()(&m, CU_TENSOR_MAP_DATA_TYPE_BFLOAT16, 3, const_cast<void*>(ptr), dims, strides, box, estr,
                CU_TENSOR_MAP_INTERLEAVE_NONE, CU_TENSOR_MAP_SWIZZLE_128B, CU_TENSOR_MAP_L2_PROMOTION_L2_128B,
                CU_TENSOR_MAP_FLOAT_OOB_FILL_NONE);
  return m;
}
template <class T> static T* sym(T& s) { void* p = nullptr; cudaGetSymbolAddress(&p, s); return (T*)p; }
#define SYM(name) ((bf16*)[] { void* p = nullptr; cudaGetSymbolAddress(&p, name); return p; }())

#define G_CTAS 36
#define B4_FIRST 11
#define O_FIRST 4
#define B3_FIRST 9
#define LN_POS 63
static int build_items(uint16_t* it) {
  using namespace gk;
  int n = 0;
  auto add = [&](int type, int nrows, int ncols, int row0 = 0) {
    for (int mb = row0; mb < nrows; mb += GCL) for (int nt = 0; nt < ncols; nt++) it[n++] = (uint16_t)(type | mb << 3 | nt << 7);
  };
  add(T_B1, 16, 4); add(T_B2, 16, 4); add(T_B3, B3_FIRST, 14); add(T_B4, 2, 4); add(T_B3, 16, 14, B3_FIRST);
  add(T_B4, B4_FIRST, 4, 2); add(T_O, O_FIRST, 4); add(T_B4, 16, 4, B4_FIRST); add(T_O, TAIL_MB0, 4, O_FIRST);
  return n;
}

extern "C" void kernel_launch(void* const* d_in, const int* in_sizes, int n_in, void* d_out, int out_size) {
  using namespace cfg;
  const bf16* x = (const bf16*)d_in[0];
  const bf16* mem0 = (const bf16*)d_in[1];
  const bf16* Wq = (const bf16*)d_in[2];
  const bf16* Wk = (const bf16*)d_in[3];
  const bf16* Wv = (const bf16*)d_in[4];
  const bf16* Wo = (const bf16*)d_in[5];
  const bf16* w1 = (const bf16*)d_in[8];
  const bf16* w2 = (const bf16*)d_in[9];
  const bf16* w3 = (const bf16*)d_in[10];
  const bf16* w4 = (const bf16*)d_in[11];
  bf16* out = (bf16*)d_out;
  cudaStream_t st = cudaStreamPerThread;

  bf16 *xn = SYM(g_xn), *xn2 = SYM(g_xn2), *hb = SYM(g_h), *x1 = SYM(g_x1), *x1n = SYM(g_x1n), *u = SYM(g_u),
       *g = SYM(g_g), *o = SYM(g_o);

  {
    cudaFuncSetAttribute(f_kernel, cudaFuncAttributeMaxDynamicSharedMemorySize, fk::SMEM);
    FParams P;
    P.wq = make_map(Wq, D, HD, 64, 64, 128); P.wk = make_map(Wk, D, HD, 64, 64, 128); P.wv = make_map(Wv, D, HD, 64, 64, 128);
    P.wo = make_map(Wo, HD, D, 128, 64, 128); P.wo16 = make_map(Wo, HD, D, 128, 16, 32); P.xn = make_map3(xn, S, D, 32, 4); P.xn12 = make_map3(xn, S, D, 32, 12); P.o = make_map3(o, S, HD, 32, 2);
    P.ta = make_map(o, S, HD, 128, 64, 128); P.tb = make_map(Wo, HD, D, 64, 64, 128);
    P.tx = make_map(x, S, D, 128, 32, 64); P.tg = make_map(g, S, D, 128, 32, 64); P.out = out;
    P.mem0 = mem0;
    P.nprobe = PROBE_N;
    P.dxn = make_desc(fk::XN, 16, 1024);
    P.x = x; P.xn_ptr = xn;
    P.xch = (char*)(((uintptr_t)SYM(g_xch) + 8191) & ~(uintptr_t)8191);
    cudaLaunchConfig_t cfg = {};
    cfg.gridDim = dim3(96); cfg.blockDim = dim3(256); cfg.dynamicSmemBytes = fk::SMEM; cfg.stream = st;
    cudaLaunchAttribute at[2];
    at[0].id = cudaLaunchAttributeClusterDimension;
    at[0].val.clusterDim.x = 3; at[0].val.clusterDim.y = 1; at[0].val.clusterDim.z = 1;
    cfg.attrs = at; cfg.numAttrs = 1;
    cudaLaunchKernelEx(&cfg, f_kernel, P);
  }
  {
    cudaFuncSetAttribute(g_kernel, cudaFuncAttributeMaxDynamicSharedMemorySize, gk::SMEM);
    GParams G;
    const bf16* as[5] = {xn2, hb, x1n, u, o};
    const bf16* bs[5] = {w1, w2, w3, w4, Wo};
    bf16* cs[5] = {hb, x1, u, g, out};
    const bf16* rs[5] = {xn, xn, xn, x1, x};
    const int ks[5] = {D, D, D, F, HD}, ns[5] = {D, D, F, D, D};
    for (int i = 0; i < 5; i++) {
      G.a[i] = make_map(as[i], S, ks[i], 128, 64, 128);
      G.b[i] = make_map3(bs[i], ks[i], ns[i], 64, 4 / GCL);
      G.c[i] = cs[i];
      G.r[i] = rs[i];
    }
    G.x1n = x1n; G.xn2 = xn2; G.w1 = w1;
    G.nitems = build_items(G.items);
    G.lnpos = LN_POS * 2 / GCL;
    cudaLaunchConfig_t cfg = {};
    int dev = 0, sms = 0;
    cudaGetDevice(&dev);
    cudaDeviceGetAttribute(&sms, cudaDevAttrMultiProcessorCount, dev);
    cfg.gridDim = dim3(sms - 96 >= 4 && sms - 96 < G_CTAS ? sms - 96 : G_CTAS); cfg.blockDim = dim3(384); cfg.dynamicSmemBytes = gk::SMEM; cfg.stream = st;
    cudaLaunchAttribute at[2];
    at[0].id = cudaLaunchAttributeClusterDimension;
    at[0].val.clusterDim.x = GCL; at[0].val.clusterDim.y = 1; at[0].val.clusterDim.z = 1;
    at[1].id = cudaLaunchAttributeProgrammaticStreamSerialization;
    at[1].val.programmaticStreamSerializationAllowed = 1;
    cfg.attrs = at;
    cfg.numAttrs = 2;
    cudaLaunchKernelEx(&cfg, g_kernel, G);
  }
}
```

```cpp
#include <cuda_runtime.h>
#include <cuda_bf16.h>
#include <cuda.h>
#include <stdint.h>

typedef __nv_bfloat16 bf16;

namespace cfg {
constexpr int S = 2048;
constexpr int D = 1024;
constexpr int H = 32;
constexpr int DH = 128;
constexpr int HD = H * DH;
constexpr int M = 8;
constexpr int SEG = 32;
constexpr int NSEG = S / SEG;
constexpr int F = 3584;
}

__device__ __forceinline__ uint32_t smem_u32(const void* p) { return (uint32_t)__cvta_generic_to_shared(p); }

__device__ __forceinline__ void mbar_init(uint32_t bar, uint32_t count) {
  asm volatile("mbarrier.init.shared::cta.b64 [%0], %1;" ::"r"(bar), "r"(count) : "memory");
}
__device__ __forceinline__ void mbar_expect_tx(uint32_t bar, uint32_t bytes) {
  asm volatile("mbarrier.arrive.expect_tx.shared::cta.b64 _, [%0], %1;" ::"r"(bar), "r"(bytes) : "memory");
}
__device__ __forceinline__ void mbar_arrive(uint32_t bar) {
  asm volatile("mbarrier.arrive.shared::cta.b64 _, [%0];" ::"r"(bar) : "memory");
}
__device__ __forceinline__ bool mbar_try(uint32_t bar, uint32_t parity) {
  uint32_t done;
  asm volatile("{\n.reg .pred p;\nmbarrier.try_wait.parity.shared::cta.b64 p, [%1], %2, 20000;\nselp.u32 %0, 1, 0, p;\n}"
               : "=r"(done) : "r"(bar), "r"(parity) : "memory");
  return done != 0;
}
__device__ __forceinline__ bool mbar_try_nohint(uint32_t bar, uint32_t parity) {
  uint32_t done;
  asm volatile("{\n.reg .pred p;\nmbarrier.try_wait.parity.shared::cta.b64 p, [%1], %2;\nselp.u32 %0, 1, 0, p;\n}"
               : "=r"(done) : "r"(bar), "r"(parity) : "memory");
  return done != 0;
}
constexpr int MBAR_TRIES = 4096;
constexpr int POLL_TRIES = 1 << 16;
__device__ __forceinline__ void mbar_wait(uint32_t bar, uint32_t parity) {
#pragma unroll 1
  for (int n = 0; n < MBAR_TRIES; n++)
    if (mbar_try(bar, parity)) break;
}
__device__ __forceinline__ void mbar_wait_fast(uint32_t bar, uint32_t parity) {
#pragma unroll 1
  for (int n = 0; n < (POLL_TRIES << 4); n++)
    if (mbar_try_nohint(bar, parity)) break;
}
__device__ __forceinline__ void fence_barrier_init() { asm volatile("fence.mbarrier_init.release.cluster;" ::: "memory"); }
__device__ __forceinline__ void fence_proxy_async_smem() { asm volatile("fence.proxy.async.shared::cta;" ::: "memory"); }

__device__ __forceinline__ void tma_load_2d(uint32_t dst, const CUtensorMap* map, int x, int y, uint32_t bar) {
  asm volatile("cp.async.bulk.tensor.2d.shared::cluster.global.mbarrier::complete_tx::bytes [%0], [%1, {%3, %4}], [%2];"
               ::"r"(dst), "l"(map), "r"(bar), "r"(x), "r"(y) : "memory");
}
__device__ __forceinline__ void tma_load_3d(uint32_t dst, const CUtensorMap* map, int x, int y, int z, uint32_t bar) {
  asm volatile("cp.async.bulk.tensor.3d.shared::cluster.global.mbarrier::complete_tx::bytes [%0], [%1, {%3, %4, %5}], [%2];"
               ::"r"(dst), "l"(map), "r"(bar), "r"(x), "r"(y), "r"(z) : "memory");
}
__device__ __forceinline__ void tma_store_2d(const CUtensorMap* map, uint32_t src, int x, int y) {
  asm volatile("cp.async.bulk.tensor.2d.global.shared::cta.bulk_group [%0, {%2, %3}], [%1];"
               ::"l"(map), "r"(src), "r"(x), "r"(y) : "memory");
}
__device__ __forceinline__ void tma_store_commit() { asm volatile("cp.async.bulk.commit_group;" ::: "memory"); }
__device__ __forceinline__ void tma_store_wait_all() { asm volatile("cp.async.bulk.wait_group 0;" ::: "memory"); }
__device__ __forceinline__ void tma_store_wait_read() { asm volatile("cp.async.bulk.wait_group.read 0;" ::: "memory"); }
__device__ __forceinline__ void prefetch_tmap(const CUtensorMap* map) {
  asm volatile("prefetch.tensormap [%0];" ::"l"(map) : "memory");
}

__device__ __forceinline__ void wg_fence() { asm volatile("wgmma.fence.sync.aligned;" ::: "memory"); }
__device__ __forceinline__ void wg_commit() { asm volatile("wgmma.commit_group.sync.aligned;" ::: "memory"); }
template <int N> __device__ __forceinline__ void wg_wait() { asm volatile("wgmma.wait_group.sync.aligned %0;" ::"n"(N) : "memory"); }

#define named_bar_sync(id, n) asm volatile("bar.sync %0, %1;" ::"n"(id), "n"(n) : "memory")
#define named_bar_arrive(id, n) asm volatile("bar.arrive %0, %1;" ::"n"(id), "n"(n) : "memory")

__host__ __device__ __forceinline__ uint64_t make_desc(uint32_t addr, uint32_t lbo, uint32_t sbo) {
  return (uint64_t)((addr & 0x3FFFF) >> 4) | ((uint64_t)(lbo >> 4) << 16) | ((uint64_t)(sbo >> 4) << 32) | (1ull << 62);
}

__device__ __forceinline__ uint64_t make_desc0(uint32_t addr, uint32_t lbo, uint32_t sbo) {
  return (uint64_t)((addr & 0x3FFFF) >> 4) | ((uint64_t)(lbo >> 4) << 16) | ((uint64_t)(sbo >> 4) << 32);
}

__device__ __forceinline__ uint32_t pack_bf16(float lo, float hi) {
  uint32_t r;
  asm("cvt.rn.bf16x2.f32 %0, %1, %2;" : "=r"(r) : "f"(hi), "f"(lo));
  return r;
}
__device__ __forceinline__ float bf_lo(uint32_t v) { return __uint_as_float(v << 16); }
__device__ __forceinline__ float bf_hi(uint32_t v) { return __uint_as_float(v & 0xFFFF0000u); }
__device__ __forceinline__ float rbf(float v) { return __bfloat162float(__float2bfloat16_rn(v)); }

__device__ __forceinline__ void pdl_launch_dependents() { asm volatile("griddepcontrol.launch_dependents;" ::: "memory"); }
__device__ __forceinline__ void pdl_wait() { asm volatile("griddepcontrol.wait;" ::: "memory"); }

__device__ __forceinline__ float ex2_approx(float x) { float y; asm("ex2.approx.ftz.f32 %0, %1;" : "=f"(y) : "f"(x)); return y; }
__device__ __forceinline__ float rcp_approx(float x) { float y; asm("rcp.approx.ftz.f32 %0, %1;" : "=f"(y) : "f"(x)); return y; }

__device__ __forceinline__ void mul_sigmoid4(float (&v)[4], const float (&t)[4]) {
#pragma unroll
  for (int i = 0; i < 4; i += 2) {
    const float a = 1.0f + ex2_approx(fminf(t[i], 60.0f)), b = 1.0f + ex2_approx(fminf(t[i + 1], 60.0f));
    const float r = rcp_approx(a * b);
    v[i] *= b * r;
    v[i + 1] *= a * r;
  }
}
__device__ __forceinline__ void gelu4(float (&v)[4]) {
  float t[4];
#pragma unroll
  for (int i = 0; i < 4; i++) t[i] = v[i] * fmaf(v[i] * v[i], -0.10294324f, -2.30220819f);
  mul_sigmoid4(v, t);
}
__device__ __forceinline__ void silu4(float (&v)[4]) {
  float t[4];
#pragma unroll
  for (int i = 0; i < 4; i++) t[i] = v[i] * -1.4426950408889634f;
  mul_sigmoid4(v, t);
}

#define KT_START(id)
#define KT_END(id)

__device__ __forceinline__ void wgmma_ss_n256_tb(float (&d)[128], uint64_t da, uint64_t db, int scale_d) {
  asm volatile("{\n.reg .pred p;\nsetp.ne.b32 p, %130, 0;\n"
    "wgmma.mma_async.sync.aligned.m64n256k16.f32.bf16.bf16 "
    "{%0, %1, %2, %3, %4, %5, %6, %7, %8, %9, %10, %11, %12, %13, %14, %15, "
    "%16, %17, %18, %19, %20, %21, %22, %23, %24, %25, %26, %27, %28, %29, %30, %31, "
    "%32, %33, %34, %35, %36, %37, %38, %39, %40, %41, %42, %43, %44, %45, %46, %47, "
    "%48, %49, %50, %51, %52, %53, %54, %55, %56, %57, %58, %59, %60, %61, %62, %63, "
    "%64, %65, %66, %67, %68, %69, %70, %71, %72, %73, %74, %75, %76, %77, %78, %79, "
    "%80, %81, %82, %83, %84, %85, %86, %87, %88, %89, %90, %91, %92, %93, %94, %95, "
    "%96, %97, %98, %99, %100, %101, %102, %103, %104, %105, %106, %107, %108, %109, %110, %111, "
    "%112, %113, %114, %115, %116, %117, %118, %119, %120, %121, %122, %123, %124, %125, %126, %127}, "
    "%128, %129, p, 1, 1, 0, 1;\n}\n"
    : "+f"(d[0]), "+f"(d[1]), "+f"(d[2]), "+f"(d[3]), "+f"(d[4]), "+f"(d[5]), "+f"(d[6]), "+f"(d[7]),
      "+f"(d[8]), "+f"(d[9]), "+f"(d[10]), "+f"(d[11]), "+f"(d[12]), "+f"(d[13]), "+f"(d[14]), "+f"(d[15]),
      "+f"(d[16]), "+f"(d[17]), "+f"(d[18]), "+f"(d[19]), "+f"(d[20]), "+f"(d[21]), "+f"(d[22]), "+f"(d[23]),
      "+f"(d[24]), "+f"(d[25]), "+f"(d[26]), "+f"(d[27]), "+f"(d[28]), "+f"(d[29]), "+f"(d[30]), "+f"(d[31]),
      "+f"(d[32]), "+f"(d[33]), "+f"(d[34]), "+f"(d[35]), "+f"(d[36]), "+f"(d[37]), "+f"(d[38]), "+f"(d[39]),
      "+f"(d[40]), "+f"(d[41]), "+f"(d[42]), "+f"(d[43]), "+f"(d[44]), "+f"(d[45]), "+f"(d[46]), "+f"(d[47]),
      "+f"(d[48]), "+f"(d[49]), "+f"(d[50]), "+f"(d[51]), "+f"(d[52]), "+f"(d[53]), "+f"(d[54]), "+f"(d[55]),
      "+f"(d[56]), "+f"(d[57]), "+f"(d[58]), "+f"(d[59]), "+f"(d[60]), "+f"(d[61]), "+f"(d[62]), "+f"(d[63]),
      "+f"(d[64]), "+f"(d[65]), "+f"(d[66]), "+f"(d[67]), "+f"(d[68]), "+f"(d[69]), "+f"(d[70]), "+f"(d[71]),
      "+f"(d[72]), "+f"(d[73]), "+f"(d[74]), "+f"(d[75]), "+f"(d[76]), "+f"(d[77]), "+f"(d[78]), "+f"(d[79]),
      "+f"(d[80]), "+f"(d[81]), "+f"(d[82]), "+f"(d[83]), "+f"(d[84]), "+f"(d[85]), "+f"(d[86]), "+f"(d[87]),
      "+f"(d[88]), "+f"(d[89]), "+f"(d[90]), "+f"(d[91]), "+f"(d[92]), "+f"(d[93]), "+f"(d[94]), "+f"(d[95]),
      "+f"(d[96]), "+f"(d[97]), "+f"(d[98]), "+f"(d[99]), "+f"(d[100]), "+f"(d[101]), "+f"(d[102]), "+f"(d[103]),
      "+f"(d[104]), "+f"(d[105]), "+f"(d[106]), "+f"(d[107]), "+f"(d[108]), "+f"(d[109]), "+f"(d[110]), "+f"(d[111]),
      "+f"(d[112]), "+f"(d[113]), "+f"(d[114]), "+f"(d[115]), "+f"(d[116]), "+f"(d[117]), "+f"(d[118]), "+f"(d[119]),
      "+f"(d[120]), "+f"(d[121]), "+f"(d[122]), "+f"(d[123]), "+f"(d[124]), "+f"(d[125]), "+f"(d[126]), "+f"(d[127])
    : "l"(da), "l"(db), "r"(scale_d));
}
__device__ __forceinline__ void wgmma_rs_n32(float (&d)[16], const uint32_t* a, uint64_t db, int scale_d) {
  asm volatile("{\n.reg .pred p;\nsetp.ne.b32 p, %21, 0;\n"
    "wgmma.mma_async.sync.aligned.m64n32k16.f32.bf16.bf16 "
    "{%0, %1, %2, %3, %4, %5, %6, %7, %8, %9, %10, %11, %12, %13, %14, %15}, "
    "{%16, %17, %18, %19}, %20, p, 1, 1, 0;\n}\n"
    : "+f"(d[0]), "+f"(d[1]), "+f"(d[2]), "+f"(d[3]), "+f"(d[4]), "+f"(d[5]), "+f"(d[6]), "+f"(d[7]),
      "+f"(d[8]), "+f"(d[9]), "+f"(d[10]), "+f"(d[11]), "+f"(d[12]), "+f"(d[13]), "+f"(d[14]), "+f"(d[15])
    : "r"(a[0]), "r"(a[1]), "r"(a[2]), "r"(a[3]), "l"(db), "r"(scale_d));
}
__device__ __forceinline__ void wgmma_ss_n32_ta(float (&d)[16], uint64_t da, uint64_t db, int scale_d) {
  asm volatile("{\n.reg .pred p;\nsetp.ne.b32 p, %18, 0;\n"
    "wgmma.mma_async.sync.aligned.m64n32k16.f32.bf16.bf16 "
    "{%0, %1, %2, %3, %4, %5, %6, %7, %8, %9, %10, %11, %12, %13, %14, %15}, "
    "%16, %17, p, 1, 1, 1, 0;\n}\n"
    : "+f"(d[0]), "+f"(d[1]), "+f"(d[2]), "+f"(d[3]), "+f"(d[4]), "+f"(d[5]), "+f"(d[6]), "+f"(d[7]),
      "+f"(d[8]), "+f"(d[9]), "+f"(d[10]), "+f"(d[11]), "+f"(d[12]), "+f"(d[13]), "+f"(d[14]), "+f"(d[15])
    : "l"(da), "l"(db), "r"(scale_d));
}
__device__ __forceinline__ void wgmma_ss_n8_ta(float (&d)[4], uint64_t da, uint64_t db, int scale_d) {
  asm volatile("{\n.reg .pred p;\nsetp.ne.b32 p, %6, 0;\n"
    "wgmma.mma_async.sync.aligned.m64n8k16.f32.bf16.bf16 {%0, %1, %2, %3}, %4, %5, p, 1, 1, 1, 0;\n}\n"
    : "+f"(d[0]), "+f"(d[1]), "+f"(d[2]), "+f"(d[3]) : "l"(da), "l"(db), "r"(scale_d));
}
__device__ __forceinline__ void wgmma_ss_n48_tt(float (&d)[24], uint64_t da, uint64_t db, int scale_d) {
  asm volatile("{\n.reg .pred p;\nsetp.ne.b32 p, %26, 0;\n"
    "wgmma.mma_async.sync.aligned.m64n48k16.f32.bf16.bf16 "
    "{%0, %1, %2, %3, %4, %5, %6, %7, %8, %9, %10, %11, %12, %13, %14, %15, %16, %17, %18, %19, %20, %21, %22, %23}, "
    "%24, %25, p, 1, 1, 1, 1;\n}\n"
    : "+f"(d[0]), "+f"(d[1]), "+f"(d[2]), "+f"(d[3]), "+f"(d[4]), "+f"(d[5]), "+f"(d[6]), "+f"(d[7]), "+f"(d[8]), "+f"(d[9]), "+f"(d[10]), "+f"(d[11]), "+f"(d[12]), "+f"(d[13]), "+f"(d[14]), "+f"(d[15]), "+f"(d[16]), "+f"(d[17]), "+f"(d[18]), "+f"(d[19]), "+f"(d[20]), "+f"(d[21]), "+f"(d[22]), "+f"(d[23])
    : "l"(da), "l"(db), "r"(scale_d));
}
__device__ __forceinline__ void wgmma_ss_n32(float (&d)[16], uint64_t da, uint64_t db, int scale_d) {
  asm volatile("{\n.reg .pred p;\nsetp.ne.b32 p, %18, 0;\n"
    "wgmma.mma_async.sync.aligned.m64n32k16.f32.bf16.bf16 "
    "{%0, %1, %2, %3, %4, %5, %6, %7, %8, %9, %10, %11, %12, %13, %14, %15}, "
    "%16, %17, p, 1, 1, 0, 0;\n}\n"
    : "+f"(d[0]), "+f"(d[1]), "+f"(d[2]), "+f"(d[3]), "+f"(d[4]), "+f"(d[5]), "+f"(d[6]), "+f"(d[7]),
      "+f"(d[8]), "+f"(d[9]), "+f"(d[10]), "+f"(d[11]), "+f"(d[12]), "+f"(d[13]), "+f"(d[14]), "+f"(d[15])
    : "l"(da), "l"(db), "r"(scale_d));
}

__device__ __forceinline__ void tma_load_2d_mc(uint32_t dst, const CUtensorMap* map, int x, int y, uint32_t bar, uint16_t mask) {
  asm volatile("cp.async.bulk.tensor.2d.shared::cluster.global.mbarrier::complete_tx::bytes.multicast::cluster "
               "[%0], [%1, {%3, %4}], [%2], %5;"
               ::"r"(dst), "l"(map), "r"(bar), "r"(x), "r"(y), "h"(mask) : "memory");
}
__device__ __forceinline__ void mbar_arrive_cluster(uint32_t bar, uint32_t cta) {
  asm volatile("{\n.reg .b32 r;\nmapa.shared::cluster.u32 r, %0, %1;\nmbarrier.arrive.shared::cluster.b64 _, [r];\n}"
               ::"r"(bar), "r"(cta) : "memory");
}
__device__ __forceinline__ void cluster_sync() {
  asm volatile("barrier.cluster.arrive.release.aligned;\nbarrier.cluster.wait.acquire.aligned;" ::: "memory");
}
__device__ __forceinline__ void wait_count(const unsigned* p, unsigned need) {
#pragma unroll 1
  for (int tries = 0; tries < (1 << 18); tries++) {
    unsigned v;
    asm volatile("ld.acquire.gpu.global.u32 %0, [%1];" : "=r"(v) : "l"(p) : "memory");
    if (v >= need) break;
    __nanosleep(64);
  }
}
__device__ __forceinline__ uint32_t sub_bf16x2(uint32_t a, uint32_t b) {
  uint32_t d;
  asm("sub.rn.bf16x2 %0, %1, %2;" : "=r"(d) : "r"(a), "r"(b));
  return d;
}
__device__ __forceinline__ uint32_t add_bf16x2(uint32_t a, uint32_t b) {
  uint32_t d;
  asm("add.rn.bf16x2 %0, %1, %2;" : "=r"(d) : "r"(a), "r"(b));
  return d;
}
__device__ __forceinline__ uint32_t mul_bf16x2(uint32_t a, uint32_t b) {
  uint32_t d;
  asm("mul.rn.bf16x2 %0, %1, %2;" : "=r"(d) : "r"(a), "r"(b));
  return d;
}

template <int NR>
__device__ __forceinline__ void ln_regs(uint32_t (&raw)[NR][16]) {
  float m[NR], q[NR];
#pragma unroll
  for (int r = 0; r < NR; r++) {
    float s0 = 0.f, s1 = 0.f;
#pragma unroll
    for (int i = 0; i < 16; i++) { s0 += bf_lo(raw[r][i]); s1 += bf_hi(raw[r][i]); }
    m[r] = s0 + s1;
  }
#pragma unroll
  for (int o = 16; o > 0; o >>= 1)
#pragma unroll
    for (int r = 0; r < NR; r++) m[r] += __shfl_xor_sync(0xffffffffu, m[r], o);
#pragma unroll
  for (int r = 0; r < NR; r++) {
    m[r] *= 1.0f / 1024.0f;
    float s0 = 0.f, s1 = 0.f;
#pragma unroll
    for (int i = 0; i < 16; i++) {
      const float d0 = bf_lo(raw[r][i]) - m[r], d1 = bf_hi(raw[r][i]) - m[r];
      s0 = fmaf(d0, d0, s0); s1 = fmaf(d1, d1, s1);
    }
    q[r] = s0 + s1;
  }
#pragma unroll
  for (int o = 16; o > 0; o >>= 1)
#pragma unroll
    for (int r = 0; r < NR; r++) q[r] += __shfl_xor_sync(0xffffffffu, q[r], o);
#pragma unroll
  for (int r = 0; r < NR; r++) {
    const uint32_t mb = pack_bf16(m[r], m[r]);
    float sq;
    asm("sqrt.approx.f32 %0, %1;" : "=f"(sq) : "f"(rbf(rbf(q[r] * (1.0f / 1024.0f)) + 1e-5f)));
    const float inv = rcp_approx(rbf(sq));
#pragma unroll
    for (int i = 0; i < 16; i++) {
      const uint32_t d = sub_bf16x2(raw[r][i], mb);
      raw[r][i] = pack_bf16(bf_lo(d) * inv, bf_hi(d) * inv);
    }
  }
}
__device__ __forceinline__ void load_row16(uint32_t (&raw)[16], const bf16* src, int lane) {
#pragma unroll
  for (int j = 0; j < 4; j++) {
    const uint4 u = __ldcg(reinterpret_cast<const uint4*>(src + j * 256 + lane * 8));
    raw[4 * j] = u.x; raw[4 * j + 1] = u.y; raw[4 * j + 2] = u.z; raw[4 * j + 3] = u.w;
  }
}
__device__ __forceinline__ void store_row16(const uint32_t (&raw)[16], bf16* dst, int lane) {
#pragma unroll
  for (int j = 0; j < 4; j++)
    *reinterpret_cast<uint4*>(dst + j * 256 + lane * 8) = make_uint4(raw[4 * j], raw[4 * j + 1], raw[4 * j + 2], raw[4 * j + 3]);
}

namespace fk {
constexpr uint32_t SM0 = 1024;
constexpr uint32_t WO = SM0, WS = WO + 90112, XN = WS + 65536, VX = XN + 49152, QK = VX + 8192, PT = QK + 8192,
                   SP = PT + 4096, VM = SP + 2560, OB = VM + 2048, BAR = OB + 2048;
constexpr uint32_t MEMB = XN + 16384, RED = XN + 32768, VX2 = WO + 81920;
constexpr int SMEM = 232448;
static_assert(BAR + 512 == SM0 + SMEM, "shared memory layout");
constexpr uint32_t B_XN = BAR, B_H2 = BAR + 64, B_H1 = BAR + 120, ONES = BAR + 384, B_PF = BAR + 16, B_WO = BAR + 24, B_SM = BAR + 32, B_VM = BAR + 40, B_VX = BAR + 48, B_ST = BAR + 56, B_PB = BAR + 64, B_W = BAR + 112,
                   MASKS = BAR + 128, PROBE = BAR + 256;
constexpr int NB_M0 = 1, NB_M1 = 2, NB_C = 3, NB_O = 4, NB_ST = 5, NB_DU = 6, NB_CF = 7, NB_W1 = 8, NB_XE = 9, NB_HD = 10, NB_MX = 11, NB_O0 = 12;
#define D_H1 550
#define D_H2 1900
#define D_ST 200
#define SMQ 0x1E
#define SMV 0x1E
#define PRE_G 4
#define PRE_A 1
#define LN_DRY 1
#define MASK_AT 4
#define WO_AT 5
#define NS0 4
#define NS0V 4
#define NTA0 2
#define NTA1 1
#define PF0A 3
#define PF0 10
#define PF1V 10
#define PF1 11
#define REFILL_EARLY 1
#define GATE_MX 0
#define GATE_Q 0
#define PF1Q 4
#define PACEQ 0x60
#define PACEV 0
#define PADD 1
#define D_H2V 2200
#define D_H2L 1700
#define H2_ATV 0
#define VM_BULK 0
#define CF_AT 0
#define H2_AT 0
#define NPRE0 1
#define PROBE_N 4
#define SPACK 1
constexpr uint32_t SPW = SPACK ? 4 : 8, SP_SRC = 160 * SPW;
constexpr int H1_BYTES = 64 * 32768, H2_BYTES = 8 * 8192;
}

#define PROF(wg, i)
#define PROF2(i)
#define RETRY(i)
#define GTSYNC(i)
#define PRO(i)
#define TL(i)
#define TL2(t, i)

__device__ uint4 g_xch[(fk::H1_BYTES + fk::H2_BYTES + 8192) / 16];
__device__ __align__(16) unsigned g_mask[128];
__device__ unsigned g_cnt[8][16];
__device__ unsigned g_next;
constexpr int TAIL_MB0 = 13, GATE_CNT = 12;
__device__ __align__(16) unsigned g_tfix[96], g_lnok[4];
__device__ __align__(16) unsigned g_tcnt[96][8];
__device__ uint4 g_tpart[96][8][2][256];
__device__ unsigned g_oflag[16];

#define LD_POLL "ld.global.L1::no_allocate"
__device__ __forceinline__ uint4 ld_poll16(const void* p) {
  uint4 v;
  asm volatile(LD_POLL ".v4.u32 {%0,%1,%2,%3}, [%4];" : "=r"(v.x), "=r"(v.y), "=r"(v.z), "=r"(v.w) : "l"(p) : "memory");
  return v;
}
__device__ __forceinline__ uint2 ld_poll8(const void* p) {
  uint2 v;
  asm volatile(LD_POLL ".v2.u32 {%0,%1}, [%2];" : "=r"(v.x), "=r"(v.y) : "l"(p) : "memory");
  return v;
}
__device__ __forceinline__ uint4 ld_strong16(const void* p) {
  uint4 v;
  asm volatile("ld.relaxed.gpu.global.v4.u32 {%0,%1,%2,%3}, [%4];" : "=r"(v.x), "=r"(v.y), "=r"(v.z), "=r"(v.w) : "l"(p) : "memory");
  return v;
}
__device__ __forceinline__ uint2 ld_strong8(const void* p) {
  uint2 v;
  asm volatile("ld.relaxed.gpu.global.v2.u32 {%0,%1}, [%2];" : "=r"(v.x), "=r"(v.y) : "l"(p) : "memory");
  return v;
}
__device__ __forceinline__ void st_pub32(void* p, uint32_t v) { asm volatile("st.relaxed.gpu.global.u32 [%0], %1;" ::"l"(p), "r"(v) : "memory"); }
__device__ __forceinline__ void st_pub16(void* p, uint32_t v) {
  asm volatile("st.relaxed.gpu.global.u16 [%0], %1;" ::"l"(p), "h"((uint16_t)v) : "memory");
}
__device__ __forceinline__ uint32_t ld_strong4(const void* p) {
  uint32_t v;
  asm volatile("ld.relaxed.gpu.global.u32 %0, [%1];" : "=r"(v) : "l"(p) : "memory");
  return v;
}
__device__ __forceinline__ void st_pub64(void* p, uint32_t a, uint32_t b) {
  asm volatile("st.relaxed.gpu.global.v2.u32 [%0], {%1,%2};" ::"l"(p), "r"(a), "r"(b) : "memory");
}
__device__ __forceinline__ void st_pub128(void* p, uint32_t a) {
  asm volatile("st.relaxed.gpu.global.v4.u32 [%0], {%1,%1,%1,%1};" ::"l"(p), "r"(a) : "memory");
}
constexpr uint32_t EMPTY = 0xFFFFFFFFu;
__device__ __forceinline__ uint32_t umax4(const uint4& v) { return max(max(v.x, v.y), max(v.z, v.w)); }
__device__ __forceinline__ void sts128(uint32_t a, uint32_t x, uint32_t y, uint32_t z, uint32_t w) {
  asm volatile("st.shared.v4.u32 [%0], {%1,%2,%3,%4};" ::"r"(a), "r"(x), "r"(y), "r"(z), "r"(w) : "memory");
}
__device__ __forceinline__ void sts64(uint32_t a, uint32_t x, uint32_t y) {
  asm volatile("st.shared.v2.u32 [%0], {%1,%2};" ::"r"(a), "r"(x), "r"(y) : "memory");
}
__device__ __forceinline__ void sts32(uint32_t a, uint32_t x) { asm volatile("st.shared.u32 [%0], %1;" ::"r"(a), "r"(x) : "memory"); }
__device__ __forceinline__ void sts128f(uint32_t a, float x, float y, float z, float w) {
  asm volatile("st.shared.v4.f32 [%0], {%1,%2,%3,%4};" ::"r"(a), "f"(x), "f"(y), "f"(z), "f"(w) : "memory");
}
__device__ __forceinline__ void sts64f(uint32_t a, float x, float y) {
  asm volatile("st.shared.v2.f32 [%0], {%1,%2};" ::"r"(a), "f"(x), "f"(y) : "memory");
}
__device__ __forceinline__ float4 lds128f(uint32_t a) {
  float4 v;
  asm volatile("ld.shared.v4.f32 {%0,%1,%2,%3}, [%4];" : "=f"(v.x), "=f"(v.y), "=f"(v.z), "=f"(v.w) : "r"(a) : "memory");
  return v;
}
__device__ __forceinline__ float2 lds64f(uint32_t a) {
  float2 v;
  asm volatile("ld.shared.v2.f32 {%0,%1}, [%2];" : "=f"(v.x), "=f"(v.y) : "r"(a) : "memory");
  return v;
}
__device__ __forceinline__ float2 lds64f_if(uint32_t a, bool on, float other) {
  float2 v = make_float2(other, other);
  asm volatile("{\n.reg .pred p;\nsetp.ne.u32 p, %3, 0;\n@p ld.shared.v2.f32 {%0,%1}, [%2];\n}" : "+f"(v.x), "+f"(v.y) : "r"(a), "r"((uint32_t)on) : "memory");
  return v;
}
__device__ __forceinline__ void lds128(uint32_t* r, uint32_t a) {
  asm volatile("ld.shared.v4.u32 {%0,%1,%2,%3}, [%4];" : "=r"(r[0]), "=r"(r[1]), "=r"(r[2]), "=r"(r[3]) : "r"(a) : "memory");
}
__device__ __forceinline__ void lds64(uint32_t* r, uint32_t a) {
  asm volatile("ld.shared.v2.u32 {%0,%1}, [%2];" : "=r"(r[0]), "=r"(r[1]) : "r"(a) : "memory");
}
__device__ __forceinline__ uint32_t lds32(uint32_t a) {
  uint32_t v;
  asm volatile("ld.shared.u32 %0, [%1];" : "=r"(v) : "r"(a) : "memory");
  return v;
}
__device__ __forceinline__ void ldsm4(uint32_t* r, uint32_t a) {
  asm volatile("ldmatrix.sync.aligned.m8n8.x4.shared.b16 {%0,%1,%2,%3}, [%4];"
               : "=r"(r[0]), "=r"(r[1]), "=r"(r[2]), "=r"(r[3]) : "r"(a) : "memory");
}
__device__ __forceinline__ void ldsm4t(uint32_t* r, uint32_t a) {
  asm volatile("ldmatrix.sync.aligned.m8n8.x4.trans.shared.b16 {%0,%1,%2,%3}, [%4];"
               : "=r"(r[0]), "=r"(r[1]), "=r"(r[2]), "=r"(r[3]) : "r"(a) : "memory");
}
__device__ __forceinline__ void stsm4(uint32_t a, uint32_t r0, uint32_t r1, uint32_t r2, uint32_t r3) {
  asm volatile("stmatrix.sync.aligned.m8n8.x4.shared.b16 [%0], {%1,%2,%3,%4};"
               ::"r"(a), "r"(r0), "r"(r1), "r"(r2), "r"(r3) : "memory");
}
__device__ __forceinline__ void stsm4t(uint32_t a, uint32_t r0, uint32_t r1, uint32_t r2, uint32_t r3) {
  asm volatile("stmatrix.sync.aligned.m8n8.x4.trans.shared.b16 [%0], {%1,%2,%3,%4};"
               ::"r"(a), "r"(r0), "r"(r1), "r"(r2), "r"(r3) : "memory");
}
__device__ __forceinline__ void mma16816(float* d, const uint32_t* a, uint32_t b0, uint32_t b1) {
  asm volatile("mma.sync.aligned.m16n8k16.row.col.f32.bf16.bf16.f32 {%0,%1,%2,%3}, {%4,%5,%6,%7}, {%8,%9}, {%0,%1,%2,%3};"
               : "+f"(d[0]), "+f"(d[1]), "+f"(d[2]), "+f"(d[3])
               : "r"(a[0]), "r"(a[1]), "r"(a[2]), "r"(a[3]), "r"(b0), "r"(b1));
}
__device__ __forceinline__ void mma16816z(float* d, const uint32_t* a, uint32_t b0, uint32_t b1) {
  asm volatile("mma.sync.aligned.m16n8k16.row.col.f32.bf16.bf16.f32 {%0,%1,%2,%3}, {%4,%5,%6,%7}, {%8,%9}, {%10,%10,%10,%10};"
               : "=f"(d[0]), "=f"(d[1]), "=f"(d[2]), "=f"(d[3])
               : "r"(a[0]), "r"(a[1]), "r"(a[2]), "r"(a[3]), "r"(b0), "r"(b1), "f"(0.f));
}
__device__ __forceinline__ void mma1688(float* d, uint32_t a0, uint32_t a1, uint32_t b0) {
  asm volatile("mma.sync.aligned.m16n8k8.row.col.f32.bf16.bf16.f32 {%0,%1,%2,%3}, {%4,%5}, {%6}, {%0,%1,%2,%3};"
               : "+f"(d[0]), "+f"(d[1]), "+f"(d[2]), "+f"(d[3]) : "r"(a0), "r"(a1), "r"(b0));
}
__device__ __forceinline__ uint32_t movtrans(uint32_t a) {
  uint32_t d;
  asm volatile("movmatrix.sync.aligned.m8n8.trans.b16 %0, %1;" : "=r"(d) : "r"(a));
  return d;
}
__device__ __forceinline__ uint32_t mapa(uint32_t a, uint32_t rank) {
  uint32_t d;
  asm("mapa.shared::cluster.u32 %0, %1, %2;" : "=r"(d) : "r"(a), "r"(rank));
  return d;
}
__device__ __forceinline__ void st_async64(uint32_t a, uint32_t x, uint32_t y, uint32_t bar) {
  asm volatile("st.async.weak.shared::cluster.mbarrier::complete_tx::bytes.v2.b32 [%0], {%1,%2}, [%3];"
               ::"r"(a), "r"(x), "r"(y), "r"(bar) : "memory");
}
__device__ __forceinline__ void st_async64f(uint32_t a, float x, float y, uint32_t bar) {
  st_async64(a, __float_as_uint(x), __float_as_uint(y), bar);
}
__device__ __forceinline__ void bulk_s2s(uint32_t dst, uint32_t src, uint32_t bytes, uint32_t bar) {
  asm volatile("cp.async.bulk.shared::cluster.shared::cta.mbarrier::complete_tx::bytes [%0], [%1], %2, [%3];"
               ::"r"(dst), "r"(src), "r"(bytes), "r"(bar) : "memory");
}
__device__ __forceinline__ void tma_store_3d(const CUtensorMap* map, uint32_t src, int x, int y, int z) {
  asm volatile("cp.async.bulk.tensor.3d.global.shared::cta.bulk_group [%0, {%2, %3, %4}], [%1];"
               ::"l"(map), "r"(src), "r"(x), "r"(y), "r"(z) : "memory");
}
__device__ __forceinline__ void mbar_spin(uint32_t bar, uint32_t parity) {
  asm volatile("{\n.reg .pred p;\n.reg .b32 n;\nmov.u32 n, 0x100000;\nMW_L:\n"
               "mbarrier.try_wait.parity.shared::cta.b64 p, [%0], %1;\n@p bra.uni MW_D;\n"
               "add.s32 n, n, -1;\nsetp.ne.u32 p, n, 0;\n@p bra.uni MW_L;\nMW_D:\n}" ::"r"(bar), "r"(parity) : "memory");
}
__device__ __forceinline__ bool mbar_test(uint32_t bar, uint32_t parity) {
  uint32_t done;
  asm volatile("{\n.reg .pred p;\nmbarrier.test_wait.parity.shared::cta.b64 p, [%1], %2;\nselp.u32 %0, 1, 0, p;\n}"
               : "=r"(done) : "r"(bar), "r"(parity) : "memory");
  return done != 0;
}
__device__ __forceinline__ void mbar_arrive_remote(uint32_t bar) {
  asm volatile("mbarrier.arrive.shared::cluster.b64 _, [%0];" ::"r"(bar) : "memory");
}
__device__ __forceinline__ bool elect_one() {
  uint32_t r;
  asm volatile("{\n.reg .pred p;\nelect.sync _|p, 0xffffffff;\nselp.u32 %0, 1, 0, p;\n}" : "=r"(r));
  return r != 0;
}
__device__ __forceinline__ void st_async32(uint32_t a, uint32_t x, uint32_t bar) {
  asm volatile("st.async.weak.shared::cluster.mbarrier::complete_tx::bytes.b32 [%0], %1, [%2];" ::"r"(a), "r"(x), "r"(bar) : "memory");
}
#define named_bar_and(id, n, in, out) \
  asm volatile("{\n.reg .pred p, q;\nsetp.ne.u32 p, %1, 0;\nbar.red.and.pred q, %2, %3, p;\nselp.u32 %0, 1, 0, q;\n}" \
               : "=r"(out) : "r"(in), "n"(id), "n"(n) : "memory")
__device__ __forceinline__ void bulk_g2s(uint32_t dst, const void* src, uint32_t bytes, uint32_t bar) {
  asm volatile("cp.async.bulk.shared::cluster.global.mbarrier::complete_tx::bytes [%0], [%1], %2, [%3];"
               ::"r"(dst), "l"(src), "r"(bytes), "r"(bar) : "memory");
}
__device__ __forceinline__ void l2_prefetch(const void* p, uint32_t bytes) {
  asm volatile("cp.async.bulk.prefetch.L2.global [%0], %1;" ::"l"(p), "r"(bytes) : "memory");
}

__device__ __forceinline__ uint32_t clk32() { uint32_t c; asm volatile("mov.u32 %0, %%clock;" : "=r"(c)::"memory"); return c; }
__device__ __forceinline__ void spin_until(uint32_t t) { while ((int32_t)(clk32() - t) < 0) {} }
#define PIN(x) asm volatile("" : "+r"(x))
#define OPQ                                                                                     \
  int tid_o = tid;                                                                              \
  asm volatile("" : "+r"(tid_o));                                                               \
  const int lane = tid_o & 31, w = (tid_o >> 5) & 3, t7 = tid_o & 127, lg = lane >> 2,          \
            lq = lane & 3, mi = lane >> 3, mr = lane & 7;                                       \
  (void)w; (void)t7; (void)lg; (void)lq; (void)mi; (void)mr; (void)lane

#define SMAP                                                                                                          \
  const uint32_t SM0 = self + fk::SM0, WO = self + fk::WO, WS = self + fk::WS, XN = self + fk::XN, VX = self + fk::VX, \
                 QK = self + fk::QK, PT = self + fk::PT, SP = self + fk::SP, VM = self + fk::VM, OB = self + fk::OB,   \
                 RED = self + fk::RED, VX2 = self + fk::VX2, MEMB = self + fk::MEMB, B_XN = self + fk::B_XN, B_SM = self + fk::B_SM,       \
                 B_VM = self + fk::B_VM, B_VX = self + fk::B_VX, B_ST = self + fk::B_ST, B_PB = self + fk::B_PB,       \
                 B_W = self + fk::B_W, B_H2 = self + fk::B_H2, B_H1 = self + fk::B_H1, B_PF = self + fk::B_PF, B_WO = self + fk::B_WO, MASKS = self + fk::MASKS, PROBE = self + fk::PROBE;                             \
  (void)SM0; (void)WO; (void)WS; (void)XN; (void)VX; (void)QK; (void)PT; (void)SP; (void)VM; (void)OB; (void)RED; (void)VX2; \
  (void)MEMB; (void)B_XN; (void)B_SM; (void)B_VM; (void)B_VX; (void)B_ST; (void)B_PB; (void)B_W; (void)MASKS; (void)PROBE; (void)B_H2; (void)B_H1; (void)B_PF; (void)B_WO

struct FParams {
  CUtensorMap wq, wk, wv, wo, wo16, xn, xn12, o;
  CUtensorMap ta, tb, tx, tg;
  const bf16 *mem0, *x;
  bf16* out;
  bf16* xn_ptr;
  uint64_t dxn;
  int nprobe;
  char* xch;
};

__device__ __forceinline__ uint2 probe_pair(char* p, uint32_t val, uint32_t dummy, int n) {
  uint2 best = make_uint2(0x7FFFFFFF, 0x7FFFFFFF);
  st_pub128(p, val); st_pub128(p + 16, val); st_pub128(p + 4096, val); st_pub128(p + 4112, val);
#pragma unroll 1
  for (int r = 0; r < n; r++) {
    uint32_t v;
    const uint32_t c0 = clk32();
    asm volatile("atom.relaxed.gpu.global.exch.b32 %0, [%1], %2;" : "=r"(v) : "l"(p + (r & 1) * 4096), "r"(val) : "memory");
    asm volatile("{\n.reg .pred p;\nsetp.eq.u32 p, %0, 0x12345678;\n@p st.shared.u32 [%1], %0;\n}" ::"r"(v), "r"(dummy) : "memory");
    const uint32_t d = clk32() - c0;
    if (r & 1) best.y = min(best.y, d); else best.x = min(best.x, d);
  }
  return best;
}

typedef uint32_t WRegs[6][2][4][4];

constexpr uint32_t nth_chunks(uint32_t mask) {
  uint32_t t = 0;
  for (int c = 0, n = 0; c < 10; c++) if ((mask >> c) & 1) t |= c << (4 * n++);
  return t;
}
constexpr uint64_t chunk_pos(uint32_t mask) {
  uint64_t t = 0;
  for (int c = 0, a = 0, b = 0; c < 10; c++) t |= (uint64_t)(((mask >> c) & 1) ? a++ : b++) << (4 * c);
  return t;
}
template <bool ISV> struct Chunks {
  static constexpr uint32_t MASK = ISV ? SMV : SMQ, SMT = nth_chunks(MASK), RFT = nth_chunks(~MASK & 1023);
  static_assert(!(MASK & 1), "the first chunk initialises the accumulators");
  static __device__ __forceinline__ constexpr int rf(int wg, int i) { return wg ? 10 + i : (RFT >> (4 * i)) & 15; }
  static __device__ __forceinline__ constexpr int sm(int i) { return (SMT >> (4 * i)) & 15; }
  static constexpr uint64_t IDX = chunk_pos(MASK);
  static __device__ __forceinline__ constexpr int idx(int c) { return (IDX >> (4 * c)) & 15; }
};

template <bool ISV, int WG> struct ProjCfg {
  static constexpr int N0 = ISV ? NS0V : NS0, NS = WG ? 8 - N0 : N0, P0 = WG ? N0 : 0, NTA = WG ? NTA1 : NTA0;
};
__device__ __forceinline__ void load_pair(uint32_t (&t)[4][4], uint32_t wsa, int pp) {
#pragma unroll
  for (int f = 0; f < 4; f++) ldsm4t(t[f], wsa + ((pp >> 1) * 2 + (f & 1)) * 8192 + ((pp & 1) * 2 + (f >> 1)) * 2048);
}
template <bool ISV, int WG>
__device__ __forceinline__ void proj_mem(const WRegs& wr, uint32_t (&ta)[ProjCfg<ISV, WG>::NTA][4][4], uint32_t wsa, uint32_t mba,
                                         float (&a0)[4], float (&a1)[4]) {
  constexpr int NS = ProjCfg<ISV, WG>::NS, P0 = ProjCfg<ISV, WG>::P0, NTA = ProjCfg<ISV, WG>::NTA, NP = 12 + NS;
  float acc[4][4];
  auto spos = [](int j) { return j < NTA ? j : j + (j - NTA + 1) * 12 / (NS - NTA > 0 ? NS - NTA : 1); };
  auto which = [&](int p) { int r = -1; for (int j = 0; j < NS; j++) if (spos(j) == p) r = j; return r; };
  auto nsm_before = [&](int p) { int n = 0; for (int j = 0; j < NS; j++) if (spos(j) < p) n++; return n; };
#pragma unroll
  for (int p = 0; p < NP; p++) {
    const int j = which(p), r = j >= 0 ? 0 : p - nsm_before(p);
    uint32_t bp[4], tl[4][4];
    ldsm4(bp, mba + (j >= 0 ? Chunks<ISV>::sm((P0 + (j >= 0 ? j : 0)) >> 1) * 1024 + ((P0 + j) & 1) * 512 : Chunks<ISV>::rf(WG, r >> 1) * 1024 + (r & 1) * 512));
    if (j >= NTA) load_pair(tl, wsa, P0 + j);
#pragma unroll
    for (int u = 0; u < 2; u++)
#pragma unroll
      for (int T = 0; T < 2; T++) {
        const uint32_t* a = j >= NTA ? tl[u * 2 + T] : j >= 0 ? ta[j >= 0 ? j % NTA : 0][u * 2 + T] : wr[r >> 1][T][(r & 1) * 2 + u];
        if (p == 0) mma16816z(acc[u * 2 + T], a, bp[2 * u], bp[2 * u + 1]);
        else mma16816(acc[u * 2 + T], a, bp[2 * u], bp[2 * u + 1]);
      }
  }
#pragma unroll
  for (int i = 0; i < 4; i++) { a0[i] = acc[0][i] + acc[2][i]; a1[i] = acc[1][i] + acc[3][i]; }
}
template <bool ISV, int WG, int J0, int J1>
__device__ __forceinline__ void proj_mem_prefetch(uint32_t (&ta)[ProjCfg<ISV, WG>::NTA][4][4], uint32_t wsa) {
#pragma unroll
  for (int j = J0; j < J1; j++) load_pair(ta[j], wsa, ProjCfg<ISV, WG>::P0 + j);
}

template <bool ISV, int WG>
__device__ __forceinline__ void proj_finish(const float (&a0)[4], const float (&a1)[4], uint32_t peer0, uint32_t peer1, uint32_t self, int tid, int warp,
                                            uint32_t (&vmo)[4]) {
  using namespace fk;
  SMAP;
  OPQ;
  if (!ISV) {
    stsm4(PT + mr * 16 + ((mi >> 1) ? WG * 1024 + w * 256 + (mi & 1) * 128 : 2048 + w * 512 + (mi & 1) * 256 + WG * 128),
          pack_bf16(a0[0], a0[1]), pack_bf16(a0[2], a0[3]), pack_bf16(a1[0], a1[1]), pack_bf16(a1[2], a1[3]));
    named_bar_sync(NB_C, 256);
  } else {
    if (WG == 0) sts128f(RED + t7 * 16, a1[0], a1[1], a1[2], a1[3]);
    else sts128f(RED + 2048 + t7 * 16, a0[0], a0[1], a0[2], a0[3]);
    if (WG == 1) { lds64(vmo, VM + t7 * 8); lds64(vmo + 2, VM + 1024 + t7 * 8); }
    named_bar_sync(NB_C, 256);
    const float4 p = lds128f(RED + (1 - WG) * 2048 + t7 * 16);
    const float* k = WG == 0 ? a0 : a1;
    const uint32_t v0 = pack_bf16(k[0] + p.x, k[1] + p.y), v1 = pack_bf16(k[2] + p.z, k[3] + p.w);
    const uint32_t off = VM + WG * 1024 + t7 * 8;
    if (VM_BULK) {
      sts64(off, v0, v1);
      fence_proxy_async_smem();
      __syncwarp();
      const uint32_t a = VM + WG * 1024 + warp * 256;
      if (elect_one()) {
        bulk_s2s(peer0 + a, a, 256, peer0 + B_VM);
        bulk_s2s(peer1 + a, a, 256, peer1 + B_VM);
        mbar_arrive(B_VM);
      }
    } else {
      st_async64(peer0 + off, v0, v1, peer0 + B_VM);
      st_async64(peer1 + off, v0, v1, peer1 + B_VM);
      sts64(off, v0, v1);
      __syncwarp();
      if (lane == 0) mbar_arrive(B_VM);
    }
  }
}

__device__ __forceinline__ void send_scores(float s0, float s1, uint32_t off, uint32_t peer0, uint32_t peer1, uint32_t bar, int lane) {
  if (SPACK) {
    const uint32_t v = pack_bf16(s0, s1);
    st_async32(peer0 + off, v, peer0 + bar);
    st_async32(peer1 + off, v, peer1 + bar);
    sts32(off, v);
  } else {
    st_async64f(peer0 + off, s0, s1, peer0 + bar);
    st_async64f(peer1 + off, s0, s1, peer1 + bar);
    sts64f(off, s0, s1);
  }
  __syncwarp();
  if (lane == 0) mbar_arrive(bar);
}

template <int MODE>
__device__ __forceinline__ void wo_load(uint32_t* r, int f, uint32_t woa, uint32_t wob, bool third) {
  constexpr int NT = MODE ? 3 : 2;
  if (MODE >= 2 && f % 3 == 2)
    asm volatile("{\n.reg .pred p;\nsetp.ne.u32 p, %5, 0;\nmov.b32 %0, 0;\nmov.b32 %1, 0;\nmov.b32 %2, 0;\nmov.b32 %3, 0;\n"
                 "@p ldmatrix.sync.aligned.m8n8.x4.trans.shared.b16 {%0,%1,%2,%3}, [%4];\n}"
                 : "=r"(r[0]), "=r"(r[1]), "=r"(r[2]), "=r"(r[3]) : "r"(wob + (f / 3) * 512), "r"((uint32_t)third) : "memory");
  else ldsm4t(r, woa + (f % NT) * 32768 + (f / NT) * 2048);
}
template <int MODE, int PF>
__device__ __forceinline__ void wo_phase(uint32_t (&wf)[PF][4], uint32_t woa, uint32_t wob, bool third, uint32_t oba, char* h1p,
                                         uint32_t sel, uint32_t tag) {
  constexpr int NT = MODE ? 3 : 2;
  float c[NT][4];
  uint32_t of[2][4];
  ldsm4t(of[0], oba);
#pragma unroll
  for (int k = 0; k < 8; k++) {
    if ((k & 1) == 0 && k + 2 < 8) ldsm4t(of[((k >> 1) + 1) & 1], oba + ((k >> 1) + 1) * 512);
#pragma unroll
    for (int i = 0; i < NT; i++) {
      const int f = k * NT + i;
      const uint32_t b0 = of[(k >> 1) & 1][2 * (k & 1)], b1 = of[(k >> 1) & 1][2 * (k & 1) + 1];
      if (k == 0) mma16816z(c[i], wf[f % PF], b0, b1); else mma16816(c[i], wf[f % PF], b0, b1);
      if (f + PF < 8 * NT) wo_load<MODE>(wf[f % PF], f + PF, woa, wob, third);
    }
  }
#pragma unroll
  for (int i = 0; i < NT; i++) {
    char* p = h1p + i * (8 * 32768) + ((sel >> (2 * i)) & 3) * 2048;
    const uint32_t tm = (sel >> 10) & 1;
    if (MODE < 2 || i < 2 || third) {
      st_pub32(p, (pack_bf16(c[i][0], c[i][1]) & ~tm) | (tag & tm));
      st_pub32(p + 1024, (pack_bf16(c[i][2], c[i][3]) & ~tm) | (tag & tm));
    }
  }
}
template <int MODE, int F0, int F1, int PF>
__device__ __forceinline__ void wo_prefetch(uint32_t (&wf)[PF][4], uint32_t woa, uint32_t wob, bool third) {
#pragma unroll
  for (int f = F0; f < F1; f++) wo_load<MODE>(wf[f], f, woa, wob, third);
}

template <bool ISV> __device__ __forceinline__ uint32_t tok_addr(uint32_t base, int tid) {
  OPQ;
  return ISV ? base + w * 2048 + (mi & 1) * 1024 + (mi >> 1) * 128 + mr * 16 : base + (mi >> 1) * 1024 + w * 256 + (mi & 1) * 128 + mr * 16;
}
template <bool ISV> __device__ __forceinline__ constexpr uint32_t tok_off(int T, int i) { return ISV ? T * 512 + i * 256 : T * 4096 + i * 2048; }
template <bool ISV, int T, bool ADD>
__device__ __forceinline__ void tok_store(const float (&x)[16], uint32_t a, const uint32_t (&p)[2][4]) {
#pragma unroll
  for (int i = 0; i < 2; i++) {
    uint32_t r[4];
#pragma unroll
    for (int k = 0; k < 4; k++)
      r[k] = !ADD ? pack_bf16(x[8 * i + 2 * k], x[8 * i + 2 * k + 1])
           : PADD ? add_bf16x2(pack_bf16(x[8 * i + 2 * k], x[8 * i + 2 * k + 1]), p[i][k])
                  : pack_bf16(x[8 * i + 2 * k] + bf_lo(p[i][k]), x[8 * i + 2 * k + 1] + bf_hi(p[i][k]));
    stsm4(a + tok_off<ISV>(T, i), r[0], r[1], r[2], r[3]);
  }
}

__device__ __forceinline__ void load_xn(const FParams& P, int seg, uint32_t self) {
  SMAP;
  mbar_expect_tx(B_XN, 49152);
  tma_load_3d(XN, &P.xn12, 0, seg * 32, 0, B_XN);
}

#define DESC_ADD(d, n) asm volatile("add.s64 %0, %0, %1;" : "+l"(d) : "n"(n))

template <bool ISV>
__device__ __forceinline__ void f_wg0(const FParams& P, const WRegs& wr, const int h, const int rank, const uint32_t hw, int tid) {
  using namespace fk;
  const uint32_t self = mapa(0, (hw >> (2 * rank)) & 3), peer0 = mapa(0, (hw >> (ISV ? 0 : 2 * (rank ^ 1))) & 3) - self,
                 peer1 = mapa(0, (hw >> (ISV ? 2 : 4)) & 3) - self;
  SMAP;
  const int tile0 = rank * 22;
  const uint32_t usel = __shfl_sync(0xffffffffu, tid, 0);
  const int warp = __shfl_sync(0xffffffffu, threadIdx.x >> 5, 0);
  constexpr int WMODE = ISV ? 0 : 2;
  const bool three = warp < 2;
  uint32_t d_h2 = D_H2V, h2ph = 1;
  tid ^= 0x5500;
#pragma unroll 1
  for (int s = -1;;) {
    uint32_t ta[ProjCfg<ISV, 0>::NTA][4][4], wsa, mba;
    const char* src = P.xch + H1_BYTES + ((s & 1) * 4 + warp) * 8192 + ((usel >> (16 + (s & 1))) & 1) * 4096;
    {
      const uint32_t ph = (s + 1) & 1;
      float x0[16], x1[16];
      uint32_t t_pub = 0;
      wg_fence();
      static_assert(Chunks<ISV>::MASK == 0x1E, "chunks 1 .. 4 are in shared memory");
      uint64_t db = P.dxn;
      auto rs_chunk = [&](int ci, bool pace) {
#pragma unroll
        for (int u = 0; u < 4; u++) {
          wgmma_rs_n32(x0, wr[ci][0][u], db, (ci | u) != 0);
          wgmma_rs_n32(x1, wr[ci][1][u], db, (ci | u) != 0);
          if (u < 3) DESC_ADD(db, 2); else DESC_ADD(db, 250);
          if (pace) { wg_commit(); wg_wait<2>(); wg_fence(); }
        }
      };
      rs_chunk(0, false);
      t_pub = clk32() - 60;
      PROF(0, 8); PROF(0, 1);
#pragma unroll
      for (int c = 1; c <= 4; c++) {
#pragma unroll
        for (int u = 0; u < 4; u++) {
          const uint64_t dx = make_desc(fk::XN + c * 4096 + u * 32, 16, 1024);
          wgmma_ss_n32_ta(x0, make_desc(fk::WS + (c - 1) * 16384 + u * 2048, 8192, 1024), dx, 1);
          wgmma_ss_n32_ta(x1, make_desc(fk::WS + (c - 1) * 16384 + 8192 + u * 2048, 8192, 1024), dx, 1);
          if (c == 4 && u == 1) { wg_commit(); wg_wait<1>(); named_bar_arrive(NB_XE, 160); wg_fence(); }
        }
        if (c == 3) wg_commit();
      }
      DESC_ADD(db, 1024);
#pragma unroll
      for (int c = 5; c < 10; c++) {
        if (c == 9) named_bar_arrive(NB_ST, 256);
        rs_chunk(c - 4, ((ISV ? PACEV : PACEQ) >> c) & 1);
      }
      wg_commit();
      wg_wait<0>();
      PROF(0, 10);
      const uint32_t tb = ISV ? (ph ? VX2 : VX) : QK;
      auto h2_issue = [&]() {
        spin_until(t_pub + (ISV ? d_h2 : D_H2));
        PROF(0, 13);
        if (elect_one()) { mbar_expect_tx(B_H2 + 8 * warp, 4096); bulk_g2s(MEMB + warp * 4096, src, 4096, B_H2 + 8 * warp); }
      };
      named_bar_sync(NB_CF, ISV ? 160 : 256);
      if ((ISV ? H2_ATV : H2_AT) == 0) h2_issue();
      const uint32_t none[2][4] = {}, tka = tok_addr<ISV>(tb, tid);
      tok_store<ISV, 0, false>(x0, tka, none);
      if ((ISV ? H2_ATV : H2_AT) == 1) h2_issue();
      tok_store<ISV, 1, false>(x1, tka, none);
      if ((ISV ? H2_ATV : H2_AT) == 2) h2_issue();
      named_bar_arrive(NB_DU, 256);
    }
    {
      OPQ;
      wsa = WS + ((mi >> 1) * 8 + mr) * 128 + (((2 * w + (mi & 1)) ^ mr) << 4);
      mba = MEMB + lane * 16;
      PIN(wsa); PIN(mba);
      {
        const uint32_t chk = MEMB + w * 4096 + lane * 32 + lg * 4, bar = B_H2 + 8 * warp;
        PROF(0, 11);
        proj_mem_prefetch<ISV, 0, 0, NPRE0>(ta, wsa);
#pragma unroll 1
        for (int tries = 0; tries < POLL_TRIES; tries++) {
          mbar_spin(bar, h2ph);
          h2ph ^= 1;
          const uint32_t mx = max(max(lds32(chk), lds32(chk + 1024)), max(lds32(chk + 2048), lds32(chk + 3072)));
          if (__all_sync(0xffffffffu, mx != EMPTY)) break;
          RETRY(1);
          if (elect_one()) { mbar_expect_tx(bar, 4096); bulk_g2s(MEMB + warp * 4096, src, 4096, bar); }
        }
      }
      PROF(0, 12);
      named_bar_arrive(NB_M1, 256);
      proj_mem_prefetch<ISV, 0, NPRE0, NTA0>(ta, wsa);
      named_bar_sync(NB_M0, 128);
    }
    s++;
    tid ^= 0x5500;
    {
      float a0[4], a1[4];
      proj_mem<ISV, 0>(wr, ta, wsa, mba, a0, a1);
      PROF(0, 2);
      uint32_t unused[4];
      proj_finish<ISV, 0>(a0, a1, peer0, peer1, self, tid, warp, unused);
      PROF(0, 3);
      if (s + 1 == cfg::NSEG) break;
      uint32_t wf[PF0][4], woa, wob;
      bool xn_ok;
      {
        OPQ;
        if (!ISV) {
          uint32_t qf[4][4], kf[2][4];
          const uint32_t qa = PT + 2048 + lane * 16, ka = QK + 4096 + w * 1024 + lane * 16;
          ldsm4t(qf[0], qa); ldsm4t(kf[0], ka); ldsm4t(qf[1], qa + 512);
          ldsm4t(qf[2], qa + 1024); ldsm4t(kf[1], ka + 512); ldsm4t(qf[3], qa + 1536);
          float c0[4], c1[4];
          mma16816z(c0, qf[0], kf[0][0], kf[0][1]);
          mma16816z(c1, qf[1], kf[0][2], kf[0][3]);
          mma16816(c0, qf[2], kf[1][0], kf[1][1]);
          mma16816(c1, qf[3], kf[1][2], kf[1][3]);
          const float s0 = (c0[0] + c0[2]) + (c1[0] + c1[2]), s1 = (c0[1] + c0[3]) + (c1[1] + c1[3]);
          send_scores(s0, s1, SP + rank * SP_SRC + t7 * SPW, peer0, peer1, B_SM, lane);
        }
        PROF(0, 4);
        woa = WO + 16384 + ((mi >> 1) * 8 + mr) * 128 + (((2 * w + (mi & 1)) ^ mr) << 4);
        wob = WO + 81920 + w * 4096 + ((mi >> 1) * 8 + mr) * 32 + (((mi & 1) ^ (mr >> 2)) << 4);
        uint32_t vf[2][2][4], vm[2][2];
        if (s == 0) mbar_spin(B_WO, 0);
        if (!ISV) mbar_spin(B_VX, s & 1);
        PROF(0, 14);
#pragma unroll
        for (int T = 0; T < 2; T++)
#pragma unroll
          for (int kk = 0; kk < 2; kk++) ldsm4(vf[T][kk], ((ISV && (s & 1)) ? VX2 : VX) + w * 2048 + (mi & 1) * 1024 + (mi >> 1) * 128 + mr * 16 + T * 512 + kk * 256);
        wo_prefetch<WMODE, 0, PF0A>(wf, woa, wob, three);
        uint32_t spa = SP + lane * SPW, vma = VM + t7 * 8, oa = OB + (mi >> 1) * 1024 + w * 256 + (mi & 1) * 128 + mr * 16;
        PIN(spa); PIN(vma); PIN(oa);
        if (ISV) {
          d_h2 = D_H2L;
          if (!__all_sync(0xffffffffu, mbar_test(B_SM, s & 1))) { d_h2 = D_H2V; mbar_spin(B_SM, s & 1); }
        } else {
          mbar_spin(B_SM, s & 1);
        }
        PROF(0, 5);
        float sc[10];
#pragma unroll
        for (int j = 0; j < 5; j++) {
          if (SPACK) {
            const uint32_t x = lds32(spa + j * 128), y = lds32(spa + SP_SRC + j * 128);
            sc[2 * j] = bf_lo(x) + bf_lo(y); sc[2 * j + 1] = bf_hi(x) + bf_hi(y);
          } else {
            const float2 x = lds64f(spa + j * 256), y = lds64f(spa + SP_SRC + j * 256);
            sc[2 * j] = x.x + y.x; sc[2 * j + 1] = x.y + y.y;
          }
        }
        const bool vm_ok = mbar_test(B_VM, s & 1);
        lds64(vm[0], vma); lds64(vm[1], vma + 1024);
        float m = fmaxf(fmaxf(fmaxf(sc[0], sc[1]), fmaxf(sc[2], sc[3])), fmaxf(fmaxf(sc[4], sc[5]), fmaxf(sc[6], sc[7])));
        m = fmaxf(m, fmaxf(sc[8], sc[9]));
        const float cs = 0.08838834764831845f * 1.4426950408889634f;
        uint32_t pb[5];
        m = fmaxf(m, __shfl_xor_sync(0xffffffffu, m, 1));
        m = fmaxf(m, __shfl_xor_sync(0xffffffffu, m, 2));
        if (ISV ? GATE_MX : GATE_Q) named_bar_arrive(NB_MX, 256);
        const float mc = -m * cs;
#pragma unroll
        for (int j = 0; j < 5; j++) pb[j] = pack_bf16(ex2_approx(fmaf(sc[2 * j], cs, mc)), ex2_approx(fmaf(sc[2 * j + 1], cs, mc)));
        PROF(0, 15);
        if (!vm_ok) { mbar_spin(B_VM, s & 1); lds64(vm[0], vma); lds64(vm[1], vma + 1024); }
        PROF(0, 6);
        float o0[4], o1[4], rs[4];
        const uint32_t ones[4] = {0x3F803F80u, 0x3F803F80u, 0x3F803F80u, 0x3F803F80u};
        mma16816z(rs, ones, pb[0], pb[1]);
        mma16816z(o0, vf[0][0], pb[0], pb[1]);
        mma16816z(o1, vf[1][0], pb[0], pb[1]);
        mma16816(rs, ones, pb[2], pb[3]);
        mma16816(o0, vf[0][1], pb[2], pb[3]);
        mma16816(o1, vf[1][1], pb[2], pb[3]);
        mma1688(rs, ones[0], ones[0], pb[4]);
        mma1688(o0, vm[0][0], vm[0][1], pb[4]);
        mma1688(o1, vm[1][0], vm[1][1], pb[4]);
        const float i0 = rcp_approx(rs[0]), i1 = rcp_approx(rs[1]);
        stsm4(oa, pack_bf16(o0[0] * i0, o0[1] * i1), pack_bf16(o0[2] * i0, o0[3] * i1),
              pack_bf16(o1[0] * i0, o1[1] * i1), pack_bf16(o1[2] * i0, o1[3] * i1));
      }
      {
        OPQ;
        named_bar_arrive(NB_O, 256);
        wo_prefetch<WMODE, PF0A, PF0>(wf, woa, wob, three);
        xn_ok = mbar_test(B_XN, (s + 1) & 1);
        char* h1p = P.xch + (tile0 + 4 + w) * 32768 + (h >> 3) * 8192 + (h & 7) * 128 + (((2 * lq + (lg & 1)) ^ (h & 7)) << 4) + (lg >> 1) * 4;
        uint32_t oba = OB + lane * 16;
        PIN(oba);
        PROF(0, 7);
        named_bar_sync(NB_O0, 128);
        const uint32_t tag = ((s >> 1) & 1) ^ 1;
        wo_phase<WMODE>(wf, woa, wob, three, oba, h1p, tid >> 8, tag);
        PROF(0, 9);
        if (!xn_ok) mbar_spin(B_XN, (s + 1) & 1);
        named_bar_sync(NB_HD, 256);
      }
    }
  }
}

template <bool ISV>
__device__ __forceinline__ void f_wg1(const FParams& P, const WRegs& wr, const int h, const int rank, const uint32_t hw, int tid) {
  using namespace fk;
  const uint32_t self = mapa(0, (hw >> (2 * rank)) & 3), peer0 = mapa(0, (hw >> (ISV ? 0 : 2 * (rank ^ 1))) & 3) - self,
                 peer1 = mapa(0, (hw >> (ISV ? 2 : 4)) & 3) - self;
  SMAP;
  const int tile0 = rank * 22;
  const uint32_t usel = __shfl_sync(0xffffffffu, tid, 0);
  const int warp = __shfl_sync(0xffffffffu, (threadIdx.x >> 5) & 3, 0);
  constexpr int WMODE = 1;
  uint32_t h1ph = 0;
  auto o_done = [&](int mb) {
    tma_store_wait_all();
    asm volatile("fence.proxy.async.global;" ::: "memory");
    asm volatile("red.relaxed.gpu.global.add.u32 [%0], 1;" ::"l"(&g_oflag[mb]) : "memory");
  };
  uint32_t vmo[4] = {0, 0, 0, 0};
  if (ISV) {
    OPQ;
    sts32(PT + (t7 >> 2) * 128 + ((5 ^ lg) << 4) + lq * 4, 0);
    sts32(PT + (t7 >> 2) * 128 + ((6 ^ lg) << 4) + lq * 4, 0);
  }
  tid ^= 0x5500;
#pragma unroll 1
  for (int s = -1;;) {
    uint32_t ta[ProjCfg<ISV, 1>::NTA][4][4], wsa, mba;
    if (s + 1 < cfg::NSEG) mbar_spin(B_XN, (s + 1) & 1);
    const uint32_t t_pub = clk32();
    auto refill = [&]() {
      if (warp == 3) {
        named_bar_sync(NB_XE, 160);
        if (elect_one()) {
          mbar_expect_tx(B_XN + 8, 16384);
          tma_load_3d(XN, &P.xn, 0, (s + 1) * 32, 12, B_XN + 8);
        }
      }
    };
    auto arm = [&]() {
      if ((tid & 255) == 160) {
        if (s == 1) st_pub32(&g_mask[3 * h + rank], 0);
        if (s + 2 < cfg::NSEG) { mbar_expect_tx(B_SM, ISV ? 2 * SP_SRC : SP_SRC); if (!ISV) mbar_expect_tx(B_VX, 8192); }
        if (!ISV && s + 1 < cfg::NSEG) mbar_expect_tx(B_VM, 2048);
        if (ISV && s >= 1 && s < cfg::NSEG) mbar_expect_tx(B_ST, 7168);
      }
      if (ISV && s < cfg::NSEG && (tid & 254) == 192) mbar_arrive_remote(((tid & 1) ? peer1 : peer0) + B_ST);
      __syncwarp();
    };
    if (ISV) {
      if (s >= 0) arm();
      if (s >= 1) {
        OPQ;
        if (warp == 0 && (s & 3) == 1 && s > 1) { if (elect_one()) o_done((s - 2) >> 2); }
        const uint32_t vb = (s & 1) ? VX : VX2;
        float x0[16], x1[16];
        wg_fence();
        wgmma_rs_n32(x0, vmo, make_desc(fk::PT + 64, 16, 1024), 0);
        wgmma_rs_n32(x1, vmo, make_desc(fk::PT + 96, 16, 1024), 0);
#pragma unroll
        for (int kk = 0; kk < 2; kk++) {
          wgmma_ss_n32(x0, make_desc0(vb + kk * 256, 128, 1024), make_desc(fk::PT + kk * 32, 16, 1024), 1);
          wgmma_ss_n32(x1, make_desc0(vb + 512 + kk * 256, 128, 1024), make_desc(fk::PT + kk * 32, 16, 1024), 1);
        }
        wg_commit();
        wg_wait<0>();
        named_bar_sync(NB_W1, 128);
        PROF(1, 4);
        const uint32_t stg = vb + (8 * (mi >> 1) + mr) * 128 + (((2 * w + (mi & 1)) ^ mr) << 4);
#pragma unroll
        for (int T = 0; T < 2; T++) {
          const float* x = T ? x1 : x0;
#pragma unroll
          for (int jj = 0; jj < 4; jj += 2)
            stsm4t(stg + T * 4096 + jj * 1024, pack_bf16(x[4 * jj], x[4 * jj + 1]), pack_bf16(x[4 * jj + 2], x[4 * jj + 3]),
                   pack_bf16(x[4 * jj + 4], x[4 * jj + 5]), pack_bf16(x[4 * jj + 6], x[4 * jj + 7]));
        }
        fence_proxy_async_smem();
        named_bar_sync(NB_W1, 128);
        PROF(1, 10);
        if (warp == 0) {
          if (elect_one()) {
            tma_store_3d(&P.o, vb, 0, (s - 1) * 32, 2 * h);
            tma_store_commit();
          }
          __syncwarp();
        }
        if (s == cfg::NSEG) break;
      }
      if (s + 1 < cfg::NSEG) refill();
      PROF(1, 11);
    } else if (s < 0) {
      named_bar_arrive(NB_CF, 256);
      refill();
    } else {
      float x[24];
      wg_fence();
#pragma unroll
      for (int k = 0; k < 4; k++) wgmma_ss_n48_tt(x, make_desc0(fk::QK + k * 256, 128, 1024), make_desc0(fk::QK + 4096 + k * 256, 128, 1024), k != 0);
      wg_commit();
      arm();
      auto send_tok = [&]() {
        if (warp < 2) {
          OPQ;
          const uint32_t d0 = peer1 + QK + rank * 3584 + lane * 8 + w * 1280, d1 = d0 + 512 + w * 512, bar = peer1 + B_ST;
          mbar_spin(B_ST, s & 1);
          const float NEG = -500000000.0f / 0.08838834764831845f;
          const bool m0 = 2 * lq > lg, m1 = 2 * lq + 1 > lg;
          st_async64f(d0, x[16] + x[20], x[17] + x[21], bar);
          st_async64f(d1, x[18] + x[22], x[19] + x[23], bar);
          st_async64f(d1 + 256, x[2], x[3], bar);
          if (warp == 0) {
            st_async64f(d0 + 256, m0 ? NEG : x[0], m1 ? NEG : x[1], bar);
            st_async64f(d1 + 512, m0 ? NEG : x[6], m1 ? NEG : x[7], bar);
          } else {
            st_async64f(d0 + 256, x[0], x[1], bar);
            st_async64f(d1 + 512, x[6], x[7], bar);
            st_async64f(d0 + 512, x[4], x[5], bar);
            st_async64f(d0 + 768, m0 ? NEG : x[8], m1 ? NEG : x[9], bar);
            st_async64f(d1 + 768, x[10], x[11], bar);
            st_async64f(d1 + 1024, m0 ? NEG : x[14], m1 ? NEG : x[15], bar);
          }
        }
        PROF(1, 4);
      };
      const bool fin = s + 1 == cfg::NSEG;
      OPQ;
      const int j = 2 * h + rank;
      const char* src = P.xch + j * 32768 + warp * 8192 + (((usel >> 14) & 2) + (s & 1)) * 2048;
      char* dst = P.xch + H1_BYTES + (j >> 4) * 8192 + (lq >> 1) * 4096 + (j & 15) * 256 + (lq & 1) * 128 + (2 * w + (lg & 1)) * 16 + (lg >> 1) * 4;
      const uint32_t chk = VX + mi * 2048 + mr * 128 + (w ^ (mr >> 1)) * 32 + ((lane & 1) + 2 * mi) * 4;
      const uint32_t tmask = (s >> 1) & 1;
      if (!fin) {
        spin_until(t_pub + D_H1);
        if (elect_one()) { mbar_expect_tx(B_H1, 2048); bulk_g2s(VX + warp * 2048, src, 2048, B_H1); }
      }
      __syncwarp();
      wg_wait<0>();
      PROF(1, 6);
      send_tok();
      if (fin) { mbar_spin(B_VM, s & 1); break; }
      named_bar_arrive(NB_CF, 256);
      if (REFILL_EARLY) refill();
#pragma unroll 1
      for (int tries = 0; tries < POLL_TRIES; tries++) {
        float d0[4], d1[4], d2[4], d3[4];
        mbar_spin(B_H1, h1ph);
        h1ph ^= 1;
        PROF(1, 10);
        const uint32_t t0 = lds32(chk), t1 = lds32(chk + 1024);
        wg_fence();
        const uint64_t ones = (uint64_t)(fk::ONES >> 4);
        wgmma_ss_n8_ta(d0, make_desc(fk::VX, 8192, 2048), ones, 0);
        wgmma_ss_n8_ta(d1, make_desc(fk::VX + 1024, 8192, 2048), ones, 0);
        wgmma_ss_n8_ta(d2, make_desc(fk::VX + 4096, 8192, 2048), ones, 0);
        wgmma_ss_n8_ta(d3, make_desc(fk::VX + 5120, 8192, 2048), ones, 0);
        wg_commit();
        uint32_t tt;
        asm volatile("lop3.b32 %0, %1, %2, %3, 0x42;" : "=r"(tt) : "r"(t0), "r"(t1), "r"(tmask) : "memory");
        uint32_t ok;
        named_bar_and(NB_W1, 128, tt & 1, ok);
        if (!ok) { if (elect_one()) { mbar_expect_tx(B_H1, 2048); bulk_g2s(VX + warp * 2048, src, 2048, B_H1); } }
        wg_wait<0>();
        if (ok) {
          st_pub32(dst + (s & 1) * 32768, (lq & 1) ? pack_bf16(d1[0] + d3[0], d1[2] + d3[2]) : pack_bf16(d0[0] + d2[0], d0[2] + d2[2]));
          PROF(1, 12);
          st_pub32(dst + ((s & 1) ^ 1) * 32768, EMPTY);
          break;
        }
        RETRY(0);
      }
      named_bar_sync(NB_W1, 128);
      if ((tid & 255) == 192) mbar_arrive_remote(peer1 + B_PF);
      __syncwarp();
      if (!REFILL_EARLY) refill();
      PROF(1, 11);
    }
    if (!ISV || s + 1 < cfg::NSEG) {
      const uint32_t ph = (s + 1) & 1;
      float x0[16], x1[16];
      uint64_t db = P.dxn + 10 * 256;
      named_bar_sync(NB_ST, 256);
      wg_fence();
#pragma unroll
      for (int c = 0; c < 6; c++) {
        if (c == 2) { PROF(1, 0); mbar_spin(B_XN + 8, ph); PROF(1, 15); wg_fence(); }
        if (ISV && c == CF_AT) {
          if (warp == 0) {
            if (elect_one()) tma_store_wait_read();
            __syncwarp();
            named_bar_arrive(NB_CF, 160);
          }
          wg_fence();
        }
#pragma unroll
        for (int u = 0; u < 4; u++) {
          wgmma_rs_n32(x0, wr[c][0][u], db, (c | u) != 0);
          wgmma_rs_n32(x1, wr[c][1][u], db, (c | u) != 0);
          if (u < 3) DESC_ADD(db, 2); else if (c == 1) DESC_ADD(db, 250 - 12 * 256); else DESC_ADD(db, 250);
        }
      }
      wg_commit();
      OPQ;
      const uint32_t tb = ISV ? (ph ? VX2 : VX) : QK, tka = tok_addr<ISV>(tb, tid);
      uint32_t p0[2][4], p1[2][4];
      named_bar_sync(NB_DU, 256);
      ldsm4(p1[0], tka + tok_off<ISV>(1, 0)); ldsm4(p1[1], tka + tok_off<ISV>(1, 1));
      ldsm4(p0[0], tka + tok_off<ISV>(0, 0)); ldsm4(p0[1], tka + tok_off<ISV>(0, 1));
      if (ISV && s >= 0) mbar_spin(B_PF, s & 1);
      wg_wait<0>();
      PROF(1, 13);
      tok_store<ISV, 1, true>(x1, tka, p1);
      tok_store<ISV, 0, true>(x0, tka, p0);
      if (ISV && s + 2 < cfg::NSEG) {
        fence_proxy_async_smem();
        __syncwarp();
        if (elect_one()) {
          bulk_s2s(peer0 + VX + warp * 2048, tb + warp * 2048, 2048, peer0 + B_VX);
          bulk_s2s(peer1 + VX + warp * 2048, tb + warp * 2048, 2048, peer1 + B_VX);
        }
      }
      wsa = WS + ((mi >> 1) * 8 + mr) * 128 + (((2 * w + (mi & 1)) ^ mr) << 4);
      mba = MEMB + lane * 16;
      PIN(wsa); PIN(mba);
      proj_mem_prefetch<ISV, 1, 0, NTA1>(ta, wsa);
      PROF(1, 14);
      named_bar_sync(NB_M1, 256);
      s++;
      PROF(1, 1);
      float a0[4], a1[4];
      proj_mem<ISV, 1>(wr, ta, wsa, mba, a0, a1);
      PROF(1, 2);
      proj_finish<ISV, 1>(a0, a1, peer0, peer1, self, tid, warp, vmo);
      PROF(1, 3);
    } else {
      OPQ;
      mbar_spin(B_VM, s & 1);
      lds64(vmo, VM + t7 * 8); lds64(vmo + 2, VM + 1024 + t7 * 8);
      s++;
    }
    tid ^= 0x5500;
    const bool last = s + 1 >= cfg::NSEG;
    constexpr int PFW = ISV ? PF1V : PF1;
    uint32_t wf[PFW][4], woa;
    if (ISV) {
      OPQ;
      woa = WO + ((mi >> 1) * 8 + mr) * 128 + (((2 * w + (mi & 1)) ^ mr) << 4);
      if (s >= 1) {
        const uint32_t sa = QK + ((w * (w + 3)) >> 1) * 256 + lane * 8;
        mbar_spin(B_ST, (s - 1) & 1);
        float sc[10];
        {
          const float NEG = -1000000000.0f / 0.08838834764831845f;
          float2 x[5], y[5];
#pragma unroll
          for (int b = 0; b < 5; b++) {
            x[b] = b < 2 ? lds64f(sa + b * 256) : lds64f_if(sa + b * 256, b <= w + 1, NEG);
            y[b] = b < 2 ? lds64f(sa + 3584 + b * 256) : lds64f_if(sa + 3584 + b * 256, b <= w + 1, 0.f);
          }
#pragma unroll
          for (int b = 0; b < 5; b++) { sc[2 * b] = x[b].x + y[b].x; sc[2 * b + 1] = x[b].y + y[b].y; }
        }
        float m = fmaxf(fmaxf(fmaxf(sc[0], sc[1]), fmaxf(sc[2], sc[3])), fmaxf(fmaxf(sc[4], sc[5]), fmaxf(sc[6], sc[7])));
        m = fmaxf(m, fmaxf(sc[8], sc[9]));
        m = fmaxf(m, __shfl_xor_sync(0xffffffffu, m, 1));
        m = fmaxf(m, __shfl_xor_sync(0xffffffffu, m, 2));
        const float cs = 0.08838834764831845f * 1.4426950408889634f;
#pragma unroll
        for (int i = 0; i < 10; i++) sc[i] = ex2_approx((sc[i] - m) * cs);
        float sum = ((sc[0] + sc[1]) + (sc[2] + sc[3])) + ((sc[4] + sc[5]) + (sc[6] + sc[7])) + (sc[8] + sc[9]);
        sum += __shfl_xor_sync(0xffffffffu, sum, 1);
        sum += __shfl_xor_sync(0xffffffffu, sum, 2);
        const float inv = rcp_approx(sum);
        const uint32_t pa = PT + (w * 8 + mr) * 128, pm = pack_bf16(sc[0] * inv, sc[1] * inv);
        stsm4(pa + ((mi ^ mr) << 4), pack_bf16(sc[2] * inv, sc[3] * inv), pack_bf16(sc[4] * inv, sc[5] * inv),
              pack_bf16(sc[6] * inv, sc[7] * inv), pack_bf16(sc[8] * inv, sc[9] * inv));
        asm volatile("stmatrix.sync.aligned.m8n8.x2.shared.b16 [%0], {%1,%1};" ::"r"(pa + ((((mi & 1) ? 7 : 4) ^ mr) << 4)), "r"(pm) : "memory");
      }
      if (warp == 3 && !last) {
        mbar_spin(B_VM, s & 1);
        if (elect_one()) load_xn(P, s + 1, self);
      }
      PROF(1, 5);
    } else {
      if (warp == 0) {
        OPQ;
        uint32_t kf[4][4], qf[4][4];
        float c0[4], c1[4], d0[4], d1[4];
        const uint32_t ka = PT + (mi >> 1) * 1024 + (mi & 1) * 128 + mr * 16;
#pragma unroll
        for (int k = 0; k < 4; k++) { ldsm4t(qf[k], PT + 2048 + k * 512 + lane * 16); ldsm4t(kf[k], ka + k * 256); }
        mma16816z(c0, qf[0], kf[0][0], kf[0][1]); mma16816z(c1, qf[0], kf[0][2], kf[0][3]);
        mma16816z(d0, qf[1], kf[1][0], kf[1][1]); mma16816z(d1, qf[1], kf[1][2], kf[1][3]);
        mma16816(c0, qf[2], kf[2][0], kf[2][1]); mma16816(c1, qf[2], kf[2][2], kf[2][3]);
        mma16816(d0, qf[3], kf[3][0], kf[3][1]); mma16816(d1, qf[3], kf[3][2], kf[3][3]);
        const float s0 = ((c0[0] + c0[2]) + (c1[0] + c1[2])) + ((d0[0] + d0[2]) + (d1[0] + d1[2]));
        const float s1 = ((c0[1] + c0[3]) + (c1[1] + c1[3])) + ((d0[1] + d0[3]) + (d1[1] + d1[3]));
        if (!last) send_scores(s0, s1, SP + rank * SP_SRC + (128 + lane) * SPW, peer0, peer1, B_SM, lane);
        PROF(1, 5);
      } else {
        const uint32_t t_c = clk32() + lds32(B_XN) * 0;
        if (warp == 3 && !last) { if (elect_one()) load_xn(P, s + 1, self); }
        spin_until(t_c + D_ST);
      }
      OPQ;
      woa = WO + ((mi >> 1) * 8 + mr) * 128 + (((2 * w + (mi & 1)) ^ mr) << 4);
    }
    if (!last) {
      OPQ;
      uint32_t oba = OB + lane * 16;
      if (s == 0) mbar_spin(B_WO, 0);
      if (!ISV) wo_prefetch<WMODE, 0, PF1Q>(wf, woa, 0, true);
      if (ISV ? GATE_MX : GATE_Q) named_bar_sync(NB_MX, 256);
      wo_prefetch<WMODE, ISV ? 0 : PF1Q, PFW>(wf, woa, 0, true);
      char* h1p = P.xch + (tile0 + w) * 32768 + (h >> 3) * 8192 + (h & 7) * 128 + (((2 * lq + (lg & 1)) ^ (h & 7)) << 4) + (lg >> 1) * 4;
      fence_proxy_async_smem();
      PROF(1, 7);
      named_bar_sync(NB_O, 256);
      PROF(1, 8);
      wo_phase<WMODE>(wf, woa, 0, true, oba, h1p, tid >> 8, ((s >> 1) & 1) ^ 1);
      PROF(1, 9);
      named_bar_sync(NB_HD, 256);
    } else {
      fence_proxy_async_smem();
      named_bar_sync(NB_W1, 128);
    }
  }
  if (ISV && warp == 0) { if (elect_one()) o_done(15); }
}

template <bool ISV, int WG>
__device__ __forceinline__ void f_main(const FParams& P, const int h, const int rank, const uint32_t hw) {
  using namespace fk;
  const uint32_t self = mapa(0, (hw >> (2 * rank)) & 3);
  SMAP;
  const int tid = __shfl_sync(0xffffffffu, threadIdx.x, threadIdx.x & 31);
  const int tile0 = rank * 22, ntile = ISV ? 20 : 22;
  const CUtensorMap* m0 = ISV ? &P.wv : &P.wq;
  const CUtensorMap* m1 = ISV ? &P.wv : &P.wk;
  const int col0 = h * 128 + (ISV ? 0 : 64 * rank), col1 = h * 128 + (ISV ? 64 : 64 * rank);
  WRegs wr;
  uint32_t sel = 0;
  {
    OPQ;
    const uint32_t a = SM0 + WG * 16384 + ((mi >> 1) * 8 + mr) * 128 + (((2 * w + (mi & 1)) ^ mr) << 4);
    uint2 mi0 = make_uint2(0, 0);
    if (!ISV && WG == 1) mi0 = *reinterpret_cast<const uint2*>(P.mem0 + ((lane >> 1) & 7) * cfg::D + (2 * h + rank) * 16 + (lane >> 4) * 8 + (lane & 1) * 4);
#pragma unroll
    for (int i = 0; i < 6; i++) {
      if (i == MASK_AT && WG == 1 && w == 1) {
        uint4 v;
#pragma unroll 1
        for (int tries = 0; tries < POLL_TRIES; tries++) {
          asm volatile("ld.acquire.gpu.global.v4.u32 {%0,%1,%2,%3}, [%4];" : "=r"(v.x), "=r"(v.y), "=r"(v.z), "=r"(v.w)
                       : "l"(&g_mask[4 * min(lane, 23)]) : "memory");
          if (__all_sync(0xffffffffu, v.x & v.y & v.z & v.w & 0x100)) break;
          __nanosleep(100);
        }
        sts128(OB + lane * 16, v.x, v.y, v.z, v.w);
      }
      mbar_wait(B_PB + 8 * i, 0);
      PRO(8 + i);
#pragma unroll
      for (int T = 0; T < 2; T++)
#pragma unroll
        for (int u = 0; u < 4; u++) ldsm4t(wr[i][T][u], a + i * 32768 + T * 8192 + u * 2048);
      named_bar_sync(NB_C, 256);
      if (WG == 1 && w == (i & 3)) {
        if (elect_one()) {
          if (i <= 2 && i + PRE_G < 6) {
#pragma unroll 1
            for (int n = 2 * (i + PRE_G); n < (i == 2 ? 12 : 2 * (i + PRE_G) + 2); n++) {
              const int ii = n >> 1, row = Chunks<ISV>::rf(n & 1, ii) * 64;
              if (!(n & 1)) mbar_expect_tx(B_PB + 8 * ii, 32768);
              tma_load_2d(SM0 + n * 16384, m0, col0, row, B_PB + 8 * ii);
              tma_load_2d(SM0 + n * 16384 + 8192, m1, col1, row, B_PB + 8 * ii);
            }
          }
          if (i == 3 || i == 4) {
            const int p0 = i == 3 ? 0 : 5, p1 = i == 3 ? 5 : 8;
            mbar_expect_tx(B_W, (p1 - p0) * 8192);
#pragma unroll 1
            for (int p = p0; p < p1; p++) tma_load_2d(WS + p * 8192, (p & 1) ? m1 : m0, (p & 1) ? col1 : col0, Chunks<ISV>::sm(p >> 1) * 64, B_W);
          }
          if (i == 5) {
            asm volatile("fence.proxy.async.global;" ::: "memory");
            load_xn(P, 0, self);
          }
          if (i == WO_AT) {
            mbar_expect_tx(B_WO, ntile * 4096);
#pragma unroll 1
            for (int t = 0; t < 5; t++) tma_load_2d(WO + t * 16384, &P.wo, tile0 * 16 + t * 64, h * 128, B_WO);
            if (!ISV) {
              tma_load_2d(WO + 81920, &P.wo16, tile0 * 16 + 320, h * 128, B_WO);
              tma_load_2d(WO + 86016, &P.wo16, tile0 * 16 + 336, h * 128, B_WO);
            }
          }
        }
      }
    }
    PROF2(1);
    if (!ISV && WG == 1 && w < 2) st_pub64(P.xch + H1_BYTES + 32768 + (h >> 3) * 8192 + w * 4096 + ((2 * h + rank) & 15) * 256 + lane * 8, mi0.x, mi0.y);
    if (blockIdx.x == 2 && tid == 160) { __threadfence(); st_pub128(g_lnok, 0x100); }
#pragma unroll
    for (int i = 0; i < 3; i++) {
      const int t = min(tile0 + 8 * i + w + (WG ? 0 : 4), 63);
      sel |= ((lds32(OB + ((t >> 1) * 3 + (t & 1)) * 4) >> (h >> 3)) & 1) << (2 * i + 1);
    }
    const uint32_t own = lds32(OB + (3 * h + rank) * 4) >> w, m2 = lds32(OB + (3 * h + 2) * 4) >> w;
    sel |= (own & 1) << 7 | (m2 & 1) << 8 | (m2 & 16) << 5;
    sel |= (((((lg ^ h) & 1) << 2) | (lg >> 1)) == (h & 1) + 2 * (h >> 3)) << 10;
  }
  asm volatile("barrier.cluster.wait.aligned;" ::: "memory");
  PRO(14);
  mbar_wait(B_W, 0);
  mbar_wait(B_XN, 0);
  PRO(15);
  PROF2(4);
  GTSYNC(0);
  PROF2(2);
  KT_END(8);
  if (WG == 0) f_wg0<ISV>(P, wr, h, rank, hw, tid | sel << 8); else f_wg1<ISV>(P, wr, h, rank, hw, tid | sel << 8);
}

__device__ __forceinline__ void f_tail(const FParams& P, const int h, const uint32_t rank, const bool isv) {
  using namespace fk;
  const uint32_t self = mapa(0, rank), base = self + SM0;
  const uint32_t FULL = self + SP, EMPT = FULL + 32, NOG = FULL + 64, RES = FULL + 72;
  const int tid = threadIdx.x, lane = tid & 31, wv = __shfl_sync(0xffffffffu, tid >> 5, 0), wg = wv >> 2;
  const int kq = h & 7, nt = h >> 3, mb = TAIL_MB0 + rank;
  auto a_off = [](uint32_t st) { return (0x98685800u >> (8 * st) & 255) * 1024; };
  auto b_off = [](uint32_t st) { return (0xA8783010u >> (8 * st) & 255) * 1024; };
  static_assert(VX2 - SM0 == 80 * 1024 && VX - SM0 == 200 * 1024, "stage layout");
  auto load_b = [&](int kb) {
    const uint32_t sb = base + b_off(kb & 3), full = FULL + 8 * (kb & 3);
    mbar_expect_tx(full, 49152);
    tma_load_2d_mc(sb + rank * 8192, &P.tb, nt * 256 + ((rank + (kq >> 1)) & 3) * 64, (kq * 8 + kb) * 64, full, 7);
    if (kb % 3 == rank) tma_load_2d_mc(sb + 3 * 8192, &P.tb, nt * 256 + ((3 + (kq >> 1)) & 3) * 64, (kq * 8 + kb) * 64, full, 7);
  };
  auto load_a = [&](int kb) { tma_load_2d(base + a_off(kb & 3), &P.ta, (kq * 8 + kb) * 64, mb * 128, FULL + 8 * (kb & 3)); };
  TL(0);
  TL2(128, 10); TL2(160, 11);
  if (wv == 0) {
    if (elect_one()) {
      prefetch_tmap(&P.tb); prefetch_tmap(&P.ta);
      if (isv) mbar_spin(self + B_VM, (cfg::NSEG - 1) & 1);
      for (int i = 0; i < 4; i++) { mbar_init(FULL + 8 * i, 1); mbar_init(EMPT + 8 * i, 24); }
      mbar_init(RES, 1);
      fence_barrier_init();
      mbar_arrive_cluster(self + B_W, rank == 0 ? 1 : 0);
      mbar_arrive_cluster(self + B_W, rank == 2 ? 1 : 2);
      mbar_spin(self + B_W, 1);
#pragma unroll 1
      for (int kb = 0; kb < 4; kb++) load_b(kb);
      TL2(0, 12);
      wait_count(&g_oflag[mb], 32);
      asm volatile("fence.proxy.async.global;" ::: "memory");
      TL2(0, 13);
#pragma unroll 1
      for (int kb = 0; kb < 4; kb++) load_a(kb);
      TL2(0, 14);
    }
  } else if (wv == 1) {
    if (lane == 0) {
      prefetch_tmap(&P.tx); prefetch_tmap(&P.tg);
      const bool ng = ld_strong4(&g_next) == 0;
      sts32(NOG, ng);
      if (ng) g_tfix[blockIdx.x] = 1; else wait_count(&g_cnt[3][mb], GATE_CNT);
    }
  }
  float acc[128];
  __syncthreads();
  KT_START(7);
  const bool nog = lds32(NOG);
  if (nog) TL(15); else TL(15);
  if (wv == 1) {
    if (elect_one()) {
      asm volatile("fence.proxy.async.global;" ::: "memory");
      mbar_expect_tx(RES, 16384);
      tma_load_2d(self + VX, &P.tx, nt * 256 + kq * 32, mb * 128, RES);
      tma_load_2d(self + QK, &P.tg, nt * 256 + kq * 32, mb * 128, RES);
    }
  }
#pragma unroll 1
  for (int kb = 0; kb < 8; kb++) {
    const uint32_t st = kb & 3, sa = base + a_off(st) + wg * 8192, sb = base + b_off(st);
    mbar_spin(FULL + 8 * st, kb >> 2);
    if (kb == 0) TL(2);
    if (kb == 4) TL(3);
    wg_fence();
#pragma unroll
    for (int k = 0; k < 4; k++) {
      wgmma_ss_n256_tb(acc, make_desc(sa + k * 32, 16, 1024), make_desc(sb + k * 2048, 8192, 1024), (kb | k) != 0);
      if (k == 0) {
        wg_commit();
        wg_wait<1>();
        if (kb > 0 && kb <= 4 && lane < 3) mbar_arrive_cluster(EMPT + 8 * (kb - 1), lane);
        wg_fence();
      }
    }
    wg_commit();
    if (kb >= 2 && kb < 6 && wv == ((kb & 1) << 2)) {
      if (elect_one()) {
        mbar_spin(EMPT + 8 * (kb - 2), 0);
        load_b(kb + 2);
        load_a(kb + 2);
      }
      __syncwarp();
    }
  }
  wg_wait<0>();
  TL(5);
#pragma unroll
  for (int j = 0; j < 8; j++) {
    uint4* dst = &g_tpart[((h & ~7) + ((j + (kq & 6)) & 7)) * 3 + rank][kq][0][tid];
    if (j >= 2 || j != (kq & 1)) {
#pragma unroll
      for (int i = 0; i < 2; i++) {
        const float* a = &acc[16 * j + 8 * i];
        dst[i * 256] = make_uint4(pack_bf16(a[0], a[1]), pack_bf16(a[2], a[3]), pack_bf16(a[4], a[5]), pack_bf16(a[6], a[7]));
      }
    }
  }
#pragma unroll
  for (int i = 0; i < 16; i++) acc[i] = (kq & 1) ? acc[16 + i] : acc[i];
  TL(6);
  __syncwarp();
  if (lane < 8) asm volatile("red.release.gpu.global.add.u32 [%0], 1;" ::"l"(&g_tcnt[((h & ~7) + lane) * 3 + rank][wv]) : "memory");
  TL(7);
  const size_t off = (size_t)(mb * 128 + wv * 16 + (lane >> 2)) * cfg::D + nt * 256 + kq * 32 + (lane & 3) * 2;
  uint32_t x[8], g[8];
  const uint32_t xa = self + VX + (wv * 16 + (lane & 15)) * 64 + (((lane >> 4) ^ ((lane >> 1) & 3)) << 4);
  mbar_spin(RES, 0);
  ldsm4(x, xa); ldsm4(x + 4, xa ^ 32);
  ldsm4(g, xa + (QK - VX)); ldsm4(g + 4, (xa ^ 32) + (QK - VX));
#pragma unroll 1
  for (int tries = 0; tries < POLL_TRIES; tries++) {
    uint32_t v;
    asm volatile("ld.acquire.gpu.global.u32 %0, [%1];" : "=r"(v) : "l"(&g_tcnt[blockIdx.x][wv]) : "memory");
    if (v >= 8) break;
  }
  uint4 pt[14];
#pragma unroll
  for (int i = 0; i < 14; i++) pt[i] = __ldcg(&g_tpart[blockIdx.x][(kq + 1 + (i >> 1)) & 7][i & 1][tid]);
  TL(8);
#pragma unroll 1
  for (int j = 0; j < 2; j++) {
#pragma unroll
    for (int i = 0; i < 28; i++) {
      const uint32_t v = (&pt[2 * (i >> 2)].x)[i & 3];
      acc[2 * (i & 3)] += bf_lo(v); acc[2 * (i & 3) + 1] += bf_hi(v);
    }
#pragma unroll
    for (int i = 0; i < 4; i++) {
      const uint32_t sv = pack_bf16(acc[2 * i], acc[2 * i + 1]);
      *reinterpret_cast<uint32_t*>(P.out + off + (i & 1) * 8 * cfg::D + (i >> 1) * 8 + j * 16) = nog ? sv : add_bf16x2(x[i], mul_bf16x2(sv, g[i]));
      x[i] = x[i + 4]; g[i] = g[i + 4];
      acc[2 * i] = acc[8 + 2 * i]; acc[2 * i + 1] = acc[9 + 2 * i];
    }
#pragma unroll
    for (int i = 0; i < 7; i++) pt[2 * i] = pt[2 * i + 1];
  }
  TL(9);
  KT_END(7);
}

__global__ void __launch_bounds__(256, 1) f_kernel(const __grid_constant__ FParams P) {
  using namespace fk;
  extern __shared__ __align__(1024) uint8_t smem_f[];
  uint32_t crank, rank, hw;
  asm("mov.u32 %0, %%cluster_ctarank;" : "=r"(crank));
  const int h = blockIdx.x / 3;
  if (smem_u32(smem_f) != mapa(0, crank) + SM0) return;
  PROF2(0);
  KT_START(1);
  KT_START(0);
  {
    const uint32_t self = mapa(0, crank);
    SMAP;
    const int tid = threadIdx.x, lane = tid & 31, wv = __shfl_sync(0xffffffffu, tid >> 5, 0);
    PRO(0);
    if (wv == 0) {
      uint32_t sm;
      asm("mov.u32 %0, %%smid;" : "=r"(sm));
      sts32(PROBE + 96, sm >> 1);
      asm volatile("fence.release.sync_restrict::shared::cta.cluster;" ::: "memory");
    }
    asm volatile("barrier.cluster.arrive.relaxed.aligned;" ::: "memory");
    if (wv == 7) {
      if (blockIdx.x == 2) {
#pragma unroll
        for (int i = 0; i < 4; i++) { (&g_cnt[0][0])[32 * i + lane] = 0; if (i < 3) g_tfix[32 * i + lane] = 0; }
        if (lane < 16) g_oflag[lane] = 0;
        if (lane == 0) { g_next = 0; g_lnok[0] = 0; }
        __threadfence();
        __syncwarp();
      }
      pdl_launch_dependents();
    }
    const int row0 = blockIdx.x * 8 + wv;
    const bool third = row0 + 1536 < cfg::S;
    uint32_t cur[1][16] = {}, raw[3][16];
    load_row16(raw[0], P.x + (size_t)row0 * cfg::D, lane);
    load_row16(raw[1], P.x + (size_t)(row0 + 768) * cfg::D, lane);
    load_row16(raw[2], P.x + (size_t)(row0 + (third ? 1536 : 0)) * cfg::D, lane);
    {
      uint32_t tpc;
      asm volatile("barrier.cluster.wait.aligned;" ::: "memory");
      asm volatile("ld.shared::cluster.u32 %0, [%1];" : "=r"(tpc) : "r"(mapa(PROBE + 96, lane % 3)) : "memory");
      const uint32_t t0 = __shfl_sync(0xffffffffu, tpc, 0), t1 = __shfl_sync(0xffffffffu, tpc, 1), t2 = __shfl_sync(0xffffffffu, tpc, 2);
      hw = t1 == t2 ? 0x09 : t0 == t2 ? 0x18 : 0x24;
      rank = (hw & 3) == crank ? 0 : ((hw >> 2) & 3) == crank ? 1 : 2;
    }
    const bool isv = rank == 2;
    const CUtensorMap* m0 = isv ? &P.wv : &P.wq;
    const CUtensorMap* m1 = isv ? &P.wv : &P.wk;
    const int col0 = h * 128 + (isv ? 0 : 64 * rank), col1 = h * 128 + (isv ? 64 : 64 * rank);
    auto req_weights = [&](int n0, int n1) {
#pragma unroll 1
        for (int n = n0; n < n1; n++) {
          const int i = n >> 1, g = n & 1, row = (isv ? Chunks<true>::rf(g, i) : Chunks<false>::rf(g, i)) * 64;
          if (!g) mbar_expect_tx(B_PB + 8 * i, 32768);
          tma_load_2d(SM0 + n * 16384, m0, col0, row, B_PB + 8 * i);
          tma_load_2d(SM0 + n * 16384 + 8192, m1, col1, row, B_PB + 8 * i);
        }
    };
    if (wv == 0) {
      if (elect_one()) {
        for (int i = 0; i < 2; i++) mbar_init(B_XN + 8 * i, 1);
        mbar_init(B_H1, 4);
        mbar_init(B_SM, isv ? 1 : 6);
        mbar_init(B_VM, isv ? 8 : 1);
        mbar_init(B_VX, 1);
        mbar_init(B_ST, 1);
        mbar_init(B_PF, 2);
        for (int i = 0; i < 6; i++) mbar_init(B_PB + 8 * i, 1);
        mbar_init(B_W, 2);
        mbar_init(B_WO, 1);
        fence_barrier_init();
        if (PRE_A) req_weights(0, 2 * PRE_A);
        mbar_expect_tx(B_SM, isv ? 2 * SP_SRC : SP_SRC);
        if (isv) mbar_expect_tx(B_ST, 7168);
        else { mbar_expect_tx(B_VM, 2048); mbar_expect_tx(B_VX, 8192); }
      }
    }
    const int j = 2 * h + rank;
    const bool dry = LN_DRY && !isv && wv == 6;
    if (dry) sts64(PROBE + wv * 8, 0x7FFFFFFF, 0x7FFFFFFF);
    if (lane == 0 && !dry) {
      const uint2 b = probe_pair(P.xch + (isv ? H1_BYTES + wv * 8192 + h * 128 : j * 32768 + (wv & 3) * 8192 + (wv >> 2) * 128),
                                 isv ? EMPTY : 0, PROBE + 64, P.nprobe);
      sts64(PROBE + wv * 8, b.x, b.y);
    }
    uint32_t mask = 0;
#pragma unroll 1
    for (int it = -1; it < (third ? 3 : 2); it++) {
      if (it >= 0 || dry) {
        ln_regs<1>(cur);
        if (it >= 0) store_row16(cur[0], P.xn_ptr + (size_t)(row0 + it * 768) * cfg::D, lane);
      }
      if (it == 0) PRO(4);
      if (it < 0) {
    PROF2(3);
    PRO(1);
    __syncwarp();
    if (wv == 0) {
      asm volatile("{\n.reg .pred p;\nsetp.eq.u32 p, %0, %1;\n@p st.shared.u32 [%2], %0;\n}" ::"r"(raw[2][15]), "r"(raw[0][0] ^ raw[1][15]), "r"(PROBE + 64) : "memory");
      if (elect_one()) {
        req_weights(2 * PRE_A, 2 * PRE_G);
      }
    }
    __syncthreads();
    PRO(2);
    asm volatile("barrier.cluster.arrive.relaxed.aligned;" ::: "memory");
    PRO(3);
    if (tid < 8) g_tcnt[blockIdx.x][tid] = 0;
    if (wv == 2) sts32(self + ONES + lane * 4, 0x3F803F80u);
    uint32_t pb[2], pc[2];
    lds64(pb, PROBE + (lane & 7) * 8);
    lds64(pc, PROBE + ((lane & 7) ^ 4) * 8);
    mask = __ballot_sync(0xffffffffu, isv ? pb[1] < pb[0] : min(pb[1], pc[1]) < min(pb[0], pc[0])) & (isv ? 255 : 15);
    if (!isv) {
#pragma unroll
      for (int i = 0; i < 4; i++) st_pub128(P.xch + j * 32768 + i * 8192 + ((mask >> i) & 1) * 4096 + tid * 16, 0);
      if (wv < 4) st_pub64(P.xch + H1_BYTES + (wv >> 1) * 32768 + (j >> 4) * 8192 + (wv & 1) * 4096 + (j & 15) * 256 + lane * 8, EMPTY, EMPTY);
    }
      }
#pragma unroll
      for (int i = 0; i < 16; i++) { cur[0][i] = raw[0][i]; raw[0][i] = raw[1][i]; raw[1][i] = raw[2][i]; }
    }
    PRO(5);
    __syncthreads();
    PRO(6);
    if (tid == 64) {
      __threadfence();
      PRO(7);
      st_pub32(&g_mask[3 * h + rank], 0x100 | mask);
    }
    KT_END(0);
    __syncwarp();
  }
  const int wg = __shfl_sync(0xffffffffu, threadIdx.x >> 7, 0);
  if (rank == 2) { if (wg == 0) f_main<true, 0>(P, h, 2, hw); else f_main<true, 1>(P, h, 2, hw); }
  else { if (wg == 0) f_main<false, 0>(P, h, rank, hw); else f_main<false, 1>(P, h, rank, hw); }
  PROF2(5);
  KT_END(1);
  __syncwarp();
  f_tail(P, h, crank, rank == 2);
}

#define G_AH 3
#define G_PF 3
#define G_LATE 0
namespace gk {
enum { T_B1 = 0, T_B2 = 1, T_B3 = 2, T_B4 = 3, T_O = 4, T_LN = 5, T_LN0 = 6, T_END = 7 };
constexpr int NST = 3, STAGE = 49152, MAXITEMS = 512, NEW = 3;
constexpr uint32_t OUTB = NST * STAGE, BARS = OUTB + 65536;
constexpr uint32_t B_FULL = BARS, B_EMPTY = BARS + 32, B_ITEM = BARS + 64, B_FILL = BARS + 128, B_FREE = BARS + 160, B_LN = BARS + 176, B_LNGO = BARS + 184, ITEMS = BARS + 192;
constexpr int SMEM = BARS + 256;
static_assert(GATE_CNT == 4 * NEW && T_B4 == 3, "gate counter");
}
struct GParams {
  CUtensorMap a[5], b[5];
  bf16* c[5];
  const bf16* r[5];
  bf16 *x1n, *xn2;
  const bf16* w1;
  int nitems, lnpos;
  uint16_t items[gk::MAXITEMS];
};
#define ILOG(i)
#define SLOG(i)

__device__ __forceinline__ float tanh_approx(float x) { float y; asm("tanh.approx.f32 %0, %1;" : "=f"(y) : "f"(x)); return y; }
__global__ void __launch_bounds__(384, 1) g_kernel(const __grid_constant__ GParams P) {
  using namespace gk;
  extern __shared__ __align__(1024) uint8_t smem_g[];
  const uint32_t base = smem_u32(smem_g);
  const int tid = threadIdx.x, warp = __shfl_sync(0xffffffffu, tid >> 5, 0), lane = tid & 31;
  KT_START(2);
  if (tid == 0) {
    for (int s = 0; s < NST; s++) { mbar_init(base + B_FULL + 8 * s, 1); mbar_init(base + B_EMPTY + 8 * s, 8); }
    for (int s = 0; s < 8; s++) mbar_init(base + B_ITEM + 8 * s, 1);
    for (int s = 0; s < 2; s++) { mbar_init(base + B_FILL + 8 * s, 4); mbar_init(base + B_FREE + 8 * s, NEW); }
    mbar_init(base + B_LN, 1);
    mbar_init(base + B_LNGO, 1);
    fence_barrier_init();
  }
  __syncthreads();
  auto release = [&](uint32_t st) { if (lane == 0) mbar_arrive(base + B_EMPTY + 8 * st); };
  auto get_item = [&](int q) {
    mbar_wait(base + B_ITEM + 8 * (q & 7), (q >> 3) & 1);
    return lds32(base + ITEMS + 4 * (q & 7));
  };

  if (warp == 8) {
    if (lane < 10) prefetch_tmap(&P.a[0] + lane);
    for (int r = blockIdx.x * 4 + lane; r < cfg::D / 8 && lane < 4; r += gridDim.x * 4) l2_prefetch(P.w1 + r * 8 * cfg::D, 16384);
    __syncwarp();
    auto fetch = [&](int q) {
      uint32_t v = 0;
      if (lane == 0) {
        const unsigned idx = atomicAdd(&g_next, 1), ln = idx - P.lnpos;
        v = (idx < (unsigned)P.nitems ? P.items[idx] : T_END) | (ln < 64 ? (ln + 1) << 16 : 0);
        sts32(base + ITEMS + 4 * (q & 7), v);
        mbar_arrive(base + B_ITEM + 8 * (q & 7));
        ILOG(1);
      }
      return __shfl_sync(0xffffffffu, v, 0);
    };
    auto open_deps = [&](uint32_t item) {
      const int type = item & 7, mb = (item >> 3) & 15;
      const unsigned* p = type == T_O ? &g_oflag[mb]
                        : &g_cnt[type == T_B1 ? T_LN0 : type == T_B2 ? T_B1 : type == T_B3 ? T_LN : T_B3][type == T_B2 ? min(max(mb + min(lane, 2) - 1, 0), 15) : mb];
      unsigned need = type == T_O ? 32 : type == T_B2 ? 4 * NEW : type == T_B4 ? 14 * NEW : 64;
      if (lane == 3) { p = &g_cnt[T_B2][(((item >> 16) - 1) >> 2) & 15]; need = item >> 16 ? 4 * NEW : 0; }
      unsigned v;
      asm volatile("ld.acquire.gpu.global.u32 %0, [%1];" : "=r"(v) : "l"(p) : "memory");
      return __ballot_sync(0xffffffffu, v < need) & 15;
    };
    uint32_t st = 0, ph = 1, next = fetch(0), open = 15;
    if (lane == 0) { __threadfence(); sts32(base + ITEMS + 32, ld_strong4(&g_oflag[14]) >= 32); }
    __syncwarp();
#pragma unroll 1
    for (int q = 0;; q++) {
      const uint32_t item = next;
      const int type = item & 7, mb = (item >> 3) & 15, nt = (item >> 7) & 15;
      if (type == T_END) break;
      const CUtensorMap *ma = &P.a[type], *mbm = &P.b[type];
      const int nkb = type == T_B4 ? cfg::F / 64 : type == T_O ? cfg::HD / 64 : cfg::D / 64;
#pragma unroll 1
      for (int kb = 0; kb < nkb; kb++) {
        mbar_wait(base + B_EMPTY + 8 * st, ph);
        const uint32_t sa = base + st * STAGE, full = base + B_FULL + 8 * st;
        if (elect_one()) {
          mbar_expect_tx(full, STAGE);
          tma_load_3d(sa + 16384, mbm, 0, kb * 64, nt * 4, full);
        }
        if (kb == 0) {
          bool go = (item >> 16) != 0;
#pragma unroll 1
          for (int tries = 0; tries < (1 << 18); tries++) {
            if (go && !(open & 8)) { go = false; if (lane == 0) mbar_arrive(base + B_LNGO); }
            if (!open) break;
            if (tries) __nanosleep(64);
            open = open_deps(item);
          }
          asm volatile("fence.proxy.async.global;" ::: "memory");
          if (lane == 0) ILOG(2);
        }
        int arow = mb * 128;
        if (type == T_B2) { const int qd = kb >> 2; arow += (qd == 0) ? -1 : (qd == 1) ? 1 : (qd == 2) ? -2 : 2; }
        if (elect_one()) {
          tma_load_2d(sa, ma, kb * 64, arow, full);
          if (type >= T_B4 && kb + G_PF < nkb)
            asm volatile("cp.async.bulk.prefetch.tensor.2d.L2.global [%0, {%1, %2}];" ::"l"(ma), "r"((kb + G_PF) * 64), "r"(arow) : "memory");
        }
        if (++st == NST) { st = 0; ph ^= 1; }
        if (kb == nkb - G_AH) next = fetch(q + 1);
        if (kb == nkb - G_AH + 1) open = open_deps(next);
      }
    }
  } else {
    const int wg = warp >> 2, ew = warp > 8 ? warp - 9 : warp + NEW;
    const uint32_t outa = base + OUTB + (warp * 16 + ((lane >> 3) & 1) * 8 + (lane & 7)) * 512 + (((lane >> 4) ^ (lane & 7)) << 4);
    uint32_t st = 0, ph = 0;
    float acc[128];
    auto kill_acc = [&]() {
#pragma unroll
      for (int i = 0; i < 128; i++) acc[i] = 0.f;
    };
    uint32_t next = T_LN0, lnph = 0;
#pragma unroll 1
    for (int q = -1;; q++) {
      const uint32_t item = next;
      const int type = item & 7, mb = (item >> 3) & 15, nt = (item >> 7) & 15;
      if (type == T_END) break;
      const bool first = q < 0;
      if (first || (warp < 8 && (item >> 16))) {
        const int ln = (item >> 16) - 1, lb = ln >> 2, pstr = first ? gridDim.x * 11 : 1;
#pragma unroll 1
        for (int p0 = first ? blockIdx.x * 11 + ew : lb * 64 + (ln & 3) * 16 + warp * 2; p0 < cfg::S / 2; p0 += first ? 3 * pstr : cfg::S) {
          const int np = first ? min(3, (cfg::S / 2 - 1 - p0) / pstr + 1) : 2;
          const bf16* src = (first ? P.r[T_O] : P.c[T_B2]) + (size_t)p0 * 2 * cfg::D;
          bf16* dst = (first ? P.xn2 : P.x1n) + (size_t)p0 * 2 * cfg::D;
          if (!first) { mbar_wait(base + B_LNGO, lnph); lnph ^= 1; }
          SLOG(0);
          uint32_t cur[2][16], n1[2][16], n2[2][16];
#pragma unroll
          for (int r = 0; r < 2; r++) {
            load_row16(cur[r], src + r * cfg::D, lane);
            load_row16(n1[r], src + (size_t)(min(1, np - 1) * pstr * 2 + r) * cfg::D, lane);
#pragma unroll
            for (int i = 0; i < 16; i++) n2[r][i] = 0;
            if (np > 2) load_row16(n2[r], src + (size_t)(pstr * 4 + r) * cfg::D, lane);
          }
#pragma unroll 1
          for (int it = first ? 0 : 1; it < 2 * np; it += first ? 1 : 2) {
            ln_regs<2>(cur);
            SLOG(1 + it);
            if (it & 1) {
#pragma unroll
              for (int r = 0; r < 2; r++) {
                store_row16(cur[r], dst + (size_t)((it >> 1) * pstr * 2 + r) * cfg::D, lane);
#pragma unroll
                for (int i = 0; i < 16; i++) { cur[r][i] = n1[r][i]; n1[r][i] = n2[r][i]; }
              }
            }
          }
          if (first) __syncwarp(); else named_bar_sync(3, 256);
          if (first ? lane < np : tid == 0)
            asm volatile("red.release.gpu.global.add.u32 [%0], %1;" ::"l"(&g_cnt[first ? T_LN0 : T_LN][(p0 + lane * pstr) >> 6]), "r"(first ? 1 : 16) : "memory");
          __syncwarp();
          SLOG(7);
        }
        if (tid == 0 && !first) ILOG(6);
        kill_acc();
        if (first) {
    if (warp == 9) {
#pragma unroll 1
      for (int tries = 0; tries < POLL_TRIES; tries++) {
        uint4 v;
        asm volatile("ld.acquire.gpu.global.v4.u32 {%0,%1,%2,%3}, [%4];" : "=r"(v.x), "=r"(v.y), "=r"(v.z), "=r"(v.w)
                     : "l"(lane < 24 ? &g_mask[4 * lane] : &g_lnok[0]) : "memory");
        const uint32_t ok = __ballot_sync(0xffffffffu, v.x & v.y & v.z & v.w & 0x100);
        if ((ok & 0xFFFFFF) == 0xFFFFFF || (ok >> 24)) break;
        __nanosleep(200);
      }
      if (lane == 0) mbar_arrive(base + B_LN);
    }
          next = get_item(0);
          continue;
        }
      }
      if (warp < 8) {
      const int nkb = type == T_B4 ? cfg::F / 64 : type == T_O ? cfg::HD / 64 : cfg::D / 64;
      uint32_t prev = 0;
      mbar_wait(base + B_FULL + 8 * st, ph);
#pragma unroll 1
      for (int kb = 0; kb < nkb; kb++) {
        mbar_spin(base + B_FULL + 8 * st, ph);
        if (kb == 0 && tid == 0) ILOG(3);
        const uint64_t da = make_desc(base + wg * 8192, 16, 1024) + st * (STAGE >> 4), db = make_desc(base + 16384, 8192, 1024) + st * (STAGE >> 4);
        wg_fence();
#pragma unroll
        for (int k = 0; k < 4; k++) {
          wgmma_ss_n256_tb(acc, da + k * 2, db + k * 128, (kb | k) != 0);
          if (k == 0) {
            wg_commit();
            wg_wait<1>();
            if (kb > 0) release(prev);
            wg_fence();
          }
        }
        wg_commit();
        prev = st;
        if (++st == NST) { st = 0; ph ^= 1; }
      }
      next = get_item(q + 1);
      if (q > 0) mbar_wait(base + B_FREE + 8 * wg, (q - 1) & 1);
      wg_wait<0>();
      if (tid == 0) ILOG(4);
      release(prev);
#pragma unroll
      for (int j = 0; j < 16; j++)
        stsm4((outa ^ ((j & 3) << 5)) + (j >> 2) * 128, pack_bf16(acc[8 * j], acc[8 * j + 1]), pack_bf16(acc[8 * j + 2], acc[8 * j + 3]),
              pack_bf16(acc[8 * j + 4], acc[8 * j + 5]), pack_bf16(acc[8 * j + 6], acc[8 * j + 7]));
      __syncwarp();
      if (lane == 0) mbar_arrive(base + B_FILL + 8 * wg);
      if (tid == 0) ILOG(5);
      if ((next & 7) != T_END) continue;
      }
      if (type == T_O) wait_count(&g_cnt[T_B4][mb], 4 * NEW);
      const int ldc = type == T_B3 ? cfg::F : cfg::D;
      bf16* cp = P.c[type] + (size_t)mb * 128 * ldc + nt * 256 + lane * 8;
      const size_t roff = (size_t)mb * 128 * cfg::D + nt * 256 + lane * 8;
      const bf16 *rp = P.r[type] + roff, *gp = P.c[T_B4] + roff;
      const bool gelu = type == T_B1 || type == T_B3;
      uint32_t yn[4][4];
      uint4 rn[4], gn[4];
#pragma unroll
      for (int i = 0; i < 4; i++) rn[i] = gn[i] = make_uint4(0, 0, 0, 0);
      auto fetch_res = [&](int grp) {
#pragma unroll
        for (int i = 0; i < 4; i++) {
          rn[i] = __ldcg(reinterpret_cast<const uint4*>(rp + (grp * 4 + i) * cfg::D));
          if (type == T_O) gn[i] = __ldcg(reinterpret_cast<const uint4*>(gp + (grp * 4 + i) * cfg::D));
        }
      };
      auto fetch_y = [&](int grp) {
        const uint32_t a = base + OUTB + grp * 2048 + ((lane ^ ((grp & 1) << 2)) << 4);
#pragma unroll
        for (int i = 0; i < 4; i++) lds128(yn[i], (a ^ (i << 4)) + i * 512);
      };
      auto store_y = [&](int grp, const uint32_t (&y)[4][4]) {
        char* p = reinterpret_cast<char*>(cp) + (uint32_t)(grp * 8 * ldc);
#pragma unroll
        for (int i = 0; i < 4; i++) *reinterpret_cast<uint4*>(p + (uint32_t)(i * 2 * ldc)) = make_uint4(y[i][0], y[i][1], y[i][2], y[i][3]);
      };
      if (type == T_B2) mbar_wait(base + B_LN, 0);
      if (type == T_B4) wait_count(&g_cnt[T_B2][mb], 4 * NEW);
      if (type >= T_B4 && warp > 8) for (int r = tid - 288; r < 128; r += 96) l2_prefetch(rp - lane * 8 + r * cfg::D, 512);
      if (!gelu) fetch_res(ew);
      mbar_wait(base + B_FILL, q & 1);
      fetch_y(ew);
      next = get_item(q + 1);
      mbar_wait(base + B_FILL + 8, q & 1);
      const int stride = (next & 7) == T_END ? NEW + 8 : NEW;
      if (gelu) {
#pragma unroll 1
        for (int grp = ew; grp < 32; grp += stride) {
          uint32_t y[4][4];
#pragma unroll
          for (int i = 0; i < 16; i++) y[i >> 2][i & 3] = mul_bf16x2(yn[i >> 2][i & 3], 0x3F003F00u);
          const int nx = grp + stride;
          if (nx >= 16 && grp < 16 && lane == 0 && warp > 8) mbar_arrive(base + B_FREE);
          if (!G_LATE) fetch_y(min(nx, 31));
#pragma unroll
          for (int i = 0; i < 16; i++) {
            uint32_t& v = y[i >> 2][i & 3];
            const float h0 = bf_lo(v), h1 = bf_hi(v);
            const float t0 = tanh_approx(h0 * fmaf(h0 * h0, 0.285419265090401f, 1.5957691216057308f));
            const float t1 = tanh_approx(h1 * fmaf(h1 * h1, 0.285419265090401f, 1.5957691216057308f));
            v = pack_bf16(fmaf(h0, t0, h0), fmaf(h1, t1, h1));
          }
          if (G_LATE) fetch_y(min(nx, 31));
          store_y(grp, y);
        }
      } else {
#pragma unroll 1
        for (int grp = ew; grp < 32; grp += stride) {
          uint32_t y[4][4];
          if (type == T_O) {
#pragma unroll
            for (int i = 0; i < 16; i++) yn[i >> 2][i & 3] = mul_bf16x2(yn[i >> 2][i & 3], (&gn[i >> 2].x)[i & 3]);
          }
#pragma unroll
          for (int i = 0; i < 16; i++) y[i >> 2][i & 3] = add_bf16x2(yn[i >> 2][i & 3], (&rn[i >> 2].x)[i & 3]);
          const int nx = grp + stride;
          if (nx >= 16 && grp < 16 && lane == 0 && warp > 8) mbar_arrive(base + B_FREE);
          fetch_res(min(nx, 31));
          fetch_y(min(nx, 31));
          if (type == T_B4) {
#pragma unroll
            for (int i = 0; i < 16; i++) {
              uint32_t& v = y[i >> 2][i & 3];
              const float h0 = 0.5f * bf_lo(v), h1 = 0.5f * bf_hi(v);
              v = pack_bf16(fmaf(h0, tanh_approx(h0), h0), fmaf(h1, tanh_approx(h1), h1));
            }
          }
          store_y(grp, y);
        }
      }
      __syncwarp();
      if (lane == 0 && warp > 8) mbar_arrive(base + B_FREE + 8);
      if (stride != NEW) named_bar_sync(2, 352);
      if (type != T_O && lane == 0 && warp > 8) asm volatile("red.release.gpu.global.add.u32 [%0], 1;" ::"l"(&g_cnt[type][mb]) : "memory");
      __syncwarp();
      if (tid == 288) ILOG(7);
      kill_acc();
    }
    KT_END(2);
  }
  __syncwarp();
  if (warp >= 8) {
   named_bar_sync(1, 128);
   const bool late = lds32(base + ITEMS + 32);
   if (late) pdl_wait();
#pragma unroll 1
   for (int c = blockIdx.x; late && c < 96; c += gridDim.x) {
     if (__ldcg(&g_tfix[c]) == 0) continue;
     const int hh = c / 3, mb = TAIL_MB0 + c % 3;
     wait_count(&g_cnt[T_B4][mb], GATE_CNT);
#pragma unroll 1
     for (int i = tid - 256; i < 512; i += 128) {
       const size_t off = (size_t)(mb * 128 + (i >> 2)) * cfg::D + hh * 32 + (i & 3) * 8;
       const uint4 sv = __ldcg(reinterpret_cast<const uint4*>(P.c[T_O] + off)), gv = __ldcg(reinterpret_cast<const uint4*>(P.c[T_B4] + off)),
                   xv = __ldcg(reinterpret_cast<const uint4*>(P.r[T_O] + off));
       *reinterpret_cast<uint4*>(P.c[T_O] + off) = make_uint4(add_bf16x2(xv.x, mul_bf16x2(sv.x, gv.x)), add_bf16x2(xv.y, mul_bf16x2(sv.y, gv.y)),
                                                              add_bf16x2(xv.z, mul_bf16x2(sv.z, gv.z)), add_bf16x2(xv.w, mul_bf16x2(sv.w, gv.w)));
     }
   }
  }
}

__device__ bf16 g_xn[cfg::S * cfg::D];
__device__ bf16 g_xn2[cfg::S * cfg::D];
__device__ bf16 g_h[cfg::S * cfg::D];
__device__ bf16 g_x1[cfg::S * cfg::D];
__device__ bf16 g_x1n[cfg::S * cfg::D];
__device__ bf16 g_u[cfg::S * cfg::F];
__device__ bf16 g_g[cfg::S * cfg::D];
__device__ bf16 g_o[cfg::S * cfg::HD];

typedef CUresult (*PFN_encodeTiled)(CUtensorMap*, CUtensorMapDataType, cuuint32_t, void*, const cuuint64_t*,
                                    const cuuint64_t*, const cuuint32_t*, const cuuint32_t*, CUtensorMapInterleave,
                                    CUtensorMapSwizzle, CUtensorMapL2promotion, CUtensorMapFloatOOBfill);

static PFN_encodeTiled get_encoder() {
  static PFN_encodeTiled fn = nullptr;
  if (!fn) {
    void* p = nullptr;
    cudaDriverEntryPointQueryResult st;
    cudaGetDriverEntryPoint("cuTensorMapEncodeTiled", &p, cudaEnableDefault, &st);
    fn = (PFN_encodeTiled)p;
  }
  return fn;
}
static CUtensorMap make_map(const void* ptr, int rows, int cols, int box_rows, int box_cols, int swizzle_bytes) {
  CUtensorMap m;
  cuuint64_t dims[2] = {(cuuint64_t)cols, (cuuint64_t)rows};
  cuuint64_t strides[1] = {(cuuint64_t)cols * 2};
  cuuint32_t box[2] = {(cuuint32_t)box_cols, (cuuint32_t)box_rows};
  cuuint32_t estr[2] = {1, 1};
  CUtensorMapSwizzle sw = swizzle_bytes == 128 ? CU_TENSOR_MAP_SWIZZLE_128B
                        : swizzle_bytes == 64 ? CU_TENSOR_MAP_SWIZZLE_64B
                        : swizzle_bytes == 32 ? CU_TENSOR_MAP_SWIZZLE_32B : CU_TENSOR_MAP_SWIZZLE_NONE;
  get_encoder()(&m, CU_TENSOR_MAP_DATA_TYPE_BFLOAT16, 2, const_cast<void*>(ptr), dims, strides, box, estr,
                CU_TENSOR_MAP_INTERLEAVE_NONE, sw, CU_TENSOR_MAP_L2_PROMOTION_L2_128B, CU_TENSOR_MAP_FLOAT_OOB_FILL_NONE);
  return m;
}
static CUtensorMap make_map3(const void* ptr, int rows, int cols, int box_rows, int nblk) {
  CUtensorMap m;
  cuuint64_t dims[3] = {64, (cuuint64_t)rows, (cuuint64_t)(cols / 64)};
  cuuint64_t strides[2] = {(cuuint64_t)cols * 2, 128};
  cuuint32_t box[3] = {64, (cuuint32_t)box_rows, (cuuint32_t)nblk};
  cuuint32_t estr[3] = {1, 1, 1};
  get_encoder()(&m, CU_TENSOR_MAP_DATA_TYPE_BFLOAT16, 3, const_cast<void*>(ptr), dims, strides, box, estr,
                CU_TENSOR_MAP_INTERLEAVE_NONE, CU_TENSOR_MAP_SWIZZLE_128B, CU_TENSOR_MAP_L2_PROMOTION_L2_128B,
                CU_TENSOR_MAP_FLOAT_OOB_FILL_NONE);
  return m;
}
template <class T> static T* sym(T& s) { void* p = nullptr; cudaGetSymbolAddress(&p, s); return (T*)p; }
#define SYM(name) ((bf16*)[] { void* p = nullptr; cudaGetSymbolAddress(&p, name); return p; }())

#define G_CTAS 36
#define B4_FIRST 11
#define O_FIRST 4
#define B3_FIRST 9
#define LN_POS 63
static int build_items(uint16_t* it) {
  using namespace gk;
  int n = 0;
  auto add = [&](int type, int nrows, int ncols, int row0 = 0) {
    for (int mb = row0; mb < nrows; mb++) for (int nt = 0; nt < ncols; nt++) it[n++] = (uint16_t)(type | mb << 3 | nt << 7);
  };
  add(T_B1, 16, 4); add(T_B2, 16, 4); add(T_B3, B3_FIRST, 14); add(T_B4, 2, 4); add(T_B3, 16, 14, B3_FIRST);
  add(T_B4, B4_FIRST, 4, 2); add(T_O, O_FIRST, 4); add(T_B4, 16, 4, B4_FIRST); add(T_O, TAIL_MB0, 4, O_FIRST);
  return n;
}

extern "C" void kernel_launch(void* const* d_in, const int* in_sizes, int n_in, void* d_out, int out_size) {
  using namespace cfg;
  const bf16* x = (const bf16*)d_in[0];
  const bf16* mem0 = (const bf16*)d_in[1];
  const bf16* Wq = (const bf16*)d_in[2];
  const bf16* Wk = (const bf16*)d_in[3];
  const bf16* Wv = (const bf16*)d_in[4];
  const bf16* Wo = (const bf16*)d_in[5];
  const bf16* w1 = (const bf16*)d_in[8];
  const bf16* w2 = (const bf16*)d_in[9];
  const bf16* w3 = (const bf16*)d_in[10];
  const bf16* w4 = (const bf16*)d_in[11];
  bf16* out = (bf16*)d_out;
  cudaStream_t st = cudaStreamPerThread;

  bf16 *xn = SYM(g_xn), *xn2 = SYM(g_xn2), *hb = SYM(g_h), *x1 = SYM(g_x1), *x1n = SYM(g_x1n), *u = SYM(g_u),
       *g = SYM(g_g), *o = SYM(g_o);

  {
    cudaFuncSetAttribute(f_kernel, cudaFuncAttributeMaxDynamicSharedMemorySize, fk::SMEM);
    FParams P;
    P.wq = make_map(Wq, D, HD, 64, 64, 128); P.wk = make_map(Wk, D, HD, 64, 64, 128); P.wv = make_map(Wv, D, HD, 64, 64, 128);
    P.wo = make_map(Wo, HD, D, 128, 64, 128); P.wo16 = make_map(Wo, HD, D, 128, 16, 32); P.xn = make_map3(xn, S, D, 32, 4); P.xn12 = make_map3(xn, S, D, 32, 12); P.o = make_map3(o, S, HD, 32, 2);
    P.ta = make_map(o, S, HD, 128, 64, 128); P.tb = make_map(Wo, HD, D, 64, 64, 128);
    P.tx = make_map(x, S, D, 128, 32, 64); P.tg = make_map(g, S, D, 128, 32, 64); P.out = out;
    P.mem0 = mem0;
    P.nprobe = PROBE_N;
    P.dxn = make_desc(fk::XN, 16, 1024);
    P.x = x; P.xn_ptr = xn;
    P.xch = (char*)(((uintptr_t)SYM(g_xch) + 8191) & ~(uintptr_t)8191);
    cudaLaunchConfig_t cfg = {};
    cfg.gridDim = dim3(96); cfg.blockDim = dim3(256); cfg.dynamicSmemBytes = fk::SMEM; cfg.stream = st;
    cudaLaunchAttribute at[2];
    at[0].id = cudaLaunchAttributeClusterDimension;
    at[0].val.clusterDim.x = 3; at[0].val.clusterDim.y = 1; at[0].val.clusterDim.z = 1;
    cfg.attrs = at; cfg.numAttrs = 1;
    cudaLaunchKernelEx(&cfg, f_kernel, P);
  }
  {
    cudaFuncSetAttribute(g_kernel, cudaFuncAttributeMaxDynamicSharedMemorySize, gk::SMEM);
    GParams G;
    const bf16* as[5] = {xn2, hb, x1n, u, o};
    const bf16* bs[5] = {w1, w2, w3, w4, Wo};
    bf16* cs[5] = {hb, x1, u, g, out};
    const bf16* rs[5] = {xn, xn, xn, x1, x};
    const int ks[5] = {D, D, D, F, HD}, ns[5] = {D, D, F, D, D};
    for (int i = 0; i < 5; i++) {
      G.a[i] = make_map(as[i], S, ks[i], 128, 64, 128);
      G.b[i] = make_map3(bs[i], ks[i], ns[i], 64, 4);
      G.c[i] = cs[i];
      G.r[i] = rs[i];
    }
    G.x1n = x1n; G.xn2 = xn2; G.w1 = w1;
    G.nitems = build_items(G.items);
    G.lnpos = LN_POS * 2;
    cudaLaunchConfig_t cfg = {};
    int dev = 0, sms = 0;
    cudaGetDevice(&dev);
    cudaDeviceGetAttribute(&sms, cudaDevAttrMultiProcessorCount, dev);
    cfg.gridDim = dim3(sms - 96 >= 4 && sms - 96 < G_CTAS ? sms - 96 : G_CTAS); cfg.blockDim = dim3(384); cfg.dynamicSmemBytes = gk::SMEM; cfg.stream = st;
    cudaLaunchAttribute at[1];
    at[0].id = cudaLaunchAttributeProgrammaticStreamSerialization;
    at[0].val.programmaticStreamSerializationAllowed = 1;
    cfg.attrs = at;
    cfg.numAttrs = 1;
    cudaLaunchKernelEx(&cfg, g_kernel, G);
  }
}
```

```cpp
#include <cuda_runtime.h>
#include <cuda_bf16.h>
#include <cuda.h>
#include <stdint.h>

typedef __nv_bfloat16 bf16;

namespace cfg {
constexpr int S = 2048;
constexpr int D = 1024;
constexpr int H = 32;
constexpr int DH = 128;
constexpr int HD = H * DH;
constexpr int M = 8;
constexpr int SEG = 32;
constexpr int NSEG = S / SEG;
constexpr int F = 3584;
}

__device__ __forceinline__ uint32_t smem_u32(const void* p) { return (uint32_t)__cvta_generic_to_shared(p); }

__device__ __forceinline__ void mbar_init(uint32_t bar, uint32_t count) {
  asm volatile("mbarrier.init.shared::cta.b64 [%0], %1;" ::"r"(bar), "r"(count) : "memory");
}
__device__ __forceinline__ void mbar_expect_tx(uint32_t bar, uint32_t bytes) {
  asm volatile("mbarrier.arrive.expect_tx.shared::cta.b64 _, [%0], %1;" ::"r"(bar), "r"(bytes) : "memory");
}
__device__ __forceinline__ void mbar_arrive(uint32_t bar) {
  asm volatile("mbarrier.arrive.shared::cta.b64 _, [%0];" ::"r"(bar) : "memory");
}
__device__ __forceinline__ bool mbar_try(uint32_t bar, uint32_t parity) {
  uint32_t done;
  asm volatile("{\n.reg .pred p;\nmbarrier.try_wait.parity.shared::cta.b64 p, [%1], %2, 20000;\nselp.u32 %0, 1, 0, p;\n}"
               : "=r"(done) : "r"(bar), "r"(parity) : "memory");
  return done != 0;
}
__device__ __forceinline__ bool mbar_try_nohint(uint32_t bar, uint32_t parity) {
  uint32_t done;
  asm volatile("{\n.reg .pred p;\nmbarrier.try_wait.parity.shared::cta.b64 p, [%1], %2;\nselp.u32 %0, 1, 0, p;\n}"
               : "=r"(done) : "r"(bar), "r"(parity) : "memory");
  return done != 0;
}
constexpr int MBAR_TRIES = 4096;
constexpr int POLL_TRIES = 1 << 16;
__device__ __forceinline__ void mbar_wait(uint32_t bar, uint32_t parity) {
#pragma unroll 1
  for (int n = 0; n < MBAR_TRIES; n++)
    if (mbar_try(bar, parity)) break;
}
__device__ __forceinline__ void mbar_wait_fast(uint32_t bar, uint32_t parity) {
#pragma unroll 1
  for (int n = 0; n < (POLL_TRIES << 4); n++)
    if (mbar_try_nohint(bar, parity)) break;
}
__device__ __forceinline__ void fence_barrier_init() { asm volatile("fence.mbarrier_init.release.cluster;" ::: "memory"); }
__device__ __forceinline__ void fence_proxy_async_smem() { asm volatile("fence.proxy.async.shared::cta;" ::: "memory"); }

__device__ __forceinline__ void tma_load_2d(uint32_t dst, const CUtensorMap* map, int x, int y, uint32_t bar) {
  asm volatile("cp.async.bulk.tensor.2d.shared::cluster.global.mbarrier::complete_tx::bytes [%0], [%1, {%3, %4}], [%2];"
               ::"r"(dst), "l"(map), "r"(bar), "r"(x), "r"(y) : "memory");
}
__device__ __forceinline__ void tma_load_3d(uint32_t dst, const CUtensorMap* map, int x, int y, int z, uint32_t bar) {
  asm volatile("cp.async.bulk.tensor.3d.shared::cluster.global.mbarrier::complete_tx::bytes [%0], [%1, {%3, %4, %5}], [%2];"
               ::"r"(dst), "l"(map), "r"(bar), "r"(x), "r"(y), "r"(z) : "memory");
}
__device__ __forceinline__ void tma_store_2d(const CUtensorMap* map, uint32_t src, int x, int y) {
  asm volatile("cp.async.bulk.tensor.2d.global.shared::cta.bulk_group [%0, {%2, %3}], [%1];"
               ::"l"(map), "r"(src), "r"(x), "r"(y) : "memory");
}
__device__ __forceinline__ void tma_store_commit() { asm volatile("cp.async.bulk.commit_group;" ::: "memory"); }
__device__ __forceinline__ void tma_store_wait_all() { asm volatile("cp.async.bulk.wait_group 0;" ::: "memory"); }
__device__ __forceinline__ void tma_store_wait_read() { asm volatile("cp.async.bulk.wait_group.read 0;" ::: "memory"); }
__device__ __forceinline__ void prefetch_tmap(const CUtensorMap* map) {
  asm volatile("prefetch.tensormap [%0];" ::"l"(map) : "memory");
}

__device__ __forceinline__ void wg_fence() { asm volatile("wgmma.fence.sync.aligned;" ::: "memory"); }
__device__ __forceinline__ void wg_commit() { asm volatile("wgmma.commit_group.sync.aligned;" ::: "memory"); }
template <int N> __device__ __forceinline__ void wg_wait() { asm volatile("wgmma.wait_group.sync.aligned %0;" ::"n"(N) : "memory"); }

#define named_bar_sync(id, n) asm volatile("bar.sync %0, %1;" ::"n"(id), "n"(n) : "memory")
#define named_bar_arrive(id, n) asm volatile("bar.arrive %0, %1;" ::"n"(id), "n"(n) : "memory")

__host__ __device__ __forceinline__ uint64_t make_desc(uint32_t addr, uint32_t lbo, uint32_t sbo) {
  return (uint64_t)((addr & 0x3FFFF) >> 4) | ((uint64_t)(lbo >> 4) << 16) | ((uint64_t)(sbo >> 4) << 32) | (1ull << 62);
}

__device__ __forceinline__ uint64_t make_desc0(uint32_t addr, uint32_t lbo, uint32_t sbo) {
  return (uint64_t)((addr & 0x3FFFF) >> 4) | ((uint64_t)(lbo >> 4) << 16) | ((uint64_t)(sbo >> 4) << 32);
}

__device__ __forceinline__ uint32_t pack_bf16(float lo, float hi) {
  uint32_t r;
  asm("cvt.rn.bf16x2.f32 %0, %1, %2;" : "=r"(r) : "f"(hi), "f"(lo));
  return r;
}
__device__ __forceinline__ float bf_lo(uint32_t v) { return __uint_as_float(v << 16); }
__device__ __forceinline__ float bf_hi(uint32_t v) { return __uint_as_float(v & 0xFFFF0000u); }
__device__ __forceinline__ float rbf(float v) { return __bfloat162float(__float2bfloat16_rn(v)); }

__device__ __forceinline__ void pdl_launch_dependents() { asm volatile("griddepcontrol.launch_dependents;" ::: "memory"); }
__device__ __forceinline__ void pdl_wait() { asm volatile("griddepcontrol.wait;" ::: "memory"); }

__device__ __forceinline__ float ex2_approx(float x) { float y; asm("ex2.approx.ftz.f32 %0, %1;" : "=f"(y) : "f"(x)); return y; }
__device__ __forceinline__ float rcp_approx(float x) { float y; asm("rcp.approx.ftz.f32 %0, %1;" : "=f"(y) : "f"(x)); return y; }

__device__ __forceinline__ void mul_sigmoid4(float (&v)[4], const float (&t)[4]) {
#pragma unroll
  for (int i = 0; i < 4; i += 2) {
    const float a = 1.0f + ex2_approx(fminf(t[i], 60.0f)), b = 1.0f + ex2_approx(fminf(t[i + 1], 60.0f));
    const float r = rcp_approx(a * b);
    v[i] *= b * r;
    v[i + 1] *= a * r;
  }
}
__device__ __forceinline__ void gelu4(float (&v)[4]) {
  float t[4];
#pragma unroll
  for (int i = 0; i < 4; i++) t[i] = v[i] * fmaf(v[i] * v[i], -0.10294324f, -2.30220819f);
  mul_sigmoid4(v, t);
}
__device__ __forceinline__ void silu4(float (&v)[4]) {
  float t[4];
#pragma unroll
  for (int i = 0; i < 4; i++) t[i] = v[i] * -1.4426950408889634f;
  mul_sigmoid4(v, t);
}

#define KT_START(id)
#define KT_END(id)

__device__ __forceinline__ void wgmma_ss_n256_tb(float (&d)[128], uint64_t da, uint64_t db, int scale_d) {
  asm volatile("{\n.reg .pred p;\nsetp.ne.b32 p, %130, 0;\n"
    "wgmma.mma_async.sync.aligned.m64n256k16.f32.bf16.bf16 "
    "{%0, %1, %2, %3, %4, %5, %6, %7, %8, %9, %10, %11, %12, %13, %14, %15, "
    "%16, %17, %18, %19, %20, %21, %22, %23, %24, %25, %26, %27, %28, %29, %30, %31, "
    "%32, %33, %34, %35, %36, %37, %38, %39, %40, %41, %42, %43, %44, %45, %46, %47, "
    "%48, %49, %50, %51, %52, %53, %54, %55, %56, %57, %58, %59, %60, %61, %62, %63, "
    "%64, %65, %66, %67, %68, %69, %70, %71, %72, %73, %74, %75, %76, %77, %78, %79, "
    "%80, %81, %82, %83, %84, %85, %86, %87, %88, %89, %90, %91, %92, %93, %94, %95, "
    "%96, %97, %98, %99, %100, %101, %102, %103, %104, %105, %106, %107, %108, %109, %110, %111, "
    "%112, %113, %114, %115, %116, %117, %118, %119, %120, %121, %122, %123, %124, %125, %126, %127}, "
    "%128, %129, p, 1, 1, 0, 1;\n}\n"
    : "+f"(d[0]), "+f"(d[1]), "+f"(d[2]), "+f"(d[3]), "+f"(d[4]), "+f"(d[5]), "+f"(d[6]), "+f"(d[7]),
      "+f"(d[8]), "+f"(d[9]), "+f"(d[10]), "+f"(d[11]), "+f"(d[12]), "+f"(d[13]), "+f"(d[14]), "+f"(d[15]),
      "+f"(d[16]), "+f"(d[17]), "+f"(d[18]), "+f"(d[19]), "+f"(d[20]), "+f"(d[21]), "+f"(d[22]), "+f"(d[23]),
      "+f"(d[24]), "+f"(d[25]), "+f"(d[26]), "+f"(d[27]), "+f"(d[28]), "+f"(d[29]), "+f"(d[30]), "+f"(d[31]),
      "+f"(d[32]), "+f"(d[33]), "+f"(d[34]), "+f"(d[35]), "+f"(d[36]), "+f"(d[37]), "+f"(d[38]), "+f"(d[39]),
      "+f"(d[40]), "+f"(d[41]), "+f"(d[42]), "+f"(d[43]), "+f"(d[44]), "+f"(d[45]), "+f"(d[46]), "+f"(d[47]),
      "+f"(d[48]), "+f"(d[49]), "+f"(d[50]), "+f"(d[51]), "+f"(d[52]), "+f"(d[53]), "+f"(d[54]), "+f"(d[55]),
      "+f"(d[56]), "+f"(d[57]), "+f"(d[58]), "+f"(d[59]), "+f"(d[60]), "+f"(d[61]), "+f"(d[62]), "+f"(d[63]),
      "+f"(d[64]), "+f"(d[65]), "+f"(d[66]), "+f"(d[67]), "+f"(d[68]), "+f"(d[69]), "+f"(d[70]), "+f"(d[71]),
      "+f"(d[72]), "+f"(d[73]), "+f"(d[74]), "+f"(d[75]), "+f"(d[76]), "+f"(d[77]), "+f"(d[78]), "+f"(d[79]),
      "+f"(d[80]), "+f"(d[81]), "+f"(d[82]), "+f"(d[83]), "+f"(d[84]), "+f"(d[85]), "+f"(d[86]), "+f"(d[87]),
      "+f"(d[88]), "+f"(d[89]), "+f"(d[90]), "+f"(d[91]), "+f"(d[92]), "+f"(d[93]), "+f"(d[94]), "+f"(d[95]),
      "+f"(d[96]), "+f"(d[97]), "+f"(d[98]), "+f"(d[99]), "+f"(d[100]), "+f"(d[101]), "+f"(d[102]), "+f"(d[103]),
      "+f"(d[104]), "+f"(d[105]), "+f"(d[106]), "+f"(d[107]), "+f"(d[108]), "+f"(d[109]), "+f"(d[110]), "+f"(d[111]),
      "+f"(d[112]), "+f"(d[113]), "+f"(d[114]), "+f"(d[115]), "+f"(d[116]), "+f"(d[117]), "+f"(d[118]), "+f"(d[119]),
      "+f"(d[120]), "+f"(d[121]), "+f"(d[122]), "+f"(d[123]), "+f"(d[124]), "+f"(d[125]), "+f"(d[126]), "+f"(d[127])
    : "l"(da), "l"(db), "r"(scale_d));
}
__device__ __forceinline__ void wgmma_rs_n32(float (&d)[16], const uint32_t* a, uint64_t db, int scale_d) {
  asm volatile("{\n.reg .pred p;\nsetp.ne.b32 p, %21, 0;\n"
    "wgmma.mma_async.sync.aligned.m64n32k16.f32.bf16.bf16 "
    "{%0, %1, %2, %3, %4, %5, %6, %7, %8, %9, %10, %11, %12, %13, %14, %15}, "
    "{%16, %17, %18, %19}, %20, p, 1, 1, 0;\n}\n"
    : "+f"(d[0]), "+f"(d[1]), "+f"(d[2]), "+f"(d[3]), "+f"(d[4]), "+f"(d[5]), "+f"(d[6]), "+f"(d[7]),
      "+f"(d[8]), "+f"(d[9]), "+f"(d[10]), "+f"(d[11]), "+f"(d[12]), "+f"(d[13]), "+f"(d[14]), "+f"(d[15])
    : "r"(a[0]), "r"(a[1]), "r"(a[2]), "r"(a[3]), "l"(db), "r"(scale_d));
}
__device__ __forceinline__ void wgmma_ss_n32_ta(float (&d)[16], uint64_t da, uint64_t db, int scale_d) {
  asm volatile("{\n.reg .pred p;\nsetp.ne.b32 p, %18, 0;\n"
    "wgmma.mma_async.sync.aligned.m64n32k16.f32.bf16.bf16 "
    "{%0, %1, %2, %3, %4, %5, %6, %7, %8, %9, %10, %11, %12, %13, %14, %15}, "
    "%16, %17, p, 1, 1, 1, 0;\n}\n"
    : "+f"(d[0]), "+f"(d[1]), "+f"(d[2]), "+f"(d[3]), "+f"(d[4]), "+f"(d[5]), "+f"(d[6]), "+f"(d[7]),
      "+f"(d[8]), "+f"(d[9]), "+f"(d[10]), "+f"(d[11]), "+f"(d[12]), "+f"(d[13]), "+f"(d[14]), "+f"(d[15])
    : "l"(da), "l"(db), "r"(scale_d));
}
__device__ __forceinline__ void wgmma_ss_n8_ta(float (&d)[4], uint64_t da, uint64_t db, int scale_d) {
  asm volatile("{\n.reg .pred p;\nsetp.ne.b32 p, %6, 0;\n"
    "wgmma.mma_async.sync.aligned.m64n8k16.f32.bf16.bf16 {%0, %1, %2, %3}, %4, %5, p, 1, 1, 1, 0;\n}\n"
    : "+f"(d[0]), "+f"(d[1]), "+f"(d[2]), "+f"(d[3]) : "l"(da), "l"(db), "r"(scale_d));
}
__device__ __forceinline__ void wgmma_ss_n48_tt(float (&d)[24], uint64_t da, uint64_t db, int scale_d) {
  asm volatile("{\n.reg .pred p;\nsetp.ne.b32 p, %26, 0;\n"
    "wgmma.mma_async.sync.aligned.m64n48k16.f32.bf16.bf16 "
    "{%0, %1, %2, %3, %4, %5, %6, %7, %8, %9, %10, %11, %12, %13, %14, %15, %16, %17, %18, %19, %20, %21, %22, %23}, "
    "%24, %25, p, 1, 1, 1, 1;\n}\n"
    : "+f"(d[0]), "+f"(d[1]), "+f"(d[2]), "+f"(d[3]), "+f"(d[4]), "+f"(d[5]), "+f"(d[6]), "+f"(d[7]), "+f"(d[8]), "+f"(d[9]), "+f"(d[10]), "+f"(d[11]), "+f"(d[12]), "+f"(d[13]), "+f"(d[14]), "+f"(d[15]), "+f"(d[16]), "+f"(d[17]), "+f"(d[18]), "+f"(d[19]), "+f"(d[20]), "+f"(d[21]), "+f"(d[22]), "+f"(d[23])
    : "l"(da), "l"(db), "r"(scale_d));
}
__device__ __forceinline__ void wgmma_ss_n32(float (&d)[16], uint64_t da, uint64_t db, int scale_d) {
  asm volatile("{\n.reg .pred p;\nsetp.ne.b32 p, %18, 0;\n"
    "wgmma.mma_async.sync.aligned.m64n32k16.f32.bf16.bf16 "
    "{%0, %1, %2, %3, %4, %5, %6, %7, %8, %9, %10, %11, %12, %13, %14, %15}, "
    "%16, %17, p, 1, 1, 0, 0;\n}\n"
    : "+f"(d[0]), "+f"(d[1]), "+f"(d[2]), "+f"(d[3]), "+f"(d[4]), "+f"(d[5]), "+f"(d[6]), "+f"(d[7]),
      "+f"(d[8]), "+f"(d[9]), "+f"(d[10]), "+f"(d[11]), "+f"(d[12]), "+f"(d[13]), "+f"(d[14]), "+f"(d[15])
    : "l"(da), "l"(db), "r"(scale_d));
}

__device__ __forceinline__ void tma_load_2d_mc(uint32_t dst, const CUtensorMap* map, int x, int y, uint32_t bar, uint16_t mask) {
  asm volatile("cp.async.bulk.tensor.2d.shared::cluster.global.mbarrier::complete_tx::bytes.multicast::cluster "
               "[%0], [%1, {%3, %4}], [%2], %5;"
               ::"r"(dst), "l"(map), "r"(bar), "r"(x), "r"(y), "h"(mask) : "memory");
}
__device__ __forceinline__ void mbar_arrive_cluster(uint32_t bar, uint32_t cta) {
  asm volatile("{\n.reg .b32 r;\nmapa.shared::cluster.u32 r, %0, %1;\nmbarrier.arrive.shared::cluster.b64 _, [r];\n}"
               ::"r"(bar), "r"(cta) : "memory");
}
__device__ __forceinline__ void cluster_sync() {
  asm volatile("barrier.cluster.arrive.release.aligned;\nbarrier.cluster.wait.acquire.aligned;" ::: "memory");
}
__device__ __forceinline__ void wait_count(const unsigned* p, unsigned need) {
#pragma unroll 1
  for (int tries = 0; tries < (1 << 18); tries++) {
    unsigned v;
    asm volatile("ld.acquire.gpu.global.u32 %0, [%1];" : "=r"(v) : "l"(p) : "memory");
    if (v >= need) break;
    __nanosleep(64);
  }
}
__device__ __forceinline__ uint32_t sub_bf16x2(uint32_t a, uint32_t b) {
  uint32_t d;
  asm("sub.rn.bf16x2 %0, %1, %2;" : "=r"(d) : "r"(a), "r"(b));
  return d;
}
__device__ __forceinline__ uint32_t add_bf16x2(uint32_t a, uint32_t b) {
  uint32_t d;
  asm("add.rn.bf16x2 %0, %1, %2;" : "=r"(d) : "r"(a), "r"(b));
  return d;
}
__device__ __forceinline__ uint32_t mul_bf16x2(uint32_t a, uint32_t b) {
  uint32_t d;
  asm("mul.rn.bf16x2 %0, %1, %2;" : "=r"(d) : "r"(a), "r"(b));
  return d;
}

template <int NR>
__device__ __forceinline__ void ln_regs(uint32_t (&raw)[NR][16]) {
  float m[NR], q[NR];
#pragma unroll
  for (int r = 0; r < NR; r++) {
    float s0 = 0.f, s1 = 0.f;
#pragma unroll
    for (int i = 0; i < 16; i++) { s0 += bf_lo(raw[r][i]); s1 += bf_hi(raw[r][i]); }
    m[r] = s0 + s1;
  }
#pragma unroll
  for (int o = 16; o > 0; o >>= 1)
#pragma unroll
    for (int r = 0; r < NR; r++) m[r] += __shfl_xor_sync(0xffffffffu, m[r], o);
#pragma unroll
  for (int r = 0; r < NR; r++) {
    m[r] *= 1.0f / 1024.0f;
    float s0 = 0.f, s1 = 0.f;
#pragma unroll
    for (int i = 0; i < 16; i++) {
      const float d0 = bf_lo(raw[r][i]) - m[r], d1 = bf_hi(raw[r][i]) - m[r];
      s0 = fmaf(d0, d0, s0); s1 = fmaf(d1, d1, s1);
    }
    q[r] = s0 + s1;
  }
#pragma unroll
  for (int o = 16; o > 0; o >>= 1)
#pragma unroll
    for (int r = 0; r < NR; r++) q[r] += __shfl_xor_sync(0xffffffffu, q[r], o);
#pragma unroll
  for (int r = 0; r < NR; r++) {
    const uint32_t mb = pack_bf16(m[r], m[r]);
    float sq;
    asm("sqrt.approx.f32 %0, %1;" : "=f"(sq) : "f"(rbf(rbf(q[r] * (1.0f / 1024.0f)) + 1e-5f)));
    const float inv = rcp_approx(rbf(sq));
#pragma unroll
    for (int i = 0; i < 16; i++) {
      const uint32_t d = sub_bf16x2(raw[r][i], mb);
      raw[r][i] = pack_bf16(bf_lo(d) * inv, bf_hi(d) * inv);
    }
  }
}
__device__ __forceinline__ void load_row16(uint32_t (&raw)[16], const bf16* src, int lane) {
#pragma unroll
  for (int j = 0; j < 4; j++) {
    const uint4 u = __ldcg(reinterpret_cast<const uint4*>(src + j * 256 + lane * 8));
    raw[4 * j] = u.x; raw[4 * j + 1] = u.y; raw[4 * j + 2] = u.z; raw[4 * j + 3] = u.w;
  }
}
__device__ __forceinline__ void store_row16(const uint32_t (&raw)[16], bf16* dst, int lane) {
#pragma unroll
  for (int j = 0; j < 4; j++)
    *reinterpret_cast<uint4*>(dst + j * 256 + lane * 8) = make_uint4(raw[4 * j], raw[4 * j + 1], raw[4 * j + 2], raw[4 * j + 3]);
}

namespace fk {
constexpr uint32_t SM0 = 1024;
constexpr uint32_t WO = SM0, WS = WO + 90112, XN = WS + 65536, VX = XN + 49152, QK = VX + 8192, PT = QK + 8192,
                   SP = PT + 4096, VM = SP + 2560, OB = VM + 2048, BAR = OB + 2048;
constexpr uint32_t MEMB = XN + 16384, RED = XN + 32768, VX2 = WO + 81920;
constexpr int SMEM = 232448;
static_assert(BAR + 512 == SM0 + SMEM, "shared memory layout");
constexpr uint32_t B_XN = BAR, B_H2 = BAR + 64, B_H1 = BAR + 120, ONES = BAR + 384, B_PF = BAR + 16, B_WO = BAR + 24, B_SM = BAR + 32, B_VM = BAR + 40, B_VX = BAR + 48, B_ST = BAR + 56, B_PB = BAR + 64, B_W = BAR + 112,
                   MASKS = BAR + 128, PROBE = BAR + 256;
constexpr int NB_M0 = 1, NB_M1 = 2, NB_C = 3, NB_O = 4, NB_ST = 5, NB_DU = 6, NB_CF = 7, NB_W1 = 8, NB_XE = 9, NB_HD = 10, NB_MX = 11, NB_O0 = 12;
#define D_H1 550
#define D_H2 1900
#define D_ST 200
#define SMQ 0x1E
#define SMV 0x1E
#define PRE_G 4
#define PRE_A 1
#define LN_DRY 1
#define MASK_AT 4
#define WO_AT 5
#define NS0 4
#define NS0V 4
#define NTA0 2
#define NTA1 1
#define PF0A 3
#define PF0 10
#define PF1V 10
#define PF1 11
#define REFILL_EARLY 1
#define GATE_MX 0
#define GATE_Q 0
#define PF1Q 4
#define PACEQ 0x60
#define PACEV 0
#define PADD 1
#define D_H2V 2200
#define D_H2L 1700
#define H2_ATV 0
#define XPF 1
#define VM_BULK 0
#define CF_AT 0
#define H2_AT 0
#define NPRE0 1
#define PROBE_N 4
#define SPACK 1
constexpr uint32_t SPW = SPACK ? 4 : 8, SP_SRC = 160 * SPW;
constexpr int H1_BYTES = 64 * 32768, H2_BYTES = 8 * 8192;
}

#define PROF(wg, i)
#define PROF2(i)
#define RETRY(i)
#define GTSYNC(i)
#define PRO(i)
#define TL(i)
#define TL2(t, i)

__device__ uint4 g_xch[(fk::H1_BYTES + fk::H2_BYTES + 8192) / 16];
__device__ __align__(16) unsigned g_mask[128];
__device__ unsigned g_cnt[8][16];
__device__ unsigned g_next;
constexpr int TAIL_MB0 = 13, GATE_CNT = 12;
__device__ __align__(16) unsigned g_tfix[96], g_lnok[4];
__device__ __align__(16) unsigned g_tcnt[96][8];
__device__ uint4 g_tpart[96][8][2][256];
__device__ unsigned g_oflag[16];

#define LD_POLL "ld.global.L1::no_allocate"
__device__ __forceinline__ uint4 ld_poll16(const void* p) {
  uint4 v;
  asm volatile(LD_POLL ".v4.u32 {%0,%1,%2,%3}, [%4];" : "=r"(v.x), "=r"(v.y), "=r"(v.z), "=r"(v.w) : "l"(p) : "memory");
  return v;
}
__device__ __forceinline__ uint2 ld_poll8(const void* p) {
  uint2 v;
  asm volatile(LD_POLL ".v2.u32 {%0,%1}, [%2];" : "=r"(v.x), "=r"(v.y) : "l"(p) : "memory");
  return v;
}
__device__ __forceinline__ uint4 ld_strong16(const void* p) {
  uint4 v;
  asm volatile("ld.relaxed.gpu.global.v4.u32 {%0,%1,%2,%3}, [%4];" : "=r"(v.x), "=r"(v.y), "=r"(v.z), "=r"(v.w) : "l"(p) : "memory");
  return v;
}
__device__ __forceinline__ uint2 ld_strong8(const void* p) {
  uint2 v;
  asm volatile("ld.relaxed.gpu.global.v2.u32 {%0,%1}, [%2];" : "=r"(v.x), "=r"(v.y) : "l"(p) : "memory");
  return v;
}
__device__ __forceinline__ void st_pub32(void* p, uint32_t v) { asm volatile("st.relaxed.gpu.global.u32 [%0], %1;" ::"l"(p), "r"(v) : "memory"); }
__device__ __forceinline__ void st_pub16(void* p, uint32_t v) {
  asm volatile("st.relaxed.gpu.global.u16 [%0], %1;" ::"l"(p), "h"((uint16_t)v) : "memory");
}
__device__ __forceinline__ uint32_t ld_strong4(const void* p) {
  uint32_t v;
  asm volatile("ld.relaxed.gpu.global.u32 %0, [%1];" : "=r"(v) : "l"(p) : "memory");
  return v;
}
__device__ __forceinline__ void st_pub64(void* p, uint32_t a, uint32_t b) {
  asm volatile("st.relaxed.gpu.global.v2.u32 [%0], {%1,%2};" ::"l"(p), "r"(a), "r"(b) : "memory");
}
__device__ __forceinline__ void st_pub128(void* p, uint32_t a) {
  asm volatile("st.relaxed.gpu.global.v4.u32 [%0], {%1,%1,%1,%1};" ::"l"(p), "r"(a) : "memory");
}
constexpr uint32_t EMPTY = 0xFFFFFFFFu;
__device__ __forceinline__ uint32_t umax4(const uint4& v) { return max(max(v.x, v.y), max(v.z, v.w)); }
__device__ __forceinline__ void sts128(uint32_t a, uint32_t x, uint32_t y, uint32_t z, uint32_t w) {
  asm volatile("st.shared.v4.u32 [%0], {%1,%2,%3,%4};" ::"r"(a), "r"(x), "r"(y), "r"(z), "r"(w) : "memory");
}
__device__ __forceinline__ void sts64(uint32_t a, uint32_t x, uint32_t y) {
  asm volatile("st.shared.v2.u32 [%0], {%1,%2};" ::"r"(a), "r"(x), "r"(y) : "memory");
}
__device__ __forceinline__ void sts32(uint32_t a, uint32_t x) { asm volatile("st.shared.u32 [%0], %1;" ::"r"(a), "r"(x) : "memory"); }
__device__ __forceinline__ void sts128f(uint32_t a, float x, float y, float z, float w) {
  asm volatile("st.shared.v4.f32 [%0], {%1,%2,%3,%4};" ::"r"(a), "f"(x), "f"(y), "f"(z), "f"(w) : "memory");
}
__device__ __forceinline__ void sts64f(uint32_t a, float x, float y) {
  asm volatile("st.shared.v2.f32 [%0], {%1,%2};" ::"r"(a), "f"(x), "f"(y) : "memory");
}
__device__ __forceinline__ float4 lds128f(uint32_t a) {
  float4 v;
  asm volatile("ld.shared.v4.f32 {%0,%1,%2,%3}, [%4];" : "=f"(v.x), "=f"(v.y), "=f"(v.z), "=f"(v.w) : "r"(a) : "memory");
  return v;
}
__device__ __forceinline__ float2 lds64f(uint32_t a) {
  float2 v;
  asm volatile("ld.shared.v2.f32 {%0,%1}, [%2];" : "=f"(v.x), "=f"(v.y) : "r"(a) : "memory");
  return v;
}
__device__ __forceinline__ float2 lds64f_if(uint32_t a, bool on, float other) {
  float2 v = make_float2(other, other);
  asm volatile("{\n.reg .pred p;\nsetp.ne.u32 p, %3, 0;\n@p ld.shared.v2.f32 {%0,%1}, [%2];\n}" : "+f"(v.x), "+f"(v.y) : "r"(a), "r"((uint32_t)on) : "memory");
  return v;
}
__device__ __forceinline__ void lds128(uint32_t* r, uint32_t a) {
  asm volatile("ld.shared.v4.u32 {%0,%1,%2,%3}, [%4];" : "=r"(r[0]), "=r"(r[1]), "=r"(r[2]), "=r"(r[3]) : "r"(a) : "memory");
}
__device__ __forceinline__ void lds64(uint32_t* r, uint32_t a) {
  asm volatile("ld.shared.v2.u32 {%0,%1}, [%2];" : "=r"(r[0]), "=r"(r[1]) : "r"(a) : "memory");
}
__device__ __forceinline__ uint32_t lds32(uint32_t a) {
  uint32_t v;
  asm volatile("ld.shared.u32 %0, [%1];" : "=r"(v) : "r"(a) : "memory");
  return v;
}
__device__ __forceinline__ void ldsm4(uint32_t* r, uint32_t a) {
  asm volatile("ldmatrix.sync.aligned.m8n8.x4.shared.b16 {%0,%1,%2,%3}, [%4];"
               : "=r"(r[0]), "=r"(r[1]), "=r"(r[2]), "=r"(r[3]) : "r"(a) : "memory");
}
__device__ __forceinline__ void ldsm4t(uint32_t* r, uint32_t a) {
  asm volatile("ldmatrix.sync.aligned.m8n8.x4.trans.shared.b16 {%0,%1,%2,%3}, [%4];"
               : "=r"(r[0]), "=r"(r[1]), "=r"(r[2]), "=r"(r[3]) : "r"(a) : "memory");
}
__device__ __forceinline__ void stsm4(uint32_t a, uint32_t r0, uint32_t r1, uint32_t r2, uint32_t r3) {
  asm volatile("stmatrix.sync.aligned.m8n8.x4.shared.b16 [%0], {%1,%2,%3,%4};"
               ::"r"(a), "r"(r0), "r"(r1), "r"(r2), "r"(r3) : "memory");
}
__device__ __forceinline__ void stsm4t(uint32_t a, uint32_t r0, uint32_t r1, uint32_t r2, uint32_t r3) {
  asm volatile("stmatrix.sync.aligned.m8n8.x4.trans.shared.b16 [%0], {%1,%2,%3,%4};"
               ::"r"(a), "r"(r0), "r"(r1), "r"(r2), "r"(r3) : "memory");
}
__device__ __forceinline__ void mma16816(float* d, const uint32_t* a, uint32_t b0, uint32_t b1) {
  asm volatile("mma.sync.aligned.m16n8k16.row.col.f32.bf16.bf16.f32 {%0,%1,%2,%3}, {%4,%5,%6,%7}, {%8,%9}, {%0,%1,%2,%3};"
               : "+f"(d[0]), "+f"(d[1]), "+f"(d[2]), "+f"(d[3])
               : "r"(a[0]), "r"(a[1]), "r"(a[2]), "r"(a[3]), "r"(b0), "r"(b1));
}
__device__ __forceinline__ void mma16816z(float* d, const uint32_t* a, uint32_t b0, uint32_t b1) {
  asm volatile("mma.sync.aligned.m16n8k16.row.col.f32.bf16.bf16.f32 {%0,%1,%2,%3}, {%4,%5,%6,%7}, {%8,%9}, {%10,%10,%10,%10};"
               : "=f"(d[0]), "=f"(d[1]), "=f"(d[2]), "=f"(d[3])
               : "r"(a[0]), "r"(a[1]), "r"(a[2]), "r"(a[3]), "r"(b0), "r"(b1), "f"(0.f));
}
__device__ __forceinline__ void mma1688(float* d, uint32_t a0, uint32_t a1, uint32_t b0) {
  asm volatile("mma.sync.aligned.m16n8k8.row.col.f32.bf16.bf16.f32 {%0,%1,%2,%3}, {%4,%5}, {%6}, {%0,%1,%2,%3};"
               : "+f"(d[0]), "+f"(d[1]), "+f"(d[2]), "+f"(d[3]) : "r"(a0), "r"(a1), "r"(b0));
}
__device__ __forceinline__ uint32_t movtrans(uint32_t a) {
  uint32_t d;
  asm volatile("movmatrix.sync.aligned.m8n8.trans.b16 %0, %1;" : "=r"(d) : "r"(a));
  return d;
}
__device__ __forceinline__ uint32_t mapa(uint32_t a, uint32_t rank) {
  uint32_t d;
  asm("mapa.shared::cluster.u32 %0, %1, %2;" : "=r"(d) : "r"(a), "r"(rank));
  return d;
}
__device__ __forceinline__ void st_async64(uint32_t a, uint32_t x, uint32_t y, uint32_t bar) {
  asm volatile("st.async.weak.shared::cluster.mbarrier::complete_tx::bytes.v2.b32 [%0], {%1,%2}, [%3];"
               ::"r"(a), "r"(x), "r"(y), "r"(bar) : "memory");
}
__device__ __forceinline__ void st_async64f(uint32_t a, float x, float y, uint32_t bar) {
  st_async64(a, __float_as_uint(x), __float_as_uint(y), bar);
}
__device__ __forceinline__ void bulk_s2s(uint32_t dst, uint32_t src, uint32_t bytes, uint32_t bar) {
  asm volatile("cp.async.bulk.shared::cluster.shared::cta.mbarrier::complete_tx::bytes [%0], [%1], %2, [%3];"
               ::"r"(dst), "r"(src), "r"(bytes), "r"(bar) : "memory");
}
__device__ __forceinline__ void tma_store_3d(const CUtensorMap* map, uint32_t src, int x, int y, int z) {
  asm volatile("cp.async.bulk.tensor.3d.global.shared::cta.bulk_group [%0, {%2, %3, %4}], [%1];"
               ::"l"(map), "r"(src), "r"(x), "r"(y), "r"(z) : "memory");
}
__device__ __forceinline__ void mbar_spin(uint32_t bar, uint32_t parity) {
  asm volatile("{\n.reg .pred p;\n.reg .b32 n;\nmov.u32 n, 0x100000;\nMW_L:\n"
               "mbarrier.try_wait.parity.shared::cta.b64 p, [%0], %1;\n@p bra.uni MW_D;\n"
               "add.s32 n, n, -1;\nsetp.ne.u32 p, n, 0;\n@p bra.uni MW_L;\nMW_D:\n}" ::"r"(bar), "r"(parity) : "memory");
}
__device__ __forceinline__ bool mbar_test(uint32_t bar, uint32_t parity) {
  uint32_t done;
  asm volatile("{\n.reg .pred p;\nmbarrier.test_wait.parity.shared::cta.b64 p, [%1], %2;\nselp.u32 %0, 1, 0, p;\n}"
               : "=r"(done) : "r"(bar), "r"(parity) : "memory");
  return done != 0;
}
__device__ __forceinline__ void mbar_arrive_remote(uint32_t bar) {
  asm volatile("mbarrier.arrive.shared::cluster.b64 _, [%0];" ::"r"(bar) : "memory");
}
__device__ __forceinline__ bool elect_one() {
  uint32_t r;
  asm volatile("{\n.reg .pred p;\nelect.sync _|p, 0xffffffff;\nselp.u32 %0, 1, 0, p;\n}" : "=r"(r));
  return r != 0;
}
__device__ __forceinline__ void st_async32(uint32_t a, uint32_t x, uint32_t bar) {
  asm volatile("st.async.weak.shared::cluster.mbarrier::complete_tx::bytes.b32 [%0], %1, [%2];" ::"r"(a), "r"(x), "r"(bar) : "memory");
}
#define named_bar_and(id, n, in, out) \
  asm volatile("{\n.reg .pred p, q;\nsetp.ne.u32 p, %1, 0;\nbar.red.and.pred q, %2, %3, p;\nselp.u32 %0, 1, 0, q;\n}" \
               : "=r"(out) : "r"(in), "n"(id), "n"(n) : "memory")
__device__ __forceinline__ void bulk_g2s(uint32_t dst, const void* src, uint32_t bytes, uint32_t bar) {
  asm volatile("cp.async.bulk.shared::cluster.global.mbarrier::complete_tx::bytes [%0], [%1], %2, [%3];"
               ::"r"(dst), "l"(src), "r"(bytes), "r"(bar) : "memory");
}
__device__ __forceinline__ void l2_prefetch(const void* p, uint32_t bytes) {
  asm volatile("cp.async.bulk.prefetch.L2.global [%0], %1;" ::"l"(p), "r"(bytes) : "memory");
}

__device__ __forceinline__ uint32_t clk32() { uint32_t c; asm volatile("mov.u32 %0, %%clock;" : "=r"(c)::"memory"); return c; }
__device__ __forceinline__ void spin_until(uint32_t t) { while ((int32_t)(clk32() - t) < 0) {} }
#define PIN(x) asm volatile("" : "+r"(x))
#define OPQ                                                                                     \
  int tid_o = tid;                                                                              \
  asm volatile("" : "+r"(tid_o));                                                               \
  const int lane = tid_o & 31, w = (tid_o >> 5) & 3, t7 = tid_o & 127, lg = lane >> 2,          \
            lq = lane & 3, mi = lane >> 3, mr = lane & 7;                                       \
  (void)w; (void)t7; (void)lg; (void)lq; (void)mi; (void)mr; (void)lane

#define SMAP                                                                                                          \
  const uint32_t SM0 = self + fk::SM0, WO = self + fk::WO, WS = self + fk::WS, XN = self + fk::XN, VX = self + fk::VX, \
                 QK = self + fk::QK, PT = self + fk::PT, SP = self + fk::SP, VM = self + fk::VM, OB = self + fk::OB,   \
                 RED = self + fk::RED, VX2 = self + fk::VX2, MEMB = self + fk::MEMB, B_XN = self + fk::B_XN, B_SM = self + fk::B_SM,       \
                 B_VM = self + fk::B_VM, B_VX = self + fk::B_VX, B_ST = self + fk::B_ST, B_PB = self + fk::B_PB,       \
                 B_W = self + fk::B_W, B_H2 = self + fk::B_H2, B_H1 = self + fk::B_H1, B_PF = self + fk::B_PF, B_WO = self + fk::B_WO, MASKS = self + fk::MASKS, PROBE = self + fk::PROBE;                             \
  (void)SM0; (void)WO; (void)WS; (void)XN; (void)VX; (void)QK; (void)PT; (void)SP; (void)VM; (void)OB; (void)RED; (void)VX2; \
  (void)MEMB; (void)B_XN; (void)B_SM; (void)B_VM; (void)B_VX; (void)B_ST; (void)B_PB; (void)B_W; (void)MASKS; (void)PROBE; (void)B_H2; (void)B_H1; (void)B_PF; (void)B_WO

struct FParams {
  CUtensorMap wq, wk, wv, wo, wo16, xn, xn12, o;
  CUtensorMap ta, tb, tx, tg;
  const bf16 *mem0, *x;
  bf16* out;
  bf16* xn_ptr;
  uint64_t dxn;
  int nprobe;
  char* xch;
};

__device__ __forceinline__ uint2 probe_pair(char* p, uint32_t val, uint32_t dummy, int n) {
  uint2 best = make_uint2(0x7FFFFFFF, 0x7FFFFFFF);
  st_pub128(p, val); st_pub128(p + 16, val); st_pub128(p + 4096, val); st_pub128(p + 4112, val);
#pragma unroll 1
  for (int r = 0; r < n; r++) {
    uint32_t v;
    const uint32_t c0 = clk32();
    asm volatile("atom.relaxed.gpu.global.exch.b32 %0, [%1], %2;" : "=r"(v) : "l"(p + (r & 1) * 4096), "r"(val) : "memory");
    asm volatile("{\n.reg .pred p;\nsetp.eq.u32 p, %0, 0x12345678;\n@p st.shared.u32 [%1], %0;\n}" ::"r"(v), "r"(dummy) : "memory");
    const uint32_t d = clk32() - c0;
    if (r & 1) best.y = min(best.y, d); else best.x = min(best.x, d);
  }
  return best;
}

typedef uint32_t WRegs[6][2][4][4];

constexpr uint32_t nth_chunks(uint32_t mask) {
  uint32_t t = 0;
  for (int c = 0, n = 0; c < 10; c++) if ((mask >> c) & 1) t |= c << (4 * n++);
  return t;
}
constexpr uint64_t chunk_pos(uint32_t mask) {
  uint64_t t = 0;
  for (int c = 0, a = 0, b = 0; c < 10; c++) t |= (uint64_t)(((mask >> c) & 1) ? a++ : b++) << (4 * c);
  return t;
}
template <bool ISV> struct Chunks {
  static constexpr uint32_t MASK = ISV ? SMV : SMQ, SMT = nth_chunks(MASK), RFT = nth_chunks(~MASK & 1023);
  static_assert(!(MASK & 1), "the first chunk initialises the accumulators");
  static __device__ __forceinline__ constexpr int rf(int wg, int i) { return wg ? 10 + i : (RFT >> (4 * i)) & 15; }
  static __device__ __forceinline__ constexpr int sm(int i) { return (SMT >> (4 * i)) & 15; }
  static constexpr uint64_t IDX = chunk_pos(MASK);
  static __device__ __forceinline__ constexpr int idx(int c) { return (IDX >> (4 * c)) & 15; }
};

template <bool ISV, int WG> struct ProjCfg {
  static constexpr int N0 = ISV ? NS0V : NS0, NS = WG ? 8 - N0 : N0, P0 = WG ? N0 : 0, NTA = WG ? NTA1 : NTA0;
};
__device__ __forceinline__ void load_pair(uint32_t (&t)[4][4], uint32_t wsa, int pp) {
#pragma unroll
  for (int f = 0; f < 4; f++) ldsm4t(t[f], wsa + ((pp >> 1) * 2 + (f & 1)) * 8192 + ((pp & 1) * 2 + (f >> 1)) * 2048);
}
template <bool ISV, int WG>
__device__ __forceinline__ void proj_mem(const WRegs& wr, uint32_t (&ta)[ProjCfg<ISV, WG>::NTA][4][4], uint32_t wsa, uint32_t mba,
                                         float (&a0)[4], float (&a1)[4]) {
  constexpr int NS = ProjCfg<ISV, WG>::NS, P0 = ProjCfg<ISV, WG>::P0, NTA = ProjCfg<ISV, WG>::NTA, NP = 12 + NS;
  float acc[4][4];
  auto spos = [](int j) { return j < NTA ? j : j + (j - NTA + 1) * 12 / (NS - NTA > 0 ? NS - NTA : 1); };
  auto which = [&](int p) { int r = -1; for (int j = 0; j < NS; j++) if (spos(j) == p) r = j; return r; };
  auto nsm_before = [&](int p) { int n = 0; for (int j = 0; j < NS; j++) if (spos(j) < p) n++; return n; };
#pragma unroll
  for (int p = 0; p < NP; p++) {
    const int j = which(p), r = j >= 0 ? 0 : p - nsm_before(p);
    uint32_t bp[4], tl[4][4];
    ldsm4(bp, mba + (j >= 0 ? Chunks<ISV>::sm((P0 + (j >= 0 ? j : 0)) >> 1) * 1024 + ((P0 + j) & 1) * 512 : Chunks<ISV>::rf(WG, r >> 1) * 1024 + (r & 1) * 512));
    if (j >= NTA) load_pair(tl, wsa, P0 + j);
#pragma unroll
    for (int u = 0; u < 2; u++)
#pragma unroll
      for (int T = 0; T < 2; T++) {
        const uint32_t* a = j >= NTA ? tl[u * 2 + T] : j >= 0 ? ta[j >= 0 ? j % NTA : 0][u * 2 + T] : wr[r >> 1][T][(r & 1) * 2 + u];
        if (p == 0) mma16816z(acc[u * 2 + T], a, bp[2 * u], bp[2 * u + 1]);
        else mma16816(acc[u * 2 + T], a, bp[2 * u], bp[2 * u + 1]);
      }
  }
#pragma unroll
  for (int i = 0; i < 4; i++) { a0[i] = acc[0][i] + acc[2][i]; a1[i] = acc[1][i] + acc[3][i]; }
}
template <bool ISV, int WG, int J0, int J1>
__device__ __forceinline__ void proj_mem_prefetch(uint32_t (&ta)[ProjCfg<ISV, WG>::NTA][4][4], uint32_t wsa) {
#pragma unroll
  for (int j = J0; j < J1; j++) load_pair(ta[j], wsa, ProjCfg<ISV, WG>::P0 + j);
}

template <bool ISV, int WG>
__device__ __forceinline__ void proj_finish(const float (&a0)[4], const float (&a1)[4], uint32_t peer0, uint32_t peer1, uint32_t self, int tid, int warp,
                                            uint32_t (&vmo)[4]) {
  using namespace fk;
  SMAP;
  OPQ;
  if (!ISV) {
    stsm4(PT + mr * 16 + ((mi >> 1) ? WG * 1024 + w * 256 + (mi & 1) * 128 : 2048 + w * 512 + (mi & 1) * 256 + WG * 128),
          pack_bf16(a0[0], a0[1]), pack_bf16(a0[2], a0[3]), pack_bf16(a1[0], a1[1]), pack_bf16(a1[2], a1[3]));
    named_bar_sync(NB_C, 256);
  } else {
    if (WG == 0) sts128f(RED + t7 * 16, a1[0], a1[1], a1[2], a1[3]);
    else sts128f(RED + 2048 + t7 * 16, a0[0], a0[1], a0[2], a0[3]);
    if (WG == 1) { lds64(vmo, VM + t7 * 8); lds64(vmo + 2, VM + 1024 + t7 * 8); }
    named_bar_sync(NB_C, 256);
    const float4 p = lds128f(RED + (1 - WG) * 2048 + t7 * 16);
    const float* k = WG == 0 ? a0 : a1;
    const uint32_t v0 = pack_bf16(k[0] + p.x, k[1] + p.y), v1 = pack_bf16(k[2] + p.z, k[3] + p.w);
    const uint32_t off = VM + WG * 1024 + t7 * 8;
    if (VM_BULK) {
      sts64(off, v0, v1);
      fence_proxy_async_smem();
      __syncwarp();
      const uint32_t a = VM + WG * 1024 + warp * 256;
      if (elect_one()) {
        bulk_s2s(peer0 + a, a, 256, peer0 + B_VM);
        bulk_s2s(peer1 + a, a, 256, peer1 + B_VM);
        mbar_arrive(B_VM);
      }
    } else {
      st_async64(peer0 + off, v0, v1, peer0 + B_VM);
      st_async64(peer1 + off, v0, v1, peer1 + B_VM);
      sts64(off, v0, v1);
      __syncwarp();
      if (lane == 0) mbar_arrive(B_VM);
    }
  }
}

__device__ __forceinline__ void send_scores(float s0, float s1, uint32_t off, uint32_t peer0, uint32_t peer1, uint32_t bar, int lane) {
  if (SPACK) {
    const uint32_t v = pack_bf16(s0, s1);
    st_async32(peer0 + off, v, peer0 + bar);
    st_async32(peer1 + off, v, peer1 + bar);
    sts32(off, v);
  } else {
    st_async64f(peer0 + off, s0, s1, peer0 + bar);
    st_async64f(peer1 + off, s0, s1, peer1 + bar);
    sts64f(off, s0, s1);
  }
  __syncwarp();
  if (lane == 0) mbar_arrive(bar);
}

template <int MODE>
__device__ __forceinline__ void wo_load(uint32_t* r, int f, uint32_t woa, uint32_t wob, bool third) {
  constexpr int NT = MODE ? 3 : 2;
  if (MODE >= 2 && f % 3 == 2)
    asm volatile("{\n.reg .pred p;\nsetp.ne.u32 p, %5, 0;\nmov.b32 %0, 0;\nmov.b32 %1, 0;\nmov.b32 %2, 0;\nmov.b32 %3, 0;\n"
                 "@p ldmatrix.sync.aligned.m8n8.x4.trans.shared.b16 {%0,%1,%2,%3}, [%4];\n}"
                 : "=r"(r[0]), "=r"(r[1]), "=r"(r[2]), "=r"(r[3]) : "r"(wob + (f / 3) * 512), "r"((uint32_t)third) : "memory");
  else ldsm4t(r, woa + (f % NT) * 32768 + (f / NT) * 2048);
}
template <int MODE, int PF>
__device__ __forceinline__ void wo_phase(uint32_t (&wf)[PF][4], uint32_t woa, uint32_t wob, bool third, uint32_t oba, char* h1p,
                                         uint32_t sel, uint32_t tag) {
  constexpr int NT = MODE ? 3 : 2;
  float c[NT][4];
  uint32_t of[2][4];
  ldsm4t(of[0], oba);
#pragma unroll
  for (int k = 0; k < 8; k++) {
    if ((k & 1) == 0 && k + 2 < 8) ldsm4t(of[((k >> 1) + 1) & 1], oba + ((k >> 1) + 1) * 512);
#pragma unroll
    for (int i = 0; i < NT; i++) {
      const int f = k * NT + i;
      const uint32_t b0 = of[(k >> 1) & 1][2 * (k & 1)], b1 = of[(k >> 1) & 1][2 * (k & 1) + 1];
      if (k == 0) mma16816z(c[i], wf[f % PF], b0, b1); else mma16816(c[i], wf[f % PF], b0, b1);
      if (f + PF < 8 * NT) wo_load<MODE>(wf[f % PF], f + PF, woa, wob, third);
    }
  }
#pragma unroll
  for (int i = 0; i < NT; i++) {
    char* p = h1p + i * (8 * 32768) + ((sel >> (2 * i)) & 3) * 2048;
    const uint32_t tm = (sel >> 10) & 1;
    if (MODE < 2 || i < 2 || third) {
      st_pub32(p, (pack_bf16(c[i][0], c[i][1]) & ~tm) | (tag & tm));
      st_pub32(p + 1024, (pack_bf16(c[i][2], c[i][3]) & ~tm) | (tag & tm));
    }
  }
}
template <int MODE, int F0, int F1, int PF>
__device__ __forceinline__ void wo_prefetch(uint32_t (&wf)[PF][4], uint32_t woa, uint32_t wob, bool third) {
#pragma unroll
  for (int f = F0; f < F1; f++) wo_load<MODE>(wf[f], f, woa, wob, third);
}

template <bool ISV> __device__ __forceinline__ uint32_t tok_addr(uint32_t base, int tid) {
  OPQ;
  return ISV ? base + w * 2048 + (mi & 1) * 1024 + (mi >> 1) * 128 + mr * 16 : base + (mi >> 1) * 1024 + w * 256 + (mi & 1) * 128 + mr * 16;
}
template <bool ISV> __device__ __forceinline__ constexpr uint32_t tok_off(int T, int i) { return ISV ? T * 512 + i * 256 : T * 4096 + i * 2048; }
template <bool ISV, int T, bool ADD>
__device__ __forceinline__ void tok_store(const float (&x)[16], uint32_t a, const uint32_t (&p)[2][4]) {
#pragma unroll
  for (int i = 0; i < 2; i++) {
    uint32_t r[4];
#pragma unroll
    for (int k = 0; k < 4; k++)
      r[k] = !ADD ? pack_bf16(x[8 * i + 2 * k], x[8 * i + 2 * k + 1])
           : PADD ? add_bf16x2(pack_bf16(x[8 * i + 2 * k], x[8 * i + 2 * k + 1]), p[i][k])
                  : pack_bf16(x[8 * i + 2 * k] + bf_lo(p[i][k]), x[8 * i + 2 * k + 1] + bf_hi(p[i][k]));
    stsm4(a + tok_off<ISV>(T, i), r[0], r[1], r[2], r[3]);
  }
}

__device__ __forceinline__ void load_xn(const FParams& P, int seg, uint32_t self) {
  SMAP;
  mbar_expect_tx(B_XN, 49152);
  tma_load_3d(XN, &P.xn12, 0, seg * 32, 0, B_XN);
}

#define DESC_ADD(d, n) asm volatile("add.s64 %0, %0, %1;" : "+l"(d) : "n"(n))

template <bool ISV>
__device__ __forceinline__ void f_wg0(const FParams& P, const WRegs& wr, const int h, const int rank, const uint32_t hw, int tid) {
  using namespace fk;
  const uint32_t self = mapa(0, (hw >> (2 * rank)) & 3), peer0 = mapa(0, (hw >> (ISV ? 0 : 2 * (rank ^ 1))) & 3) - self,
                 peer1 = mapa(0, (hw >> (ISV ? 2 : 4)) & 3) - self;
  SMAP;
  const int tile0 = rank * 22;
  const uint32_t usel = __shfl_sync(0xffffffffu, tid, 0);
  const int warp = __shfl_sync(0xffffffffu, threadIdx.x >> 5, 0);
  constexpr int WMODE = ISV ? 0 : 2;
  const bool three = warp < 2;
  uint32_t d_h2 = D_H2V, h2ph = 1;
  tid ^= 0x5500;
#pragma unroll 1
  for (int s = -1;;) {
    uint32_t ta[ProjCfg<ISV, 0>::NTA][4][4], wsa, mba;
    const char* src = P.xch + H1_BYTES + ((s & 1) * 4 + warp) * 8192 + ((usel >> (16 + (s & 1))) & 1) * 4096;
    {
      const uint32_t ph = (s + 1) & 1;
      float x0[16], x1[16];
      uint32_t t_pub = 0;
      wg_fence();
      static_assert(Chunks<ISV>::MASK == 0x1E, "chunks 1 .. 4 are in shared memory");
      uint64_t db = P.dxn;
      auto rs_chunk = [&](int ci, bool pace) {
#pragma unroll
        for (int u = 0; u < 4; u++) {
          wgmma_rs_n32(x0, wr[ci][0][u], db, (ci | u) != 0);
          wgmma_rs_n32(x1, wr[ci][1][u], db, (ci | u) != 0);
          if (u < 3) DESC_ADD(db, 2); else DESC_ADD(db, 250);
          if (pace) { wg_commit(); wg_wait<2>(); wg_fence(); }
        }
      };
      rs_chunk(0, false);
      t_pub = clk32() - 60;
      PROF(0, 8); PROF(0, 1);
#pragma unroll
      for (int c = 1; c <= 4; c++) {
#pragma unroll
        for (int u = 0; u < 4; u++) {
          const uint64_t dx = make_desc(fk::XN + c * 4096 + u * 32, 16, 1024);
          wgmma_ss_n32_ta(x0, make_desc(fk::WS + (c - 1) * 16384 + u * 2048, 8192, 1024), dx, 1);
          wgmma_ss_n32_ta(x1, make_desc(fk::WS + (c - 1) * 16384 + 8192 + u * 2048, 8192, 1024), dx, 1);
          if (c == 4 && u == 1) { wg_commit(); wg_wait<1>(); named_bar_arrive(NB_XE, 160); wg_fence(); }
        }
        if (c == 3) wg_commit();
      }
      DESC_ADD(db, 1024);
#pragma unroll
      for (int c = 5; c < 10; c++) {
        if (c == 9) named_bar_arrive(NB_ST, 256);
        rs_chunk(c - 4, ((ISV ? PACEV : PACEQ) >> c) & 1);
      }
      wg_commit();
      wg_wait<0>();
      PROF(0, 10);
      const uint32_t tb = ISV ? (ph ? VX2 : VX) : QK;
      auto h2_issue = [&]() {
        spin_until(t_pub + (ISV ? d_h2 : D_H2));
        PROF(0, 13);
        if (elect_one()) { mbar_expect_tx(B_H2 + 8 * warp, 4096); bulk_g2s(MEMB + warp * 4096, src, 4096, B_H2 + 8 * warp); }
      };
      named_bar_sync(NB_CF, ISV ? 160 : 256);
      if ((ISV ? H2_ATV : H2_AT) == 0) h2_issue();
      const uint32_t none[2][4] = {}, tka = tok_addr<ISV>(tb, tid);
      tok_store<ISV, 0, false>(x0, tka, none);
      if ((ISV ? H2_ATV : H2_AT) == 1) h2_issue();
      tok_store<ISV, 1, false>(x1, tka, none);
      if ((ISV ? H2_ATV : H2_AT) == 2) h2_issue();
      named_bar_arrive(NB_DU, 256);
    }
    {
      OPQ;
      wsa = WS + ((mi >> 1) * 8 + mr) * 128 + (((2 * w + (mi & 1)) ^ mr) << 4);
      mba = MEMB + lane * 16;
      PIN(wsa); PIN(mba);
      {
        const uint32_t chk = MEMB + w * 4096 + lane * 32 + lg * 4, bar = B_H2 + 8 * warp;
        PROF(0, 11);
        proj_mem_prefetch<ISV, 0, 0, NPRE0>(ta, wsa);
#pragma unroll 1
        for (int tries = 0; tries < POLL_TRIES; tries++) {
          mbar_spin(bar, h2ph);
          h2ph ^= 1;
          const uint32_t mx = max(max(lds32(chk), lds32(chk + 1024)), max(lds32(chk + 2048), lds32(chk + 3072)));
          if (__all_sync(0xffffffffu, mx != EMPTY)) break;
          RETRY(1);
          if (elect_one()) { mbar_expect_tx(bar, 4096); bulk_g2s(MEMB + warp * 4096, src, 4096, bar); }
        }
      }
      PROF(0, 12);
      named_bar_arrive(NB_M1, 256);
      proj_mem_prefetch<ISV, 0, NPRE0, NTA0>(ta, wsa);
      named_bar_sync(NB_M0, 128);
    }
    s++;
    tid ^= 0x5500;
    {
      float a0[4], a1[4];
      proj_mem<ISV, 0>(wr, ta, wsa, mba, a0, a1);
      PROF(0, 2);
      uint32_t unused[4];
      proj_finish<ISV, 0>(a0, a1, peer0, peer1, self, tid, warp, unused);
      PROF(0, 3);
      if (s + 1 == cfg::NSEG) break;
      uint32_t wf[PF0][4], woa, wob;
      bool xn_ok;
      {
        OPQ;
        if (!ISV) {
          uint32_t qf[4][4], kf[2][4];
          const uint32_t qa = PT + 2048 + lane * 16, ka = QK + 4096 + w * 1024 + lane * 16;
          ldsm4t(qf[0], qa); ldsm4t(kf[0], ka); ldsm4t(qf[1], qa + 512);
          ldsm4t(qf[2], qa + 1024); ldsm4t(kf[1], ka + 512); ldsm4t(qf[3], qa + 1536);
          float c0[4], c1[4];
          mma16816z(c0, qf[0], kf[0][0], kf[0][1]);
          mma16816z(c1, qf[1], kf[0][2], kf[0][3]);
          mma16816(c0, qf[2], kf[1][0], kf[1][1]);
          mma16816(c1, qf[3], kf[1][2], kf[1][3]);
          const float s0 = (c0[0] + c0[2]) + (c1[0] + c1[2]), s1 = (c0[1] + c0[3]) + (c1[1] + c1[3]);
          send_scores(s0, s1, SP + rank * SP_SRC + t7 * SPW, peer0, peer1, B_SM, lane);
        }
        PROF(0, 4);
        woa = WO + 16384 + ((mi >> 1) * 8 + mr) * 128 + (((2 * w + (mi & 1)) ^ mr) << 4);
        wob = WO + 81920 + w * 4096 + ((mi >> 1) * 8 + mr) * 32 + (((mi & 1) ^ (mr >> 2)) << 4);
        uint32_t vf[2][2][4], vm[2][2];
        if (s == 0) mbar_spin(B_WO, 0);
        if (!ISV) mbar_spin(B_VX, s & 1);
        PROF(0, 14);
#pragma unroll
        for (int T = 0; T < 2; T++)
#pragma unroll
          for (int kk = 0; kk < 2; kk++) ldsm4(vf[T][kk], ((ISV && (s & 1)) ? VX2 : VX) + w * 2048 + (mi & 1) * 1024 + (mi >> 1) * 128 + mr * 16 + T * 512 + kk * 256);
        wo_prefetch<WMODE, 0, PF0A>(wf, woa, wob, three);
        uint32_t spa = SP + lane * SPW, vma = VM + t7 * 8, oa = OB + (mi >> 1) * 1024 + w * 256 + (mi & 1) * 128 + mr * 16;
        PIN(spa); PIN(vma); PIN(oa);
        if (ISV) {
          d_h2 = D_H2L;
          if (!__all_sync(0xffffffffu, mbar_test(B_SM, s & 1))) { d_h2 = D_H2V; mbar_spin(B_SM, s & 1); }
        } else {
          mbar_spin(B_SM, s & 1);
        }
        PROF(0, 5);
        float sc[10];
#pragma unroll
        for (int j = 0; j < 5; j++) {
          if (SPACK) {
            const uint32_t x = lds32(spa + j * 128), y = lds32(spa + SP_SRC + j * 128);
            sc[2 * j] = bf_lo(x) + bf_lo(y); sc[2 * j + 1] = bf_hi(x) + bf_hi(y);
          } else {
            const float2 x = lds64f(spa + j * 256), y = lds64f(spa + SP_SRC + j * 256);
            sc[2 * j] = x.x + y.x; sc[2 * j + 1] = x.y + y.y;
          }
        }
        const bool vm_ok = mbar_test(B_VM, s & 1);
        lds64(vm[0], vma); lds64(vm[1], vma + 1024);
        float m = fmaxf(fmaxf(fmaxf(sc[0], sc[1]), fmaxf(sc[2], sc[3])), fmaxf(fmaxf(sc[4], sc[5]), fmaxf(sc[6], sc[7])));
        m = fmaxf(m, fmaxf(sc[8], sc[9]));
        const float cs = 0.08838834764831845f * 1.4426950408889634f;
        uint32_t pb[5];
        m = fmaxf(m, __shfl_xor_sync(0xffffffffu, m, 1));
        m = fmaxf(m, __shfl_xor_sync(0xffffffffu, m, 2));
        if (ISV ? GATE_MX : GATE_Q) named_bar_arrive(NB_MX, 256);
        const float mc = -m * cs;
#pragma unroll
        for (int j = 0; j < 5; j++) pb[j] = pack_bf16(ex2_approx(fmaf(sc[2 * j], cs, mc)), ex2_approx(fmaf(sc[2 * j + 1], cs, mc)));
        PROF(0, 15);
        if (!vm_ok) { mbar_spin(B_VM, s & 1); lds64(vm[0], vma); lds64(vm[1], vma + 1024); }
        PROF(0, 6);
        float o0[4], o1[4], rs[4];
        const uint32_t ones[4] = {0x3F803F80u, 0x3F803F80u, 0x3F803F80u, 0x3F803F80u};
        mma16816z(rs, ones, pb[0], pb[1]);
        mma16816z(o0, vf[0][0], pb[0], pb[1]);
        mma16816z(o1, vf[1][0], pb[0], pb[1]);
        mma16816(rs, ones, pb[2], pb[3]);
        mma16816(o0, vf[0][1], pb[2], pb[3]);
        mma16816(o1, vf[1][1], pb[2], pb[3]);
        mma1688(rs, ones[0], ones[0], pb[4]);
        mma1688(o0, vm[0][0], vm[0][1], pb[4]);
        mma1688(o1, vm[1][0], vm[1][1], pb[4]);
        const float i0 = rcp_approx(rs[0]), i1 = rcp_approx(rs[1]);
        stsm4(oa, pack_bf16(o0[0] * i0, o0[1] * i1), pack_bf16(o0[2] * i0, o0[3] * i1),
              pack_bf16(o1[0] * i0, o1[1] * i1), pack_bf16(o1[2] * i0, o1[3] * i1));
      }
      {
        OPQ;
        named_bar_arrive(NB_O, 256);
        wo_prefetch<WMODE, PF0A, PF0>(wf, woa, wob, three);
        xn_ok = mbar_test(B_XN, (s + 1) & 1);
        char* h1p = P.xch + (tile0 + 4 + w) * 32768 + (h >> 3) * 8192 + (h & 7) * 128 + (((2 * lq + (lg & 1)) ^ (h & 7)) << 4) + (lg >> 1) * 4;
        uint32_t oba = OB + lane * 16;
        PIN(oba);
        PROF(0, 7);
        named_bar_sync(NB_O0, 128);
        const uint32_t tag = ((s >> 1) & 1) ^ 1;
        wo_phase<WMODE>(wf, woa, wob, three, oba, h1p, tid >> 8, tag);
        PROF(0, 9);
        if (!xn_ok) mbar_spin(B_XN, (s + 1) & 1);
        named_bar_sync(NB_HD, 256);
      }
    }
  }
}

template <bool ISV>
__device__ __forceinline__ void f_wg1(const FParams& P, const WRegs& wr, const int h, const int rank, const uint32_t hw, int tid) {
  using namespace fk;
  const uint32_t self = mapa(0, (hw >> (2 * rank)) & 3), peer0 = mapa(0, (hw >> (ISV ? 0 : 2 * (rank ^ 1))) & 3) - self,
                 peer1 = mapa(0, (hw >> (ISV ? 2 : 4)) & 3) - self;
  SMAP;
  const int tile0 = rank * 22;
  const uint32_t usel = __shfl_sync(0xffffffffu, tid, 0);
  const int warp = __shfl_sync(0xffffffffu, (threadIdx.x >> 5) & 3, 0);
  constexpr int WMODE = 1;
  uint32_t h1ph = 0;
  auto o_done = [&](int mb) {
    tma_store_wait_all();
    asm volatile("fence.proxy.async.global;" ::: "memory");
    asm volatile("red.relaxed.gpu.global.add.u32 [%0], 1;" ::"l"(&g_oflag[mb]) : "memory");
  };
  uint32_t vmo[4] = {0, 0, 0, 0};
  if (ISV) {
    OPQ;
    sts32(PT + (t7 >> 2) * 128 + ((5 ^ lg) << 4) + lq * 4, 0);
    sts32(PT + (t7 >> 2) * 128 + ((6 ^ lg) << 4) + lq * 4, 0);
  }
  tid ^= 0x5500;
#pragma unroll 1
  for (int s = -1;;) {
    uint32_t ta[ProjCfg<ISV, 1>::NTA][4][4], wsa, mba;
    if (s + 1 < cfg::NSEG) mbar_spin(B_XN, (s + 1) & 1);
    const uint32_t t_pub = clk32();
    auto refill = [&]() {
      if (warp == 3) {
        named_bar_sync(NB_XE, 160);
        if (elect_one()) {
          mbar_expect_tx(B_XN + 8, 16384);
          tma_load_3d(XN, &P.xn, 0, (s + 1) * 32, 12, B_XN + 8);
        }
      }
    };
    auto arm = [&]() {
      if ((tid & 255) == 160) {
        if (s == 1) st_pub32(&g_mask[3 * h + rank], 0);
        if (s + 2 < cfg::NSEG) { mbar_expect_tx(B_SM, ISV ? 2 * SP_SRC : SP_SRC); if (!ISV) mbar_expect_tx(B_VX, 8192); }
        if (!ISV && s + 1 < cfg::NSEG) mbar_expect_tx(B_VM, 2048);
        if (ISV && s >= 1 && s < cfg::NSEG) mbar_expect_tx(B_ST, 7168);
      }
      if (ISV && s < cfg::NSEG && (tid & 254) == 192) mbar_arrive_remote(((tid & 1) ? peer1 : peer0) + B_ST);
      __syncwarp();
    };
    if (ISV) {
      if (s >= 0) arm();
      if (s >= 1) {
        OPQ;
        if (warp == 0 && (s & 3) == 1 && s > 1) { if (elect_one()) o_done((s - 2) >> 2); }
        const uint32_t vb = (s & 1) ? VX : VX2;
        float x0[16], x1[16];
        wg_fence();
        wgmma_rs_n32(x0, vmo, make_desc(fk::PT + 64, 16, 1024), 0);
        wgmma_rs_n32(x1, vmo, make_desc(fk::PT + 96, 16, 1024), 0);
#pragma unroll
        for (int kk = 0; kk < 2; kk++) {
          wgmma_ss_n32(x0, make_desc0(vb + kk * 256, 128, 1024), make_desc(fk::PT + kk * 32, 16, 1024), 1);
          wgmma_ss_n32(x1, make_desc0(vb + 512 + kk * 256, 128, 1024), make_desc(fk::PT + kk * 32, 16, 1024), 1);
        }
        wg_commit();
        wg_wait<0>();
        named_bar_sync(NB_W1, 128);
        PROF(1, 4);
        const uint32_t stg = vb + (8 * (mi >> 1) + mr) * 128 + (((2 * w + (mi & 1)) ^ mr) << 4);
#pragma unroll
        for (int T = 0; T < 2; T++) {
          const float* x = T ? x1 : x0;
#pragma unroll
          for (int jj = 0; jj < 4; jj += 2)
            stsm4t(stg + T * 4096 + jj * 1024, pack_bf16(x[4 * jj], x[4 * jj + 1]), pack_bf16(x[4 * jj + 2], x[4 * jj + 3]),
                   pack_bf16(x[4 * jj + 4], x[4 * jj + 5]), pack_bf16(x[4 * jj + 6], x[4 * jj + 7]));
        }
        fence_proxy_async_smem();
        named_bar_sync(NB_W1, 128);
        PROF(1, 10);
        if (warp == 0) {
          if (elect_one()) {
            tma_store_3d(&P.o, vb, 0, (s - 1) * 32, 2 * h);
            tma_store_commit();
          }
          __syncwarp();
        }
        if (s == cfg::NSEG) break;
      }
      if (s + 1 < cfg::NSEG) refill();
      PROF(1, 11);
    } else if (s < 0) {
      named_bar_arrive(NB_CF, 256);
      refill();
    } else {
      float x[24];
      wg_fence();
#pragma unroll
      for (int k = 0; k < 4; k++) wgmma_ss_n48_tt(x, make_desc0(fk::QK + k * 256, 128, 1024), make_desc0(fk::QK + 4096 + k * 256, 128, 1024), k != 0);
      wg_commit();
      arm();
      auto send_tok = [&]() {
        if (warp < 2) {
          OPQ;
          const uint32_t d0 = peer1 + QK + rank * 3584 + lane * 8 + w * 1280, d1 = d0 + 512 + w * 512, bar = peer1 + B_ST;
          mbar_spin(B_ST, s & 1);
          const float NEG = -500000000.0f / 0.08838834764831845f;
          const bool m0 = 2 * lq > lg, m1 = 2 * lq + 1 > lg;
          st_async64f(d0, x[16] + x[20], x[17] + x[21], bar);
          st_async64f(d1, x[18] + x[22], x[19] + x[23], bar);
          st_async64f(d1 + 256, x[2], x[3], bar);
          if (warp == 0) {
            st_async64f(d0 + 256, m0 ? NEG : x[0], m1 ? NEG : x[1], bar);
            st_async64f(d1 + 512, m0 ? NEG : x[6], m1 ? NEG : x[7], bar);
          } else {
            st_async64f(d0 + 256, x[0], x[1], bar);
            st_async64f(d1 + 512, x[6], x[7], bar);
            st_async64f(d0 + 512, x[4], x[5], bar);
            st_async64f(d0 + 768, m0 ? NEG : x[8], m1 ? NEG : x[9], bar);
            st_async64f(d1 + 768, x[10], x[11], bar);
            st_async64f(d1 + 1024, m0 ? NEG : x[14], m1 ? NEG : x[15], bar);
          }
        }
        PROF(1, 4);
      };
      const bool fin = s + 1 == cfg::NSEG;
      OPQ;
      const int j = 2 * h + rank;
      const char* src = P.xch + j * 32768 + warp * 8192 + (((usel >> 14) & 2) + (s & 1)) * 2048;
      char* dst = P.xch + H1_BYTES + (j >> 4) * 8192 + (lq >> 1) * 4096 + (j & 15) * 256 + (lq & 1) * 128 + (2 * w + (lg & 1)) * 16 + (lg >> 1) * 4;
      const uint32_t chk = VX + mi * 2048 + mr * 128 + (w ^ (mr >> 1)) * 32 + ((lane & 1) + 2 * mi) * 4;
      const uint32_t tmask = (s >> 1) & 1;
      if (!fin) {
        spin_until(t_pub + D_H1);
        if (elect_one()) { mbar_expect_tx(B_H1, 2048); bulk_g2s(VX + warp * 2048, src, 2048, B_H1); }
      }
      __syncwarp();
      wg_wait<0>();
      PROF(1, 6);
      send_tok();
      if (fin) { mbar_spin(B_VM, s & 1); break; }
      named_bar_arrive(NB_CF, 256);
      if (REFILL_EARLY) refill();
#pragma unroll 1
      for (int tries = 0; tries < POLL_TRIES; tries++) {
        float d0[4], d1[4], d2[4], d3[4];
        mbar_spin(B_H1, h1ph);
        h1ph ^= 1;
        PROF(1, 10);
        const uint32_t t0 = lds32(chk), t1 = lds32(chk + 1024);
        wg_fence();
        const uint64_t ones = (uint64_t)(fk::ONES >> 4);
        wgmma_ss_n8_ta(d0, make_desc(fk::VX, 8192, 2048), ones, 0);
        wgmma_ss_n8_ta(d1, make_desc(fk::VX + 1024, 8192, 2048), ones, 0);
        wgmma_ss_n8_ta(d2, make_desc(fk::VX + 4096, 8192, 2048), ones, 0);
        wgmma_ss_n8_ta(d3, make_desc(fk::VX + 5120, 8192, 2048), ones, 0);
        wg_commit();
        uint32_t tt;
        asm volatile("lop3.b32 %0, %1, %2, %3, 0x42;" : "=r"(tt) : "r"(t0), "r"(t1), "r"(tmask) : "memory");
        uint32_t ok;
        named_bar_and(NB_W1, 128, tt & 1, ok);
        if (!ok) { if (elect_one()) { mbar_expect_tx(B_H1, 2048); bulk_g2s(VX + warp * 2048, src, 2048, B_H1); } }
        wg_wait<0>();
        if (ok) {
          st_pub32(dst + (s & 1) * 32768, (lq & 1) ? pack_bf16(d1[0] + d3[0], d1[2] + d3[2]) : pack_bf16(d0[0] + d2[0], d0[2] + d2[2]));
          PROF(1, 12);
          st_pub32(dst + ((s & 1) ^ 1) * 32768, EMPTY);
          break;
        }
        RETRY(0);
      }
      named_bar_sync(NB_W1, 128);
      if ((tid & 255) == 192) mbar_arrive_remote(peer1 + B_PF);
      __syncwarp();
      if (!REFILL_EARLY) refill();
      PROF(1, 11);
    }
    if (!ISV || s + 1 < cfg::NSEG) {
      const uint32_t ph = (s + 1) & 1;
      float x0[16], x1[16];
      uint64_t db = P.dxn + 10 * 256;
      named_bar_sync(NB_ST, 256);
      wg_fence();
#pragma unroll
      for (int c = 0; c < 6; c++) {
        if (c == 2) { PROF(1, 0); mbar_spin(B_XN + 8, ph); PROF(1, 15); wg_fence(); }
        if (ISV && c == CF_AT) {
          if (warp == 0) {
            if (elect_one()) tma_store_wait_read();
            __syncwarp();
            named_bar_arrive(NB_CF, 160);
          }
          wg_fence();
        }
#pragma unroll
        for (int u = 0; u < 4; u++) {
          wgmma_rs_n32(x0, wr[c][0][u], db, (c | u) != 0);
          wgmma_rs_n32(x1, wr[c][1][u], db, (c | u) != 0);
          if (u < 3) DESC_ADD(db, 2); else if (c == 1) DESC_ADD(db, 250 - 12 * 256); else DESC_ADD(db, 250);
        }
      }
      wg_commit();
      OPQ;
      const uint32_t tb = ISV ? (ph ? VX2 : VX) : QK, tka = tok_addr<ISV>(tb, tid);
      uint32_t p0[2][4], p1[2][4];
      named_bar_sync(NB_DU, 256);
      ldsm4(p1[0], tka + tok_off<ISV>(1, 0)); ldsm4(p1[1], tka + tok_off<ISV>(1, 1));
      ldsm4(p0[0], tka + tok_off<ISV>(0, 0)); ldsm4(p0[1], tka + tok_off<ISV>(0, 1));
      if (ISV && s >= 0) mbar_spin(B_PF, s & 1);
      wg_wait<0>();
      PROF(1, 13);
      tok_store<ISV, 1, true>(x1, tka, p1);
      tok_store<ISV, 0, true>(x0, tka, p0);
      if (ISV && s + 2 < cfg::NSEG) {
        fence_proxy_async_smem();
        __syncwarp();
        if (elect_one()) {
          bulk_s2s(peer0 + VX + warp * 2048, tb + warp * 2048, 2048, peer0 + B_VX);
          bulk_s2s(peer1 + VX + warp * 2048, tb + warp * 2048, 2048, peer1 + B_VX);
        }
      }
      wsa = WS + ((mi >> 1) * 8 + mr) * 128 + (((2 * w + (mi & 1)) ^ mr) << 4);
      mba = MEMB + lane * 16;
      PIN(wsa); PIN(mba);
      proj_mem_prefetch<ISV, 1, 0, NTA1>(ta, wsa);
      PROF(1, 14);
      named_bar_sync(NB_M1, 256);
      s++;
      PROF(1, 1);
      float a0[4], a1[4];
      proj_mem<ISV, 1>(wr, ta, wsa, mba, a0, a1);
      PROF(1, 2);
      proj_finish<ISV, 1>(a0, a1, peer0, peer1, self, tid, warp, vmo);
      PROF(1, 3);
    } else {
      OPQ;
      mbar_spin(B_VM, s & 1);
      lds64(vmo, VM + t7 * 8); lds64(vmo + 2, VM + 1024 + t7 * 8);
      s++;
    }
    tid ^= 0x5500;
    const bool last = s + 1 >= cfg::NSEG;
    constexpr int PFW = ISV ? PF1V : PF1;
    uint32_t wf[PFW][4], woa;
    if (ISV) {
      OPQ;
      woa = WO + ((mi >> 1) * 8 + mr) * 128 + (((2 * w + (mi & 1)) ^ mr) << 4);
      if (s >= 1) {
        const uint32_t sa = QK + ((w * (w + 3)) >> 1) * 256 + lane * 8;
        mbar_spin(B_ST, (s - 1) & 1);
        float sc[10];
        {
          const float NEG = -1000000000.0f / 0.08838834764831845f;
          float2 x[5], y[5];
#pragma unroll
          for (int b = 0; b < 5; b++) {
            x[b] = b < 2 ? lds64f(sa + b * 256) : lds64f_if(sa + b * 256, b <= w + 1, NEG);
            y[b] = b < 2 ? lds64f(sa + 3584 + b * 256) : lds64f_if(sa + 3584 + b * 256, b <= w + 1, 0.f);
          }
#pragma unroll
          for (int b = 0; b < 5; b++) { sc[2 * b] = x[b].x + y[b].x; sc[2 * b + 1] = x[b].y + y[b].y; }
        }
        float m = fmaxf(fmaxf(fmaxf(sc[0], sc[1]), fmaxf(sc[2], sc[3])), fmaxf(fmaxf(sc[4], sc[5]), fmaxf(sc[6], sc[7])));
        m = fmaxf(m, fmaxf(sc[8], sc[9]));
        m = fmaxf(m, __shfl_xor_sync(0xffffffffu, m, 1));
        m = fmaxf(m, __shfl_xor_sync(0xffffffffu, m, 2));
        const float cs = 0.08838834764831845f * 1.4426950408889634f;
#pragma unroll
        for (int i = 0; i < 10; i++) sc[i] = ex2_approx((sc[i] - m) * cs);
        float sum = ((sc[0] + sc[1]) + (sc[2] + sc[3])) + ((sc[4] + sc[5]) + (sc[6] + sc[7])) + (sc[8] + sc[9]);
        sum += __shfl_xor_sync(0xffffffffu, sum, 1);
        sum += __shfl_xor_sync(0xffffffffu, sum, 2);
        const float inv = rcp_approx(sum);
        const uint32_t pa = PT + (w * 8 + mr) * 128, pm = pack_bf16(sc[0] * inv, sc[1] * inv);
        stsm4(pa + ((mi ^ mr) << 4), pack_bf16(sc[2] * inv, sc[3] * inv), pack_bf16(sc[4] * inv, sc[5] * inv),
              pack_bf16(sc[6] * inv, sc[7] * inv), pack_bf16(sc[8] * inv, sc[9] * inv));
        asm volatile("stmatrix.sync.aligned.m8n8.x2.shared.b16 [%0], {%1,%1};" ::"r"(pa + ((((mi & 1) ? 7 : 4) ^ mr) << 4)), "r"(pm) : "memory");
      }
      if (warp == 3 && !last) {
        mbar_spin(B_VM, s & 1);
        if (elect_one()) load_xn(P, s + 1, self);
      }
      PROF(1, 5);
    } else {
      if (warp == 0) {
        OPQ;
        uint32_t kf[4][4], qf[4][4];
        float c0[4], c1[4], d0[4], d1[4];
        const uint32_t ka = PT + (mi >> 1) * 1024 + (mi & 1) * 128 + mr * 16;
#pragma unroll
        for (int k = 0; k < 4; k++) { ldsm4t(qf[k], PT + 2048 + k * 512 + lane * 16); ldsm4t(kf[k], ka + k * 256); }
        mma16816z(c0, qf[0], kf[0][0], kf[0][1]); mma16816z(c1, qf[0], kf[0][2], kf[0][3]);
        mma16816z(d0, qf[1], kf[1][0], kf[1][1]); mma16816z(d1, qf[1], kf[1][2], kf[1][3]);
        mma16816(c0, qf[2], kf[2][0], kf[2][1]); mma16816(c1, qf[2], kf[2][2], kf[2][3]);
        mma16816(d0, qf[3], kf[3][0], kf[3][1]); mma16816(d1, qf[3], kf[3][2], kf[3][3]);
        const float s0 = ((c0[0] + c0[2]) + (c1[0] + c1[2])) + ((d0[0] + d0[2]) + (d1[0] + d1[2]));
        const float s1 = ((c0[1] + c0[3]) + (c1[1] + c1[3])) + ((d0[1] + d0[3]) + (d1[1] + d1[3]));
        if (!last) send_scores(s0, s1, SP + rank * SP_SRC + (128 + lane) * SPW, peer0, peer1, B_SM, lane);
        PROF(1, 5);
      } else {
        const uint32_t t_c = clk32() + lds32(B_XN) * 0;
        if (warp == 3 && !last) { if (elect_one()) load_xn(P, s + 1, self); }
        if (XPF && warp == 2 && s + 3 < cfg::NSEG) {
          if (elect_one()) {
            if (XPF == 1) l2_prefetch(P.xn_ptr + (size_t)((s + 2) * 32 + ((h + 16 * rank) & 31)) * cfg::D, 2048);
            if (XPF == 2) l2_prefetch(P.xn_ptr + (size_t)((s + 1) * 32 + ((h + 16 * rank) & 31)) * cfg::D + 768, 512);
            if (XPF == 3 && rank == 0) asm volatile("cp.async.bulk.prefetch.tensor.3d.L2.global [%0, {0, %1, 12}];" ::"l"(&P.xn), "r"((s + 1) * 32) : "memory");
          }
        }
        spin_until(t_c + D_ST);
      }
      OPQ;
      woa = WO + ((mi >> 1) * 8 + mr) * 128 + (((2 * w + (mi & 1)) ^ mr) << 4);
    }
    if (!last) {
      OPQ;
      uint32_t oba = OB + lane * 16;
      if (s == 0) mbar_spin(B_WO, 0);
      if (!ISV) wo_prefetch<WMODE, 0, PF1Q>(wf, woa, 0, true);
      if (ISV ? GATE_MX : GATE_Q) named_bar_sync(NB_MX, 256);
      wo_prefetch<WMODE, ISV ? 0 : PF1Q, PFW>(wf, woa, 0, true);
      char* h1p = P.xch + (tile0 + w) * 32768 + (h >> 3) * 8192 + (h & 7) * 128 + (((2 * lq + (lg & 1)) ^ (h & 7)) << 4) + (lg >> 1) * 4;
      fence_proxy_async_smem();
      PROF(1, 7);
      named_bar_sync(NB_O, 256);
      PROF(1, 8);
      wo_phase<WMODE>(wf, woa, 0, true, oba, h1p, tid >> 8, ((s >> 1) & 1) ^ 1);
      PROF(1, 9);
      named_bar_sync(NB_HD, 256);
    } else {
      fence_proxy_async_smem();
      named_bar_sync(NB_W1, 128);
    }
  }
  if (ISV && warp == 0) { if (elect_one()) o_done(15); }
}

template <bool ISV, int WG>
__device__ __forceinline__ void f_main(const FParams& P, const int h, const int rank, const uint32_t hw) {
  using namespace fk;
  const uint32_t self = mapa(0, (hw >> (2 * rank)) & 3);
  SMAP;
  const int tid = __shfl_sync(0xffffffffu, threadIdx.x, threadIdx.x & 31);
  const int tile0 = rank * 22, ntile = ISV ? 20 : 22;
  const CUtensorMap* m0 = ISV ? &P.wv : &P.wq;
  const CUtensorMap* m1 = ISV ? &P.wv : &P.wk;
  const int col0 = h * 128 + (ISV ? 0 : 64 * rank), col1 = h * 128 + (ISV ? 64 : 64 * rank);
  WRegs wr;
  uint32_t sel = 0;
  {
    OPQ;
    const uint32_t a = SM0 + WG * 16384 + ((mi >> 1) * 8 + mr) * 128 + (((2 * w + (mi & 1)) ^ mr) << 4);
    uint2 mi0 = make_uint2(0, 0);
    if (!ISV && WG == 1) mi0 = *reinterpret_cast<const uint2*>(P.mem0 + ((lane >> 1) & 7) * cfg::D + (2 * h + rank) * 16 + (lane >> 4) * 8 + (lane & 1) * 4);
#pragma unroll
    for (int i = 0; i < 6; i++) {
      if (i == MASK_AT && WG == 1 && w == 1) {
        uint4 v;
#pragma unroll 1
        for (int tries = 0; tries < POLL_TRIES; tries++) {
          asm volatile("ld.acquire.gpu.global.v4.u32 {%0,%1,%2,%3}, [%4];" : "=r"(v.x), "=r"(v.y), "=r"(v.z), "=r"(v.w)
                       : "l"(&g_mask[4 * min(lane, 23)]) : "memory");
          if (__all_sync(0xffffffffu, v.x & v.y & v.z & v.w & 0x100)) break;
          __nanosleep(100);
        }
        sts128(OB + lane * 16, v.x, v.y, v.z, v.w);
      }
      mbar_wait(B_PB + 8 * i, 0);
      PRO(8 + i);
#pragma unroll
      for (int T = 0; T < 2; T++)
#pragma unroll
        for (int u = 0; u < 4; u++) ldsm4t(wr[i][T][u], a + i * 32768 + T * 8192 + u * 2048);
      named_bar_sync(NB_C, 256);
      if (WG == 1 && w == (i & 3)) {
        if (elect_one()) {
          if (i <= 2 && i + PRE_G < 6) {
#pragma unroll 1
            for (int n = 2 * (i + PRE_G); n < (i == 2 ? 12 : 2 * (i + PRE_G) + 2); n++) {
              const int ii = n >> 1, row = Chunks<ISV>::rf(n & 1, ii) * 64;
              if (!(n & 1)) mbar_expect_tx(B_PB + 8 * ii, 32768);
              tma_load_2d(SM0 + n * 16384, m0, col0, row, B_PB + 8 * ii);
              tma_load_2d(SM0 + n * 16384 + 8192, m1, col1, row, B_PB + 8 * ii);
            }
          }
          if (i == 3 || i == 4) {
            const int p0 = i == 3 ? 0 : 5, p1 = i == 3 ? 5 : 8;
            mbar_expect_tx(B_W, (p1 - p0) * 8192);
#pragma unroll 1
            for (int p = p0; p < p1; p++) tma_load_2d(WS + p * 8192, (p & 1) ? m1 : m0, (p & 1) ? col1 : col0, Chunks<ISV>::sm(p >> 1) * 64, B_W);
          }
          if (i == 5) {
            asm volatile("fence.proxy.async.global;" ::: "memory");
            load_xn(P, 0, self);
          }
          if (i == WO_AT) {
            mbar_expect_tx(B_WO, ntile * 4096);
#pragma unroll 1
            for (int t = 0; t < 5; t++) tma_load_2d(WO + t * 16384, &P.wo, tile0 * 16 + t * 64, h * 128, B_WO);
            if (!ISV) {
              tma_load_2d(WO + 81920, &P.wo16, tile0 * 16 + 320, h * 128, B_WO);
              tma_load_2d(WO + 86016, &P.wo16, tile0 * 16 + 336, h * 128, B_WO);
            }
          }
        }
      }
    }
    PROF2(1);
    if (!ISV && WG == 1 && w < 2) st_pub64(P.xch + H1_BYTES + 32768 + (h >> 3) * 8192 + w * 4096 + ((2 * h + rank) & 15) * 256 + lane * 8, mi0.x, mi0.y);
    if (blockIdx.x == 2 && tid == 160) { __threadfence(); st_pub128(g_lnok, 0x100); }
#pragma unroll
    for (int i = 0; i < 3; i++) {
      const int t = min(tile0 + 8 * i + w + (WG ? 0 : 4), 63);
      sel |= ((lds32(OB + ((t >> 1) * 3 + (t & 1)) * 4) >> (h >> 3)) & 1) << (2 * i + 1);
    }
    const uint32_t own = lds32(OB + (3 * h + rank) * 4) >> w, m2 = lds32(OB + (3 * h + 2) * 4) >> w;
    sel |= (own & 1) << 7 | (m2 & 1) << 8 | (m2 & 16) << 5;
    sel |= (((((lg ^ h) & 1) << 2) | (lg >> 1)) == (h & 1) + 2 * (h >> 3)) << 10;
  }
  asm volatile("barrier.cluster.wait.aligned;" ::: "memory");
  PRO(14);
  mbar_wait(B_W, 0);
  mbar_wait(B_XN, 0);
  PRO(15);
  PROF2(4);
  GTSYNC(0);
  PROF2(2);
  KT_END(8);
  if (WG == 0) f_wg0<ISV>(P, wr, h, rank, hw, tid | sel << 8); else f_wg1<ISV>(P, wr, h, rank, hw, tid | sel << 8);
}

__device__ __forceinline__ void f_tail(const FParams& P, const int h, const uint32_t rank, const bool isv) {
  using namespace fk;
  const uint32_t self = mapa(0, rank), base = self + SM0;
  const uint32_t FULL = self + SP, EMPT = FULL + 32, NOG = FULL + 64, RES = FULL + 72;
  const int tid = threadIdx.x, lane = tid & 31, wv = __shfl_sync(0xffffffffu, tid >> 5, 0), wg = wv >> 2;
  const int kq = h & 7, nt = h >> 3, mb = TAIL_MB0 + rank;
  auto a_off = [](uint32_t st) { return (0x98685800u >> (8 * st) & 255) * 1024; };
  auto b_off = [](uint32_t st) { return (0xA8783010u >> (8 * st) & 255) * 1024; };
  static_assert(VX2 - SM0 == 80 * 1024 && VX - SM0 == 200 * 1024, "stage layout");
  auto load_b = [&](int kb) {
    const uint32_t sb = base + b_off(kb & 3), full = FULL + 8 * (kb & 3);
    mbar_expect_tx(full, 49152);
    tma_load_2d_mc(sb + rank * 8192, &P.tb, nt * 256 + ((rank + (kq >> 1)) & 3) * 64, (kq * 8 + kb) * 64, full, 7);
    if (kb % 3 == rank) tma_load_2d_mc(sb + 3 * 8192, &P.tb, nt * 256 + ((3 + (kq >> 1)) & 3) * 64, (kq * 8 + kb) * 64, full, 7);
  };
  auto load_a = [&](int kb) { tma_load_2d(base + a_off(kb & 3), &P.ta, (kq * 8 + kb) * 64, mb * 128, FULL + 8 * (kb & 3)); };
  TL(0);
  TL2(128, 10); TL2(160, 11);
  if (wv == 0) {
    if (elect_one()) {
      prefetch_tmap(&P.tb); prefetch_tmap(&P.ta);
      if (isv) mbar_spin(self + B_VM, (cfg::NSEG - 1) & 1);
      for (int i = 0; i < 4; i++) { mbar_init(FULL + 8 * i, 1); mbar_init(EMPT + 8 * i, 24); }
      mbar_init(RES, 1);
      fence_barrier_init();
      mbar_arrive_cluster(self + B_W, rank == 0 ? 1 : 0);
      mbar_arrive_cluster(self + B_W, rank == 2 ? 1 : 2);
      mbar_spin(self + B_W, 1);
#pragma unroll 1
      for (int kb = 0; kb < 4; kb++) load_b(kb);
      TL2(0, 12);
      wait_count(&g_oflag[mb], 32);
      asm volatile("fence.proxy.async.global;" ::: "memory");
      TL2(0, 13);
#pragma unroll 1
      for (int kb = 0; kb < 4; kb++) load_a(kb);
      TL2(0, 14);
    }
  } else if (wv == 1) {
    if (lane == 0) {
      prefetch_tmap(&P.tx); prefetch_tmap(&P.tg);
      const bool ng = ld_strong4(&g_next) == 0;
      sts32(NOG, ng);
      if (ng) g_tfix[blockIdx.x] = 1; else wait_count(&g_cnt[3][mb], GATE_CNT);
    }
  }
  float acc[128];
  __syncthreads();
  KT_START(7);
  const bool nog = lds32(NOG);
  if (nog) TL(15); else TL(15);
  if (wv == 1) {
    if (elect_one()) {
      asm volatile("fence.proxy.async.global;" ::: "memory");
      mbar_expect_tx(RES, 16384);
      tma_load_2d(self + VX, &P.tx, nt * 256 + kq * 32, mb * 128, RES);
      tma_load_2d(self + QK, &P.tg, nt * 256 + kq * 32, mb * 128, RES);
    }
  }
#pragma unroll 1
  for (int kb = 0; kb < 8; kb++) {
    const uint32_t st = kb & 3, sa = base + a_off(st) + wg * 8192, sb = base + b_off(st);
    mbar_spin(FULL + 8 * st, kb >> 2);
    if (kb == 0) TL(2);
    if (kb == 4) TL(3);
    wg_fence();
#pragma unroll
    for (int k = 0; k < 4; k++) {
      wgmma_ss_n256_tb(acc, make_desc(sa + k * 32, 16, 1024), make_desc(sb + k * 2048, 8192, 1024), (kb | k) != 0);
      if (k == 0) {
        wg_commit();
        wg_wait<1>();
        if (kb > 0 && kb <= 4 && lane < 3) mbar_arrive_cluster(EMPT + 8 * (kb - 1), lane);
        wg_fence();
      }
    }
    wg_commit();
    if (kb >= 2 && kb < 6 && wv == ((kb & 1) << 2)) {
      if (elect_one()) {
        mbar_spin(EMPT + 8 * (kb - 2), 0);
        load_b(kb + 2);
        load_a(kb + 2);
      }
      __syncwarp();
    }
  }
  wg_wait<0>();
  TL(5);
#pragma unroll
  for (int j = 0; j < 8; j++) {
    uint4* dst = &g_tpart[((h & ~7) + ((j + (kq & 6)) & 7)) * 3 + rank][kq][0][tid];
    if (j >= 2 || j != (kq & 1)) {
#pragma unroll
      for (int i = 0; i < 2; i++) {
        const float* a = &acc[16 * j + 8 * i];
        dst[i * 256] = make_uint4(pack_bf16(a[0], a[1]), pack_bf16(a[2], a[3]), pack_bf16(a[4], a[5]), pack_bf16(a[6], a[7]));
      }
    }
  }
#pragma unroll
  for (int i = 0; i < 16; i++) acc[i] = (kq & 1) ? acc[16 + i] : acc[i];
  TL(6);
  __syncwarp();
  if (lane < 8) asm volatile("red.release.gpu.global.add.u32 [%0], 1;" ::"l"(&g_tcnt[((h & ~7) + lane) * 3 + rank][wv]) : "memory");
  TL(7);
  const size_t off = (size_t)(mb * 128 + wv * 16 + (lane >> 2)) * cfg::D + nt * 256 + kq * 32 + (lane & 3) * 2;
  uint32_t x[8], g[8];
  const uint32_t xa = self + VX + (wv * 16 + (lane & 15)) * 64 + (((lane >> 4) ^ ((lane >> 1) & 3)) << 4);
  mbar_spin(RES, 0);
  ldsm4(x, xa); ldsm4(x + 4, xa ^ 32);
  ldsm4(g, xa + (QK - VX)); ldsm4(g + 4, (xa ^ 32) + (QK - VX));
#pragma unroll 1
  for (int tries = 0; tries < POLL_TRIES; tries++) {
    uint32_t v;
    asm volatile("ld.acquire.gpu.global.u32 %0, [%1];" : "=r"(v) : "l"(&g_tcnt[blockIdx.x][wv]) : "memory");
    if (v >= 8) break;
  }
  uint4 pt[14];
#pragma unroll
  for (int i = 0; i < 14; i++) pt[i] = __ldcg(&g_tpart[blockIdx.x][(kq + 1 + (i >> 1)) & 7][i & 1][tid]);
  TL(8);
#pragma unroll 1
  for (int j = 0; j < 2; j++) {
#pragma unroll
    for (int i = 0; i < 28; i++) {
      const uint32_t v = (&pt[2 * (i >> 2)].x)[i & 3];
      acc[2 * (i & 3)] += bf_lo(v); acc[2 * (i & 3) + 1] += bf_hi(v);
    }
#pragma unroll
    for (int i = 0; i < 4; i++) {
      const uint32_t sv = pack_bf16(acc[2 * i], acc[2 * i + 1]);
      *reinterpret_cast<uint32_t*>(P.out + off + (i & 1) * 8 * cfg::D + (i >> 1) * 8 + j * 16) = nog ? sv : add_bf16x2(x[i], mul_bf16x2(sv, g[i]));
      x[i] = x[i + 4]; g[i] = g[i + 4];
      acc[2 * i] = acc[8 + 2 * i]; acc[2 * i + 1] = acc[9 + 2 * i];
    }
#pragma unroll
    for (int i = 0; i < 7; i++) pt[2 * i] = pt[2 * i + 1];
  }
  TL(9);
  KT_END(7);
}

__global__ void __launch_bounds__(256, 1) f_kernel(const __grid_constant__ FParams P) {
  using namespace fk;
  extern __shared__ __align__(1024) uint8_t smem_f[];
  uint32_t crank, rank, hw;
  asm("mov.u32 %0, %%cluster_ctarank;" : "=r"(crank));
  const int h = blockIdx.x / 3;
  if (smem_u32(smem_f) != mapa(0, crank) + SM0) return;
  PROF2(0);
  KT_START(1);
  KT_START(0);
  {
    const uint32_t self = mapa(0, crank);
    SMAP;
    const int tid = threadIdx.x, lane = tid & 31, wv = __shfl_sync(0xffffffffu, tid >> 5, 0);
    PRO(0);
    if (wv == 0) {
      uint32_t sm;
      asm("mov.u32 %0, %%smid;" : "=r"(sm));
      sts32(PROBE + 96, sm >> 1);
      asm volatile("fence.release.sync_restrict::shared::cta.cluster;" ::: "memory");
    }
    asm volatile("barrier.cluster.arrive.relaxed.aligned;" ::: "memory");
    if (wv == 7) {
      if (blockIdx.x == 2) {
#pragma unroll
        for (int i = 0; i < 4; i++) { (&g_cnt[0][0])[32 * i + lane] = 0; if (i < 3) g_tfix[32 * i + lane] = 0; }
        if (lane < 16) g_oflag[lane] = 0;
        if (lane == 0) { g_next = 0; g_lnok[0] = 0; }
        __threadfence();
        __syncwarp();
      }
      pdl_launch_dependents();
    }
    const int row0 = blockIdx.x * 8 + wv;
    const bool third = row0 + 1536 < cfg::S;
    uint32_t cur[1][16] = {}, raw[3][16];
    load_row16(raw[0], P.x + (size_t)row0 * cfg::D, lane);
    load_row16(raw[1], P.x + (size_t)(row0 + 768) * cfg::D, lane);
    load_row16(raw[2], P.x + (size_t)(row0 + (third ? 1536 : 0)) * cfg::D, lane);
    {
      uint32_t tpc;
      asm volatile("barrier.cluster.wait.aligned;" ::: "memory");
      asm volatile("ld.shared::cluster.u32 %0, [%1];" : "=r"(tpc) : "r"(mapa(PROBE + 96, lane % 3)) : "memory");
      const uint32_t t0 = __shfl_sync(0xffffffffu, tpc, 0), t1 = __shfl_sync(0xffffffffu, tpc, 1), t2 = __shfl_sync(0xffffffffu, tpc, 2);
      hw = t1 == t2 ? 0x09 : t0 == t2 ? 0x18 : 0x24;
      rank = (hw & 3) == crank ? 0 : ((hw >> 2) & 3) == crank ? 1 : 2;
    }
    const bool isv = rank == 2;
    const CUtensorMap* m0 = isv ? &P.wv : &P.wq;
    const CUtensorMap* m1 = isv ? &P.wv : &P.wk;
    const int col0 = h * 128 + (isv ? 0 : 64 * rank), col1 = h * 128 + (isv ? 64 : 64 * rank);
    auto req_weights = [&](int n0, int n1) {
#pragma unroll 1
        for (int n = n0; n < n1; n++) {
          const int i = n >> 1, g = n & 1, row = (isv ? Chunks<true>::rf(g, i) : Chunks<false>::rf(g, i)) * 64;
          if (!g) mbar_expect_tx(B_PB + 8 * i, 32768);
          tma_load_2d(SM0 + n * 16384, m0, col0, row, B_PB + 8 * i);
          tma_load_2d(SM0 + n * 16384 + 8192, m1, col1, row, B_PB + 8 * i);
        }
    };
    if (wv == 0) {
      if (elect_one()) {
        for (int i = 0; i < 2; i++) mbar_init(B_XN + 8 * i, 1);
        mbar_init(B_H1, 4);
        mbar_init(B_SM, isv ? 1 : 6);
        mbar_init(B_VM, isv ? 8 : 1);
        mbar_init(B_VX, 1);
        mbar_init(B_ST, 1);
        mbar_init(B_PF, 2);
        for (int i = 0; i < 6; i++) mbar_init(B_PB + 8 * i, 1);
        mbar_init(B_W, 2);
        mbar_init(B_WO, 1);
        fence_barrier_init();
        if (PRE_A) req_weights(0, 2 * PRE_A);
        mbar_expect_tx(B_SM, isv ? 2 * SP_SRC : SP_SRC);
        if (isv) mbar_expect_tx(B_ST, 7168);
        else { mbar_expect_tx(B_VM, 2048); mbar_expect_tx(B_VX, 8192); }
      }
    }
    const int j = 2 * h + rank;
    const bool dry = LN_DRY && !isv && wv == 6;
    if (dry) sts64(PROBE + wv * 8, 0x7FFFFFFF, 0x7FFFFFFF);
    if (lane == 0 && !dry) {
      const uint2 b = probe_pair(P.xch + (isv ? H1_BYTES + wv * 8192 + h * 128 : j * 32768 + (wv & 3) * 8192 + (wv >> 2) * 128),
                                 isv ? EMPTY : 0, PROBE + 64, P.nprobe);
      sts64(PROBE + wv * 8, b.x, b.y);
    }
    uint32_t mask = 0;
#pragma unroll 1
    for (int it = -1; it < (third ? 3 : 2); it++) {
      if (it >= 0 || dry) {
        ln_regs<1>(cur);
        if (it >= 0) store_row16(cur[0], P.xn_ptr + (size_t)(row0 + it * 768) * cfg::D, lane);
      }
      if (it == 0) PRO(4);
      if (it < 0) {
    PROF2(3);
    PRO(1);
    __syncwarp();
    if (wv == 0) {
      asm volatile("{\n.reg .pred p;\nsetp.eq.u32 p, %0, %1;\n@p st.shared.u32 [%2], %0;\n}" ::"r"(raw[2][15]), "r"(raw[0][0] ^ raw[1][15]), "r"(PROBE + 64) : "memory");
      if (elect_one()) {
        req_weights(2 * PRE_A, 2 * PRE_G);
      }
    }
    __syncthreads();
    PRO(2);
    asm volatile("barrier.cluster.arrive.relaxed.aligned;" ::: "memory");
    PRO(3);
    if (tid < 8) g_tcnt[blockIdx.x][tid] = 0;
    if (wv == 2) sts32(self + ONES + lane * 4, 0x3F803F80u);
    uint32_t pb[2], pc[2];
    lds64(pb, PROBE + (lane & 7) * 8);
    lds64(pc, PROBE + ((lane & 7) ^ 4) * 8);
    mask = __ballot_sync(0xffffffffu, isv ? pb[1] < pb[0] : min(pb[1], pc[1]) < min(pb[0], pc[0])) & (isv ? 255 : 15);
    if (!isv) {
#pragma unroll
      for (int i = 0; i < 4; i++) st_pub128(P.xch + j * 32768 + i * 8192 + ((mask >> i) & 1) * 4096 + tid * 16, 0);
      if (wv < 4) st_pub64(P.xch + H1_BYTES + (wv >> 1) * 32768 + (j >> 4) * 8192 + (wv & 1) * 4096 + (j & 15) * 256 + lane * 8, EMPTY, EMPTY);
    }
      }
#pragma unroll
      for (int i = 0; i < 16; i++) { cur[0][i] = raw[0][i]; raw[0][i] = raw[1][i]; raw[1][i] = raw[2][i]; }
    }
    PRO(5);
    __syncthreads();
    PRO(6);
    if (tid == 64) {
      __threadfence();
      PRO(7);
      st_pub32(&g_mask[3 * h + rank], 0x100 | mask);
    }
    KT_END(0);
    __syncwarp();
  }
  const int wg = __shfl_sync(0xffffffffu, threadIdx.x >> 7, 0);
  if (rank == 2) { if (wg == 0) f_main<true, 0>(P, h, 2, hw); else f_main<true, 1>(P, h, 2, hw); }
  else { if (wg == 0) f_main<false, 0>(P, h, rank, hw); else f_main<false, 1>(P, h, rank, hw); }
  PROF2(5);
  KT_END(1);
  __syncwarp();
  f_tail(P, h, crank, rank == 2);
}

#define G_AH 3
#define G_PF 3
#define G_LATE 0
namespace gk {
enum { T_B1 = 0, T_B2 = 1, T_B3 = 2, T_B4 = 3, T_O = 4, T_LN = 5, T_LN0 = 6, T_END = 7 };
constexpr int NST = 3, STAGE = 49152, MAXITEMS = 512, NEW = 3;
constexpr uint32_t OUTB = NST * STAGE, BARS = OUTB + 65536;
constexpr uint32_t B_FULL = BARS, B_EMPTY = BARS + 32, B_ITEM = BARS + 64, B_FILL = BARS + 128, B_FREE = BARS + 160, B_LN = BARS + 176, B_LNGO = BARS + 184, ITEMS = BARS + 192;
constexpr int SMEM = BARS + 256;
static_assert(GATE_CNT == 4 * NEW && T_B4 == 3, "gate counter");
}
struct GParams {
  CUtensorMap a[5], b[5];
  bf16* c[5];
  const bf16* r[5];
  bf16 *x1n, *xn2;
  const bf16* w1;
  int nitems, lnpos;
  uint16_t items[gk::MAXITEMS];
};
#define ILOG(i)
#define SLOG(i)

__device__ __forceinline__ float tanh_approx(float x) { float y; asm("tanh.approx.f32 %0, %1;" : "=f"(y) : "f"(x)); return y; }
__global__ void __launch_bounds__(384, 1) g_kernel(const __grid_constant__ GParams P) {
  using namespace gk;
  extern __shared__ __align__(1024) uint8_t smem_g[];
  const uint32_t base = smem_u32(smem_g);
  const int tid = threadIdx.x, warp = __shfl_sync(0xffffffffu, tid >> 5, 0), lane = tid & 31;
  KT_START(2);
  if (tid == 0) {
    for (int s = 0; s < NST; s++) { mbar_init(base + B_FULL + 8 * s, 1); mbar_init(base + B_EMPTY + 8 * s, 8); }
    for (int s = 0; s < 8; s++) mbar_init(base + B_ITEM + 8 * s, 1);
    for (int s = 0; s < 2; s++) { mbar_init(base + B_FILL + 8 * s, 4); mbar_init(base + B_FREE + 8 * s, NEW); }
    mbar_init(base + B_LN, 1);
    mbar_init(base + B_LNGO, 1);
    fence_barrier_init();
  }
  __syncthreads();
  auto release = [&](uint32_t st) { if (lane == 0) mbar_arrive(base + B_EMPTY + 8 * st); };
  auto get_item = [&](int q) {
    mbar_wait(base + B_ITEM + 8 * (q & 7), (q >> 3) & 1);
    return lds32(base + ITEMS + 4 * (q & 7));
  };

  if (warp == 8) {
    if (lane < 10) prefetch_tmap(&P.a[0] + lane);
    for (int r = blockIdx.x * 4 + lane; r < cfg::D / 8 && lane < 4; r += gridDim.x * 4) l2_prefetch(P.w1 + r * 8 * cfg::D, 16384);
    __syncwarp();
    auto fetch = [&](int q) {
      uint32_t v = 0;
      if (lane == 0) {
        const unsigned idx = atomicAdd(&g_next, 1), ln = idx - P.lnpos;
        v = (idx < (unsigned)P.nitems ? P.items[idx] : T_END) | (ln < 64 ? (ln + 1) << 16 : 0);
        sts32(base + ITEMS + 4 * (q & 7), v);
        mbar_arrive(base + B_ITEM + 8 * (q & 7));
        ILOG(1);
      }
      return __shfl_sync(0xffffffffu, v, 0);
    };
    auto open_deps = [&](uint32_t item) {
      const int type = item & 7, mb = (item >> 3) & 15;
      const unsigned* p = type == T_O ? &g_oflag[mb]
                        : &g_cnt[type == T_B1 ? T_LN0 : type == T_B2 ? T_B1 : type == T_B3 ? T_LN : T_B3][type == T_B2 ? min(max(mb + min(lane, 2) - 1, 0), 15) : mb];
      unsigned need = type == T_O ? 32 : type == T_B2 ? 4 * NEW : type == T_B4 ? 14 * NEW : 64;
      if (lane == 3) { p = &g_cnt[T_B2][(((item >> 16) - 1) >> 2) & 15]; need = item >> 16 ? 4 * NEW : 0; }
      unsigned v;
      asm volatile("ld.acquire.gpu.global.u32 %0, [%1];" : "=r"(v) : "l"(p) : "memory");
      return __ballot_sync(0xffffffffu, v < need) & 15;
    };
    uint32_t st = 0, ph = 1, next = fetch(0), open = 15;
    if (lane == 0) { __threadfence(); sts32(base + ITEMS + 32, ld_strong4(&g_oflag[14]) >= 32); }
    __syncwarp();
#pragma unroll 1
    for (int q = 0;; q++) {
      const uint32_t item = next;
      const int type = item & 7, mb = (item >> 3) & 15, nt = (item >> 7) & 15;
      if (type == T_END) break;
      const CUtensorMap *ma = &P.a[type], *mbm = &P.b[type];
      const int nkb = type == T_B4 ? cfg::F / 64 : type == T_O ? cfg::HD / 64 : cfg::D / 64;
#pragma unroll 1
      for (int kb = 0; kb < nkb; kb++) {
        mbar_wait(base + B_EMPTY + 8 * st, ph);
        const uint32_t sa = base + st * STAGE, full = base + B_FULL + 8 * st;
        if (elect_one()) {
          mbar_expect_tx(full, STAGE);
          tma_load_3d(sa + 16384, mbm, 0, kb * 64, nt * 4, full);
        }
        if (kb == 0) {
          bool go = (item >> 16) != 0;
#pragma unroll 1
          for (int tries = 0; tries < (1 << 18); tries++) {
            if (go && !(open & 8)) { go = false; if (lane == 0) mbar_arrive(base + B_LNGO); }
            if (!open) break;
            if (tries) __nanosleep(64);
            open = open_deps(item);
          }
          asm volatile("fence.proxy.async.global;" ::: "memory");
          if (lane == 0) ILOG(2);
        }
        int arow = mb * 128;
        if (type == T_B2) { const int qd = kb >> 2; arow += (qd == 0) ? -1 : (qd == 1) ? 1 : (qd == 2) ? -2 : 2; }
        if (elect_one()) {
          tma_load_2d(sa, ma, kb * 64, arow, full);
          if (type >= T_B4 && kb + G_PF < nkb)
            asm volatile("cp.async.bulk.prefetch.tensor.2d.L2.global [%0, {%1, %2}];" ::"l"(ma), "r"((kb + G_PF) * 64), "r"(arow) : "memory");
        }
        if (++st == NST) { st = 0; ph ^= 1; }
        if (kb == nkb - G_AH) next = fetch(q + 1);
        if (kb == nkb - G_AH + 1) open = open_deps(next);
      }
    }
  } else {
    const int wg = warp >> 2, ew = warp > 8 ? warp - 9 : warp + NEW;
    const uint32_t outa = base + OUTB + (warp * 16 + ((lane >> 3) & 1) * 8 + (lane & 7)) * 512 + (((lane >> 4) ^ (lane & 7)) << 4);
    uint32_t st = 0, ph = 0;
    float acc[128];
    auto kill_acc = [&]() {
#pragma unroll
      for (int i = 0; i < 128; i++) acc[i] = 0.f;
    };
    uint32_t next = T_LN0, lnph = 0;
#pragma unroll 1
    for (int q = -1;; q++) {
      const uint32_t item = next;
      const int type = item & 7, mb = (item >> 3) & 15, nt = (item >> 7) & 15;
      if (type == T_END) break;
      const bool first = q < 0;
      if (first || (warp < 8 && (item >> 16))) {
        const int ln = (item >> 16) - 1, lb = ln >> 2, pstr = first ? gridDim.x * 11 : 1;
#pragma unroll 1
        for (int p0 = first ? blockIdx.x * 11 + ew : lb * 64 + (ln & 3) * 16 + warp * 2; p0 < cfg::S / 2; p0 += first ? 3 * pstr : cfg::S) {
          const int np = first ? min(3, (cfg::S / 2 - 1 - p0) / pstr + 1) : 2;
          const bf16* src = (first ? P.r[T_O] : P.c[T_B2]) + (size_t)p0 * 2 * cfg::D;
          bf16* dst = (first ? P.xn2 : P.x1n) + (size_t)p0 * 2 * cfg::D;
          if (!first) { mbar_wait(base + B_LNGO, lnph); lnph ^= 1; }
          SLOG(0);
          uint32_t cur[2][16], n1[2][16], n2[2][16];
#pragma unroll
          for (int r = 0; r < 2; r++) {
            load_row16(cur[r], src + r * cfg::D, lane);
            load_row16(n1[r], src + (size_t)(min(1, np - 1) * pstr * 2 + r) * cfg::D, lane);
#pragma unroll
            for (int i = 0; i < 16; i++) n2[r][i] = 0;
            if (np > 2) load_row16(n2[r], src + (size_t)(pstr * 4 + r) * cfg::D, lane);
          }
#pragma unroll 1
          for (int it = first ? 0 : 1; it < 2 * np; it += first ? 1 : 2) {
            ln_regs<2>(cur);
            SLOG(1 + it);
            if (it & 1) {
#pragma unroll
              for (int r = 0; r < 2; r++) {
                store_row16(cur[r], dst + (size_t)((it >> 1) * pstr * 2 + r) * cfg::D, lane);
#pragma unroll
                for (int i = 0; i < 16; i++) { cur[r][i] = n1[r][i]; n1[r][i] = n2[r][i]; }
              }
            }
          }
          if (first) __syncwarp(); else named_bar_sync(3, 256);
          if (first ? lane < np : tid == 0)
            asm volatile("red.release.gpu.global.add.u32 [%0], %1;" ::"l"(&g_cnt[first ? T_LN0 : T_LN][(p0 + lane * pstr) >> 6]), "r"(first ? 1 : 16) : "memory");
          __syncwarp();
          SLOG(7);
        }
        if (tid == 0 && !first) ILOG(6);
        kill_acc();
        if (first) {
    if (warp == 9) {
#pragma unroll 1
      for (int tries = 0; tries < POLL_TRIES; tries++) {
        uint4 v;
        asm volatile("ld.acquire.gpu.global.v4.u32 {%0,%1,%2,%3}, [%4];" : "=r"(v.x), "=r"(v.y), "=r"(v.z), "=r"(v.w)
                     : "l"(lane < 24 ? &g_mask[4 * lane] : &g_lnok[0]) : "memory");
        const uint32_t ok = __ballot_sync(0xffffffffu, v.x & v.y & v.z & v.w & 0x100);
        if ((ok & 0xFFFFFF) == 0xFFFFFF || (ok >> 24)) break;
        __nanosleep(200);
      }
      if (lane == 0) mbar_arrive(base + B_LN);
    }
          next = get_item(0);
          continue;
        }
      }
      if (warp < 8) {
      const int nkb = type == T_B4 ? cfg::F / 64 : type == T_O ? cfg::HD / 64 : cfg::D / 64;
      uint32_t prev = 0;
      mbar_wait(base + B_FULL + 8 * st, ph);
#pragma unroll 1
      for (int kb = 0; kb < nkb; kb++) {
        mbar_spin(base + B_FULL + 8 * st, ph);
        if (kb == 0 && tid == 0) ILOG(3);
        const uint64_t da = make_desc(base + wg * 8192, 16, 1024) + st * (STAGE >> 4), db = make_desc(base + 16384, 8192, 1024) + st * (STAGE >> 4);
        wg_fence();
#pragma unroll
        for (int k = 0; k < 4; k++) {
          wgmma_ss_n256_tb(acc, da + k * 2, db + k * 128, (kb | k) != 0);
          if (k == 0) {
            wg_commit();
            wg_wait<1>();
            if (kb > 0) release(prev);
            wg_fence();
          }
        }
        wg_commit();
        prev = st;
        if (++st == NST) { st = 0; ph ^= 1; }
      }
      next = get_item(q + 1);
      if (q > 0) mbar_wait(base + B_FREE + 8 * wg, (q - 1) & 1);
      wg_wait<0>();
      if (tid == 0) ILOG(4);
      release(prev);
#pragma unroll
      for (int j = 0; j < 16; j++)
        stsm4((outa ^ ((j & 3) << 5)) + (j >> 2) * 128, pack_bf16(acc[8 * j], acc[8 * j + 1]), pack_bf16(acc[8 * j + 2], acc[8 * j + 3]),
              pack_bf16(acc[8 * j + 4], acc[8 * j + 5]), pack_bf16(acc[8 * j + 6], acc[8 * j + 7]));
      __syncwarp();
      if (lane == 0) mbar_arrive(base + B_FILL + 8 * wg);
      if (tid == 0) ILOG(5);
      if ((next & 7) != T_END) continue;
      }
      if (type == T_O) wait_count(&g_cnt[T_B4][mb], 4 * NEW);
      const int ldc = type == T_B3 ? cfg::F : cfg::D;
      bf16* cp = P.c[type] + (size_t)mb * 128 * ldc + nt * 256 + lane * 8;
      const size_t roff = (size_t)mb * 128 * cfg::D + nt * 256 + lane * 8;
      const bf16 *rp = P.r[type] + roff, *gp = P.c[T_B4] + roff;
      const bool gelu = type == T_B1 || type == T_B3;
      uint32_t yn[4][4];
      uint4 rn[4], gn[4];
#pragma unroll
      for (int i = 0; i < 4; i++) rn[i] = gn[i] = make_uint4(0, 0, 0, 0);
      auto fetch_res = [&](int grp) {
#pragma unroll
        for (int i = 0; i < 4; i++) {
          rn[i] = __ldcg(reinterpret_cast<const uint4*>(rp + (grp * 4 + i) * cfg::D));
          if (type == T_O) gn[i] = __ldcg(reinterpret_cast<const uint4*>(gp + (grp * 4 + i) * cfg::D));
        }
      };
      auto fetch_y = [&](int grp) {
        const uint32_t a = base + OUTB + grp * 2048 + ((lane ^ ((grp & 1) << 2)) << 4);
#pragma unroll
        for (int i = 0; i < 4; i++) lds128(yn[i], (a ^ (i << 4)) + i * 512);
      };
      auto store_y = [&](int grp, const uint32_t (&y)[4][4]) {
        char* p = reinterpret_cast<char*>(cp) + (uint32_t)(grp * 8 * ldc);
#pragma unroll
        for (int i = 0; i < 4; i++) *reinterpret_cast<uint4*>(p + (uint32_t)(i * 2 * ldc)) = make_uint4(y[i][0], y[i][1], y[i][2], y[i][3]);
      };
      if (type == T_B2) mbar_wait(base + B_LN, 0);
      if (type == T_B4) wait_count(&g_cnt[T_B2][mb], 4 * NEW);
      if (type >= T_B4 && warp > 8) for (int r = tid - 288; r < 128; r += 96) l2_prefetch(rp - lane * 8 + r * cfg::D, 512);
      if (!gelu) fetch_res(ew);
      mbar_wait(base + B_FILL, q & 1);
      fetch_y(ew);
      next = get_item(q + 1);
      mbar_wait(base + B_FILL + 8, q & 1);
      const int stride = (next & 7) == T_END ? NEW + 8 : NEW;
      if (gelu) {
#pragma unroll 1
        for (int grp = ew; grp < 32; grp += stride) {
          uint32_t y[4][4];
#pragma unroll
          for (int i = 0; i < 16; i++) y[i >> 2][i & 3] = mul_bf16x2(yn[i >> 2][i & 3], 0x3F003F00u);
          const int nx = grp + stride;
          if (nx >= 16 && grp < 16 && lane == 0 && warp > 8) mbar_arrive(base + B_FREE);
          if (!G_LATE) fetch_y(min(nx, 31));
#pragma unroll
          for (int i = 0; i < 16; i++) {
            uint32_t& v = y[i >> 2][i & 3];
            const float h0 = bf_lo(v), h1 = bf_hi(v);
            const float t0 = tanh_approx(h0 * fmaf(h0 * h0, 0.285419265090401f, 1.5957691216057308f));
            const float t1 = tanh_approx(h1 * fmaf(h1 * h1, 0.285419265090401f, 1.5957691216057308f));
            v = pack_bf16(fmaf(h0, t0, h0), fmaf(h1, t1, h1));
          }
          if (G_LATE) fetch_y(min(nx, 31));
          store_y(grp, y);
        }
      } else {
#pragma unroll 1
        for (int grp = ew; grp < 32; grp += stride) {
          uint32_t y[4][4];
          if (type == T_O) {
#pragma unroll
            for (int i = 0; i < 16; i++) yn[i >> 2][i & 3] = mul_bf16x2(yn[i >> 2][i & 3], (&gn[i >> 2].x)[i & 3]);
          }
#pragma unroll
          for (int i = 0; i < 16; i++) y[i >> 2][i & 3] = add_bf16x2(yn[i >> 2][i & 3], (&rn[i >> 2].x)[i & 3]);
          const int nx = grp + stride;
          if (nx >= 16 && grp < 16 && lane == 0 && warp > 8) mbar_arrive(base + B_FREE);
          fetch_res(min(nx, 31));
          fetch_y(min(nx, 31));
          if (type == T_B4) {
#pragma unroll
            for (int i = 0; i < 16; i++) {
              uint32_t& v = y[i >> 2][i & 3];
              const float h0 = 0.5f * bf_lo(v), h1 = 0.5f * bf_hi(v);
              v = pack_bf16(fmaf(h0, tanh_approx(h0), h0), fmaf(h1, tanh_approx(h1), h1));
            }
          }
          store_y(grp, y);
        }
      }
      __syncwarp();
      if (lane == 0 && warp > 8) mbar_arrive(base + B_FREE + 8);
      if (stride != NEW) named_bar_sync(2, 352);
      if (type != T_O && lane == 0 && warp > 8) asm volatile("red.release.gpu.global.add.u32 [%0], 1;" ::"l"(&g_cnt[type][mb]) : "memory");
      __syncwarp();
      if (tid == 288) ILOG(7);
      kill_acc();
    }
    KT_END(2);
  }
  __syncwarp();
  if (warp >= 8) {
   named_bar_sync(1, 128);
   const bool late = lds32(base + ITEMS + 32);
   if (late) pdl_wait();
#pragma unroll 1
   for (int c = blockIdx.x; late && c < 96; c += gridDim.x) {
     if (__ldcg(&g_tfix[c]) == 0) continue;
     const int hh = c / 3, mb = TAIL_MB0 + c % 3;
     wait_count(&g_cnt[T_B4][mb], GATE_CNT);
#pragma unroll 1
     for (int i = tid - 256; i < 512; i += 128) {
       const size_t off = (size_t)(mb * 128 + (i >> 2)) * cfg::D + hh * 32 + (i & 3) * 8;
       const uint4 sv = __ldcg(reinterpret_cast<const uint4*>(P.c[T_O] + off)), gv = __ldcg(reinterpret_cast<const uint4*>(P.c[T_B4] + off)),
                   xv = __ldcg(reinterpret_cast<const uint4*>(P.r[T_O] + off));
       *reinterpret_cast<uint4*>(P.c[T_O] + off) = make_uint4(add_bf16x2(xv.x, mul_bf16x2(sv.x, gv.x)), add_bf16x2(xv.y, mul_bf16x2(sv.y, gv.y)),
                                                              add_bf16x2(xv.z, mul_bf16x2(sv.z, gv.z)), add_bf16x2(xv.w, mul_bf16x2(sv.w, gv.w)));
     }
   }
  }
}

__device__ bf16 g_xn[cfg::S * cfg::D];
__device__ bf16 g_xn2[cfg::S * cfg::D];
__device__ bf16 g_h[cfg::S * cfg::D];
__device__ bf16 g_x1[cfg::S * cfg::D];
__device__ bf16 g_x1n[cfg::S * cfg::D];
__device__ bf16 g_u[cfg::S * cfg::F];
__device__ bf16 g_g[cfg::S * cfg::D];
__device__ bf16 g_o[cfg::S * cfg::HD];

typedef CUresult (*PFN_encodeTiled)(CUtensorMap*, CUtensorMapDataType, cuuint32_t, void*, const cuuint64_t*,
                                    const cuuint64_t*, const cuuint32_t*, const cuuint32_t*, CUtensorMapInterleave,
                                    CUtensorMapSwizzle, CUtensorMapL2promotion, CUtensorMapFloatOOBfill);

static PFN_encodeTiled get_encoder() {
  static PFN_encodeTiled fn = nullptr;
  if (!fn) {
    void* p = nullptr;
    cudaDriverEntryPointQueryResult st;
    cudaGetDriverEntryPoint("cuTensorMapEncodeTiled", &p, cudaEnableDefault, &st);
    fn = (PFN_encodeTiled)p;
  }
  return fn;
}
static CUtensorMap make_map(const void* ptr, int rows, int cols, int box_rows, int box_cols, int swizzle_bytes) {
  CUtensorMap m;
  cuuint64_t dims[2] = {(cuuint64_t)cols, (cuuint64_t)rows};
  cuuint64_t strides[1] = {(cuuint64_t)cols * 2};
  cuuint32_t box[2] = {(cuuint32_t)box_cols, (cuuint32_t)box_rows};
  cuuint32_t estr[2] = {1, 1};
  CUtensorMapSwizzle sw = swizzle_bytes == 128 ? CU_TENSOR_MAP_SWIZZLE_128B
                        : swizzle_bytes == 64 ? CU_TENSOR_MAP_SWIZZLE_64B
                        : swizzle_bytes == 32 ? CU_TENSOR_MAP_SWIZZLE_32B : CU_TENSOR_MAP_SWIZZLE_NONE;
  get_encoder()(&m, CU_TENSOR_MAP_DATA_TYPE_BFLOAT16, 2, const_cast<void*>(ptr), dims, strides, box, estr,
                CU_TENSOR_MAP_INTERLEAVE_NONE, sw, CU_TENSOR_MAP_L2_PROMOTION_L2_128B, CU_TENSOR_MAP_FLOAT_OOB_FILL_NONE);
  return m;
}
static CUtensorMap make_map3(const void* ptr, int rows, int cols, int box_rows, int nblk) {
  CUtensorMap m;
  cuuint64_t dims[3] = {64, (cuuint64_t)rows, (cuuint64_t)(cols / 64)};
  cuuint64_t strides[2] = {(cuuint64_t)cols * 2, 128};
  cuuint32_t box[3] = {64, (cuuint32_t)box_rows, (cuuint32_t)nblk};
  cuuint32_t estr[3] = {1, 1, 1};
  get_encoder()(&m, CU_TENSOR_MAP_DATA_TYPE_BFLOAT16, 3, const_cast<void*>(ptr), dims, strides, box, estr,
                CU_TENSOR_MAP_INTERLEAVE_NONE, CU_TENSOR_MAP_SWIZZLE_128B, CU_TENSOR_MAP_L2_PROMOTION_L2_128B,
                CU_TENSOR_MAP_FLOAT_OOB_FILL_NONE);
  return m;
}
template <class T> static T* sym(T& s) { void* p = nullptr; cudaGetSymbolAddress(&p, s); return (T*)p; }
#define SYM(name) ((bf16*)[] { void* p = nullptr; cudaGetSymbolAddress(&p, name); return p; }())

#define G_CTAS 36
#define B4_FIRST 11
#define O_FIRST 4
#define B3_FIRST 9
#define LN_POS 63
static int build_items(uint16_t* it) {
  using namespace gk;
  int n = 0;
  auto add = [&](int type, int nrows, int ncols, int row0 = 0) {
    for (int mb = row0; mb < nrows; mb++) for (int nt = 0; nt < ncols; nt++) it[n++] = (uint16_t)(type | mb << 3 | nt << 7);
  };
  add(T_B1, 16, 4); add(T_B2, 16, 4); add(T_B3, B3_FIRST, 14); add(T_B4, 2, 4); add(T_B3, 16, 14, B3_FIRST);
  add(T_B4, B4_FIRST, 4, 2); add(T_O, O_FIRST, 4); add(T_B4, 16, 4, B4_FIRST); add(T_O, TAIL_MB0, 4, O_FIRST);
  return n;
}

extern "C" void kernel_launch(void* const* d_in, const int* in_sizes, int n_in, void* d_out, int out_size) {
  using namespace cfg;
  const bf16* x = (const bf16*)d_in[0];
  const bf16* mem0 = (const bf16*)d_in[1];
  const bf16* Wq = (const bf16*)d_in[2];
  const bf16* Wk = (const bf16*)d_in[3];
  const bf16* Wv = (const bf16*)d_in[4];
  const bf16* Wo = (const bf16*)d_in[5];
  const bf16* w1 = (const bf16*)d_in[8];
  const bf16* w2 = (const bf16*)d_in[9];
  const bf16* w3 = (const bf16*)d_in[10];
  const bf16* w4 = (const bf16*)d_in[11];
  bf16* out = (bf16*)d_out;
  cudaStream_t st = cudaStreamPerThread;

  bf16 *xn = SYM(g_xn), *xn2 = SYM(g_xn2), *hb = SYM(g_h), *x1 = SYM(g_x1), *x1n = SYM(g_x1n), *u = SYM(g_u),
       *g = SYM(g_g), *o = SYM(g_o);

  {
    cudaFuncSetAttribute(f_kernel, cudaFuncAttributeMaxDynamicSharedMemorySize, fk::SMEM);
    FParams P;
    P.wq = make_map(Wq, D, HD, 64, 64, 128); P.wk = make_map(Wk, D, HD, 64, 64, 128); P.wv = make_map(Wv, D, HD, 64, 64, 128);
    P.wo = make_map(Wo, HD, D, 128, 64, 128); P.wo16 = make_map(Wo, HD, D, 128, 16, 32); P.xn = make_map3(xn, S, D, 32, 4); P.xn12 = make_map3(xn, S, D, 32, 12); P.o = make_map3(o, S, HD, 32, 2);
    P.ta = make_map(o, S, HD, 128, 64, 128); P.tb = make_map(Wo, HD, D, 64, 64, 128);
    P.tx = make_map(x, S, D, 128, 32, 64); P.tg = make_map(g, S, D, 128, 32, 64); P.out = out;
    P.mem0 = mem0;
    P.nprobe = PROBE_N;
    P.dxn = make_desc(fk::XN, 16, 1024);
    P.x = x; P.xn_ptr = xn;
    P.xch = (char*)(((uintptr_t)SYM(g_xch) + 8191) & ~(uintptr_t)8191);
    cudaLaunchConfig_t cfg = {};
    cfg.gridDim = dim3(96); cfg.blockDim = dim3(256); cfg.dynamicSmemBytes = fk::SMEM; cfg.stream = st;
    cudaLaunchAttribute at[2];
    at[0].id = cudaLaunchAttributeClusterDimension;
    at[0].val.clusterDim.x = 3; at[0].val.clusterDim.y = 1; at[0].val.clusterDim.z = 1;
    cfg.attrs = at; cfg.numAttrs = 1;
    cudaLaunchKernelEx(&cfg, f_kernel, P);
  }
  {
    cudaFuncSetAttribute(g_kernel, cudaFuncAttributeMaxDynamicSharedMemorySize, gk::SMEM);
    GParams G;
    const bf16* as[5] = {xn2, hb, x1n, u, o};
    const bf16* bs[5] = {w1, w2, w3, w4, Wo};
    bf16* cs[5] = {hb, x1, u, g, out};
    const bf16* rs[5] = {xn, xn, xn, x1, x};
    const int ks[5] = {D, D, D, F, HD}, ns[5] = {D, D, F, D, D};
    for (int i = 0; i < 5; i++) {
      G.a[i] = make_map(as[i], S, ks[i], 128, 64, 128);
      G.b[i] = make_map3(bs[i], ks[i], ns[i], 64, 4);
      G.c[i] = cs[i];
      G.r[i] = rs[i];
    }
    G.x1n = x1n; G.xn2 = xn2; G.w1 = w1;
    G.nitems = build_items(G.items);
    G.lnpos = LN_POS * 2;
    cudaLaunchConfig_t cfg = {};
    int dev = 0, sms = 0;
    cudaGetDevice(&dev);
    cudaDeviceGetAttribute(&sms, cudaDevAttrMultiProcessorCount, dev);
    cfg.gridDim = dim3(sms - 96 >= 4 && sms - 96 < G_CTAS ? sms - 96 : G_CTAS); cfg.blockDim = dim3(384); cfg.dynamicSmemBytes = gk::SMEM; cfg.stream = st;
    cudaLaunchAttribute at[1];
    at[0].id = cudaLaunchAttributeProgrammaticStreamSerialization;
    at[0].val.programmaticStreamSerializationAllowed = 1;
    cfg.attrs = at;
    cfg.numAttrs = 1;
    cudaLaunchKernelEx(&cfg, g_kernel, G);
  }
}
```
